```python
import torch

def _softmax(x, axis=-1):
    return torch.softmax(x, dim=axis)
def _gelu(x):
    return torch.nn.functional.gelu(x, approximate="tanh")
def _silu(x):
    return torch.nn.functional.silu(x)
def _sigmoid(x):
    return torch.sigmoid(x)
def _layernorm(x, axis=-1, eps=1e-5):
    m = x.mean(dim=axis, keepdim=True)
    v = x.var(dim=axis, keepdim=True, unbiased=False)
    return (x - m) / torch.sqrt(v + eps)
def _scatter_add(tgt, idx, src, axis=0):
    return tgt.clone().index_add_(axis, idx, src)
def _segment_sum(src, seg, n):
    out = torch.zeros((n,) + src.shape[1:], dtype=src.dtype)
    return out.index_add_(0, seg, src)
def _pad(x, pw):
    flat = tuple(v for pair in reversed(pw) for v in pair)
    return torch.nn.functional.pad(x, flat)

kernel_name = 'gated_mix__spectral_gfnet__swiglu_ffn__prompt'

def setup_inputs():

    _w = (lambda a: (lambda t: t.to(torch.bfloat16) if t.is_floating_point() else t)(torch.as_tensor(a)))
    def _A_setup():
        B, S, D = 1, 2048, 448
        Df = D // 2 + 1
        return {
            "x": _w((lambda *s: torch.randn(*s, dtype=torch.bfloat16) * 0.05)(B, S, D)),
            "w_r": _w((lambda *s: torch.randn(*s, dtype=torch.bfloat16) * 0.8)(S, Df) * 0.02),
            "w_i": _w((lambda *s: torch.randn(*s, dtype=torch.bfloat16) * 0.8)(S, Df) * 0.02),
        }
    _A_in = _A_setup()

    def _B_setup():
        B, S, D, F = 1, 2048, 448, 1792
        return {
            "x": _w((lambda *s: torch.randn(*s, dtype=torch.bfloat16) * 0.05)(B, S, D)),
            "w_gate": _w((lambda *s: torch.randn(*s, dtype=torch.bfloat16) * 0.05)(D, F)),
            "w_up": _w((lambda *s: torch.randn(*s, dtype=torch.bfloat16) * 0.05)(D, F)),
            "w_down": _w((lambda *s: torch.randn(*s, dtype=torch.bfloat16) * 0.05)(F, D)),
        }
    _B_in = _B_setup()

    return {
        "A_x": _A_in["x"],
        "A_w_r": _A_in["w_r"],
        "A_w_i": _A_in["w_i"],
        "B_x": _B_in["x"],
        "B_w_gate": _B_in["w_gate"],
        "B_w_up": _B_in["w_up"],
        "B_w_down": _B_in["w_down"],
        "gate_w": _w((lambda *s: torch.randn(*s, dtype=torch.bfloat16) * 0.05)(448) * 16.0),
    }

def reference(A_x, A_w_r, A_w_i, B_x, B_w_gate, B_w_up, B_w_down, gate_w):
    def _A_ref(x, w_r, w_i):
        B, S, D = x.shape
        X = (lambda x, axes=(-2,-1): torch.fft.rfft2(x.float(), dim=axes))(x, axes=(-2, -1))
        W = w_r + 1j * w_i
        X = X * W
        y = (lambda x, s, axes=(-2,-1): torch.fft.irfft2(x, s=s, dim=axes).to(torch.bfloat16))(X, (S, D), axes=(-2, -1))
        return y

    def _B_ref(x, w_gate, w_up, w_down):
        g = _silu(x @ w_gate)
        u = x @ w_up
        return (g * u) @ w_down

    x = A_x
    g = _sigmoid((x * gate_w).sum(-1, keepdims=True))
    a = _A_ref(x, A_w_r, A_w_i)
    b = _B_ref(x, B_w_gate, B_w_up, B_w_down)
    return g * a + (1 - g) * b
```

```cpp
#include <cuda_runtime.h>
#include <cuda_bf16.h>
#include <cuda.h>
#include <stdint.h>

namespace {

constexpr int S_ = 2048, D_ = 448, F_ = 1792, DF_ = 225;
constexpr int NTHREADS = 512;
constexpr int SLOT = 16384, NSLOT = 7;
constexpr int OFF_XR = NSLOT * SLOT;
constexpr int HALF_XR = 57344;
constexpr int OFF_HOWN = OFF_XR;
constexpr int OFF_PQ = OFF_XR + HALF_XR;
constexpr int OFF_EXCH = OFF_PQ;
constexpr int OFF_STASH = OFF_EXCH + 18432;
constexpr int OFF_WS = OFF_STASH + 16384;
constexpr int OFF_TW2 = OFF_WS + 16384;
constexpr int OFF_MISC = OFF_XR + 2 * HALF_XR;
constexpr int OFF_G = OFF_MISC;
constexpr int OFF_BAR = OFF_MISC + 512;
constexpr int SMEM_BYTES = OFF_BAR + 512;
constexpr int B_FULL = 0, B_EMPTY = 7, B_XFULL = 14  , B_XFREE = 28  , B_PUB = 30  , B_PQFULL = 34, B_RECV = 35, B_RFREE = 36, B_NBAR = 37;

constexpr int WD_IMG = 896 * 112 * 2;
constexpr int G_IMG = 224 * 56 * 2;

__device__ __align__(1024) float2 g_Xc[2 * 112 * S_];
__device__ __align__(1024) unsigned char g_H[16 * 8 * HALF_XR];
__device__ __align__(1024) unsigned char g_PQ[2 * 16 * HALF_XR];
__device__ __align__(1024) unsigned char g_Wd[8 * WD_IMG];
__device__ __align__(1024) unsigned char g_G[8 * G_IMG];
__device__ __align__(1024) float g_gate[S_];
__device__ __align__(128) unsigned int g_hflag[128 * 4];
__device__ __align__(128) unsigned int g_ep[128 * 2];
__device__ __align__(128) unsigned int g_cnt[8 * 32];

#define PROF(role, idx) do {} while (0)

__device__ __forceinline__ uint32_t s2u(const void* p) { return (uint32_t)__cvta_generic_to_shared(p); }
__device__ __forceinline__ void mbar_init(uint32_t b, int c) { asm volatile("mbarrier.init.shared::cta.b64 [%0], %1;" :: "r"(b), "r"(c) : "memory"); }
__device__ __forceinline__ void mbar_expect(uint32_t b, int bytes) { asm volatile("mbarrier.arrive.expect_tx.shared::cta.b64 _, [%0], %1;" :: "r"(b), "r"(bytes) : "memory"); }
__device__ __forceinline__ void mbar_arrive(uint32_t b) { asm volatile("mbarrier.arrive.shared::cta.b64 _, [%0];" :: "r"(b) : "memory"); }
__device__ __forceinline__ bool mbar_try(uint32_t b, int ph) {
  uint32_t ok;
  asm volatile("{\n.reg .pred p;\nmbarrier.try_wait.parity.shared::cta.b64 p, [%1], %2;\nselp.u32 %0, 1, 0, p;\n}" : "=r"(ok) : "r"(b), "r"(ph) : "memory");
  return ok;
}
__device__ __forceinline__ void mbar_wait(uint32_t b, int ph) {
  if (mbar_try(b, ph)) return;
#pragma unroll 1
  for (int i = 0; i < (1 << 22); i++) if (mbar_try(b, ph)) return;
  __trap();
}
__device__ __forceinline__ void mbar_wait_cluster(uint32_t b, int ph) {
#pragma unroll 1
  for (int i = 0; i < (1 << 22); i++) {
    uint32_t ok;
    asm volatile("{\n.reg .pred p;\nmbarrier.try_wait.parity.acquire.cluster.shared::cta.b64 p, [%1], %2;\nselp.u32 %0, 1, 0, p;\n}" : "=r"(ok) : "r"(b), "r"(ph) : "memory");
    if (ok) return;
  }
  __trap();
}
__device__ __forceinline__ uint32_t ld_acquire(const unsigned int* p) { uint32_t v; asm volatile("ld.acquire.gpu.global.u32 %0, [%1];" : "=r"(v) : "l"(p) : "memory"); return v; }
__device__ __forceinline__ uint32_t ld_relaxed(const unsigned int* p) { uint32_t v; asm volatile("ld.relaxed.gpu.global.u32 %0, [%1];" : "=r"(v) : "l"(p) : "memory"); return v; }
__device__ __forceinline__ void wait_ge(const unsigned int* p, uint32_t target) {
#pragma unroll 1
  for (int i = 0; i < (1 << 22); i++) { if ((int)(ld_acquire(p) - target) >= 0) return; }
  __trap();
}
__device__ __forceinline__ void fence_gpu() { asm volatile("fence.acq_rel.gpu;" ::: "memory"); }
__device__ __forceinline__ void red_add(unsigned int* p) { asm volatile("red.relaxed.gpu.global.add.u32 [%0], 1;" :: "l"(p) : "memory"); }
__device__ __forceinline__ void fence_async_smem() { asm volatile("fence.proxy.async.shared::cta;" ::: "memory"); }
__device__ __forceinline__ void fence_async_all() { asm volatile("fence.proxy.async;" ::: "memory"); }
template <int ID, int N> __device__ __forceinline__ void bar_sync() { asm volatile("bar.sync %0, %1;" :: "n"(ID), "n"(N) : "memory"); }
template <int ID, int N> __device__ __forceinline__ void bar_arrive() { asm volatile("bar.arrive %0, %1;" :: "n"(ID), "n"(N) : "memory"); }
__device__ __forceinline__ void tma2d(uint32_t dst, const CUtensorMap* tm, int c0, int c1, uint32_t bar) {
  asm volatile("cp.async.bulk.tensor.2d.shared::cluster.global.mbarrier::complete_tx::bytes [%0], [%1, {%3, %4}], [%2];"
               :: "r"(dst), "l"(tm), "r"(bar), "r"(c0), "r"(c1) : "memory");
}
__device__ __forceinline__ void bulk_g2s(uint32_t dst, const void* src, int bytes, uint32_t bar) {
  asm volatile("cp.async.bulk.shared::cluster.global.mbarrier::complete_tx::bytes [%0], [%1], %2, [%3];"
               :: "r"(dst), "l"(src), "r"(bytes), "r"(bar) : "memory");
}
__device__ __forceinline__ void prefetch_l2(const void* src, int bytes) {
  asm volatile("cp.async.bulk.prefetch.L2.global [%0], %1;" :: "l"(src), "r"(bytes) : "memory");
}
__device__ __forceinline__ uint64_t mkdesc(uint32_t addr, uint32_t lbo, uint32_t sbo, uint32_t mode) {
  return (uint64_t)((addr & 0x3FFFF) >> 4) | ((uint64_t)(lbo >> 4) << 16) | ((uint64_t)(sbo >> 4) << 32) | ((uint64_t)mode << 62);
}
__device__ __forceinline__ void wg_fence() { asm volatile("wgmma.fence.sync.aligned;" ::: "memory"); }
__device__ __forceinline__ void wg_commit() { asm volatile("wgmma.commit_group.sync.aligned;" ::: "memory"); }
template <int N> __device__ __forceinline__ void wg_wait() { asm volatile("wgmma.wait_group.sync.aligned %0;" :: "n"(N) : "memory"); }
template <int N> __device__ __forceinline__ void keep(float (&d)[N]) {
#pragma unroll
  for (int i = 0; i < N; i++) asm volatile("" : "+f"(d[i]) :: "memory");
}
__device__ __forceinline__ uint32_t pack_bf16(float lo, float hi) { uint32_t r; asm("cvt.rn.bf16x2.f32 %0, %1, %2;" : "=r"(r) : "f"(hi), "f"(lo)); return r; }
__device__ __forceinline__ float bf16_round(float v) { return __bfloat162float(__float2bfloat16_rn(v)); }
__device__ __forceinline__ void sts128(uint32_t a, uint32_t x, uint32_t y, uint32_t z, uint32_t w) { asm volatile("st.shared.v4.b32 [%0], {%1,%2,%3,%4};" :: "r"(a), "r"(x), "r"(y), "r"(z), "r"(w) : "memory"); }
__device__ __forceinline__ void sts128f(uint32_t a, float x, float y, float z, float w) { asm volatile("st.shared.v4.f32 [%0], {%1,%2,%3,%4};" :: "r"(a), "f"(x), "f"(y), "f"(z), "f"(w) : "memory"); }
__device__ __forceinline__ void sts64f(uint32_t a, float x, float y) { asm volatile("st.shared.v2.f32 [%0], {%1,%2};" :: "r"(a), "f"(x), "f"(y) : "memory"); }
__device__ __forceinline__ void sts32(uint32_t a, uint32_t x) { asm volatile("st.shared.b32 [%0], %1;" :: "r"(a), "r"(x) : "memory"); }
__device__ __forceinline__ float4 lds128f(uint32_t a) { float4 v; asm volatile("ld.shared.v4.f32 {%0,%1,%2,%3}, [%4];" : "=f"(v.x), "=f"(v.y), "=f"(v.z), "=f"(v.w) : "r"(a) : "memory"); return v; }
__device__ __forceinline__ float2 lds64f(uint32_t a) { float2 v; asm volatile("ld.shared.v2.f32 {%0,%1}, [%2];" : "=f"(v.x), "=f"(v.y) : "r"(a) : "memory"); return v; }
__device__ __forceinline__ uint32_t lds32(uint32_t a) { uint32_t v; asm volatile("ld.shared.b32 %0, [%1];" : "=r"(v) : "r"(a) : "memory"); return v; }

template <int TB> __device__ __forceinline__ void wgmma_rs_128(float (&d)[64], const uint32_t (&a)[4], uint64_t db, int sc) {
  asm volatile("{\n.reg .pred p;\nsetp.ne.b32 p, %69, 0;\n"
    "wgmma.mma_async.sync.aligned.m64n128k16.f32.bf16.bf16 {%0, %1, %2, %3, %4, %5, %6, %7, %8, %9, %10, %11, %12, %13, %14, %15, %16, %17, %18, %19, %20, %21, %22, %23, %24, %25, %26, %27, %28, %29, %30, %31, %32, %33, %34, %35, %36, %37, %38, %39, %40, %41, %42, %43, %44, %45, %46, %47, %48, %49, %50, %51, %52, %53, %54, %55, %56, %57, %58, %59, %60, %61, %62, %63}, {%64, %65, %66, %67}, %68, p, 1, 1, %70;\n}\n"
    : "+f"(d[0]), "+f"(d[1]), "+f"(d[2]), "+f"(d[3]), "+f"(d[4]), "+f"(d[5]), "+f"(d[6]), "+f"(d[7]), "+f"(d[8]), "+f"(d[9]), "+f"(d[10]), "+f"(d[11]), "+f"(d[12]), "+f"(d[13]), "+f"(d[14]), "+f"(d[15]), "+f"(d[16]), "+f"(d[17]), "+f"(d[18]), "+f"(d[19]), "+f"(d[20]), "+f"(d[21]), "+f"(d[22]), "+f"(d[23]), "+f"(d[24]), "+f"(d[25]), "+f"(d[26]), "+f"(d[27]), "+f"(d[28]), "+f"(d[29]), "+f"(d[30]), "+f"(d[31]), "+f"(d[32]), "+f"(d[33]), "+f"(d[34]), "+f"(d[35]), "+f"(d[36]), "+f"(d[37]), "+f"(d[38]), "+f"(d[39]), "+f"(d[40]), "+f"(d[41]), "+f"(d[42]), "+f"(d[43]), "+f"(d[44]), "+f"(d[45]), "+f"(d[46]), "+f"(d[47]), "+f"(d[48]), "+f"(d[49]), "+f"(d[50]), "+f"(d[51]), "+f"(d[52]), "+f"(d[53]), "+f"(d[54]), "+f"(d[55]), "+f"(d[56]), "+f"(d[57]), "+f"(d[58]), "+f"(d[59]), "+f"(d[60]), "+f"(d[61]), "+f"(d[62]), "+f"(d[63])
    : "r"(a[0]), "r"(a[1]), "r"(a[2]), "r"(a[3]), "l"(db), "r"(sc), "n"(TB));
}
template <int TB> __device__ __forceinline__ void wgmma_rs_64(float (&d)[32], const uint32_t (&a)[4], uint64_t db, int sc) {
  asm volatile("{\n.reg .pred p;\nsetp.ne.b32 p, %37, 0;\n"
    "wgmma.mma_async.sync.aligned.m64n64k16.f32.bf16.bf16 {%0, %1, %2, %3, %4, %5, %6, %7, %8, %9, %10, %11, %12, %13, %14, %15, %16, %17, %18, %19, %20, %21, %22, %23, %24, %25, %26, %27, %28, %29, %30, %31}, {%32, %33, %34, %35}, %36, p, 1, 1, %38;\n}\n"
    : "+f"(d[0]), "+f"(d[1]), "+f"(d[2]), "+f"(d[3]), "+f"(d[4]), "+f"(d[5]), "+f"(d[6]), "+f"(d[7]), "+f"(d[8]), "+f"(d[9]), "+f"(d[10]), "+f"(d[11]), "+f"(d[12]), "+f"(d[13]), "+f"(d[14]), "+f"(d[15]), "+f"(d[16]), "+f"(d[17]), "+f"(d[18]), "+f"(d[19]), "+f"(d[20]), "+f"(d[21]), "+f"(d[22]), "+f"(d[23]), "+f"(d[24]), "+f"(d[25]), "+f"(d[26]), "+f"(d[27]), "+f"(d[28]), "+f"(d[29]), "+f"(d[30]), "+f"(d[31])
    : "r"(a[0]), "r"(a[1]), "r"(a[2]), "r"(a[3]), "l"(db), "r"(sc), "n"(TB));
}
template <int TB> __device__ __forceinline__ void wgmma_rs_56(float (&d)[28], const uint32_t (&a)[4], uint64_t db, int sc) {
  asm volatile("{\n.reg .pred p;\nsetp.ne.b32 p, %33, 0;\n"
    "wgmma.mma_async.sync.aligned.m64n56k16.f32.bf16.bf16 {%0, %1, %2, %3, %4, %5, %6, %7, %8, %9, %10, %11, %12, %13, %14, %15, %16, %17, %18, %19, %20, %21, %22, %23, %24, %25, %26, %27}, {%28, %29, %30, %31}, %32, p, 1, 1, %34;\n}\n"
    : "+f"(d[0]), "+f"(d[1]), "+f"(d[2]), "+f"(d[3]), "+f"(d[4]), "+f"(d[5]), "+f"(d[6]), "+f"(d[7]), "+f"(d[8]), "+f"(d[9]), "+f"(d[10]), "+f"(d[11]), "+f"(d[12]), "+f"(d[13]), "+f"(d[14]), "+f"(d[15]), "+f"(d[16]), "+f"(d[17]), "+f"(d[18]), "+f"(d[19]), "+f"(d[20]), "+f"(d[21]), "+f"(d[22]), "+f"(d[23]), "+f"(d[24]), "+f"(d[25]), "+f"(d[26]), "+f"(d[27])
    : "r"(a[0]), "r"(a[1]), "r"(a[2]), "r"(a[3]), "l"(db), "r"(sc), "n"(TB));
}
template <int TA, int TB> __device__ __forceinline__ void wgmma_ss_112(float (&d)[56], uint64_t da, uint64_t db, int sc) {
  asm volatile("{\n.reg .pred p;\nsetp.ne.b32 p, %58, 0;\n"
    "wgmma.mma_async.sync.aligned.m64n112k16.f32.bf16.bf16 {%0, %1, %2, %3, %4, %5, %6, %7, %8, %9, %10, %11, %12, %13, %14, %15, %16, %17, %18, %19, %20, %21, %22, %23, %24, %25, %26, %27, %28, %29, %30, %31, %32, %33, %34, %35, %36, %37, %38, %39, %40, %41, %42, %43, %44, %45, %46, %47, %48, %49, %50, %51, %52, %53, %54, %55}, %56, %57, p, 1, 1, %59, %60;\n}\n"
    : "+f"(d[0]), "+f"(d[1]), "+f"(d[2]), "+f"(d[3]), "+f"(d[4]), "+f"(d[5]), "+f"(d[6]), "+f"(d[7]), "+f"(d[8]), "+f"(d[9]), "+f"(d[10]), "+f"(d[11]), "+f"(d[12]), "+f"(d[13]), "+f"(d[14]), "+f"(d[15]), "+f"(d[16]), "+f"(d[17]), "+f"(d[18]), "+f"(d[19]), "+f"(d[20]), "+f"(d[21]), "+f"(d[22]), "+f"(d[23]), "+f"(d[24]), "+f"(d[25]), "+f"(d[26]), "+f"(d[27]), "+f"(d[28]), "+f"(d[29]), "+f"(d[30]), "+f"(d[31]), "+f"(d[32]), "+f"(d[33]), "+f"(d[34]), "+f"(d[35]), "+f"(d[36]), "+f"(d[37]), "+f"(d[38]), "+f"(d[39]), "+f"(d[40]), "+f"(d[41]), "+f"(d[42]), "+f"(d[43]), "+f"(d[44]), "+f"(d[45]), "+f"(d[46]), "+f"(d[47]), "+f"(d[48]), "+f"(d[49]), "+f"(d[50]), "+f"(d[51]), "+f"(d[52]), "+f"(d[53]), "+f"(d[54]), "+f"(d[55])
    : "l"(da), "l"(db), "r"(sc), "n"(TA), "n"(TB));
}
template <int TA, int TB> __device__ __forceinline__ void wgmma_ss_56(float (&d)[28], uint64_t da, uint64_t db, int sc) {
  asm volatile("{\n.reg .pred p;\nsetp.ne.b32 p, %30, 0;\n"
    "wgmma.mma_async.sync.aligned.m64n56k16.f32.bf16.bf16 {%0, %1, %2, %3, %4, %5, %6, %7, %8, %9, %10, %11, %12, %13, %14, %15, %16, %17, %18, %19, %20, %21, %22, %23, %24, %25, %26, %27}, %28, %29, p, 1, 1, %31, %32;\n}\n"
    : "+f"(d[0]), "+f"(d[1]), "+f"(d[2]), "+f"(d[3]), "+f"(d[4]), "+f"(d[5]), "+f"(d[6]), "+f"(d[7]), "+f"(d[8]), "+f"(d[9]), "+f"(d[10]), "+f"(d[11]), "+f"(d[12]), "+f"(d[13]), "+f"(d[14]), "+f"(d[15]), "+f"(d[16]), "+f"(d[17]), "+f"(d[18]), "+f"(d[19]), "+f"(d[20]), "+f"(d[21]), "+f"(d[22]), "+f"(d[23]), "+f"(d[24]), "+f"(d[25]), "+f"(d[26]), "+f"(d[27])
    : "l"(da), "l"(db), "r"(sc), "n"(TA), "n"(TB));
}

__device__ __forceinline__ void cs448(int idx, float& c, float& s) {
  if (idx > 224) idx -= 448;
  float a = (float)idx * (6.283185307179586f / 448.0f);
  c = __cosf(a); s = __sinf(a);
}

__device__ __forceinline__ float2 cmul(float2 a, float2 b) { return make_float2(a.x * b.x - a.y * b.y, a.x * b.y + a.y * b.x); }
__device__ __forceinline__ void fft4(float2& a0, float2& a1, float2& a2, float2& a3) {
  float2 t0 = make_float2(a0.x + a2.x, a0.y + a2.y), t1 = make_float2(a0.x - a2.x, a0.y - a2.y);
  float2 t2 = make_float2(a1.x + a3.x, a1.y + a3.y), t3 = make_float2(a1.x - a3.x, a1.y - a3.y);
  a0 = make_float2(t0.x + t2.x, t0.y + t2.y); a2 = make_float2(t0.x - t2.x, t0.y - t2.y);
  a1 = make_float2(t1.x + t3.y, t1.y - t3.x); a3 = make_float2(t1.x - t3.y, t1.y + t3.x);
}
__device__ __forceinline__ float2 mul_w8_1(float2 a) { const float r = 0.70710678118654752f; return make_float2((a.x + a.y) * r, (a.y - a.x) * r); }
__device__ __forceinline__ float2 mul_w8_3(float2 a) { const float r = 0.70710678118654752f; return make_float2((a.y - a.x) * r, -(a.x + a.y) * r); }
__device__ __forceinline__ float2 mul_mi(float2 a) { return make_float2(a.y, -a.x); }
template <int O, int ST, int N> __device__ __forceinline__ void fft8(float2 (&v)[N]) {
  fft4(v[O], v[O + 2 * ST], v[O + 4 * ST], v[O + 6 * ST]);
  fft4(v[O + ST], v[O + 3 * ST], v[O + 5 * ST], v[O + 7 * ST]);
  float2 o0 = v[O + ST], o1 = mul_w8_1(v[O + 3 * ST]), o2 = mul_mi(v[O + 5 * ST]), o3 = mul_w8_3(v[O + 7 * ST]);
  float2 e0 = v[O], e1 = v[O + 2 * ST], e2 = v[O + 4 * ST], e3 = v[O + 6 * ST];
  v[O] = make_float2(e0.x + o0.x, e0.y + o0.y);          v[O + 4 * ST] = make_float2(e0.x - o0.x, e0.y - o0.y);
  v[O + ST] = make_float2(e1.x + o1.x, e1.y + o1.y);     v[O + 5 * ST] = make_float2(e1.x - o1.x, e1.y - o1.y);
  v[O + 2 * ST] = make_float2(e2.x + o2.x, e2.y + o2.y); v[O + 6 * ST] = make_float2(e2.x - o2.x, e2.y - o2.y);
  v[O + 3 * ST] = make_float2(e3.x + o3.x, e3.y + o3.y); v[O + 7 * ST] = make_float2(e3.x - o3.x, e3.y - o3.y);
}
__device__ __forceinline__ void fft16(float2 (&v)[16]) {
  const float c1 = 0.92387953251128674f, s1 = 0.38268343236508977f;
#pragma unroll
  for (int a = 0; a < 4; a++) fft4(v[a], v[a + 4], v[a + 8], v[a + 12]);
  v[5] = cmul(v[5], make_float2(c1, -s1)); v[9] = mul_w8_1(v[9]); v[13] = cmul(v[13], make_float2(s1, -c1));
  v[6] = mul_w8_1(v[6]); v[10] = mul_mi(v[10]); v[14] = mul_w8_3(v[14]);
  v[7] = cmul(v[7], make_float2(s1, -c1)); v[11] = mul_w8_3(v[11]); v[15] = cmul(v[15], make_float2(-c1, s1));
#pragma unroll
  for (int b = 0; b < 4; b++) fft4(v[4 * b], v[4 * b + 1], v[4 * b + 2], v[4 * b + 3]);
  float2 t;
  t = v[1]; v[1] = v[4]; v[4] = t;  t = v[2]; v[2] = v[8]; v[8] = t;  t = v[3]; v[3] = v[12]; v[12] = t;
  t = v[6]; v[6] = v[9]; v[9] = t;  t = v[7]; v[7] = v[13]; v[13] = t; t = v[11]; v[11] = v[14]; v[14] = t;
}
template <int E> __device__ __forceinline__ void tw8(float2 (&v)[16], float2 w) {
  float2 w2 = cmul(w, w), w3 = cmul(w2, w), w4 = cmul(w2, w2);
  v[E + 2] = cmul(v[E + 2], w); v[E + 4] = cmul(v[E + 4], w2); v[E + 6] = cmul(v[E + 6], w3); v[E + 8] = cmul(v[E + 8], w4);
  v[E + 10] = cmul(v[E + 10], cmul(w4, w)); v[E + 12] = cmul(v[E + 12], cmul(w3, w3)); v[E + 14] = cmul(v[E + 14], cmul(w4, w3));
}

__device__ __forceinline__ void column(float2 (&v)[16], uint32_t sb, int t, float2 wa, float2 wb, uint32_t ws) {
  const uint32_t ex = sb + OFF_EXCH;
  const uint32_t row = ex + (t >> 4) * 2304;
  const int l16 = t & 15;
  const uint32_t tw = sb + OFF_TW2 + l16 * 8;
  fft8<0, 2>(v); fft8<1, 2>(v);
  tw8<0>(v, wa); tw8<1>(v, wb);
#pragma unroll
  for (int q = 0; q < 8; q++) sts128f(ex + q * 2304 + t * 16, v[2 * q].x, v[2 * q].y, v[2 * q + 1].x, v[2 * q + 1].y);
  bar_sync<3, 128>();
#pragma unroll
  for (int j = 0; j < 16; j++) v[j] = lds64f(row + (l16 + 16 * j) * 8);
  fft16(v);
  __syncwarp();
#pragma unroll
  for (int q = 0; q < 16; q++) {
    float2 r = q ? cmul(v[q], lds64f(tw + q * 128)) : v[q];
    sts64f(row + q * 144 + l16 * 8, r.x, r.y);
  }
  __syncwarp();
#pragma unroll
  for (int j = 0; j < 8; j++) { float4 a = lds128f(row + l16 * 144 + j * 16); v[2 * j] = make_float2(a.x, a.y); v[2 * j + 1] = make_float2(a.z, a.w); }
  fft16(v);
#pragma unroll
  for (int q = 0; q < 16; q++) {
    uint32_t w = lds32(ws + q * 512);
    float wr = __uint_as_float(w << 16), wi = __uint_as_float(w & 0xffff0000u);
    v[q] = make_float2(v[q].x * wi + v[q].y * wr, v[q].x * wr - v[q].y * wi);
  }
  fft16(v);
  __syncwarp();
#pragma unroll
  for (int j = 0; j < 8; j++) {
    float2 a = j ? cmul(v[2 * j], lds64f(tw + (2 * j) * 128)) : v[0];
    float2 b = cmul(v[2 * j + 1], lds64f(tw + (2 * j + 1) * 128));
    sts128f(row + l16 * 144 + j * 16, a.x, a.y, b.x, b.y);
  }
  __syncwarp();
#pragma unroll
  for (int q = 0; q < 16; q++) v[q] = lds64f(row + q * 144 + l16 * 8);
  fft16(v);
  __syncwarp();
#pragma unroll
  for (int j = 0; j < 16; j++) sts64f(row + (l16 + 16 * j) * 8, v[j].x, v[j].y);
  bar_sync<3, 128>();
#pragma unroll
  for (int q = 0; q < 8; q++) { float4 a = lds128f(ex + q * 2304 + t * 16); v[2 * q] = make_float2(a.x, a.y); v[2 * q + 1] = make_float2(a.z, a.w); }
  bar_sync<3, 128>();
  tw8<0>(v, wa); tw8<1>(v, wb);
  fft8<0, 2>(v); fft8<1, 2>(v);
}

__device__ __forceinline__ int unit_col(int j, int u) {
  return (j & 1) ? (u == 1 ? 0 : (u == 0 ? 32 : 64 * u - 32)) : (u == 1 ? 192 : (u == 0 ? 0 : 64 * u - 64));
}
__device__ __forceinline__ int unit_k(int u) { return u == 0 ? 0 : (u == 1 ? 64 : 64 * u - 32); }

__device__ __forceinline__ int g2_block(int i) {
  const unsigned long long tab = 0xFB73EA62D951C840ull;
  return (int)((tab >> (4 * i)) & 15);
}
constexpr int G2_SPEC_AT = 12;
constexpr int G2_FREE_AFTER = 8;

template <int NH> __device__ __forceinline__ void h_epilogue(float (&acc)[NH * 8], uint32_t sdst, unsigned char* gdst) {
#pragma unroll
  for (int c = 0; c < NH / 4; c++) {
#pragma unroll
    for (int rr = 0; rr < 2; rr++) {
      uint32_t pk[4];
#pragma unroll
      for (int i = 0; i < 4; i++) {
        float hv[2];
#pragma unroll
        for (int e = 0; e < 2; e++) {
          float gt = acc[(4 * c + i) * 4 + rr * 2 + e], up = acc[(NH + 4 * c + i) * 4 + rr * 2 + e];
          float ex; asm("ex2.approx.ftz.f32 %0, %1;" : "=f"(ex) : "f"(gt * -1.4426950408889634f));
          float rc; asm("rcp.approx.ftz.f32 %0, %1;" : "=f"(rc) : "f"(1.0f + ex));
          hv[e] = gt * rc * up;
        }
        pk[i] = pack_bf16(hv[0], hv[1]);
      }
      sts128(sdst + c * 4096 + rr * 128, pk[0], pk[1], pk[2], pk[3]);
      *reinterpret_cast<uint4*>(gdst + c * 4096 + rr * 128) = make_uint4(pk[0], pk[1], pk[2], pk[3]);
    }
  }
}

__global__ void __cluster_dims__(2, 1, 1) __launch_bounds__(NTHREADS, 1)
fused_kernel(const __grid_constant__ CUtensorMap tm_x, const __grid_constant__ CUtensorMap tm_g, const __grid_constant__ CUtensorMap tm_u,
             const __grid_constant__ CUtensorMap tm_g32, const __grid_constant__ CUtensorMap tm_u32,
             const __nv_bfloat16* __restrict__ x, const __nv_bfloat16* __restrict__ w_r, const __nv_bfloat16* __restrict__ w_i,
             const __nv_bfloat16* __restrict__ w_gate, const __nv_bfloat16* __restrict__ w_up,
             const __nv_bfloat16* __restrict__ w_down, const __nv_bfloat16* __restrict__ gate_w, __nv_bfloat16* __restrict__ out) {
  extern __shared__ __align__(1024) unsigned char smem[];
  const uint32_t sb = s2u(smem);
  const uint32_t bars = sb + OFF_BAR;
  const int tid = threadIdx.x, warp = tid >> 5, lane = tid & 31;
  const int bid = blockIdx.x, m = bid >> 3, n = (bid >> 1) & 3, kh = bid & 1, j = kh * 4 + n;

  if (tid == 0) {
    PROF(0, 0);
    for (int i = 0; i < NSLOT; i++) { mbar_init(bars + (B_FULL + i) * 8, 1); mbar_init(bars + (B_EMPTY + i) * 8, 8); }
    for (int i = 0; i < 14; i++) mbar_init(bars + (B_XFULL + i) * 8, 1);
    mbar_init(bars + B_XFREE * 8, 4); mbar_init(bars + (B_XFREE + 1) * 8, 4);
    for (int i = 0; i < 4; i++) mbar_init(bars + (B_PUB + i) * 8, 8);
    mbar_init(bars + B_PQFULL * 8, 1); mbar_init(bars + B_RECV * 8, 1); mbar_init(bars + B_RFREE * 8, 8);
    asm volatile("fence.mbarrier_init.release.cluster;" ::: "memory");
    mbar_expect(bars + B_RECV * 8, 64 * 112 * 4);
  }
  __syncthreads();
  asm volatile("barrier.cluster.arrive.relaxed.aligned;" ::: "memory");

  if (warp < 8) {
    asm volatile("setmaxnreg.inc.sync.aligned.u32 208;");
    const int wg = warp >> 2, w4 = warp & 3, g = lane >> 2, t = lane & 3;
    const int rh = wg ^ kh ^ 1;
    const int p = j & 1, r = (j >> 1) & 1, hh = j >> 2;
    for (int it = tid; it < 392; it += 256) {
      int kc = it / 28, sg = it - kc * 28;
      int k = 2 * (28 * hh + sg) + r;
      float c[8], s[8];
#pragma unroll
      for (int q = 0; q < 8; q++) {
        int d = 16 * kc + 8 * (q & 1) + 2 * (q >> 1) + p;
        cs448((d * k) % 448, c[q], s[q]);
        s[q] = -s[q];
        if (k == 0) s[q] = (float)(p ? ((d & 2) - 1) : (1 - (d & 2)));
      }
      uint32_t a = sb + 6 * SLOT + (kc * 56 + 2 * sg) * 16;
      sts128(a, pack_bf16(c[0], c[1]), pack_bf16(c[2], c[3]), pack_bf16(c[4], c[5]), pack_bf16(c[6], c[7]));
      sts128(a + 16, pack_bf16(s[0], s[1]), pack_bf16(s[2], s[3]), pack_bf16(s[4], s[5]), pack_bf16(s[6], s[7]));
    }
    fence_async_smem();
    bar_sync<1, 256>();
    if (wg == 1) bar_sync<2, 256>();

    uint32_t xa[28][4];
    const uint32_t hs = sb + OFF_HOWN + t * 1024 + (w4 * 16 + g) * 16;
    unsigned char* hg = g_H + (size_t)(m * 8 + j) * HALF_XR + t * 1024 + (w4 * 16 + g) * 16;
    int slot = 0, ph = 0;
    auto adv = [&]() { if (++slot == NSLOT) { slot = 0; ph ^= 1; } };
    int prev = -1;
    if (tid == 0 || tid == 128) PROF(wg, 1);
    {
      float acc[64];
      const uint32_t xrow = w4 * 16 + (lane & 7) + ((lane >> 3) & 1) * 8;
      const uint32_t xb = sb + OFF_XR + wg * HALF_XR + xrow * 128;
#pragma unroll
      for (int kb = 0; kb < 7; kb++) {
        mbar_wait(bars + (B_XFULL + wg * 7 + kb) * 8, 0);
#pragma unroll
        for (int kk = 0; kk < 4; kk++) {
          uint32_t a = xb + kb * 8192 + (((2 * kk + (lane >> 4)) ^ (lane & 7)) << 4);
          asm volatile("ldmatrix.sync.aligned.m8n8.x4.shared.b16 {%0,%1,%2,%3}, [%4];"
                       : "=r"(xa[kb * 4 + kk][0]), "=r"(xa[kb * 4 + kk][1]), "=r"(xa[kb * 4 + kk][2]), "=r"(xa[kb * 4 + kk][3]) : "r"(a) : "memory");
        }
        if (kb == 6) { __syncwarp(); if (lane == 0) mbar_arrive(bars + (B_XFREE + wg) * 8); }
        mbar_wait(bars + (B_FULL + slot) * 8, ph);
        if (kb == 0 && (tid == 0 || tid == 128)) PROF(wg, 2);
        wg_fence();
        uint64_t db = mkdesc(sb + slot * SLOT, 8192, 1024, 1);
#pragma unroll
        for (int kk = 0; kk < 4; kk++) wgmma_rs_128<1>(acc, xa[kb * 4 + kk], db + kk * 128, (kb | kk) != 0);
        wg_commit();
        if (kb == 2 && wg == 0) bar_arrive<2, 256>();
        if (kb > 0) { wg_wait<1>(); if (lane == 0) mbar_arrive(bars + (B_EMPTY + prev) * 8); }
        prev = slot; adv();
        if (kb == 5) adv();
      }
      wg_wait<0>(); keep(acc);
      if (lane == 0) mbar_arrive(bars + (B_EMPTY + prev) * 8);
      if (tid == 0 || tid == 128) PROF(wg, 3);
      mbar_wait(bars + B_XFREE * 8, 0);
      h_epilogue<8>(acc, hs + rh * 8192, hg + rh * 8192);
    }
    if (tid == 0 || tid == 128) PROF(wg, 4);
    {
      uint32_t ad[7][4];
      const uint32_t sel = p ? 0x7632 : 0x5410;
      const uint32_t sgn = r ? 0xBF80BF80u : 0x3F803F80u;
#pragma unroll
      for (int jj = 0; jj < 7; jj++) {
#pragma unroll
        for (int i = 0; i < 4; i++) {
          int ks = 2 * jj + (i >> 1), rr = i & 1;
          uint32_t lo = __byte_perm(xa[ks][rr], xa[ks][rr + 2], sel);
          uint32_t hi = __byte_perm(xa[ks + 14][rr], xa[ks + 14][rr + 2], sel);
          asm("fma.rn.bf16x2 %0, %1, %2, %3;" : "=r"(ad[jj][i]) : "r"(hi), "r"(sgn), "r"(lo));
        }
      }
      float acc[28];
      wg_fence();
      uint64_t db = mkdesc(sb + 6 * SLOT, 896, 128, 0);
#pragma unroll
      for (int jj = 0; jj < 7; jj++) wgmma_rs_56<0>(acc, ad[jj], db + jj * 112, jj != 0);
      wg_commit();
      wg_wait<0>(); keep(acc);
      if (lane == 0) mbar_arrive(bars + (B_EMPTY + 6) * 8);
      float2* xc = g_Xc + (size_t)(p * 112 + 2 * (28 * hh + t) + r) * S_ + m * 128 + rh * 64 + w4 * 16 + g;
#pragma unroll
      for (int i = 0; i < 7; i++) {
        xc[i * 8 * S_] = make_float2(acc[4 * i], acc[4 * i + 1]);
        xc[i * 8 * S_ + 8] = make_float2(acc[4 * i + 2], acc[4 * i + 3]);
      }
      __syncwarp();
      if (lane == 0) mbar_arrive(bars + (B_PUB + 0) * 8);
    }
    if (tid == 0 || tid == 128) PROF(wg, 5);
    {
      float acc[32];
#pragma unroll
      for (int it = 0; it < 4; it++) {
        mbar_wait(bars + (B_FULL + slot) * 8, ph);
        wg_fence();
        uint64_t db = mkdesc(sb + slot * SLOT, 8192, 512, 2);
#pragma unroll
        for (int kk = 0; kk < 8; kk++) if (it * 8 + kk < 28) wgmma_rs_64<1>(acc, xa[it * 8 + kk], db + kk * 64, (it | kk) != 0);
        wg_commit();
        if (it > 0) { wg_wait<1>(); if (lane == 0) mbar_arrive(bars + (B_EMPTY + prev) * 8); }
        prev = slot; adv();
      }
      wg_wait<0>(); keep(acc);
      if (lane == 0) mbar_arrive(bars + (B_EMPTY + prev) * 8);
      if (tid == 0 || tid == 128) PROF(wg, 6);
      h_epilogue<4>(acc, hs + 16384 + rh * 4096, hg + 16384 + rh * 4096);
      __syncwarp();
      if (lane == 0) mbar_arrive(bars + (B_PUB + 1) * 8);
    }
    if (tid == 0 || tid == 128) PROF(wg, 7);
#pragma unroll 1
    for (int u = 2; u < 4; u++) {
      float acc[64];
#pragma unroll
      for (int kb = 0; kb < 7; kb++) {
        mbar_wait(bars + (B_FULL + slot) * 8, ph);
        wg_fence();
        uint64_t db = mkdesc(sb + slot * SLOT, 8192, 1024, 1);
#pragma unroll
        for (int kk = 0; kk < 4; kk++) wgmma_rs_128<1>(acc, xa[kb * 4 + kk], db + kk * 128, (kb | kk) != 0);
        wg_commit();
        if (kb > 0) { wg_wait<1>(); if (lane == 0) mbar_arrive(bars + (B_EMPTY + prev) * 8); }
        prev = slot; adv();
      }
      wg_wait<0>(); keep(acc);
      if (lane == 0) mbar_arrive(bars + (B_EMPTY + prev) * 8);
      if (tid == 0 || tid == 128) PROF(wg, 4 + 2 * u);
      const int uo = u * 16384 - 8192 + rh * 8192;
      h_epilogue<8>(acc, hs + uo, hg + uo);
      __syncwarp();
      if (lane == 0) mbar_arrive(bars + (B_PUB + u) * 8);
      if (tid == 0 || tid == 128) PROF(wg, 5 + 2 * u);
    }
    fence_async_smem();
    if (wg) bar_sync<5, 128>(); else bar_sync<4, 128>();
    asm volatile("barrier.cluster.wait.aligned;" ::: "memory");

    float acc[56], spec[28];
    int prevA = -1; prev = -1;
#pragma unroll 1
    for (int i = 0; i < 16; i++) {
      if (i == G2_SPEC_AT) {
        if (tid == 0 || tid == 128) PROF(wg, 12);
        mbar_wait(bars + B_PQFULL * 8, 0);
        uint64_t da = mkdesc(sb + OFF_PQ + rh * 28672, 1024, 1024, 1);
#pragma unroll
        for (int hf = 0; hf < 2; hf++) {
          mbar_wait(bars + (B_FULL + slot) * 8, ph);
          wg_fence();
          uint64_t db = mkdesc(sb + slot * SLOT, 896, 128, 0);
#pragma unroll
          for (int kk = 0; kk < 7; kk++) wgmma_ss_56<1, 0>(spec, da + (hf * 7 + kk) * 128, db + kk * 112, (hf | kk) != 0);
          wg_commit();
          wg_wait<1>();
          if (lane == 0) { mbar_arrive(bars + (B_EMPTY + prev) * 8); if (prevA >= 0) mbar_arrive(bars + (B_EMPTY + prevA) * 8); }
          prev = slot; prevA = -1; adv();
        }
        if (tid == 0 || tid == 128) PROF(wg, 13);
      }
      const int blk = g2_block(i), src = blk >> 2, u = blk & 3;
      const int hsz = (u == 1) ? 4096 : 8192;
      uint32_t abase; int curA = -1;
      if (src == 0) abase = sb + OFF_HOWN + unit_k(u) * 256;
      else { mbar_wait(bars + (B_FULL + slot) * 8, ph); abase = sb + slot * SLOT; curA = slot; adv(); }
      mbar_wait(bars + (B_FULL + slot) * 8, ph);
      wg_fence();
      uint64_t da = mkdesc(abase + rh * hsz, 1024, 128, 0);
      uint64_t db = mkdesc(sb + slot * SLOT, 1792, 128, 0);
      wgmma_ss_112<0, 1>(acc, da, db, i != 0);
      wgmma_ss_112<0, 1>(acc, da + 128, db + 224, 1);
      if (u != 1) {
        wgmma_ss_112<0, 1>(acc, da + 256, db + 448, 1);
        wgmma_ss_112<0, 1>(acc, da + 384, db + 672, 1);
      }
      wg_commit();
      if (i > 0) {
        wg_wait<1>();
        if (lane == 0) {
          mbar_arrive(bars + (B_EMPTY + prev) * 8); if (prevA >= 0) mbar_arrive(bars + (B_EMPTY + prevA) * 8);
          if (i == G2_FREE_AFTER + 1) {
            asm volatile("{\n.reg .b32 ra;\nmapa.shared::cluster.u32 ra, %0, %1;\nmbarrier.arrive.release.cluster.shared::cluster.b64 _, [ra];\n}"
                         :: "r"(bars + B_RFREE * 8), "r"(kh ^ 1) : "memory");
          }
        }
      }
      prev = slot; prevA = curA; adv();
    }
    wg_wait<0>(); keep(acc); keep(spec);
    if (tid == 0 || tid == 128) PROF(wg, 14);

    {
      const float* gs = reinterpret_cast<const float*>(smem + OFF_G) + rh * 64 + w4 * 16 + g;
      const float g0 = gs[0], g1 = gs[8];
      const float o0 = bf16_round(1.0f - g0), o1 = bf16_round(1.0f - g1);
#pragma unroll
      for (int i = 0; i < 14; i++) {
        float s0 = g0 * spec[(i >> 1) * 4 + (i & 1)], s1 = g1 * spec[(i >> 1) * 4 + 2 + (i & 1)];
        acc[4 * i] = acc[4 * i] * o0 + (kh ? 0.f : s0);
        acc[4 * i + 1] = acc[4 * i + 1] * o0 + (kh ? s0 : 0.f);
        acc[4 * i + 2] = acc[4 * i + 2] * o1 + (kh ? 0.f : s1);
        acc[4 * i + 3] = acc[4 * i + 3] * o1 + (kh ? s1 : 0.f);
      }
    }
    const int t128 = tid & 127;
    if (wg == 0) {
      mbar_wait_cluster(bars + B_RFREE * 8, 0);
      uint32_t rdst, rbar;
      asm volatile("mapa.shared::cluster.u32 %0, %1, %2;" : "=r"(rdst) : "r"(sb + OFF_HOWN + t128 * 16), "r"(kh ^ 1));
      asm volatile("mapa.shared::cluster.u32 %0, %1, %2;" : "=r"(rbar) : "r"(bars + B_RECV * 8), "r"(kh ^ 1));
#pragma unroll
      for (int i = 0; i < 14; i++)
        asm volatile("st.async.weak.shared::cluster.mbarrier::complete_tx::bytes.v4.f32 [%0], {%1,%2,%3,%4}, [%5];"
                     :: "r"(rdst + i * 2048), "f"(acc[4 * i]), "f"(acc[4 * i + 1]), "f"(acc[4 * i + 2]), "f"(acc[4 * i + 3]), "r"(rbar) : "memory");
    } else {
      mbar_wait_cluster(bars + B_RECV * 8, 0);
      bar_sync<5, 128>();
      const uint32_t st = sb + OFF_PQ + rh * 28672 + w4 * 3840;
#pragma unroll
      for (int i = 0; i < 14; i++) {
        float4 o = lds128f(sb + OFF_HOWN + t128 * 16 + i * 2048);
        sts32(st + g * 240 + i * 16 + t * 4, pack_bf16(acc[4 * i] + o.x, acc[4 * i + 1] + o.y));
        sts32(st + (g + 8) * 240 + i * 16 + t * 4, pack_bf16(acc[4 * i + 2] + o.z, acc[4 * i + 3] + o.w));
      }
      __syncwarp();
      unsigned char* ob = reinterpret_cast<unsigned char*>(out) + (size_t)(m * 128 + rh * 64 + w4 * 16) * (D_ * 2) + n * 224;
#pragma unroll
      for (int i = 0; i < 7; i++) {
        int c = i * 32 + lane, rr = c / 14, cc = c - rr * 14;
        float4 v = lds128f(st + rr * 240 + cc * 16);
        *reinterpret_cast<float4*>(ob + rr * (D_ * 2) + cc * 16) = v;
      }
    }
    if (tid == 0 || tid == 128) PROF(wg, 15);
  } else if (warp < 12) {
    asm volatile("setmaxnreg.dec.sync.aligned.u32 72;");
    const int t = tid - 256;
    uint32_t epoch = 0;
    if (t == 0) epoch = ld_relaxed(&g_ep[bid * 2]);
    const bool has_fft = bid < 113;
    const int k = bid;
    if (t == 0) PROF(2, 0);
    {
      const int row = m * 128 + j * 16 + (t >> 3), l8 = t & 7;
      const uint4* xr = reinterpret_cast<const uint4*>(x + (size_t)row * D_);
      const uint4* gw = reinterpret_cast<const uint4*>(gate_w);
      float sum = 0.f;
#pragma unroll
      for (int i = 0; i < 7; i++) {
        uint4 a = __ldg(xr + i * 8 + l8), b = __ldg(gw + i * 8 + l8);
        uint32_t aa[4] = {a.x, a.y, a.z, a.w}, bb[4] = {b.x, b.y, b.z, b.w};
#pragma unroll
        for (int e = 0; e < 4; e++) {
          uint32_t pr; asm("mul.rn.bf16x2 %0, %1, %2;" : "=r"(pr) : "r"(aa[e]), "r"(bb[e]));
          sum += __uint_as_float(pr << 16) + __uint_as_float(pr & 0xffff0000u);
        }
      }
      sum += __shfl_xor_sync(0xffffffffu, sum, 1); sum += __shfl_xor_sync(0xffffffffu, sum, 2); sum += __shfl_xor_sync(0xffffffffu, sum, 4);
      if (l8 == 0) g_gate[row] = bf16_round(1.0f / (1.0f + __expf(-bf16_round(sum))));
    }
    {
      const uint4* src = reinterpret_cast<const uint4*>(w_down) + bid * 784;
#pragma unroll
      for (int i = 0; i < 7; i++) {
        int c = i * 128 + t;
        if (c < 784) {
          uint4 v = __ldg(src + c);
          int rr = c / 56, ch = c - rr * 56, row = bid * 14 + rr;
          int js = row / 224, col = row - js * 224;
          int grp = col >> 5;
          int kg = (js & 1) ? (grp == 0 ? 2 : (grp <= 2 ? grp - 1 : grp)) : (grp == 6 ? 2 : (grp <= 1 ? grp : grp + 1));
          int c32 = col & 31;
          int kpos = (js & 3) * 224 + kg * 32 + ((c32 >> 1) & 3) * 8 + (c32 >> 3) * 2 + (c32 & 1);
          int nn = ch / 14, cc = ch - nn * 14;
          *reinterpret_cast<uint4*>(g_Wd + (size_t)((js >> 2) * 4 + nn) * WD_IMG + (kpos >> 3) * 1792 + cc * 128 + (kpos & 7) * 16) = v;
        }
      }
    }
    if (t < 98) {
      int cid = m * 98 + t, kc = cid / 56, nn = cid - kc * 56;
      int d = 112 * n + 8 * (2 * (nn >> 3) + (nn & 1)) + (nn & 6) + kh;
      uint32_t pk[4];
#pragma unroll
      for (int e = 0; e < 4; e++) {
        int kk = 4 * kc + e; float c, s;
        cs448((d * kk) % 448, c, s); s = -s;
        if (kk == 0) s = (float)(kh ? ((d & 2) - 1) : (1 - (d & 2)));
        pk[e] = pack_bf16(c, s);
      }
      *reinterpret_cast<uint4*>(g_G + (size_t)j * G_IMG + cid * 16) = make_uint4(pk[0], pk[1], pk[2], pk[3]);
    }
    bar_sync<3, 128>();
    if (t == 0) { fence_gpu(); red_add(&g_cnt[4 * 32]); PROF(2, 1); }
    if (has_fft) {
      uint32_t wv[32];
      {
        const unsigned short* wr16 = reinterpret_cast<const unsigned short*>(w_r);
        const unsigned short* wi16 = reinterpret_cast<const unsigned short*>(w_i);
        const int ks0 = (t >> 4) + 8 * (t & 15);
#pragma unroll
        for (int q = 0; q < 16; q++) {
          int ks = ks0 + 128 * q, kb = (S_ - ks) & (S_ - 1);
          uint32_t a = __ldg(wr16 + ks * DF_ + k), b = __ldg(wi16 + ks * DF_ + k);
          uint32_t c = __ldg(wr16 + kb * DF_ + 224 - k), d = __ldg(wi16 + kb * DF_ + 224 - k);
          wv[q] = a | (b << 16); wv[16 + q] = c | ((d ^ 0x8000u) << 16);
        }
      }
      float2 wa, wb, t0, t1;
      sincospif(-(float)(2 * t) / 1024.0f, &wa.y, &wa.x);
      sincospif(-(float)(2 * t + 1) / 1024.0f, &wb.y, &wb.x);
      sincospif(-(float)((t >> 4) * (t & 15)) / 128.0f, &t0.y, &t0.x);
      sincospif(-(float)(((t >> 4) + 8) * (t & 15)) / 128.0f, &t1.y, &t1.x);
      mbar_wait(bars + (B_XFREE + 1) * 8, 0);
#pragma unroll
      for (int q = 0; q < 32; q++) sts32(sb + OFF_WS + q * 512 + t * 4, wv[q]);
      sts64f(sb + OFF_TW2 + t * 8, t0.x, t0.y); sts64f(sb + OFF_TW2 + 1024 + t * 8, t1.x, t1.y);
      const int sl = (k == 112) ? 0 : k;
      if (t == 0) { PROF(2, 2); wait_ge(&g_cnt[((sl & 1) + 2 * ((sl >> 1) / 28)) * 32], (epoch + 1) * 32); PROF(2, 3); }
      bar_sync<3, 128>();
      const float4* xe = reinterpret_cast<const float4*>(g_Xc + (size_t)sl * S_) + t;
      const float4* xo = reinterpret_cast<const float4*>(g_Xc + (size_t)(112 + sl) * S_) + t;
      const float sc = ((k == 0 || k == 112) ? 1.0f : 2.0f) / (float)(S_ * D_);
      uint32_t* pq = reinterpret_cast<uint32_t*>(g_PQ);
#pragma unroll 1
      for (int col = 0; col < 2; col++) {
        float2 v[16];
        const float sg = col ? -1.0f : 1.0f;
#pragma unroll
        for (int jj = 0; jj < 8; jj++) {
          float4 e = __ldcg(xe + jj * 128), o = __ldcg(xo + jj * 128);
          if (k == 0) { e.y = 0.f; e.w = 0.f; o.y = 0.f; o.w = 0.f; }
          if (k == 112) { e.x = e.y; e.y = 0.f; e.z = e.w; e.w = 0.f; o.x = 0.f; o.z = 0.f; }
          v[2 * jj] = make_float2(e.x + sg * o.x, e.y + sg * o.y); v[2 * jj + 1] = make_float2(e.z + sg * o.z, e.w + sg * o.w);
        }
        column(v, sb, t, wa, wb, sb + OFF_WS + col * 8192 + t * 4);
        if (col == 0) {
#pragma unroll
          for (int jj = 0; jj < 8; jj++) sts128f(sb + OFF_STASH + jj * 2048 + t * 16, v[2 * jj].x * sc, v[2 * jj].y * sc, v[2 * jj + 1].x * sc, v[2 * jj + 1].y * sc);
          if (t == 0) PROF(2, 4);
        } else {
          const int pre = (k == 112) ? 1 : 2 * k, pim = (k == 112) ? 1 : 2 * k + 1;
          const int wbase = (t >> 5) * 7168;
          const int ore = wbase + pre * 32 + ((((lane >> 2) ^ pre) & 7) << 2) + (lane & 3);
          const int oim = wbase + pim * 32 + ((((lane >> 2) ^ pim) & 7) << 2) + (lane & 3);
#pragma unroll
          for (int jj = 0; jj < 8; jj++) {
            float4 a = lds128f(sb + OFF_STASH + jj * 2048 + t * 16);
            uint32_t* pb = pq + jj * 28672;
            uint32_t p_re = pack_bf16(a.y + sc * v[2 * jj].y, a.w + sc * v[2 * jj + 1].y), p_im = pack_bf16(a.x + sc * v[2 * jj].x, a.z + sc * v[2 * jj + 1].x);
            uint32_t q_re = pack_bf16(a.y - sc * v[2 * jj].y, a.w - sc * v[2 * jj + 1].y), q_im = pack_bf16(a.x - sc * v[2 * jj].x, a.z - sc * v[2 * jj + 1].x);
            pb[ore] = p_re;
            if (k != 112) pb[16 * 14336 + ore] = q_re;
            if (k != 0) pb[16 * 14336 + oim] = q_im;
            if (k != 0 && k != 112) pb[oim] = p_im;
          }
        }
      }
      fence_async_smem();
    } else {
      mbar_wait(bars + (B_XFREE + 1) * 8, 0);
    }
    bar_sync<3, 128>();
    if (t == 0) {
      PROF(2, 5);
      fence_gpu(); red_add(&g_cnt[5 * 32]);
      wait_ge(&g_cnt[5 * 32], (epoch + 1) * 128);
      PROF(2, 6);
      fence_async_all();
      mbar_expect(bars + B_PQFULL * 8, HALF_XR + 512);
      const unsigned char* src = g_PQ + (size_t)(kh * 16 + m) * HALF_XR;
      bulk_g2s(sb + OFF_PQ, src, 28672, bars + B_PQFULL * 8);
      bulk_g2s(sb + OFF_PQ + 28672, src + 28672, 28672, bars + B_PQFULL * 8);
      bulk_g2s(sb + OFF_G, g_gate + m * 128, 512, bars + B_PQFULL * 8);
      g_ep[bid * 2] = epoch + 1;
    }
    __syncwarp();
    asm volatile("barrier.cluster.wait.aligned;" ::: "memory");
  } else {
    asm volatile("setmaxnreg.dec.sync.aligned.u32 24;");
    if (warp == 12) {
      if (lane == 0) {
        const uint32_t epoch = ld_relaxed(&g_ep[bid * 2 + 1]);
        int slot = 0, ph = 1;
        auto adv = [&]() { if (++slot == NSLOT) { slot = 0; ph ^= 1; } };
#pragma unroll 1
        for (int u = 0; u < 4; u++) {
          const int c0 = 224 * j + unit_col(j, u);
          const int nit = (u == 1) ? 4 : 7;
          const CUtensorMap* mg = (u == 1) ? &tm_g32 : &tm_g;
          const CUtensorMap* mu = (u == 1) ? &tm_u32 : &tm_u;
          const int rstep = (u == 1) ? 128 : 64;
#pragma unroll 1
          for (int it = 0; it < nit; it++) {
            if (u == 0 && it == 6) { mbar_arrive(bars + (B_FULL + 6) * 8); adv(); }
            mbar_wait(bars + (B_EMPTY + slot) * 8, ph);
            const uint32_t fb = bars + (B_FULL + slot) * 8;
            mbar_expect(fb, SLOT);
            tma2d(sb + slot * SLOT, mg, c0, it * rstep, fb);
            tma2d(sb + slot * SLOT + 8192, mu, c0, it * rstep, fb);
            adv();
          }
        }
        PROF(3, 0);
        wait_ge(&g_cnt[4 * 32], (epoch + 1) * 128);
        fence_async_all();
        PROF(3, 1);
#pragma unroll 1
        for (int i = 0; i < 16; i++) {
          if (i == G2_SPEC_AT) {
#pragma unroll 1
            for (int hf = 0; hf < 2; hf++) {
              mbar_wait(bars + (B_EMPTY + slot) * 8, ph);
              const uint32_t fb = bars + (B_FULL + slot) * 8;
              mbar_expect(fb, G_IMG / 2);
              bulk_g2s(sb + slot * SLOT, g_G + (size_t)j * G_IMG + hf * (G_IMG / 2), G_IMG / 2, fb);
              adv();
            }
          }
          const int blk = g2_block(i), src = blk >> 2, u = blk & 3;
          const int ns = (n + src) & 3;
          const int kw = (u == 1) ? 32 : 64;
          if (src != 0) {
            wait_ge(&g_hflag[(m * 8 + ns * 2 + kh) * 4 + u], epoch + 1);
            fence_async_all();
            mbar_wait(bars + (B_EMPTY + slot) * 8, ph);
            const uint32_t fb = bars + (B_FULL + slot) * 8;
            mbar_expect(fb, kw * 256);
            bulk_g2s(sb + slot * SLOT, g_H + (size_t)(m * 8 + kh * 4 + ns) * HALF_XR + unit_k(u) * 256, kw * 256, fb);
            adv();
          }
          mbar_wait(bars + (B_EMPTY + slot) * 8, ph);
          const uint32_t fb = bars + (B_FULL + slot) * 8;
          mbar_expect(fb, kw * 224);
          bulk_g2s(sb + slot * SLOT, g_Wd + (size_t)j * WD_IMG + (ns * 224 + unit_k(u)) * 224, kw * 224, fb);
          adv();
        }
        PROF(3, 2);
        g_ep[bid * 2 + 1] = epoch + 1;
      }
    } else if (warp == 13) {
      if (lane == 0) {
#pragma unroll 1
        for (int i = 0; i < 14; i++) {
          int wgx, kb;
          if (i < 3) { wgx = 0; kb = i; } else if (i < 11) { wgx = (i & 1); kb = (i & 1) ? (i - 3) >> 1 : (i + 2) >> 1; } else { wgx = 1; kb = i - 7; }
          const uint32_t fb = bars + (B_XFULL + wgx * 7 + kb) * 8;
          mbar_expect(fb, 8192);
          tma2d(sb + OFF_XR + wgx * HALF_XR + kb * 8192, &tm_x, kb * 64, m * 128 + (wgx ^ kh ^ 1) * 64, fb);
        }
        prefetch_l2(reinterpret_cast<const unsigned char*>(w_gate) + bid * 12544, 12544);
        prefetch_l2(reinterpret_cast<const unsigned char*>(w_up) + bid * 12544, 12544);
        const int p = j & 1, r = (j >> 1) & 1, hh = j >> 2; (void)p;
#pragma unroll 1
        for (int u = 0; u < 4; u++) {
          mbar_wait(bars + (B_PUB + u) * 8, 0);
          fence_gpu();
          if (u == 0) red_add(&g_cnt[(r + 2 * hh) * 32]);
          red_add(&g_hflag[bid * 4 + u]);
          PROF(3, 4 + u);
        }
      }
    }
    __syncwarp();
    asm volatile("barrier.cluster.wait.aligned;" ::: "memory");
  }
}

typedef CUresult (*EncodeFn)(CUtensorMap*, CUtensorMapDataType, cuuint32_t, void*, const cuuint64_t*, const cuuint64_t*, const cuuint32_t*,
                             const cuuint32_t*, CUtensorMapInterleave, CUtensorMapSwizzle, CUtensorMapL2promotion, CUtensorMapFloatOOBfill);

void make_map(EncodeFn enc, CUtensorMap* tm, const void* base, int cols, int rows, int bc, int br, CUtensorMapSwizzle sw) {
  cuuint64_t gd[2] = {(cuuint64_t)cols, (cuuint64_t)rows};
  cuuint64_t gs[1] = {(cuuint64_t)cols * 2};
  cuuint32_t bd[2] = {(cuuint32_t)bc, (cuuint32_t)br};
  cuuint32_t es[2] = {1, 1};
  enc(tm, CU_TENSOR_MAP_DATA_TYPE_BFLOAT16, 2, const_cast<void*>(base), gd, gs, bd, es, CU_TENSOR_MAP_INTERLEAVE_NONE, sw,
      CU_TENSOR_MAP_L2_PROMOTION_L2_128B, CU_TENSOR_MAP_FLOAT_OOB_FILL_NONE);
}

}

extern "C" void kernel_launch(void* const* d_in, const int* in_sizes, int n_in, void* d_out, int out_size) {
  (void)in_sizes; (void)n_in; (void)out_size;
  const __nv_bfloat16* x = (const __nv_bfloat16*)d_in[0];
  const __nv_bfloat16* w_r = (const __nv_bfloat16*)d_in[1];
  const __nv_bfloat16* w_i = (const __nv_bfloat16*)d_in[2];
  const __nv_bfloat16* w_gate = (const __nv_bfloat16*)d_in[4];
  const __nv_bfloat16* w_up = (const __nv_bfloat16*)d_in[5];
  const __nv_bfloat16* w_down = (const __nv_bfloat16*)d_in[6];
  const __nv_bfloat16* gate_w = (const __nv_bfloat16*)d_in[7];
  static EncodeFn enc = nullptr;
  static bool ok = false;
  if (!enc) {
    cudaDriverEntryPointQueryResult qr;
    cudaGetDriverEntryPoint("cuTensorMapEncodeTiled", (void**)&enc, cudaEnableDefault, &qr);
    cudaFuncSetAttribute(fused_kernel, cudaFuncAttributeMaxDynamicSharedMemorySize, SMEM_BYTES);
    cudaFuncAttributes fa;
    cudaFuncGetAttributes(&fa, fused_kernel);
    ok = (fa.numRegs == 128);
  }
  if (!ok) return;
  CUtensorMap tx, tg, tu, tg32, tu32;
  make_map(enc, &tx, x, D_, S_, 64, 64, CU_TENSOR_MAP_SWIZZLE_128B);
  make_map(enc, &tg, w_gate, F_, D_, 64, 64, CU_TENSOR_MAP_SWIZZLE_128B);
  make_map(enc, &tu, w_up, F_, D_, 64, 64, CU_TENSOR_MAP_SWIZZLE_128B);
  make_map(enc, &tg32, w_gate, F_, D_, 32, 128, CU_TENSOR_MAP_SWIZZLE_64B);
  make_map(enc, &tu32, w_up, F_, D_, 32, 128, CU_TENSOR_MAP_SWIZZLE_64B);
  fused_kernel<<<128, NTHREADS, SMEM_BYTES>>>(tx, tg, tu, tg32, tu32, x, w_r, w_i, w_gate, w_up, w_down, gate_w, (__nv_bfloat16*)d_out);
}
```

```cpp
#include <cuda_runtime.h>
#include <cuda_bf16.h>
#include <cuda.h>
#include <stdint.h>

namespace {

constexpr int S_ = 2048, D_ = 448, F_ = 1792, DF_ = 225;
constexpr int NTHREADS = 512;
constexpr int SLOT = 16384, NSLOT = 7;
constexpr int OFF_XR = NSLOT * SLOT;
constexpr int HALF_XR = 57344;
constexpr int OFF_HOWN = OFF_XR;
constexpr int OFF_PQ = OFF_XR + HALF_XR;
constexpr int OFF_EXCH = OFF_PQ;
constexpr int OFF_STASH = OFF_EXCH + 18432;
constexpr int OFF_WS = OFF_STASH + 16384;
constexpr int OFF_TW2 = OFF_WS + 16384;
constexpr int OFF_MISC = OFF_XR + 2 * HALF_XR;
constexpr int OFF_G = OFF_MISC;
constexpr int OFF_BAR = OFF_MISC + 512;
constexpr int SMEM_BYTES = OFF_BAR + 512;
constexpr int B_FULL = 0, B_EMPTY = 7, B_XFULL = 14  ;
constexpr int B_XFREE = 16  , B_PUB = 18  , B_RFREE = 23;
constexpr int B_PQFULL = 24, B_RECV = 25, B_WFULL = 26, B_XCFULL = 27, B_PREP = 28, B_HRDY = 29  , B_END = 41;

constexpr int WD_IMG = 896 * 112 * 2;
constexpr int G_IMG = 224 * 56 * 2;

__device__ __align__(1024) uint32_t g_Xc[112 * 2 * S_];
__device__ __align__(1024) unsigned char g_H[16 * 8 * HALF_XR];
__device__ __align__(1024) unsigned char g_PQ[32 * HALF_XR];
__device__ __align__(1024) unsigned char g_Wd[8 * WD_IMG];
__device__ __align__(1024) unsigned char g_G[8 * G_IMG];
__device__ __align__(1024) uint32_t g_Wt[113 * 2 * S_];
__device__ __align__(1024) float g_gate[S_];
__device__ __align__(128) unsigned int g_hflag[128 * 4];
__device__ __align__(128) unsigned int g_ep[128 * 2];
__device__ __align__(128) unsigned int g_cnt[8 * 32];

#define PROF(role, idx) do {} while (0)
#define PROFG(role, idx) do {} while (0)

__device__ __forceinline__ uint32_t s2u(const void* p) { return (uint32_t)__cvta_generic_to_shared(p); }
__device__ __forceinline__ void mbar_init(uint32_t b, int c) { asm volatile("mbarrier.init.shared::cta.b64 [%0], %1;" :: "r"(b), "r"(c) : "memory"); }
__device__ __forceinline__ void mbar_expect(uint32_t b, int bytes) { asm volatile("mbarrier.arrive.expect_tx.shared::cta.b64 _, [%0], %1;" :: "r"(b), "r"(bytes) : "memory"); }
__device__ __forceinline__ void mbar_arrive(uint32_t b) { asm volatile("mbarrier.arrive.shared::cta.b64 _, [%0];" :: "r"(b) : "memory"); }
__device__ __forceinline__ bool mbar_try(uint32_t b, int ph) {
  uint32_t ok;
  asm volatile("{\n.reg .pred p;\nmbarrier.try_wait.parity.shared::cta.b64 p, [%1], %2;\nselp.u32 %0, 1, 0, p;\n}" : "=r"(ok) : "r"(b), "r"(ph) : "memory");
  return ok;
}
__device__ __forceinline__ void mbar_wait(uint32_t b, int ph) {
  if (mbar_try(b, ph)) return;
#pragma unroll 1
  for (int i = 0; i < (1 << 22); i++) if (mbar_try(b, ph)) return;
  __trap();
}
__device__ __forceinline__ void mbar_wait_cluster(uint32_t b, int ph) {
#pragma unroll 1
  for (int i = 0; i < (1 << 22); i++) {
    uint32_t ok;
    asm volatile("{\n.reg .pred p;\nmbarrier.try_wait.parity.acquire.cluster.shared::cta.b64 p, [%1], %2;\nselp.u32 %0, 1, 0, p;\n}" : "=r"(ok) : "r"(b), "r"(ph) : "memory");
    if (ok) return;
  }
  __trap();
}
__device__ __forceinline__ uint32_t ld_acquire(const unsigned int* p) { uint32_t v; asm volatile("ld.acquire.gpu.global.u32 %0, [%1];" : "=r"(v) : "l"(p) : "memory"); return v; }
__device__ __forceinline__ uint32_t ld_relaxed(const unsigned int* p) { uint32_t v; asm volatile("ld.relaxed.gpu.global.u32 %0, [%1];" : "=r"(v) : "l"(p) : "memory"); return v; }
__device__ __forceinline__ void wait_ge(const unsigned int* p, uint32_t target) {
#pragma unroll 1
  for (int i = 0; i < (1 << 22); i++) { if ((int)(ld_acquire(p) - target) >= 0) return; }
  __trap();
}
__device__ __forceinline__ void fence_gpu() { asm volatile("fence.acq_rel.gpu;" ::: "memory"); }
__device__ __forceinline__ void red_add(unsigned int* p) { asm volatile("red.relaxed.gpu.global.add.u32 [%0], 1;" :: "l"(p) : "memory"); }
__device__ __forceinline__ void fence_async_smem() { asm volatile("fence.proxy.async.shared::cta;" ::: "memory"); }
__device__ __forceinline__ void fence_async_all() { asm volatile("fence.proxy.async;" ::: "memory"); }
template <int ID, int N> __device__ __forceinline__ void bar_sync() { asm volatile("bar.sync %0, %1;" :: "n"(ID), "n"(N) : "memory"); }
template <int ID, int N> __device__ __forceinline__ void bar_arrive() { asm volatile("bar.arrive %0, %1;" :: "n"(ID), "n"(N) : "memory"); }
__device__ __forceinline__ void tma2d(uint32_t dst, const CUtensorMap* tm, int c0, int c1, uint32_t bar) {
  asm volatile("cp.async.bulk.tensor.2d.shared::cluster.global.mbarrier::complete_tx::bytes [%0], [%1, {%3, %4}], [%2];"
               :: "r"(dst), "l"(tm), "r"(bar), "r"(c0), "r"(c1) : "memory");
}
__device__ __forceinline__ void tma3d(uint32_t dst, const CUtensorMap* tm, int c0, int c1, int c2, uint32_t bar) {
  asm volatile("cp.async.bulk.tensor.3d.shared::cluster.global.mbarrier::complete_tx::bytes [%0], [%1, {%3, %4, %5}], [%2];"
               :: "r"(dst), "l"(tm), "r"(bar), "r"(c0), "r"(c1), "r"(c2) : "memory");
}
__device__ __forceinline__ void bulk_g2s(uint32_t dst, const void* src, int bytes, uint32_t bar) {
  asm volatile("cp.async.bulk.shared::cluster.global.mbarrier::complete_tx::bytes [%0], [%1], %2, [%3];"
               :: "r"(dst), "l"(src), "r"(bytes), "r"(bar) : "memory");
}
__device__ __forceinline__ void prefetch_l2(const void* src, int bytes) {
  asm volatile("cp.async.bulk.prefetch.L2.global [%0], %1;" :: "l"(src), "r"(bytes) : "memory");
}
__device__ __forceinline__ uint64_t mkdesc(uint32_t addr, uint32_t lbo, uint32_t sbo, uint32_t mode) {
  return (uint64_t)((addr & 0x3FFFF) >> 4) | ((uint64_t)(lbo >> 4) << 16) | ((uint64_t)(sbo >> 4) << 32) | ((uint64_t)mode << 62);
}
__device__ __forceinline__ void wg_fence() { asm volatile("wgmma.fence.sync.aligned;" ::: "memory"); }
__device__ __forceinline__ void wg_commit() { asm volatile("wgmma.commit_group.sync.aligned;" ::: "memory"); }
template <int N> __device__ __forceinline__ void wg_wait() { asm volatile("wgmma.wait_group.sync.aligned %0;" :: "n"(N) : "memory"); }
template <int N> __device__ __forceinline__ void keep(float (&d)[N]) {
#pragma unroll
  for (int i = 0; i < N; i++) asm volatile("" : "+f"(d[i]) :: "memory");
}
__device__ __forceinline__ uint32_t pack_bf16(float lo, float hi) { uint32_t r; asm("cvt.rn.bf16x2.f32 %0, %1, %2;" : "=r"(r) : "f"(hi), "f"(lo)); return r; }
__device__ __forceinline__ float bf16_round(float v) { return __bfloat162float(__float2bfloat16_rn(v)); }
__device__ __forceinline__ void sts128(uint32_t a, uint32_t x, uint32_t y, uint32_t z, uint32_t w) { asm volatile("st.shared.v4.b32 [%0], {%1,%2,%3,%4};" :: "r"(a), "r"(x), "r"(y), "r"(z), "r"(w) : "memory"); }
__device__ __forceinline__ void sts128f(uint32_t a, float x, float y, float z, float w) { asm volatile("st.shared.v4.f32 [%0], {%1,%2,%3,%4};" :: "r"(a), "f"(x), "f"(y), "f"(z), "f"(w) : "memory"); }
__device__ __forceinline__ void sts64f(uint32_t a, float x, float y) { asm volatile("st.shared.v2.f32 [%0], {%1,%2};" :: "r"(a), "f"(x), "f"(y) : "memory"); }
__device__ __forceinline__ void sts32(uint32_t a, uint32_t x) { asm volatile("st.shared.b32 [%0], %1;" :: "r"(a), "r"(x) : "memory"); }
__device__ __forceinline__ float4 lds128f(uint32_t a) { float4 v; asm volatile("ld.shared.v4.f32 {%0,%1,%2,%3}, [%4];" : "=f"(v.x), "=f"(v.y), "=f"(v.z), "=f"(v.w) : "r"(a) : "memory"); return v; }
__device__ __forceinline__ float2 lds64f(uint32_t a) { float2 v; asm volatile("ld.shared.v2.f32 {%0,%1}, [%2];" : "=f"(v.x), "=f"(v.y) : "r"(a) : "memory"); return v; }
__device__ __forceinline__ uint32_t lds32(uint32_t a) { uint32_t v; asm volatile("ld.shared.b32 %0, [%1];" : "=r"(v) : "r"(a) : "memory"); return v; }

__device__ __forceinline__ uint2 lds64(uint32_t a) { uint2 v; asm volatile("ld.shared.v2.b32 {%0,%1}, [%2];" : "=r"(v.x), "=r"(v.y) : "r"(a) : "memory"); return v; }
__device__ __forceinline__ float bf_lo(uint32_t w) { return __uint_as_float(w << 16); }
__device__ __forceinline__ float bf_hi(uint32_t w) { return __uint_as_float(w & 0xffff0000u); }
__device__ __forceinline__ uint32_t opaque(uint32_t v) { asm volatile("" : "+r"(v)); return v; }
template <int TB> __device__ __forceinline__ void wgmma_rs_128(float (&d)[64], const uint32_t (&a)[4], uint64_t db, int sc) {
  asm volatile("{\n.reg .pred p;\nsetp.ne.b32 p, %69, 0;\n"
    "wgmma.mma_async.sync.aligned.m64n128k16.f32.bf16.bf16 {%0, %1, %2, %3, %4, %5, %6, %7, %8, %9, %10, %11, %12, %13, %14, %15, %16, %17, %18, %19, %20, %21, %22, %23, %24, %25, %26, %27, %28, %29, %30, %31, %32, %33, %34, %35, %36, %37, %38, %39, %40, %41, %42, %43, %44, %45, %46, %47, %48, %49, %50, %51, %52, %53, %54, %55, %56, %57, %58, %59, %60, %61, %62, %63}, {%64, %65, %66, %67}, %68, p, 1, 1, %70;\n}\n"
    : "+f"(d[0]), "+f"(d[1]), "+f"(d[2]), "+f"(d[3]), "+f"(d[4]), "+f"(d[5]), "+f"(d[6]), "+f"(d[7]), "+f"(d[8]), "+f"(d[9]), "+f"(d[10]), "+f"(d[11]), "+f"(d[12]), "+f"(d[13]), "+f"(d[14]), "+f"(d[15]), "+f"(d[16]), "+f"(d[17]), "+f"(d[18]), "+f"(d[19]), "+f"(d[20]), "+f"(d[21]), "+f"(d[22]), "+f"(d[23]), "+f"(d[24]), "+f"(d[25]), "+f"(d[26]), "+f"(d[27]), "+f"(d[28]), "+f"(d[29]), "+f"(d[30]), "+f"(d[31]), "+f"(d[32]), "+f"(d[33]), "+f"(d[34]), "+f"(d[35]), "+f"(d[36]), "+f"(d[37]), "+f"(d[38]), "+f"(d[39]), "+f"(d[40]), "+f"(d[41]), "+f"(d[42]), "+f"(d[43]), "+f"(d[44]), "+f"(d[45]), "+f"(d[46]), "+f"(d[47]), "+f"(d[48]), "+f"(d[49]), "+f"(d[50]), "+f"(d[51]), "+f"(d[52]), "+f"(d[53]), "+f"(d[54]), "+f"(d[55]), "+f"(d[56]), "+f"(d[57]), "+f"(d[58]), "+f"(d[59]), "+f"(d[60]), "+f"(d[61]), "+f"(d[62]), "+f"(d[63])
    : "r"(a[0]), "r"(a[1]), "r"(a[2]), "r"(a[3]), "l"(db), "r"(sc), "n"(TB));
}
template <int TB> __device__ __forceinline__ void wgmma_rs_64(float (&d)[32], const uint32_t (&a)[4], uint64_t db, int sc) {
  asm volatile("{\n.reg .pred p;\nsetp.ne.b32 p, %37, 0;\n"
    "wgmma.mma_async.sync.aligned.m64n64k16.f32.bf16.bf16 {%0, %1, %2, %3, %4, %5, %6, %7, %8, %9, %10, %11, %12, %13, %14, %15, %16, %17, %18, %19, %20, %21, %22, %23, %24, %25, %26, %27, %28, %29, %30, %31}, {%32, %33, %34, %35}, %36, p, 1, 1, %38;\n}\n"
    : "+f"(d[0]), "+f"(d[1]), "+f"(d[2]), "+f"(d[3]), "+f"(d[4]), "+f"(d[5]), "+f"(d[6]), "+f"(d[7]), "+f"(d[8]), "+f"(d[9]), "+f"(d[10]), "+f"(d[11]), "+f"(d[12]), "+f"(d[13]), "+f"(d[14]), "+f"(d[15]), "+f"(d[16]), "+f"(d[17]), "+f"(d[18]), "+f"(d[19]), "+f"(d[20]), "+f"(d[21]), "+f"(d[22]), "+f"(d[23]), "+f"(d[24]), "+f"(d[25]), "+f"(d[26]), "+f"(d[27]), "+f"(d[28]), "+f"(d[29]), "+f"(d[30]), "+f"(d[31])
    : "r"(a[0]), "r"(a[1]), "r"(a[2]), "r"(a[3]), "l"(db), "r"(sc), "n"(TB));
}
template <int TB> __device__ __forceinline__ void wgmma_rs_56(float (&d)[28], const uint32_t (&a)[4], uint64_t db, int sc) {
  asm volatile("{\n.reg .pred p;\nsetp.ne.b32 p, %33, 0;\n"
    "wgmma.mma_async.sync.aligned.m64n56k16.f32.bf16.bf16 {%0, %1, %2, %3, %4, %5, %6, %7, %8, %9, %10, %11, %12, %13, %14, %15, %16, %17, %18, %19, %20, %21, %22, %23, %24, %25, %26, %27}, {%28, %29, %30, %31}, %32, p, 1, 1, %34;\n}\n"
    : "+f"(d[0]), "+f"(d[1]), "+f"(d[2]), "+f"(d[3]), "+f"(d[4]), "+f"(d[5]), "+f"(d[6]), "+f"(d[7]), "+f"(d[8]), "+f"(d[9]), "+f"(d[10]), "+f"(d[11]), "+f"(d[12]), "+f"(d[13]), "+f"(d[14]), "+f"(d[15]), "+f"(d[16]), "+f"(d[17]), "+f"(d[18]), "+f"(d[19]), "+f"(d[20]), "+f"(d[21]), "+f"(d[22]), "+f"(d[23]), "+f"(d[24]), "+f"(d[25]), "+f"(d[26]), "+f"(d[27])
    : "r"(a[0]), "r"(a[1]), "r"(a[2]), "r"(a[3]), "l"(db), "r"(sc), "n"(TB));
}
template <int TA, int TB> __device__ __forceinline__ void wgmma_ss_112(float (&d)[56], uint64_t da, uint64_t db, int sc) {
  asm volatile("{\n.reg .pred p;\nsetp.ne.b32 p, %58, 0;\n"
    "wgmma.mma_async.sync.aligned.m64n112k16.f32.bf16.bf16 {%0, %1, %2, %3, %4, %5, %6, %7, %8, %9, %10, %11, %12, %13, %14, %15, %16, %17, %18, %19, %20, %21, %22, %23, %24, %25, %26, %27, %28, %29, %30, %31, %32, %33, %34, %35, %36, %37, %38, %39, %40, %41, %42, %43, %44, %45, %46, %47, %48, %49, %50, %51, %52, %53, %54, %55}, %56, %57, p, 1, 1, %59, %60;\n}\n"
    : "+f"(d[0]), "+f"(d[1]), "+f"(d[2]), "+f"(d[3]), "+f"(d[4]), "+f"(d[5]), "+f"(d[6]), "+f"(d[7]), "+f"(d[8]), "+f"(d[9]), "+f"(d[10]), "+f"(d[11]), "+f"(d[12]), "+f"(d[13]), "+f"(d[14]), "+f"(d[15]), "+f"(d[16]), "+f"(d[17]), "+f"(d[18]), "+f"(d[19]), "+f"(d[20]), "+f"(d[21]), "+f"(d[22]), "+f"(d[23]), "+f"(d[24]), "+f"(d[25]), "+f"(d[26]), "+f"(d[27]), "+f"(d[28]), "+f"(d[29]), "+f"(d[30]), "+f"(d[31]), "+f"(d[32]), "+f"(d[33]), "+f"(d[34]), "+f"(d[35]), "+f"(d[36]), "+f"(d[37]), "+f"(d[38]), "+f"(d[39]), "+f"(d[40]), "+f"(d[41]), "+f"(d[42]), "+f"(d[43]), "+f"(d[44]), "+f"(d[45]), "+f"(d[46]), "+f"(d[47]), "+f"(d[48]), "+f"(d[49]), "+f"(d[50]), "+f"(d[51]), "+f"(d[52]), "+f"(d[53]), "+f"(d[54]), "+f"(d[55])
    : "l"(da), "l"(db), "r"(sc), "n"(TA), "n"(TB));
}
template <int TA, int TB> __device__ __forceinline__ void wgmma_ss_56(float (&d)[28], uint64_t da, uint64_t db, int sc) {
  asm volatile("{\n.reg .pred p;\nsetp.ne.b32 p, %30, 0;\n"
    "wgmma.mma_async.sync.aligned.m64n56k16.f32.bf16.bf16 {%0, %1, %2, %3, %4, %5, %6, %7, %8, %9, %10, %11, %12, %13, %14, %15, %16, %17, %18, %19, %20, %21, %22, %23, %24, %25, %26, %27}, %28, %29, p, 1, 1, %31, %32;\n}\n"
    : "+f"(d[0]), "+f"(d[1]), "+f"(d[2]), "+f"(d[3]), "+f"(d[4]), "+f"(d[5]), "+f"(d[6]), "+f"(d[7]), "+f"(d[8]), "+f"(d[9]), "+f"(d[10]), "+f"(d[11]), "+f"(d[12]), "+f"(d[13]), "+f"(d[14]), "+f"(d[15]), "+f"(d[16]), "+f"(d[17]), "+f"(d[18]), "+f"(d[19]), "+f"(d[20]), "+f"(d[21]), "+f"(d[22]), "+f"(d[23]), "+f"(d[24]), "+f"(d[25]), "+f"(d[26]), "+f"(d[27])
    : "l"(da), "l"(db), "r"(sc), "n"(TA), "n"(TB));
}

__device__ __forceinline__ void cs448(int idx, float& c, float& s) {
  if (idx > 224) idx -= 448;
  float a = (float)idx * (6.283185307179586f / 448.0f);
  c = __cosf(a); s = __sinf(a);
}

__device__ __forceinline__ float2 cmul(float2 a, float2 b) { return make_float2(a.x * b.x - a.y * b.y, a.x * b.y + a.y * b.x); }
__device__ __forceinline__ void fft4(float2& a0, float2& a1, float2& a2, float2& a3) {
  float2 t0 = make_float2(a0.x + a2.x, a0.y + a2.y), t1 = make_float2(a0.x - a2.x, a0.y - a2.y);
  float2 t2 = make_float2(a1.x + a3.x, a1.y + a3.y), t3 = make_float2(a1.x - a3.x, a1.y - a3.y);
  a0 = make_float2(t0.x + t2.x, t0.y + t2.y); a2 = make_float2(t0.x - t2.x, t0.y - t2.y);
  a1 = make_float2(t1.x + t3.y, t1.y - t3.x); a3 = make_float2(t1.x - t3.y, t1.y + t3.x);
}
__device__ __forceinline__ float2 mul_w8_1(float2 a) { const float r = 0.70710678118654752f; return make_float2((a.x + a.y) * r, (a.y - a.x) * r); }
__device__ __forceinline__ float2 mul_w8_3(float2 a) { const float r = 0.70710678118654752f; return make_float2((a.y - a.x) * r, -(a.x + a.y) * r); }
__device__ __forceinline__ float2 mul_mi(float2 a) { return make_float2(a.y, -a.x); }
template <int O, int ST, int N> __device__ __forceinline__ void fft8(float2 (&v)[N]) {
  fft4(v[O], v[O + 2 * ST], v[O + 4 * ST], v[O + 6 * ST]);
  fft4(v[O + ST], v[O + 3 * ST], v[O + 5 * ST], v[O + 7 * ST]);
  float2 o0 = v[O + ST], o1 = mul_w8_1(v[O + 3 * ST]), o2 = mul_mi(v[O + 5 * ST]), o3 = mul_w8_3(v[O + 7 * ST]);
  float2 e0 = v[O], e1 = v[O + 2 * ST], e2 = v[O + 4 * ST], e3 = v[O + 6 * ST];
  v[O] = make_float2(e0.x + o0.x, e0.y + o0.y);          v[O + 4 * ST] = make_float2(e0.x - o0.x, e0.y - o0.y);
  v[O + ST] = make_float2(e1.x + o1.x, e1.y + o1.y);     v[O + 5 * ST] = make_float2(e1.x - o1.x, e1.y - o1.y);
  v[O + 2 * ST] = make_float2(e2.x + o2.x, e2.y + o2.y); v[O + 6 * ST] = make_float2(e2.x - o2.x, e2.y - o2.y);
  v[O + 3 * ST] = make_float2(e3.x + o3.x, e3.y + o3.y); v[O + 7 * ST] = make_float2(e3.x - o3.x, e3.y - o3.y);
}
__device__ __forceinline__ void fft16(float2 (&v)[16]) {
  const float c1 = 0.92387953251128674f, s1 = 0.38268343236508977f;
#pragma unroll
  for (int a = 0; a < 4; a++) fft4(v[a], v[a + 4], v[a + 8], v[a + 12]);
  v[5] = cmul(v[5], make_float2(c1, -s1)); v[9] = mul_w8_1(v[9]); v[13] = cmul(v[13], make_float2(s1, -c1));
  v[6] = mul_w8_1(v[6]); v[10] = mul_mi(v[10]); v[14] = mul_w8_3(v[14]);
  v[7] = cmul(v[7], make_float2(s1, -c1)); v[11] = mul_w8_3(v[11]); v[15] = cmul(v[15], make_float2(-c1, s1));
#pragma unroll
  for (int b = 0; b < 4; b++) fft4(v[4 * b], v[4 * b + 1], v[4 * b + 2], v[4 * b + 3]);
  float2 t;
  t = v[1]; v[1] = v[4]; v[4] = t;  t = v[2]; v[2] = v[8]; v[8] = t;  t = v[3]; v[3] = v[12]; v[12] = t;
  t = v[6]; v[6] = v[9]; v[9] = t;  t = v[7]; v[7] = v[13]; v[13] = t; t = v[11]; v[11] = v[14]; v[14] = t;
}
template <int E> __device__ __forceinline__ void tw8(float2 (&v)[16], float2 w) {
  asm volatile("" : "+f"(w.x), "+f"(w.y));
  float2 w2 = cmul(w, w), w3 = cmul(w2, w), w4 = cmul(w2, w2);
  v[E + 2] = cmul(v[E + 2], w); v[E + 4] = cmul(v[E + 4], w2); v[E + 6] = cmul(v[E + 6], w3); v[E + 8] = cmul(v[E + 8], w4);
  v[E + 10] = cmul(v[E + 10], cmul(w4, w)); v[E + 12] = cmul(v[E + 12], cmul(w3, w3)); v[E + 14] = cmul(v[E + 14], cmul(w4, w3));
}

__device__ __forceinline__ void column(float2 (&v)[16], uint32_t sb, int t, float2 wa, float2 wb, uint32_t ws) {
  const uint32_t ex = sb + OFF_EXCH;
  const uint32_t row = ex + (t >> 4) * 2304;
  const int l16 = t & 15;
  const uint32_t tw = sb + OFF_TW2 + l16 * 8;
  fft8<0, 2>(v); fft8<1, 2>(v);
  tw8<0>(v, wa); tw8<1>(v, wb);
#pragma unroll
  for (int q = 0; q < 8; q++) sts128f(ex + q * 2304 + t * 16, v[2 * q].x, v[2 * q].y, v[2 * q + 1].x, v[2 * q + 1].y);
  bar_sync<3, 128>();
#pragma unroll
  for (int j = 0; j < 16; j++) v[j] = lds64f(row + (l16 + 16 * j) * 8);
  fft16(v);
  __syncwarp();
#pragma unroll
  for (int q = 0; q < 16; q++) {
    float2 r = q ? cmul(v[q], lds64f(tw + q * 128)) : v[q];
    sts64f(row + q * 144 + l16 * 8, r.x, r.y);
  }
  __syncwarp();
#pragma unroll
  for (int j = 0; j < 8; j++) { float4 a = lds128f(row + l16 * 144 + j * 16); v[2 * j] = make_float2(a.x, a.y); v[2 * j + 1] = make_float2(a.z, a.w); }
  fft16(v);
  mbar_wait(sb + OFF_BAR + B_WFULL * 8, 0);
#pragma unroll
  for (int q = 0; q < 16; q++) {
    uint32_t w = lds32(ws + q * 512);
    float wr = __uint_as_float(w << 16), wi = __uint_as_float(w & 0xffff0000u);
    v[q] = make_float2(v[q].x * wi + v[q].y * wr, v[q].x * wr - v[q].y * wi);
  }
  fft16(v);
  __syncwarp();
#pragma unroll
  for (int j = 0; j < 8; j++) {
    float2 a = j ? cmul(v[2 * j], lds64f(tw + (2 * j) * 128)) : v[0];
    float2 b = cmul(v[2 * j + 1], lds64f(tw + (2 * j + 1) * 128));
    sts128f(row + l16 * 144 + j * 16, a.x, a.y, b.x, b.y);
  }
  __syncwarp();
#pragma unroll
  for (int q = 0; q < 16; q++) v[q] = lds64f(row + q * 144 + l16 * 8);
  fft16(v);
  __syncwarp();
#pragma unroll
  for (int j = 0; j < 16; j++) sts64f(row + (l16 + 16 * j) * 8, v[j].x, v[j].y);
  bar_sync<3, 128>();
#pragma unroll
  for (int q = 0; q < 8; q++) { float4 a = lds128f(ex + q * 2304 + t * 16); v[2 * q] = make_float2(a.x, a.y); v[2 * q + 1] = make_float2(a.z, a.w); }
  bar_sync<3, 128>();
  tw8<0>(v, wa); tw8<1>(v, wb);
  fft8<0, 2>(v); fft8<1, 2>(v);
}

template <int NH> __device__ __forceinline__ void h_epilogue(float (&acc)[NH * 8], uint32_t sdst, unsigned char* gdst) {
#pragma unroll
  for (int c = 0; c < NH / 4; c++) {
#pragma unroll
    for (int rr = 0; rr < 2; rr++) {
      uint32_t pk[4];
#pragma unroll
      for (int i = 0; i < 4; i++) {
        float hv[2];
#pragma unroll
        for (int e = 0; e < 2; e++) {
          float hg = 0.5f * acc[(4 * c + i) * 4 + rr * 2 + e], up = acc[(NH + 4 * c + i) * 4 + rr * 2 + e];
          float th; asm("tanh.approx.f32 %0, %1;" : "=f"(th) : "f"(hg));
          hv[e] = fmaf(hg, th, hg) * up;
        }
        pk[i] = pack_bf16(hv[0], hv[1]);
      }
      sts128(sdst + c * 4096 + rr * 128, pk[0], pk[1], pk[2], pk[3]);
      *reinterpret_cast<uint4*>(gdst + c * 4096 + rr * 128) = make_uint4(pk[0], pk[1], pk[2], pk[3]);
    }
  }
}

#define LEAD1 2

__global__ void __cluster_dims__(2, 1, 1) __launch_bounds__(NTHREADS, 1)
fused_kernel(const __grid_constant__ CUtensorMap tm_x, const __grid_constant__ CUtensorMap tm_g, const __grid_constant__ CUtensorMap tm_u,
             const __grid_constant__ CUtensorMap tm_g32, const __grid_constant__ CUtensorMap tm_u32,
             const __nv_bfloat16* __restrict__ x, const __nv_bfloat16* __restrict__ w_r, const __nv_bfloat16* __restrict__ w_i,
             const __nv_bfloat16* __restrict__ w_gate, const __nv_bfloat16* __restrict__ w_up,
             const __nv_bfloat16* __restrict__ w_down, const __nv_bfloat16* __restrict__ gate_w, __nv_bfloat16* __restrict__ out) {
  extern __shared__ __align__(1024) unsigned char smem[];
  const uint32_t sb = s2u(smem);
  const uint32_t bars = sb + OFF_BAR;
  const int tid = threadIdx.x, warp = tid >> 5, lane = tid & 31;
  const int bid = blockIdx.x, m = bid >> 3, n = (bid >> 1) & 3, kh = bid & 1, j = kh * 4 + n;

  if (warp >= 12) {
    asm volatile("setmaxnreg.dec.sync.aligned.u32 24;");
    const int c64 = 224 * j + (j & 1) * 32;
    if (warp == 13) {
      if (lane == 0) {
        PROFG(4, 0); PROF(4, 1);
        mbar_init(bars + B_XFULL * 8, 1); mbar_init(bars + (B_XFULL + 1) * 8, 1);
        fence_async_smem();
#pragma unroll
        for (int w = 0; w < 2; w++) {
          mbar_expect(bars + (B_XFULL + w) * 8, HALF_XR);
          tma3d(sb + OFF_XR + w * HALF_XR, &tm_x, 0, m * 128 + (w ^ kh ^ 1) * 64, 0, bars + (B_XFULL + w) * 8);
        }
      }
    } else if (warp == 12) {
      if (lane == 0) {
#pragma unroll
        for (int i = 0; i < NSLOT; i++) mbar_init(bars + (B_FULL + i) * 8, 1);
        fence_async_smem();
#pragma unroll 1
        for (int i = 0; i < 6; i++) {
          const uint32_t fb = bars + (B_FULL + i) * 8;
          mbar_expect(fb, SLOT);
          tma2d(sb + i * SLOT, &tm_g, c64, i * 64, fb);
          tma2d(sb + i * SLOT + 8192, &tm_u, c64, i * 64, fb);
        }
        PROF(3, 3);
      }
    } else if (warp == 14) {
      if (lane < NSLOT) mbar_init(bars + (B_EMPTY + lane) * 8, 8);
      else mbar_init(bars + (B_XFREE - NSLOT + lane) * 8, lane < NSLOT + 2 ? 4 : (lane < NSLOT + 8 ? 8 : 1));
      asm volatile("fence.mbarrier_init.release.cluster;" ::: "memory");
      __syncwarp();
      if (lane == 0) mbar_expect(bars + B_RECV * 8, 64 * 112 * 4);
    }
    bar_sync<0, NTHREADS>();
    asm volatile("barrier.cluster.arrive.release.aligned;" ::: "memory");
    if (warp == 12) {
      if (lane == 0) {
        int slot = 6, ph = 1;
        auto next = [&](int bytes) -> uint32_t {
          mbar_wait(bars + (B_EMPTY + slot) * 8, ph ^ (slot == 6));
          mbar_expect(bars + (B_FULL + slot) * 8, bytes);
          return sb + slot * SLOT;
        };
        auto adv = [&]() { if (++slot == NSLOT) { slot = 0; ph ^= 1; } };
#pragma unroll 1
        for (int i = 6; i < 21; i++) {
          const int u = i / 7;
          const uint32_t dst = next(SLOT), fb = bars + (B_FULL + slot) * 8;
          tma2d(dst, &tm_g, c64 + 64 * u, slot * 64, fb);
          tma2d(dst + 8192, &tm_u, c64 + 64 * u, slot * 64, fb);
          adv();
        }
        const int c32 = 224 * j + ((j & 1) ? 0 : 192);
#pragma unroll 1
        for (int i = 0; i < 4; i++) {
          const uint32_t dst = next(SLOT), fb = bars + (B_FULL + slot) * 8;
          tma2d(dst, &tm_g32, c32, i * 128, fb);
          tma2d(dst + 8192, &tm_u32, c32, i * 128, fb);
          adv();
        }
        PROF(3, 0);
        mbar_wait(bars + B_PREP * 8, 0);
        PROF(3, 1);
        const unsigned char* wd = g_Wd + (size_t)j * WD_IMG;
        const unsigned char* hb = g_H + (size_t)(m * 8 + kh * 4) * HALF_XR;
#pragma unroll 1
        for (int i = 0; i < 12; i++) {
          const int u = i >> 2, src = i & 3, ns = (n + src) & 3;
          PROF(3, 16 + i);
          if (src != 0) {
            mbar_wait(bars + (B_HRDY + (src - 1) * 4 + u) * 8, 0);
            const uint32_t dst = next(16384);
            bulk_g2s(dst, hb + ns * HALF_XR + u * 16384, 16384, bars + (B_FULL + slot) * 8);
            adv();
          }
          const uint32_t dst = next(14336);
          bulk_g2s(dst, wd + (ns * 224 + u * 64) * 224, 14336, bars + (B_FULL + slot) * 8);
          adv();
        }
#pragma unroll 1
        for (int src = 0; src < 4; src++) {
          const int ns = (n + src) & 3;
          PROF(3, 28 + src);
          if (src != 0) mbar_wait(bars + (B_HRDY + (src - 1) * 4 + 3) * 8, 0);
          const uint32_t dst = next(src ? 15360 : 7168), fb = bars + (B_FULL + slot) * 8;
          bulk_g2s(dst + 8192, wd + (ns * 224 + 192) * 224, 7168, fb);
          if (src != 0) bulk_g2s(dst, hb + ns * HALF_XR + 49152, 8192, fb);
          adv();
        }
#pragma unroll 1
        for (int i = 0; i < 4; i++) {
          const uint32_t dst = next(G_IMG / 2);
          bulk_g2s(dst, g_G + (size_t)(n * 4 + i) * (G_IMG / 2), G_IMG / 2, bars + (B_FULL + slot) * 8);
          adv();
        }
        PROF(3, 2);
      }
    } else if (warp == 13) {
      if (lane == 0) {
        mbar_wait(bars + B_XFULL * 8, 0);
        PROF(4, 2);
        prefetch_l2(reinterpret_cast<const unsigned char*>(w_gate) + bid * 12544, 12544);
        prefetch_l2(reinterpret_cast<const unsigned char*>(w_up) + bid * 12544, 12544);
#pragma unroll 1
        for (int u = 0; u < 5; u++) {
          mbar_wait(bars + (B_PUB + u) * 8, 0);
          PROF(4, 8 + u);
          fence_gpu();
          red_add(u == 0 ? &g_cnt[(j >> 1) * 32] : &g_hflag[bid * 4 + u - 1]);
          PROF(4, 16 + u);
        }
      }
    } else if (warp == 14) {
      const uint32_t epoch = ld_relaxed(&g_ep[bid * 2]);
      if (lane < 13) {
        const unsigned int* fp = lane < 12 ? &g_hflag[(m * 8 + ((n + 1 + (lane >> 2)) & 3) * 2 + kh) * 4 + (lane & 3)] : &g_cnt[4 * 32];
        const uint32_t tgt = lane < 12 ? epoch + 1 : (epoch + 1) * 128;
        const uint32_t rb = bars + (lane < 12 ? B_HRDY + lane : B_PREP) * 8;
        bool done = false;
#pragma unroll 1
        for (int i = 0; i < (1 << 20); i++) {
          if (!done && (int)(ld_acquire(fp) - tgt) >= 0) { fence_async_all(); mbar_arrive(rb); done = true; PROF(5, lane); }
          if (__all_sync(0x1fff, done)) break;
        }
        if (!done) __trap();
        if (lane == 0) g_ep[bid * 2] = epoch + 1;
      }
    } else {
      if (lane == 0) {
        const uint32_t epoch = ld_relaxed(&g_ep[bid * 2 + 1]);
        mbar_wait(bars + (B_XFREE + 1) * 8, 0);
        if (bid < 113) {
          const int sl = (bid == 112) ? 0 : bid;
          wait_ge(&g_cnt[((sl & 1) + 2 * ((sl >> 1) / 28)) * 32], (epoch + 1) * 32);
          fence_async_all();
          PROF(5, 16);
          mbar_expect(bars + B_XCFULL * 8, 16384);
          bulk_g2s(sb + OFF_EXCH, g_Xc + sl * 2 * S_, 16384, bars + B_XCFULL * 8);
          mbar_wait(bars + B_PREP * 8, 0);
          mbar_expect(bars + B_WFULL * 8, 16384);
          bulk_g2s(sb + OFF_WS, g_Wt + bid * 2 * S_, 16384, bars + B_WFULL * 8);
          PROF(5, 17);
        }
        wait_ge(&g_cnt[5 * 32], (epoch + 1) * 128);
        fence_async_all();
        PROF(5, 18);
        mbar_expect(bars + B_PQFULL * 8, HALF_XR + 256);
        const unsigned char* src = g_PQ + (size_t)(m * 2 + kh) * HALF_XR;
        bulk_g2s(sb + OFF_PQ, src, 28672, bars + B_PQFULL * 8);
        bulk_g2s(sb + OFF_PQ + 28672, src + 28672, 28672, bars + B_PQFULL * 8);
        bulk_g2s(sb + OFF_G, g_gate + m * 128 + kh * 64, 256, bars + B_PQFULL * 8);
        g_ep[bid * 2 + 1] = epoch + 1;
      }
    }
    __syncwarp();
    asm volatile("barrier.cluster.wait.aligned;" ::: "memory");
  } else if (warp < 8) {
    asm volatile("setmaxnreg.inc.sync.aligned.u32 208;");
    const int wg = warp >> 2, w4 = warp & 3, g = lane >> 2, t = lane & 3;
    const int rh = wg ^ kh ^ 1;
    const int p = j & 1, r = (j >> 1) & 1, hh = j >> 2;
#pragma unroll 1
    for (int it = tid; it < 392; it += 256) {
      int kc = it / 28, sg = it - kc * 28;
      int k = 2 * (28 * hh + sg) + r;
      float c[8], s[8];
#pragma unroll
      for (int q = 0; q < 8; q++) {
        int d = 16 * kc + 8 * (q & 1) + 2 * (q >> 1) + p;
        cs448((d * k) % 448, c[q], s[q]);
        s[q] = -s[q];
        if (k == 0) s[q] = (float)(p ? ((d & 2) - 1) : (1 - (d & 2)));
      }
      uint32_t a = sb + 6 * SLOT + (kc * 56 + 2 * sg) * 16;
      sts128(a, pack_bf16(c[0], c[1]), pack_bf16(c[2], c[3]), pack_bf16(c[4], c[5]), pack_bf16(c[6], c[7]));
      sts128(a + 16, pack_bf16(s[0], s[1]), pack_bf16(s[2], s[3]), pack_bf16(s[4], s[5]), pack_bf16(s[6], s[7]));
    }
    fence_async_smem();
    bar_sync<0, NTHREADS>();
    asm volatile("barrier.cluster.arrive.release.aligned;" ::: "memory");
    if ((tid & 127) == 0) PROF(wg, 1);

    uint32_t xa[28][4];
    {
      const uint32_t xb = sb + OFF_XR + wg * HALF_XR + (w4 * 16 + (lane & 15)) * 128;
      mbar_wait(bars + (B_XFULL + wg) * 8, 0);
      if ((tid & 127) == 0) PROF(wg, 2);
#pragma unroll
      for (int kb = 0; kb < 7; kb++) {
#pragma unroll
        for (int kk = 0; kk < 4; kk++) {
          uint32_t a = xb + kb * 8192 + (((2 * kk + (lane >> 4)) ^ (lane & 7)) << 4);
          asm volatile("ldmatrix.sync.aligned.m8n8.x4.shared.b16 {%0,%1,%2,%3}, [%4];"
                       : "=r"(xa[kb * 4 + kk][0]), "=r"(xa[kb * 4 + kk][1]), "=r"(xa[kb * 4 + kk][2]), "=r"(xa[kb * 4 + kk][3]) : "r"(a) : "memory");
        }
      }
    }
    {
      uint32_t ad[7][4];
      const uint32_t sel = p ? 0x7632 : 0x5410;
      const uint32_t sgn = r ? 0xBF80BF80u : 0x3F803F80u;
#pragma unroll
      for (int jj = 0; jj < 7; jj++) {
#pragma unroll
        for (int i = 0; i < 4; i++) {
          int ks = 2 * jj + (i >> 1), rr = i & 1;
          uint32_t lo = __byte_perm(xa[ks][rr], xa[ks][rr + 2], sel);
          uint32_t hi = __byte_perm(xa[ks + 14][rr], xa[ks + 14][rr + 2], sel);
          asm("fma.rn.bf16x2 %0, %1, %2, %3;" : "=r"(ad[jj][i]) : "r"(hi), "r"(sgn), "r"(lo));
        }
      }
      __syncwarp();
      if (lane == 0) mbar_arrive(bars + (B_XFREE + wg) * 8);
      float acc[28];
      wg_fence();
      uint64_t db = mkdesc(sb + 6 * SLOT, 896, 128, 0);
#pragma unroll
      for (int jj = 0; jj < 7; jj++) wgmma_rs_56<0>(acc, ad[jj], db + jj * 112, jj != 0);
      wg_commit();
      wg_wait<0>(); keep(acc);
      if (lane == 0) mbar_arrive(bars + (B_EMPTY + 6) * 8);
      uint32_t* xc = g_Xc + (size_t)((2 * (28 * hh + t) + r) * 2 + p) * S_ + m * 128 + rh * 64 + w4 * 16 + g;
#pragma unroll
      for (int i = 0; i < 7; i++) {
        xc[i * 16 * S_] = pack_bf16(acc[4 * i], acc[4 * i + 1]);
        xc[i * 16 * S_ + 8] = pack_bf16(acc[4 * i + 2], acc[4 * i + 3]);
      }
      __syncwarp();
      if (lane == 0) mbar_arrive(bars + B_PUB * 8);
    }
    if ((tid & 127) == 0) PROF(wg, 3);
    const uint32_t hofs = t * 1024 + (w4 * 16 + g) * 16;
#pragma unroll 1
    for (int u = 0; u < 3; u++) {
      float acc[64];
      if (wg == 1) { if (u & 1) bar_sync<6, 256>(); else bar_sync<2, 256>(); }
      const uint32_t sbu = opaque(sb);
#pragma unroll
      for (int kb = 0; kb < 7; kb++) {
        mbar_wait(sbu + OFF_BAR + (B_FULL + kb) * 8, u & 1);
        wg_fence();
        uint64_t db = mkdesc(sbu + kb * SLOT, 8192, 1024, 1);
#pragma unroll
        for (int kk = 0; kk < 4; kk++) wgmma_rs_128<1>(acc, xa[kb * 4 + kk], db + kk * 128, (kb | kk) != 0);
        wg_commit();
        if (kb == LEAD1 && wg == 0) { if (u & 1) bar_arrive<6, 256>(); else bar_arrive<2, 256>(); }
        if (kb > 0) { wg_wait<1>(); if (lane == 0) mbar_arrive(sbu + OFF_BAR + (B_EMPTY + kb - 1) * 8); }
      }
      wg_wait<0>(); keep(acc);
      if (lane == 0) mbar_arrive(sbu + OFF_BAR + (B_EMPTY + 6) * 8);
      if ((tid & 127) == 0) PROF(wg, 4 + 2 * u);
      mbar_wait(sbu + OFF_BAR + B_XFREE * 8, 0);
      const uint32_t uo = u * 16384 + rh * 8192 + hofs;
      h_epilogue<8>(acc, sbu + OFF_HOWN + uo, g_H + (size_t)(m * 8 + j) * HALF_XR + uo);
      __syncwarp();
      if (lane == 0) mbar_arrive(sbu + OFF_BAR + (B_PUB + 1 + u) * 8);
      if ((tid & 127) == 0) PROF(wg, 5 + 2 * u);
    }
    {
      float acc[32];
      if (wg == 1) bar_sync<6, 256>();
      const uint32_t sbu = opaque(sb);
#pragma unroll
      for (int it = 0; it < 4; it++) {
        mbar_wait(sbu + OFF_BAR + (B_FULL + it) * 8, 1);
        wg_fence();
        uint64_t db = mkdesc(sbu + it * SLOT, 8192, 512, 2);
#pragma unroll
        for (int kk = 0; kk < 8; kk++) if (it * 8 + kk < 28) wgmma_rs_64<1>(acc, xa[it * 8 + kk], db + kk * 64, (it | kk) != 0);
        wg_commit();
        if (it == LEAD1 && wg == 0) bar_arrive<6, 256>();
        if (it > 0) { wg_wait<1>(); if (lane == 0) mbar_arrive(sbu + OFF_BAR + (B_EMPTY + it - 1) * 8); }
      }
      wg_wait<0>(); keep(acc);
      if (lane == 0) mbar_arrive(sbu + OFF_BAR + (B_EMPTY + 3) * 8);
      if ((tid & 127) == 0) PROF(wg, 10);
      const uint32_t uo = 49152 + rh * 4096 + hofs;
      h_epilogue<4>(acc, sbu + OFF_HOWN + uo, g_H + (size_t)(m * 8 + j) * HALF_XR + uo);
      __syncwarp();
      if (lane == 0) mbar_arrive(sbu + OFF_BAR + (B_PUB + 4) * 8);
    }
    fence_async_smem();
    if (wg) bar_sync<5, 128>(); else bar_sync<4, 128>();
    asm volatile("barrier.cluster.wait.aligned;" ::: "memory");
    if ((tid & 127) == 0) PROF(wg, 11);

    float acc[56];
    if (wg == 1) bar_sync<2, 256>();
#pragma unroll 1
    for (int u = 0; u < 3; u++) {
#pragma unroll
      for (int src = 0; src < 4; src++) {
        if ((tid & 127) == 0) PROF(wg, 16 + u * 4 + src);
        const int eb = 2 * src, sB = (4 + eb) % 7, sA = (3 + eb) % 7;
        if (src) mbar_wait(bars + (B_FULL + sA) * 8, (u + (eb - 1 < 3)) & 1);
        mbar_wait(bars + (B_FULL + sB) * 8, (u + (eb < 3)) & 1);
        wg_fence();
        const uint64_t da = mkdesc((src ? sb + sA * SLOT : sb + OFF_HOWN + u * 16384) + rh * 8192, 1024, 128, 0);
        const uint64_t db = mkdesc(sb + sB * SLOT, 1792, 128, 0);
#pragma unroll
        for (int kk = 0; kk < 4; kk++) wgmma_ss_112<0, 1>(acc, da + kk * 128, db + kk * 224, (src | kk) ? 1 : u);
        wg_commit();
        if (src == 1 && u == 0 && wg == 0) bar_arrive<2, 256>();
        wg_wait<1>();
        if (lane == 0 && (src | u)) {
          mbar_arrive(bars + (B_EMPTY + (src ? (2 + eb) % 7 : 3)) * 8);
          if (src != 1) mbar_arrive(bars + (B_EMPTY + (src ? (1 + eb) % 7 : 2)) * 8);
          if (src == 1 && u == 1) {
            asm volatile("{\n.reg .b32 ra;\nmapa.shared::cluster.u32 ra, %0, %1;\nmbarrier.arrive.release.cluster.shared::cluster.b64 _, [ra];\n}"
                         :: "r"(bars + B_RFREE * 8), "r"(kh ^ 1) : "memory");
          }
        }
      }
    }
#pragma unroll
    for (int src = 0; src < 4; src++) {
      if ((tid & 127) == 0) PROF(wg, 28 + src);
      const int sB = (4 + src) % 7;
      mbar_wait(bars + (B_FULL + sB) * 8, src == 3);
      wg_fence();
      const uint64_t da = mkdesc((src ? sb + sB * SLOT : sb + OFF_HOWN + 49152) + rh * 4096, 1024, 128, 0);
      const uint64_t db = mkdesc(sb + sB * SLOT + 8192, 1792, 128, 0);
#pragma unroll
      for (int kk = 0; kk < 2; kk++) wgmma_ss_112<0, 1>(acc, da + kk * 128, db + kk * 224, 1);
      wg_commit();
      if (src < 2) {
        wg_wait<1>();
        if (lane == 0) { mbar_arrive(bars + (B_EMPTY + (src ? 4 : 3)) * 8); if (src == 0) mbar_arrive(bars + (B_EMPTY + 2) * 8); }
      }
    }
    const int t128 = tid & 127;
    if (wg == 0) {
      wg_wait<0>(); keep(acc);
      if (t128 == 0) PROF(wg, 12);
      mbar_wait_cluster(bars + B_RFREE * 8, 0);
      uint32_t rdst, rbar;
      asm volatile("mapa.shared::cluster.u32 %0, %1, %2;" : "=r"(rdst) : "r"(sb + OFF_HOWN + t128 * 16), "r"(kh ^ 1));
      asm volatile("mapa.shared::cluster.u32 %0, %1, %2;" : "=r"(rbar) : "r"(bars + B_RECV * 8), "r"(kh ^ 1));
#pragma unroll
      for (int i = 0; i < 14; i++)
        asm volatile("st.async.weak.shared::cluster.mbarrier::complete_tx::bytes.v4.f32 [%0], {%1,%2,%3,%4}, [%5];"
                     :: "r"(rdst + i * 2048), "f"(acc[4 * i]), "f"(acc[4 * i + 1]), "f"(acc[4 * i + 2]), "f"(acc[4 * i + 3]), "r"(rbar) : "memory");
    } else {
      float spec[2][28];
      if (t128 == 0) PROF(wg, 12);
      mbar_wait(bars + B_PQFULL * 8, 0);
      if (t128 == 0) PROF(wg, 13);
#pragma unroll
      for (int i = 0; i < 4; i++) {
        mbar_wait(bars + (B_FULL + 1 + i) * 8, 1);
        wg_fence();
        const uint64_t da = mkdesc(sb + OFF_PQ + i * 14336, 1024, 1024, 1);
        const uint64_t db = mkdesc(sb + (1 + i) * SLOT, 896, 128, 0);
#pragma unroll
        for (int kk = 0; kk < 7; kk++) wgmma_ss_56<1, 0>(spec[i >> 1], da + kk * 128, db + kk * 112, ((i & 1) | kk) != 0);
        wg_commit();
      }
      const float* gs = reinterpret_cast<const float*>(smem + OFF_G) + w4 * 16 + g;
      const float g0 = gs[0], g1 = gs[8];
      const float o0 = bf16_round(1.0f - g0), o1 = bf16_round(1.0f - g1);
      wg_wait<0>(); keep(acc); keep(spec[0]); keep(spec[1]);
      if (t128 == 0) PROF(wg, 14);
      mbar_wait_cluster(bars + B_RECV * 8, 0);
      if (t128 == 0) PROF(wg, 0);
      bar_sync<5, 128>();
      const uint32_t st = sb + OFF_PQ + w4 * 3840;
#pragma unroll
      for (int i = 0; i < 14; i++) {
        const float4 o = lds128f(sb + OFF_HOWN + t128 * 16 + i * 2048);
        const int si = (i >> 1) * 4 + (i & 1);
        sts32(st + g * 240 + i * 16 + t * 4, pack_bf16(fmaf(acc[4 * i] + o.x, o0, g0 * spec[0][si]), fmaf(acc[4 * i + 1] + o.y, o0, g0 * spec[1][si])));
        sts32(st + (g + 8) * 240 + i * 16 + t * 4, pack_bf16(fmaf(acc[4 * i + 2] + o.z, o1, g1 * spec[0][si + 2]), fmaf(acc[4 * i + 3] + o.w, o1, g1 * spec[1][si + 2])));
      }
      __syncwarp();
      unsigned char* ob = reinterpret_cast<unsigned char*>(out) + (size_t)(m * 128 + kh * 64 + w4 * 16) * (D_ * 2) + n * 224;
#pragma unroll
      for (int i = 0; i < 7; i++) {
        int c = i * 32 + lane, rr = c / 14, cc = c - rr * 14;
        float4 v = lds128f(st + rr * 240 + cc * 16);
        *reinterpret_cast<float4*>(ob + rr * (D_ * 2) + cc * 16) = v;
      }
    }
    if (t128 == 0) { PROF(wg, 15); if (wg) { PROFG(4, 30); PROF(4, 31); } }
  } else {
    asm volatile("setmaxnreg.dec.sync.aligned.u32 72;");
    const int t = tid - 256;
    const int k = bid;
    if (t == 0) PROF(2, 0);
    if (t < 98) {
      int cid = m * 98 + t, kc = cid / 56, nn = cid - kc * 56;
      int d = 112 * n + 8 * (2 * (nn >> 3) + (nn & 1)) + (nn & 6) + kh;
      uint32_t pk[4];
#pragma unroll
      for (int e = 0; e < 4; e++) {
        int kk = 4 * kc + e; float c, s;
        cs448((d * kk) % 448, c, s); s = -s;
        if (kk == 0) s = (float)(kh ? ((d & 2) - 1) : (1 - (d & 2)));
        pk[e] = pack_bf16(c, s);
      }
      *reinterpret_cast<uint4*>(g_G + (size_t)(n * 2 + kh) * G_IMG + cid * 16) = make_uint4(pk[0], pk[1], pk[2], pk[3]);
    }
    bar_sync<0, NTHREADS>();
    asm volatile("barrier.cluster.arrive.release.aligned;" ::: "memory");
    mbar_wait(bars + B_XFULL * 8, 0);
    if (t == 0) PROF(2, 8);
    {
      const uint4* src = reinterpret_cast<const uint4*>(w_down) + bid * 784;
      if (t == 127) prefetch_l2(src, 12544);
      if (t < 114) {
        const bool rev = t >= 57;
        const int c0 = 2 * t - (rev ? 2 : 0) - (bid & 1);
        const int ks0 = (bid & 7) + 128 * (bid >> 3);
        uint32_t a[16], b[16];
#pragma unroll
        for (int i = 0; i < 16; i++) {
          const int ks = ks0 + 8 * i, row = rev ? ((S_ - ks) & (S_ - 1)) : ks;
          a[i] = __ldg(reinterpret_cast<const uint32_t*>(w_r + row * DF_ + c0));
          b[i] = __ldg(reinterpret_cast<const uint32_t*>(w_i + row * DF_ + c0));
        }
        const uint32_t cj = rev ? 0x80000000u : 0u;
#pragma unroll
        for (int e = 0; e < 2; e++) {
          const int c = c0 + e;
          if (rev ? (c >= 112 && c <= 224) : (c >= 0 && c <= 112)) {
            uint4* dst = reinterpret_cast<uint4*>(g_Wt + (rev ? 2 * (224 - c) + 1 : 2 * c) * S_ + 16 * bid);
            const uint32_t sel = e ? 0x7632 : 0x5410;
#pragma unroll
            for (int i = 0; i < 4; i++)
              dst[i] = make_uint4(__byte_perm(a[4 * i], b[4 * i], sel) ^ cj, __byte_perm(a[4 * i + 1], b[4 * i + 1], sel) ^ cj,
                                  __byte_perm(a[4 * i + 2], b[4 * i + 2], sel) ^ cj, __byte_perm(a[4 * i + 3], b[4 * i + 3], sel) ^ cj);
          }
        }
      }
      if (t == 0) PROF(2, 9);
      uint4 wd[7];
#pragma unroll
      for (int i = 0; i < 7; i++) if (i * 128 + t < 784) wd[i] = __ldg(src + i * 128 + t);
#pragma unroll
      for (int i = 0; i < 7; i++) {
        int c = i * 128 + t;
        if (c < 784) {
          int rr = c / 56, ch = c - rr * 56, row = bid * 14 + rr;
          int js = row / 224, col = row - js * 224;
          int grp = col >> 5;
          int kg = (js & 1) ? (grp ? grp - 1 : 6) : grp;
          int c32 = col & 31;
          int kpos = (js & 3) * 224 + kg * 32 + ((c32 >> 1) & 3) * 8 + (c32 >> 3) * 2 + (c32 & 1);
          int nn = ch / 14, cc = ch - nn * 14;
          *reinterpret_cast<uint4*>(g_Wd + (size_t)((js >> 2) * 4 + nn) * WD_IMG + (kpos >> 3) * 1792 + cc * 128 + (kpos & 7) * 16) = wd[i];
        }
      }
    }
    bar_sync<3, 128>();
    if (t == 96) { PROF(2, 10); fence_gpu(); red_add(&g_cnt[4 * 32]); PROF(2, 1); }
    {
      const int row = m * 128 + j * 16 + (t >> 3), l8 = t & 7;
      const uint4* xr = reinterpret_cast<const uint4*>(x + (size_t)row * D_);
      const uint4* gw = reinterpret_cast<const uint4*>(gate_w);
      float sum = 0.f;
#pragma unroll
      for (int i = 0; i < 7; i++) {
        uint4 a = __ldg(xr + i * 8 + l8), b = __ldg(gw + i * 8 + l8);
        uint32_t aa[4] = {a.x, a.y, a.z, a.w}, bb[4] = {b.x, b.y, b.z, b.w};
#pragma unroll
        for (int e = 0; e < 4; e++) {
          uint32_t pr; asm("mul.rn.bf16x2 %0, %1, %2;" : "=r"(pr) : "r"(aa[e]), "r"(bb[e]));
          sum += bf_lo(pr) + bf_hi(pr);
        }
      }
      sum += __shfl_xor_sync(0xffffffffu, sum, 1); sum += __shfl_xor_sync(0xffffffffu, sum, 2); sum += __shfl_xor_sync(0xffffffffu, sum, 4);
      if (l8 == 0) g_gate[row] = bf16_round(1.0f / (1.0f + __expf(-bf16_round(sum))));
    }
    if (t == 0) PROF(2, 11);
    if (k < 113) {
      float2 wa, wb, t0, t1;
      sincospif(-(float)(2 * t) / 1024.0f, &wa.y, &wa.x);
      sincospif(-(float)(2 * t + 1) / 1024.0f, &wb.y, &wb.x);
      sincospif(-(float)((t >> 4) * (t & 15)) / 128.0f, &t0.y, &t0.x);
      sincospif(-(float)(((t >> 4) + 8) * (t & 15)) / 128.0f, &t1.y, &t1.x);
      mbar_wait(bars + (B_XFREE + 1) * 8, 0);
      sts64f(sb + OFF_TW2 + t * 8, t0.x, t0.y); sts64f(sb + OFF_TW2 + 1024 + t * 8, t1.x, t1.y);
      if (t == 0) PROF(2, 2);
      mbar_wait(bars + B_XCFULL * 8, 0);
      if (t == 0) PROF(2, 3);
      float2 v[16];
      const uint32_t mre = (k == 112) ? 0u : 0xffffffffu, mim = (k == 0) ? 0u : 0xffff0000u;
#pragma unroll
      for (int jj = 0; jj < 8; jj++) {
        uint2 e = lds64(sb + OFF_EXCH + jj * 1024 + t * 8), o = lds64(sb + OFF_EXCH + 8192 + jj * 1024 + t * 8);
        if (k == 112) { e.x >>= 16; e.y >>= 16; }
        const float e0 = bf_lo(e.x), e1 = __uint_as_float(e.x & mim), e2 = bf_lo(e.y), e3 = __uint_as_float(e.y & mim);
        const float o0 = bf_lo(o.x & mre), o1 = __uint_as_float(o.x & mim), o2 = bf_lo(o.y & mre), o3 = __uint_as_float(o.y & mim);
        v[2 * jj] = make_float2(e0 + o0, e1 + o1); v[2 * jj + 1] = make_float2(e2 + o2, e3 + o3);
        sts128f(sb + OFF_STASH + jj * 2048 + t * 16, e0 - o0, e1 - o1, e2 - o2, e3 - o3);
      }
      bar_sync<3, 128>();
      const float sc = ((k == 0 || k == 112) ? 1.0f : 2.0f) / (float)(S_ * D_);
#pragma unroll 1
      for (int col = 0; col < 2; col++) {
        if (t == 0) PROF(2, 12 + col);
        column(v, sb, t, wa, wb, sb + OFF_WS + col * 8192 + t * 4);
        if (t == 0) PROF(2, 14 + col);
        if (col == 0) {
#pragma unroll
          for (int jj = 0; jj < 8; jj++) {
            const float4 a = lds128f(sb + OFF_STASH + jj * 2048 + t * 16);
            sts128f(sb + OFF_STASH + jj * 2048 + t * 16, v[2 * jj].x * sc, v[2 * jj].y * sc, v[2 * jj + 1].x * sc, v[2 * jj + 1].y * sc);
            v[2 * jj] = make_float2(a.x, a.y); v[2 * jj + 1] = make_float2(a.z, a.w);
          }
        }
      }
      const int pre = (k == 112) ? 1 : 2 * k, pim = (k == 112) ? 1 : 2 * k + 1;
      uint32_t* pq = reinterpret_cast<uint32_t*>(g_PQ) + (t >> 5) * 14336;
      const int ore = pre * 32 + ((((lane >> 2) ^ pre) & 7) << 2) + (lane & 3);
      const int oim = pim * 32 + ((((lane >> 2) ^ pim) & 7) << 2) + (lane & 3);
#pragma unroll
      for (int jj = 0; jj < 8; jj++) {
        float4 a = lds128f(sb + OFF_STASH + jj * 2048 + t * 16);
        uint32_t* pb = pq + jj * 57344;
        uint32_t p_re = pack_bf16(a.y + sc * v[2 * jj].y, a.w + sc * v[2 * jj + 1].y), p_im = pack_bf16(a.x + sc * v[2 * jj].x, a.z + sc * v[2 * jj + 1].x);
        uint32_t q_re = pack_bf16(a.y - sc * v[2 * jj].y, a.w - sc * v[2 * jj + 1].y), q_im = pack_bf16(a.x - sc * v[2 * jj].x, a.z - sc * v[2 * jj + 1].x);
        pb[ore] = p_re;
        if (k != 112) pb[7168 + ore] = q_re;
        if (k != 0) pb[7168 + oim] = q_im;
        if (k != 0 && k != 112) pb[oim] = p_im;
      }
      fence_async_smem();
    }
    bar_sync<3, 128>();
    if (t == 0) { PROF(2, 5); fence_gpu(); red_add(&g_cnt[5 * 32]); PROF(2, 7); }
    __syncwarp();
    asm volatile("barrier.cluster.wait.aligned;" ::: "memory");
  }
}

typedef CUresult (*EncodeFn)(CUtensorMap*, CUtensorMapDataType, cuuint32_t, void*, const cuuint64_t*, const cuuint64_t*, const cuuint32_t*,
                             const cuuint32_t*, CUtensorMapInterleave, CUtensorMapSwizzle, CUtensorMapL2promotion, CUtensorMapFloatOOBfill);

void make_map(EncodeFn enc, CUtensorMap* tm, const void* base, int cols, int rows, int bc, int br, CUtensorMapSwizzle sw) {
  cuuint64_t gd[2] = {(cuuint64_t)cols, (cuuint64_t)rows};
  cuuint64_t gs[1] = {(cuuint64_t)cols * 2};
  cuuint32_t bd[2] = {(cuuint32_t)bc, (cuuint32_t)br};
  cuuint32_t es[2] = {1, 1};
  enc(tm, CU_TENSOR_MAP_DATA_TYPE_BFLOAT16, 2, const_cast<void*>(base), gd, gs, bd, es, CU_TENSOR_MAP_INTERLEAVE_NONE, sw,
      CU_TENSOR_MAP_L2_PROMOTION_L2_128B, CU_TENSOR_MAP_FLOAT_OOB_FILL_NONE);
}

}

extern "C" void kernel_launch(void* const* d_in, const int* in_sizes, int n_in, void* d_out, int out_size) {
  (void)in_sizes; (void)n_in; (void)out_size;
  const __nv_bfloat16* x = (const __nv_bfloat16*)d_in[0];
  const __nv_bfloat16* w_r = (const __nv_bfloat16*)d_in[1];
  const __nv_bfloat16* w_i = (const __nv_bfloat16*)d_in[2];
  const __nv_bfloat16* w_gate = (const __nv_bfloat16*)d_in[4];
  const __nv_bfloat16* w_up = (const __nv_bfloat16*)d_in[5];
  const __nv_bfloat16* w_down = (const __nv_bfloat16*)d_in[6];
  const __nv_bfloat16* gate_w = (const __nv_bfloat16*)d_in[7];
  static EncodeFn enc = nullptr;
  static bool ok = false;
  if (!enc) {
    cudaDriverEntryPointQueryResult qr;
    cudaGetDriverEntryPoint("cuTensorMapEncodeTiled", (void**)&enc, cudaEnableDefault, &qr);
    cudaFuncSetAttribute(fused_kernel, cudaFuncAttributeMaxDynamicSharedMemorySize, SMEM_BYTES);
    cudaFuncAttributes fa;
    cudaFuncGetAttributes(&fa, fused_kernel);
    ok = (fa.numRegs == 128);
  }
  if (!ok) return;
  CUtensorMap tx, tg, tu, tg32, tu32;
  {
    cuuint64_t gd[3] = {64, (cuuint64_t)S_, 7};
    cuuint64_t gs[2] = {(cuuint64_t)D_ * 2, 128};
    cuuint32_t bd[3] = {64, 64, 7};
    cuuint32_t es[3] = {1, 1, 1};
    enc(&tx, CU_TENSOR_MAP_DATA_TYPE_BFLOAT16, 3, const_cast<__nv_bfloat16*>(x), gd, gs, bd, es, CU_TENSOR_MAP_INTERLEAVE_NONE, CU_TENSOR_MAP_SWIZZLE_128B,
        CU_TENSOR_MAP_L2_PROMOTION_L2_128B, CU_TENSOR_MAP_FLOAT_OOB_FILL_NONE);
  }
  make_map(enc, &tg, w_gate, F_, D_, 64, 64, CU_TENSOR_MAP_SWIZZLE_128B);
  make_map(enc, &tu, w_up, F_, D_, 64, 64, CU_TENSOR_MAP_SWIZZLE_128B);
  make_map(enc, &tg32, w_gate, F_, D_, 32, 128, CU_TENSOR_MAP_SWIZZLE_64B);
  make_map(enc, &tu32, w_up, F_, D_, 32, 128, CU_TENSOR_MAP_SWIZZLE_64B);
  fused_kernel<<<128, NTHREADS, SMEM_BYTES>>>(tx, tg, tu, tg32, tu32, x, w_r, w_i, w_gate, w_up, w_down, gate_w, (__nv_bfloat16*)d_out);
}
```

```cpp
#include <cuda_runtime.h>
#include <cuda_bf16.h>
#include <cuda.h>
#include <stdint.h>

namespace {

constexpr int S_ = 2048, D_ = 448, F_ = 1792, DF_ = 225;
constexpr int NTHREADS = 512;
constexpr int SLOT = 16384, NSLOT = 7;
constexpr int OFF_XR = NSLOT * SLOT;
constexpr int HALF_XR = 57344;
constexpr int OFF_HOWN = OFF_XR;
constexpr int OFF_PQ = OFF_XR + HALF_XR;
constexpr int OFF_EXCH = OFF_PQ;
constexpr int OFF_STASH = OFF_EXCH + 18432;
constexpr int OFF_WS = OFF_STASH + 16384;
constexpr int OFF_TW = OFF_WS + 16384;
constexpr int OFF_MISC = OFF_XR + 2 * HALF_XR;
constexpr int OFF_G = OFF_MISC;
constexpr int OFF_BAR = OFF_MISC + 512;
constexpr int SMEM_BYTES = OFF_BAR + 512;
constexpr int B_FULL = 0, B_EMPTY = 7, B_XFULL = 14  ;
constexpr int B_XFREE = 16  , B_PUB = 18  , B_RFREE = 23;
constexpr int B_PQFULL = 24, B_RECV = 25, B_WFULL = 26, B_XCFULL = 27, B_PREP = 28, B_HRDY = 29  , B_END = 41;

constexpr int WD_IMG = 896 * 112 * 2;
constexpr int G_IMG = 224 * 56 * 2;

__device__ __align__(1024) uint32_t g_Xc[112 * 2 * S_];
__device__ __align__(1024) unsigned char g_H[16 * 8 * HALF_XR];
__device__ __align__(1024) unsigned char g_PQ[32 * HALF_XR];
__device__ __align__(1024) unsigned char g_Wd[8 * WD_IMG];
__device__ __align__(1024) unsigned char g_G[8 * G_IMG];
__device__ __align__(1024) uint32_t g_Wt[226 * S_];
__device__ __align__(1024) float g_gate[S_];
__device__ __align__(128) unsigned int g_hflag[128 * 4];
__device__ __align__(128) unsigned int g_ep[128 * 2];
__device__ __align__(128) unsigned int g_cnt[8 * 32];

#define PROF(role, idx) do {} while (0)
#define PROFG(role, idx) do {} while (0)

__device__ __forceinline__ uint32_t s2u(const void* p) { return (uint32_t)__cvta_generic_to_shared(p); }
__device__ __forceinline__ void mbar_init(uint32_t b, int c) { asm volatile("mbarrier.init.shared::cta.b64 [%0], %1;" :: "r"(b), "r"(c) : "memory"); }
__device__ __forceinline__ void mbar_expect(uint32_t b, int bytes) { asm volatile("mbarrier.arrive.expect_tx.shared::cta.b64 _, [%0], %1;" :: "r"(b), "r"(bytes) : "memory"); }
__device__ __forceinline__ void mbar_arrive(uint32_t b) { asm volatile("mbarrier.arrive.shared::cta.b64 _, [%0];" :: "r"(b) : "memory"); }
__device__ __forceinline__ void mbar_wait(uint32_t b, int ph) {
  asm volatile("{\n.reg .pred p;\n.reg .u32 c;\nmov.u32 c, 0;\nL_WAIT:\nmbarrier.try_wait.parity.shared::cta.b64 p, [%0], %1;\n@p bra.uni L_DONE;\n"
               "add.u32 c, c, 1;\nsetp.lt.u32 p, c, 4194304;\n@p bra.uni L_WAIT;\ntrap;\nL_DONE:\n}" :: "r"(b), "r"(ph) : "memory");
}
__device__ __forceinline__ void mbar_wait_cluster(uint32_t b, int ph) {
  asm volatile("{\n.reg .pred p;\n.reg .u32 c;\nmov.u32 c, 0;\nL_WAIT:\nmbarrier.try_wait.parity.acquire.cluster.shared::cta.b64 p, [%0], %1;\n@p bra.uni L_DONE;\n"
               "add.u32 c, c, 1;\nsetp.lt.u32 p, c, 4194304;\n@p bra.uni L_WAIT;\ntrap;\nL_DONE:\n}" :: "r"(b), "r"(ph) : "memory");
}
__device__ __forceinline__ uint32_t ld_acquire(const unsigned int* p) { uint32_t v; asm volatile("ld.acquire.gpu.global.u32 %0, [%1];" : "=r"(v) : "l"(p) : "memory"); return v; }
__device__ __forceinline__ uint32_t ld_relaxed(const unsigned int* p) { uint32_t v; asm volatile("ld.relaxed.gpu.global.u32 %0, [%1];" : "=r"(v) : "l"(p) : "memory"); return v; }
__device__ __forceinline__ void wait_ge(const unsigned int* p, uint32_t target) {
#pragma unroll 1
  for (int i = 0; i < (1 << 22); i++) { if ((int)(ld_acquire(p) - target) >= 0) return; }
  __trap();
}
__device__ __forceinline__ void red_release(unsigned int* p) { asm volatile("red.release.gpu.global.add.u32 [%0], 1;" :: "l"(p) : "memory"); }
__device__ __forceinline__ bool elect() { uint32_t p; asm volatile("{\n.reg .pred p;\nelect.sync _|p, 0xffffffff;\nselp.u32 %0, 1, 0, p;\n}" : "=r"(p)); return p; }
__device__ __forceinline__ void fence_async_smem() { asm volatile("fence.proxy.async.shared::cta;" ::: "memory"); }
__device__ __forceinline__ void fence_async_global() { asm volatile("fence.proxy.async.global;" ::: "memory"); }
template <int ID, int N> __device__ __forceinline__ void bar_sync() { asm volatile("bar.sync %0, %1;" :: "n"(ID), "n"(N) : "memory"); }
template <int ID, int N> __device__ __forceinline__ void bar_arrive() { asm volatile("bar.arrive %0, %1;" :: "n"(ID), "n"(N) : "memory"); }
__device__ __forceinline__ void tma2d(uint32_t dst, const CUtensorMap* tm, int c0, int c1, uint32_t bar) {
  asm volatile("cp.async.bulk.tensor.2d.shared::cluster.global.mbarrier::complete_tx::bytes [%0], [%1, {%3, %4}], [%2];"
               :: "r"(dst), "l"(tm), "r"(bar), "r"(c0), "r"(c1) : "memory");
}
__device__ __forceinline__ void tma3d(uint32_t dst, const CUtensorMap* tm, int c0, int c1, int c2, uint32_t bar) {
  asm volatile("cp.async.bulk.tensor.3d.shared::cluster.global.mbarrier::complete_tx::bytes [%0], [%1, {%3, %4, %5}], [%2];"
               :: "r"(dst), "l"(tm), "r"(bar), "r"(c0), "r"(c1), "r"(c2) : "memory");
}
__device__ __forceinline__ void bulk_g2s(uint32_t dst, const void* src, int bytes, uint32_t bar) {
  asm volatile("cp.async.bulk.shared::cluster.global.mbarrier::complete_tx::bytes [%0], [%1], %2, [%3];"
               :: "r"(dst), "l"(src), "r"(bytes), "r"(bar) : "memory");
}
__device__ __forceinline__ void prefetch_l2(const void* src, int bytes) {
  asm volatile("cp.async.bulk.prefetch.L2.global [%0], %1;" :: "l"(src), "r"(bytes) : "memory");
}
__device__ __forceinline__ uint64_t mkdesc(uint32_t addr, uint32_t lbo, uint32_t sbo, uint32_t mode) {
  return (uint64_t)((addr & 0x3FFFF) >> 4) | ((uint64_t)(lbo >> 4) << 16) | ((uint64_t)(sbo >> 4) << 32) | ((uint64_t)mode << 62);
}
__device__ __forceinline__ void wg_fence() { asm volatile("wgmma.fence.sync.aligned;" ::: "memory"); }
__device__ __forceinline__ void wg_commit() { asm volatile("wgmma.commit_group.sync.aligned;" ::: "memory"); }
template <int N> __device__ __forceinline__ void wg_wait() { asm volatile("wgmma.wait_group.sync.aligned %0;" :: "n"(N) : "memory"); }
template <int N> __device__ __forceinline__ void keep(float (&d)[N]) {
#pragma unroll
  for (int i = 0; i < N; i++) asm volatile("" : "+f"(d[i]) :: "memory");
}
__device__ __forceinline__ uint32_t pack_bf16(float lo, float hi) { uint32_t r; asm("cvt.rn.bf16x2.f32 %0, %1, %2;" : "=r"(r) : "f"(hi), "f"(lo)); return r; }
__device__ __forceinline__ float bf16_round(float v) { return __bfloat162float(__float2bfloat16_rn(v)); }
__device__ __forceinline__ void sts128(uint32_t a, uint32_t x, uint32_t y, uint32_t z, uint32_t w) { asm volatile("st.shared.v4.b32 [%0], {%1,%2,%3,%4};" :: "r"(a), "r"(x), "r"(y), "r"(z), "r"(w) : "memory"); }
__device__ __forceinline__ void sts128f(uint32_t a, float x, float y, float z, float w) { asm volatile("st.shared.v4.f32 [%0], {%1,%2,%3,%4};" :: "r"(a), "f"(x), "f"(y), "f"(z), "f"(w) : "memory"); }
__device__ __forceinline__ void sts64f(uint32_t a, float x, float y) { asm volatile("st.shared.v2.f32 [%0], {%1,%2};" :: "r"(a), "f"(x), "f"(y) : "memory"); }
__device__ __forceinline__ void sts32(uint32_t a, uint32_t x) { asm volatile("st.shared.b32 [%0], %1;" :: "r"(a), "r"(x) : "memory"); }
__device__ __forceinline__ float4 lds128f(uint32_t a) { float4 v; asm volatile("ld.shared.v4.f32 {%0,%1,%2,%3}, [%4];" : "=f"(v.x), "=f"(v.y), "=f"(v.z), "=f"(v.w) : "r"(a) : "memory"); return v; }
__device__ __forceinline__ float2 lds64f(uint32_t a) { float2 v; asm volatile("ld.shared.v2.f32 {%0,%1}, [%2];" : "=f"(v.x), "=f"(v.y) : "r"(a) : "memory"); return v; }
__device__ __forceinline__ uint32_t lds32(uint32_t a) { uint32_t v; asm volatile("ld.shared.b32 %0, [%1];" : "=r"(v) : "r"(a) : "memory"); return v; }

__device__ __forceinline__ uint2 lds64(uint32_t a) { uint2 v; asm volatile("ld.shared.v2.b32 {%0,%1}, [%2];" : "=r"(v.x), "=r"(v.y) : "r"(a) : "memory"); return v; }
__device__ __forceinline__ float bf_lo(uint32_t w) { return __uint_as_float(w << 16); }
__device__ __forceinline__ float bf_hi(uint32_t w) { return __uint_as_float(w & 0xffff0000u); }
__device__ __forceinline__ uint32_t opaque(uint32_t v) { asm volatile("" : "+r"(v)); return v; }
__device__ __forceinline__ uint32_t ldg32(const void* p) { uint32_t v; asm volatile("ld.global.nc.b32 %0, [%1];" : "=r"(v) : "l"(p)); return v; }
__device__ __forceinline__ uint4 ldg128(const void* p) { uint4 v; asm volatile("ld.global.nc.v4.b32 {%0,%1,%2,%3}, [%4];" : "=r"(v.x), "=r"(v.y), "=r"(v.z), "=r"(v.w) : "l"(p)); return v; }
__device__ __forceinline__ void stg128(void* p, uint32_t x, uint32_t y, uint32_t z, uint32_t w) { asm volatile("st.global.v4.b32 [%0], {%1,%2,%3,%4};" :: "l"(p), "r"(x), "r"(y), "r"(z), "r"(w) : "memory"); }
template <int TB> __device__ __forceinline__ void wgmma_rs_128(float (&d)[64], const uint32_t (&a)[4], uint64_t db, int sc) {
  asm volatile("{\n.reg .pred p;\nsetp.ne.b32 p, %69, 0;\n"
    "wgmma.mma_async.sync.aligned.m64n128k16.f32.bf16.bf16 {%0, %1, %2, %3, %4, %5, %6, %7, %8, %9, %10, %11, %12, %13, %14, %15, %16, %17, %18, %19, %20, %21, %22, %23, %24, %25, %26, %27, %28, %29, %30, %31, %32, %33, %34, %35, %36, %37, %38, %39, %40, %41, %42, %43, %44, %45, %46, %47, %48, %49, %50, %51, %52, %53, %54, %55, %56, %57, %58, %59, %60, %61, %62, %63}, {%64, %65, %66, %67}, %68, p, 1, 1, %70;\n}\n"
    : "+f"(d[0]), "+f"(d[1]), "+f"(d[2]), "+f"(d[3]), "+f"(d[4]), "+f"(d[5]), "+f"(d[6]), "+f"(d[7]), "+f"(d[8]), "+f"(d[9]), "+f"(d[10]), "+f"(d[11]), "+f"(d[12]), "+f"(d[13]), "+f"(d[14]), "+f"(d[15]), "+f"(d[16]), "+f"(d[17]), "+f"(d[18]), "+f"(d[19]), "+f"(d[20]), "+f"(d[21]), "+f"(d[22]), "+f"(d[23]), "+f"(d[24]), "+f"(d[25]), "+f"(d[26]), "+f"(d[27]), "+f"(d[28]), "+f"(d[29]), "+f"(d[30]), "+f"(d[31]), "+f"(d[32]), "+f"(d[33]), "+f"(d[34]), "+f"(d[35]), "+f"(d[36]), "+f"(d[37]), "+f"(d[38]), "+f"(d[39]), "+f"(d[40]), "+f"(d[41]), "+f"(d[42]), "+f"(d[43]), "+f"(d[44]), "+f"(d[45]), "+f"(d[46]), "+f"(d[47]), "+f"(d[48]), "+f"(d[49]), "+f"(d[50]), "+f"(d[51]), "+f"(d[52]), "+f"(d[53]), "+f"(d[54]), "+f"(d[55]), "+f"(d[56]), "+f"(d[57]), "+f"(d[58]), "+f"(d[59]), "+f"(d[60]), "+f"(d[61]), "+f"(d[62]), "+f"(d[63])
    : "r"(a[0]), "r"(a[1]), "r"(a[2]), "r"(a[3]), "l"(db), "r"(sc), "n"(TB));
}
template <int TB> __device__ __forceinline__ void wgmma_rs_64(float (&d)[32], const uint32_t (&a)[4], uint64_t db, int sc) {
  asm volatile("{\n.reg .pred p;\nsetp.ne.b32 p, %37, 0;\n"
    "wgmma.mma_async.sync.aligned.m64n64k16.f32.bf16.bf16 {%0, %1, %2, %3, %4, %5, %6, %7, %8, %9, %10, %11, %12, %13, %14, %15, %16, %17, %18, %19, %20, %21, %22, %23, %24, %25, %26, %27, %28, %29, %30, %31}, {%32, %33, %34, %35}, %36, p, 1, 1, %38;\n}\n"
    : "+f"(d[0]), "+f"(d[1]), "+f"(d[2]), "+f"(d[3]), "+f"(d[4]), "+f"(d[5]), "+f"(d[6]), "+f"(d[7]), "+f"(d[8]), "+f"(d[9]), "+f"(d[10]), "+f"(d[11]), "+f"(d[12]), "+f"(d[13]), "+f"(d[14]), "+f"(d[15]), "+f"(d[16]), "+f"(d[17]), "+f"(d[18]), "+f"(d[19]), "+f"(d[20]), "+f"(d[21]), "+f"(d[22]), "+f"(d[23]), "+f"(d[24]), "+f"(d[25]), "+f"(d[26]), "+f"(d[27]), "+f"(d[28]), "+f"(d[29]), "+f"(d[30]), "+f"(d[31])
    : "r"(a[0]), "r"(a[1]), "r"(a[2]), "r"(a[3]), "l"(db), "r"(sc), "n"(TB));
}
template <int TB> __device__ __forceinline__ void wgmma_rs_56(float (&d)[28], const uint32_t (&a)[4], uint64_t db, int sc) {
  asm volatile("{\n.reg .pred p;\nsetp.ne.b32 p, %33, 0;\n"
    "wgmma.mma_async.sync.aligned.m64n56k16.f32.bf16.bf16 {%0, %1, %2, %3, %4, %5, %6, %7, %8, %9, %10, %11, %12, %13, %14, %15, %16, %17, %18, %19, %20, %21, %22, %23, %24, %25, %26, %27}, {%28, %29, %30, %31}, %32, p, 1, 1, %34;\n}\n"
    : "+f"(d[0]), "+f"(d[1]), "+f"(d[2]), "+f"(d[3]), "+f"(d[4]), "+f"(d[5]), "+f"(d[6]), "+f"(d[7]), "+f"(d[8]), "+f"(d[9]), "+f"(d[10]), "+f"(d[11]), "+f"(d[12]), "+f"(d[13]), "+f"(d[14]), "+f"(d[15]), "+f"(d[16]), "+f"(d[17]), "+f"(d[18]), "+f"(d[19]), "+f"(d[20]), "+f"(d[21]), "+f"(d[22]), "+f"(d[23]), "+f"(d[24]), "+f"(d[25]), "+f"(d[26]), "+f"(d[27])
    : "r"(a[0]), "r"(a[1]), "r"(a[2]), "r"(a[3]), "l"(db), "r"(sc), "n"(TB));
}
template <int TA, int TB> __device__ __forceinline__ void wgmma_ss_112(float (&d)[56], uint64_t da, uint64_t db, int sc) {
  asm volatile("{\n.reg .pred p;\nsetp.ne.b32 p, %58, 0;\n"
    "wgmma.mma_async.sync.aligned.m64n112k16.f32.bf16.bf16 {%0, %1, %2, %3, %4, %5, %6, %7, %8, %9, %10, %11, %12, %13, %14, %15, %16, %17, %18, %19, %20, %21, %22, %23, %24, %25, %26, %27, %28, %29, %30, %31, %32, %33, %34, %35, %36, %37, %38, %39, %40, %41, %42, %43, %44, %45, %46, %47, %48, %49, %50, %51, %52, %53, %54, %55}, %56, %57, p, 1, 1, %59, %60;\n}\n"
    : "+f"(d[0]), "+f"(d[1]), "+f"(d[2]), "+f"(d[3]), "+f"(d[4]), "+f"(d[5]), "+f"(d[6]), "+f"(d[7]), "+f"(d[8]), "+f"(d[9]), "+f"(d[10]), "+f"(d[11]), "+f"(d[12]), "+f"(d[13]), "+f"(d[14]), "+f"(d[15]), "+f"(d[16]), "+f"(d[17]), "+f"(d[18]), "+f"(d[19]), "+f"(d[20]), "+f"(d[21]), "+f"(d[22]), "+f"(d[23]), "+f"(d[24]), "+f"(d[25]), "+f"(d[26]), "+f"(d[27]), "+f"(d[28]), "+f"(d[29]), "+f"(d[30]), "+f"(d[31]), "+f"(d[32]), "+f"(d[33]), "+f"(d[34]), "+f"(d[35]), "+f"(d[36]), "+f"(d[37]), "+f"(d[38]), "+f"(d[39]), "+f"(d[40]), "+f"(d[41]), "+f"(d[42]), "+f"(d[43]), "+f"(d[44]), "+f"(d[45]), "+f"(d[46]), "+f"(d[47]), "+f"(d[48]), "+f"(d[49]), "+f"(d[50]), "+f"(d[51]), "+f"(d[52]), "+f"(d[53]), "+f"(d[54]), "+f"(d[55])
    : "l"(da), "l"(db), "r"(sc), "n"(TA), "n"(TB));
}
template <int TA, int TB> __device__ __forceinline__ void wgmma_ss_56(float (&d)[28], uint64_t da, uint64_t db, int sc) {
  asm volatile("{\n.reg .pred p;\nsetp.ne.b32 p, %30, 0;\n"
    "wgmma.mma_async.sync.aligned.m64n56k16.f32.bf16.bf16 {%0, %1, %2, %3, %4, %5, %6, %7, %8, %9, %10, %11, %12, %13, %14, %15, %16, %17, %18, %19, %20, %21, %22, %23, %24, %25, %26, %27}, %28, %29, p, 1, 1, %31, %32;\n}\n"
    : "+f"(d[0]), "+f"(d[1]), "+f"(d[2]), "+f"(d[3]), "+f"(d[4]), "+f"(d[5]), "+f"(d[6]), "+f"(d[7]), "+f"(d[8]), "+f"(d[9]), "+f"(d[10]), "+f"(d[11]), "+f"(d[12]), "+f"(d[13]), "+f"(d[14]), "+f"(d[15]), "+f"(d[16]), "+f"(d[17]), "+f"(d[18]), "+f"(d[19]), "+f"(d[20]), "+f"(d[21]), "+f"(d[22]), "+f"(d[23]), "+f"(d[24]), "+f"(d[25]), "+f"(d[26]), "+f"(d[27])
    : "l"(da), "l"(db), "r"(sc), "n"(TA), "n"(TB));
}

__device__ __forceinline__ void cs448(int idx, float& c, float& s) {
  if (idx > 224) idx -= 448;
  float a = (float)idx * (6.283185307179586f / 448.0f);
  c = __cosf(a); s = __sinf(a);
}

__device__ __forceinline__ float2 cmul(float2 a, float2 b) { return make_float2(a.x * b.x - a.y * b.y, a.x * b.y + a.y * b.x); }
__device__ __forceinline__ void fft4(float2& a0, float2& a1, float2& a2, float2& a3) {
  float2 t0 = make_float2(a0.x + a2.x, a0.y + a2.y), t1 = make_float2(a0.x - a2.x, a0.y - a2.y);
  float2 t2 = make_float2(a1.x + a3.x, a1.y + a3.y), t3 = make_float2(a1.x - a3.x, a1.y - a3.y);
  a0 = make_float2(t0.x + t2.x, t0.y + t2.y); a2 = make_float2(t0.x - t2.x, t0.y - t2.y);
  a1 = make_float2(t1.x + t3.y, t1.y - t3.x); a3 = make_float2(t1.x - t3.y, t1.y + t3.x);
}
__device__ __forceinline__ float2 mul_w8_1(float2 a) { const float r = 0.70710678118654752f; return make_float2((a.x + a.y) * r, (a.y - a.x) * r); }
__device__ __forceinline__ float2 mul_w8_3(float2 a) { const float r = 0.70710678118654752f; return make_float2((a.y - a.x) * r, -(a.x + a.y) * r); }
__device__ __forceinline__ float2 mul_mi(float2 a) { return make_float2(a.y, -a.x); }
template <int O, int ST, int N> __device__ __forceinline__ void fft8(float2 (&v)[N]) {
  fft4(v[O], v[O + 2 * ST], v[O + 4 * ST], v[O + 6 * ST]);
  fft4(v[O + ST], v[O + 3 * ST], v[O + 5 * ST], v[O + 7 * ST]);
  float2 o0 = v[O + ST], o1 = mul_w8_1(v[O + 3 * ST]), o2 = mul_mi(v[O + 5 * ST]), o3 = mul_w8_3(v[O + 7 * ST]);
  float2 e0 = v[O], e1 = v[O + 2 * ST], e2 = v[O + 4 * ST], e3 = v[O + 6 * ST];
  v[O] = make_float2(e0.x + o0.x, e0.y + o0.y);          v[O + 4 * ST] = make_float2(e0.x - o0.x, e0.y - o0.y);
  v[O + ST] = make_float2(e1.x + o1.x, e1.y + o1.y);     v[O + 5 * ST] = make_float2(e1.x - o1.x, e1.y - o1.y);
  v[O + 2 * ST] = make_float2(e2.x + o2.x, e2.y + o2.y); v[O + 6 * ST] = make_float2(e2.x - o2.x, e2.y - o2.y);
  v[O + 3 * ST] = make_float2(e3.x + o3.x, e3.y + o3.y); v[O + 7 * ST] = make_float2(e3.x - o3.x, e3.y - o3.y);
}
__device__ __forceinline__ void fft16(float2 (&v)[16]) {
  const float c1 = 0.92387953251128674f, s1 = 0.38268343236508977f;
#pragma unroll
  for (int a = 0; a < 4; a++) fft4(v[a], v[a + 4], v[a + 8], v[a + 12]);
  v[5] = cmul(v[5], make_float2(c1, -s1)); v[9] = mul_w8_1(v[9]); v[13] = cmul(v[13], make_float2(s1, -c1));
  v[6] = mul_w8_1(v[6]); v[10] = mul_mi(v[10]); v[14] = mul_w8_3(v[14]);
  v[7] = cmul(v[7], make_float2(s1, -c1)); v[11] = mul_w8_3(v[11]); v[15] = cmul(v[15], make_float2(-c1, s1));
#pragma unroll
  for (int b = 0; b < 4; b++) fft4(v[4 * b], v[4 * b + 1], v[4 * b + 2], v[4 * b + 3]);
  float2 t;
  t = v[1]; v[1] = v[4]; v[4] = t;  t = v[2]; v[2] = v[8]; v[8] = t;  t = v[3]; v[3] = v[12]; v[12] = t;
  t = v[6]; v[6] = v[9]; v[9] = t;  t = v[7]; v[7] = v[13]; v[13] = t; t = v[11]; v[11] = v[14]; v[14] = t;
}
__device__ __forceinline__ float2 cis(float turns) { float s, c; __sincosf(turns * -6.283185307179586f, &s, &c); return make_float2(c, s); }

__device__ __forceinline__ void column(float2 (&v)[16], uint32_t sb, int t, uint32_t ws) {
  const int l16 = t & 15;
  const uint32_t row = sb + OFF_EXCH + (t >> 4) * 2304;
  const uint32_t pos = sb + OFF_EXCH + (t >> 3) * 144 + (t & 7) * 16;
  const uint32_t tw = sb + OFF_TW;
#pragma unroll 1
  for (int ps = 0; ps < 6; ps++) {
    if (ps == 0 || ps == 5) { fft8<0, 2>(v); fft8<1, 2>(v); } else fft16(v);
    if (ps == 5) break;
    if (ps == 2) {
      mbar_wait(sb + OFF_BAR + B_WFULL * 8, 0);
#pragma unroll
      for (int q = 0; q < 16; q++) {
        const uint32_t w = lds32(ws + q * 512);
        const float wr = bf_lo(w), wi = bf_hi(w);
        v[q] = make_float2(v[q].x * wi + v[q].y * wr, v[q].x * wr - v[q].y * wi);
      }
      continue;
    }
    {
      const float4 b = lds128f(tw + (ps == 0 ? 4736 : (ps == 4 ? 2048 + t * 16 : 4096 + l16 * 16)));
      const float4 s = lds128f(tw + (ps == 0 ? t * 16 : (ps == 4 ? 4608 + (t >> 4) * 16 : 4352 + l16 * 16)));
      float2 b0 = make_float2(b.x, b.y), b1 = make_float2(b.z, b.w);
#pragma unroll
      for (int q = 0; q < 8; q++) {
        v[2 * q] = cmul(v[2 * q], b0); v[2 * q + 1] = cmul(v[2 * q + 1], b1);
        if (q < 7) { b0 = cmul(b0, make_float2(s.x, s.y)); b1 = cmul(b1, make_float2(s.z, s.w)); }
      }
    }
    if (ps == 0) {
      bar_sync<3, 128>();
#pragma unroll
      for (int q = 0; q < 8; q++) sts128f(pos + q * 2304, v[2 * q].x, v[2 * q].y, v[2 * q + 1].x, v[2 * q + 1].y);
      bar_sync<3, 128>();
#pragma unroll
      for (int q = 0; q < 16; q++) v[q] = lds64f(row + q * 144 + l16 * 8);
    } else {
      __syncwarp();
#pragma unroll
      for (int q = 0; q < 16; q++) sts64f(row + q * 144 + l16 * 8, v[q].x, v[q].y);
      if (ps == 4) {
        bar_sync<3, 128>();
#pragma unroll
        for (int q = 0; q < 8; q++) { float4 a = lds128f(pos + q * 2304); v[2 * q] = make_float2(a.x, a.y); v[2 * q + 1] = make_float2(a.z, a.w); }
      } else {
        __syncwarp();
#pragma unroll
        for (int q = 0; q < 8; q++) { float4 a = lds128f(row + l16 * 144 + q * 16); v[2 * q] = make_float2(a.x, a.y); v[2 * q + 1] = make_float2(a.z, a.w); }
      }
    }
  }
}

template <int NH> __device__ __forceinline__ void h_epilogue(float (&acc)[NH * 8], uint32_t sdst, unsigned char* gdst) {
#pragma unroll
  for (int c = 0; c < NH / 4; c++) {
#pragma unroll
    for (int rr = 0; rr < 2; rr++) {
      uint32_t pk[4];
#pragma unroll
      for (int i = 0; i < 4; i++) {
        float hv[2];
#pragma unroll
        for (int e = 0; e < 2; e++) {
          float hg = 0.5f * acc[(4 * c + i) * 4 + rr * 2 + e], up = acc[(NH + 4 * c + i) * 4 + rr * 2 + e];
          float th; asm("tanh.approx.f32 %0, %1;" : "=f"(th) : "f"(hg));
          hv[e] = fmaf(hg, th, hg) * up;
        }
        pk[i] = pack_bf16(hv[0], hv[1]);
      }
      sts128(sdst + c * 4096 + rr * 128, pk[0], pk[1], pk[2], pk[3]);
      stg128(gdst + c * 4096 + rr * 128, pk[0], pk[1], pk[2], pk[3]);
    }
  }
}

#define LEAD1 2

__global__ void __cluster_dims__(2, 1, 1) __launch_bounds__(NTHREADS, 1)
fused_kernel(const __grid_constant__ CUtensorMap tm_x, const __grid_constant__ CUtensorMap tm_g, const __grid_constant__ CUtensorMap tm_u,
             const __grid_constant__ CUtensorMap tm_g32, const __grid_constant__ CUtensorMap tm_u32,
             const __nv_bfloat16* __restrict__ x, const __nv_bfloat16* __restrict__ w_r, const __nv_bfloat16* __restrict__ w_i,
             const __nv_bfloat16* __restrict__ w_gate, const __nv_bfloat16* __restrict__ w_up,
             const __nv_bfloat16* __restrict__ w_down, const __nv_bfloat16* __restrict__ gate_w, __nv_bfloat16* __restrict__ out) {
  extern __shared__ __align__(1024) unsigned char smem[];
  const uint32_t sb = s2u(smem);
  const uint32_t bars = sb + OFF_BAR;
  const int tid = threadIdx.x, warp = __shfl_sync(0xffffffffu, tid >> 5, 0), lane = tid & 31;
  const int bid = blockIdx.x, m = bid >> 3, n = (bid >> 1) & 3, kh = bid & 1, j = kh * 4 + n;

  if (warp >= 12) {
    asm volatile("setmaxnreg.dec.sync.aligned.u32 24;");
    const int c64 = 224 * j + (j & 1) * 32;
    if (warp == 13) {
      if (elect()) {
        PROFG(4, 0); PROF(4, 1);
        mbar_init(bars + B_XFULL * 8, 1); mbar_init(bars + (B_XFULL + 1) * 8, 1);
        fence_async_smem();
#pragma unroll
        for (int w = 0; w < 2; w++) {
          mbar_expect(bars + (B_XFULL + w) * 8, HALF_XR);
          tma3d(sb + OFF_XR + w * HALF_XR, &tm_x, 0, m * 128 + (w ^ kh ^ 1) * 64, 0, bars + (B_XFULL + w) * 8);
        }
      }
    } else if (warp == 12) {
      if (lane < NSLOT) mbar_init(bars + (B_FULL + lane) * 8, 1);
      fence_async_smem();
      __syncwarp();
#pragma unroll 1
      for (int i = 0; i < 6; i++) {
        if (elect()) {
          const uint32_t fb = bars + (B_FULL + i) * 8;
          mbar_expect(fb, SLOT);
          tma2d(sb + i * SLOT, &tm_g, c64, i * 64, fb);
          tma2d(sb + i * SLOT + 8192, &tm_u, c64, i * 64, fb);
        }
      }
      if (lane == 0) PROF(3, 3);
    } else if (warp == 14) {
      if (lane < NSLOT) mbar_init(bars + (B_EMPTY + lane) * 8, 8);
      else mbar_init(bars + (B_XFREE - NSLOT + lane) * 8, lane < NSLOT + 2 ? 4 : (lane < NSLOT + 8 ? 8 : 1));
      asm volatile("fence.mbarrier_init.release.cluster;" ::: "memory");
      __syncwarp();
      if (lane == 0) mbar_expect(bars + B_RECV * 8, 64 * 112 * 4);
    }
    bar_sync<0, NTHREADS>();
    asm volatile("barrier.cluster.arrive.relaxed.aligned;" ::: "memory");
    if (warp == 12) {
      int slot = 6, ph = 1;
      auto wait_slot = [&]() { mbar_wait(bars + (B_EMPTY + slot) * 8, ph ^ (slot == 6)); };
      auto adv = [&]() { if (++slot == NSLOT) { slot = 0; ph ^= 1; } };
      const int c32 = 224 * j + ((j & 1) ? 0 : 192);
#pragma unroll 1
      for (int i = 6; i < 25; i++) {
        wait_slot();
        if (elect()) {
          const uint32_t dst = sb + slot * SLOT, fb = bars + (B_FULL + slot) * 8;
          const bool last = i >= 21;
          const int cc = last ? c32 : c64 + 64 * (i / 7), rr = last ? slot * 128 : slot * 64;
          mbar_expect(fb, SLOT);
          tma2d(dst, last ? &tm_g32 : &tm_g, cc, rr, fb);
          tma2d(dst + 8192, last ? &tm_u32 : &tm_u, cc, rr, fb);
        }
        adv();
      }
      if (lane == 0) PROF(3, 0);
      mbar_wait(bars + B_PREP * 8, 0);
      if (lane == 0) PROF(3, 1);
      const unsigned char* wd = g_Wd + (size_t)j * WD_IMG;
      const unsigned char* hb = g_H + (size_t)(m * 8 + kh * 4) * HALF_XR;
#pragma unroll 1
      for (int i = 0; i < 16; i++) {
        const int u = i >> 2, src = i & 3, ns = (n + src) & 3;
        if (lane == 0) PROF(3, 16 + i);
        if (src != 0) {
          mbar_wait(bars + (B_HRDY + (src - 1) * 4 + u) * 8, 0);
          wait_slot();
          if (elect()) {
            if (u < 3) mbar_expect(bars + (B_FULL + slot) * 8, 16384);
            bulk_g2s(sb + slot * SLOT, hb + ns * HALF_XR + u * 16384, u < 3 ? 16384 : 8192, bars + (B_FULL + slot) * 8);
          }
          if (u < 3) adv();
        }
        wait_slot();
        if (elect()) {
          mbar_expect(bars + (B_FULL + slot) * 8, u < 3 ? 14336 : (src ? 15360 : 7168));
          bulk_g2s(sb + slot * SLOT + (u < 3 ? 0 : 8192), wd + (ns * 224 + u * 64) * 224, u < 3 ? 14336 : 7168, bars + (B_FULL + slot) * 8);
        }
        adv();
      }
#pragma unroll 1
      for (int i = 0; i < 4; i++) {
        wait_slot();
        if (elect()) {
          mbar_expect(bars + (B_FULL + slot) * 8, G_IMG / 2);
          bulk_g2s(sb + slot * SLOT, g_G + (size_t)(n * 4 + i) * (G_IMG / 2), G_IMG / 2, bars + (B_FULL + slot) * 8);
        }
        adv();
      }
      if (lane == 0) PROF(3, 2);
    } else if (warp == 13) {
      mbar_wait(bars + B_XFULL * 8, 0);
      if (elect()) {
        PROF(4, 2);
        prefetch_l2(reinterpret_cast<const unsigned char*>(w_gate) + bid * 12544, 12544);
        prefetch_l2(reinterpret_cast<const unsigned char*>(w_up) + bid * 12544, 12544);
      }
#pragma unroll 1
      for (int u = 0; u < 5; u++) {
        mbar_wait(bars + (B_PUB + u) * 8, 0);
        if (lane == 0) {
          PROF(4, 8 + u);
          red_release(u == 0 ? &g_cnt[(j >> 1) * 32] : &g_hflag[bid * 4 + u - 1]);
          PROF(4, 16 + u);
        }
        __syncwarp();
      }
    } else if (warp == 14) {
      const uint32_t epoch = ld_relaxed(&g_ep[bid * 2]);
      if (lane < 13) {
        const unsigned int* fp = lane < 12 ? &g_hflag[(m * 8 + ((n + 1 + (lane >> 2)) & 3) * 2 + kh) * 4 + (lane & 3)] : &g_cnt[4 * 32];
        const uint32_t tgt = lane < 12 ? epoch + 1 : (epoch + 1) * 128;
        const uint32_t rb = bars + (lane < 12 ? B_HRDY + lane : B_PREP) * 8;
        bool done = false;
#pragma unroll 1
        for (int i = 0; i < (1 << 20); i++) {
          if (!done && (int)(ld_acquire(fp) - tgt) >= 0) { fence_async_global(); mbar_arrive(rb); done = true; PROF(5, lane); }
          if (__all_sync(0x1fff, done)) break;
        }
        if (!done) __trap();
        if (lane == 0) g_ep[bid * 2] = epoch + 1;
      }
    } else {
      const uint32_t epoch = ld_relaxed(&g_ep[bid * 2 + 1]);
      mbar_wait(bars + (B_XFREE + 1) * 8, 0);
      if (bid < 113) {
        const int sl = (bid == 112) ? 0 : bid;
        wait_ge(&g_cnt[((sl & 1) + 2 * ((sl >> 1) / 28)) * 32], (epoch + 1) * 32);
        fence_async_global();
        if (elect()) {
          PROF(5, 16);
          mbar_expect(bars + B_XCFULL * 8, 16384);
          bulk_g2s(sb + OFF_EXCH, g_Xc + sl * 2 * S_, 16384, bars + B_XCFULL * 8);
        }
        mbar_wait(bars + B_PREP * 8, 0);
        if (elect()) {
          mbar_expect(bars + B_WFULL * 8, 16384);
          bulk_g2s(sb + OFF_WS, g_Wt + bid * S_, 8192, bars + B_WFULL * 8);
          bulk_g2s(sb + OFF_WS + 8192, g_Wt + (224 - bid) * S_, 8192, bars + B_WFULL * 8);
          PROF(5, 17);
        }
      }
      wait_ge(&g_cnt[5 * 32], (epoch + 1) * 128);
      fence_async_global();
      if (elect()) {
        PROF(5, 18);
        mbar_expect(bars + B_PQFULL * 8, HALF_XR + 256);
        const unsigned char* src = g_PQ + (size_t)(m * 2 + kh) * HALF_XR;
        bulk_g2s(sb + OFF_PQ, src, 28672, bars + B_PQFULL * 8);
        bulk_g2s(sb + OFF_PQ + 28672, src + 28672, 28672, bars + B_PQFULL * 8);
        bulk_g2s(sb + OFF_G, g_gate + m * 128 + kh * 64, 256, bars + B_PQFULL * 8);
        g_ep[bid * 2 + 1] = epoch + 1;
      }
    }
    __syncwarp();
    asm volatile("barrier.cluster.wait.aligned;" ::: "memory");
  } else if (warp < 8) {
    asm volatile("setmaxnreg.inc.sync.aligned.u32 208;");
    const int wg = warp >> 2, w4 = warp & 3, g = lane >> 2, t = lane & 3;
    const int rh = wg ^ kh ^ 1;
    const int p = j & 1, r = (j >> 1) & 1, hh = j >> 2;
#pragma unroll 1
    for (int it = tid; it < 392; it += 256) {
      int kc = it / 28, sg = it - kc * 28;
      int k = 2 * (28 * hh + sg) + r;
      float c[8], s[8];
#pragma unroll
      for (int q = 0; q < 8; q++) {
        int d = 16 * kc + 8 * (q & 1) + 2 * (q >> 1) + p;
        cs448((d * k) % 448, c[q], s[q]);
        s[q] = -s[q];
        if (k == 0) s[q] = (float)(p ? ((d & 2) - 1) : (1 - (d & 2)));
      }
      uint32_t a = sb + 6 * SLOT + (kc * 56 + 2 * sg) * 16;
      sts128(a, pack_bf16(c[0], c[1]), pack_bf16(c[2], c[3]), pack_bf16(c[4], c[5]), pack_bf16(c[6], c[7]));
      sts128(a + 16, pack_bf16(s[0], s[1]), pack_bf16(s[2], s[3]), pack_bf16(s[4], s[5]), pack_bf16(s[6], s[7]));
    }
    fence_async_smem();
    bar_sync<0, NTHREADS>();
    asm volatile("barrier.cluster.arrive.relaxed.aligned;" ::: "memory");
    if ((tid & 127) == 0) PROF(wg, 1);

    uint32_t xa[28][4];
    {
      const uint32_t xb = sb + OFF_XR + wg * HALF_XR + (w4 * 16 + (lane & 15)) * 128;
      mbar_wait(bars + (B_XFULL + wg) * 8, 0);
      if ((tid & 127) == 0) PROF(wg, 2);
#pragma unroll
      for (int kb = 0; kb < 7; kb++) {
#pragma unroll
        for (int kk = 0; kk < 4; kk++) {
          uint32_t a = xb + kb * 8192 + (((2 * kk + (lane >> 4)) ^ (lane & 7)) << 4);
          asm volatile("ldmatrix.sync.aligned.m8n8.x4.shared.b16 {%0,%1,%2,%3}, [%4];"
                       : "=r"(xa[kb * 4 + kk][0]), "=r"(xa[kb * 4 + kk][1]), "=r"(xa[kb * 4 + kk][2]), "=r"(xa[kb * 4 + kk][3]) : "r"(a) : "memory");
        }
      }
    }
    {
      uint32_t ad[7][4];
      const uint32_t sel = p ? 0x7632 : 0x5410;
      const uint32_t sgn = r ? 0xBF80BF80u : 0x3F803F80u;
#pragma unroll
      for (int jj = 0; jj < 7; jj++) {
#pragma unroll
        for (int i = 0; i < 4; i++) {
          int ks = 2 * jj + (i >> 1), rr = i & 1;
          uint32_t lo = __byte_perm(xa[ks][rr], xa[ks][rr + 2], sel);
          uint32_t hi = __byte_perm(xa[ks + 14][rr], xa[ks + 14][rr + 2], sel);
          asm("fma.rn.bf16x2 %0, %1, %2, %3;" : "=r"(ad[jj][i]) : "r"(hi), "r"(sgn), "r"(lo));
        }
      }
      __syncwarp();
      if (lane == 0) mbar_arrive(bars + (B_XFREE + wg) * 8);
      float acc[28];
      wg_fence();
      uint64_t db = mkdesc(sb + 6 * SLOT, 896, 128, 0);
#pragma unroll
      for (int jj = 0; jj < 7; jj++) wgmma_rs_56<0>(acc, ad[jj], db + jj * 112, jj != 0);
      wg_commit();
      wg_wait<0>(); keep(acc);
      if (lane == 0) mbar_arrive(bars + (B_EMPTY + 6) * 8);
      uint32_t* xc = g_Xc + (size_t)((2 * (28 * hh + t) + r) * 2 + p) * S_ + m * 128 + rh * 64 + w4 * 16 + g;
#pragma unroll
      for (int i = 0; i < 7; i++) {
        xc[i * 16 * S_] = pack_bf16(acc[4 * i], acc[4 * i + 1]);
        xc[i * 16 * S_ + 8] = pack_bf16(acc[4 * i + 2], acc[4 * i + 3]);
      }
      __syncwarp();
      if (lane == 0) mbar_arrive(bars + B_PUB * 8);
    }
    if ((tid & 127) == 0) PROF(wg, 3);
    const uint32_t hofs = t * 1024 + (w4 * 16 + g) * 16;
#pragma unroll 1
    for (int u = 0; u < 3; u++) {
      float acc[64];
      if (wg == 1) { if (u & 1) bar_sync<6, 256>(); else bar_sync<2, 256>(); }
      const uint32_t sbu = opaque(sb);
#pragma unroll
      for (int kb = 0; kb < 7; kb++) {
        mbar_wait(sbu + OFF_BAR + (B_FULL + kb) * 8, u & 1);
        wg_fence();
        uint64_t db = mkdesc(sbu + kb * SLOT, 8192, 1024, 1);
#pragma unroll
        for (int kk = 0; kk < 4; kk++) wgmma_rs_128<1>(acc, xa[kb * 4 + kk], db + kk * 128, (kb | kk) != 0);
        wg_commit();
        if (kb == LEAD1 && wg == 0) { if (u & 1) bar_arrive<6, 256>(); else bar_arrive<2, 256>(); }
        if (kb > 0) { wg_wait<1>(); if (lane == 0) mbar_arrive(sbu + OFF_BAR + (B_EMPTY + kb - 1) * 8); }
      }
      wg_wait<0>(); keep(acc);
      if (lane == 0) mbar_arrive(sbu + OFF_BAR + (B_EMPTY + 6) * 8);
      if ((tid & 127) == 0) PROF(wg, 4 + 2 * u);
      mbar_wait(sbu + OFF_BAR + B_XFREE * 8, 0);
      const uint32_t uo = u * 16384 + rh * 8192 + hofs;
      h_epilogue<8>(acc, sbu + OFF_HOWN + uo, g_H + (size_t)(m * 8 + j) * HALF_XR + uo);
      __syncwarp();
      if (lane == 0) mbar_arrive(sbu + OFF_BAR + (B_PUB + 1 + u) * 8);
      if ((tid & 127) == 0) PROF(wg, 5 + 2 * u);
    }
    {
      float acc[32];
      if (wg == 1) bar_sync<6, 256>();
      const uint32_t sbu = opaque(sb);
#pragma unroll
      for (int it = 0; it < 4; it++) {
        mbar_wait(sbu + OFF_BAR + (B_FULL + it) * 8, 1);
        wg_fence();
        uint64_t db = mkdesc(sbu + it * SLOT, 8192, 512, 2);
#pragma unroll
        for (int kk = 0; kk < 8; kk++) if (it * 8 + kk < 28) wgmma_rs_64<1>(acc, xa[it * 8 + kk], db + kk * 64, (it | kk) != 0);
        wg_commit();
        if (it == LEAD1 && wg == 0) bar_arrive<6, 256>();
        if (it > 0) { wg_wait<1>(); if (lane == 0) mbar_arrive(sbu + OFF_BAR + (B_EMPTY + it - 1) * 8); }
      }
      wg_wait<0>(); keep(acc);
      if (lane == 0) mbar_arrive(sbu + OFF_BAR + (B_EMPTY + 3) * 8);
      if ((tid & 127) == 0) PROF(wg, 10);
      const uint32_t uo = 49152 + rh * 4096 + hofs;
      h_epilogue<4>(acc, sbu + OFF_HOWN + uo, g_H + (size_t)(m * 8 + j) * HALF_XR + uo);
      __syncwarp();
      if (lane == 0) mbar_arrive(sbu + OFF_BAR + (B_PUB + 4) * 8);
    }
    fence_async_smem();
    if (wg) bar_sync<5, 128>(); else bar_sync<4, 128>();
    asm volatile("barrier.cluster.wait.aligned;" ::: "memory");
    if ((tid & 127) == 0) PROF(wg, 11);

    float acc[56];
    if (wg == 1) bar_sync<2, 256>();
#pragma unroll 1
    for (int u = 0; u < 3; u++) {
#pragma unroll
      for (int src = 0; src < 4; src++) {
        if ((tid & 127) == 0) PROF(wg, 16 + u * 4 + src);
        const int eb = 2 * src, sB = (4 + eb) % 7, sA = (3 + eb) % 7;
        if (src) mbar_wait(bars + (B_FULL + sA) * 8, (u + (eb - 1 < 3)) & 1);
        mbar_wait(bars + (B_FULL + sB) * 8, (u + (eb < 3)) & 1);
        wg_fence();
        const uint64_t da = mkdesc((src ? sb + sA * SLOT : sb + OFF_HOWN + u * 16384) + rh * 8192, 1024, 128, 0);
        const uint64_t db = mkdesc(sb + sB * SLOT, 1792, 128, 0);
#pragma unroll
        for (int kk = 0; kk < 4; kk++) wgmma_ss_112<0, 1>(acc, da + kk * 128, db + kk * 224, (src | kk) ? 1 : u);
        wg_commit();
        if (src == 1 && u == 0 && wg == 0) bar_arrive<2, 256>();
        wg_wait<1>();
        if (lane == 0 && (src | u)) {
          mbar_arrive(bars + (B_EMPTY + (src ? (2 + eb) % 7 : 3)) * 8);
          if (src != 1) mbar_arrive(bars + (B_EMPTY + (src ? (1 + eb) % 7 : 2)) * 8);
          if (src == 1 && u == 1) {
            asm volatile("{\n.reg .b32 ra;\nmapa.shared::cluster.u32 ra, %0, %1;\nmbarrier.arrive.relaxed.cluster.shared::cluster.b64 _, [ra];\n}"
                         :: "r"(bars + B_RFREE * 8), "r"(kh ^ 1) : "memory");
          }
        }
      }
    }
#pragma unroll
    for (int src = 0; src < 4; src++) {
      if ((tid & 127) == 0) PROF(wg, 28 + src);
      const int sB = (4 + src) % 7;
      mbar_wait(bars + (B_FULL + sB) * 8, src == 3);
      wg_fence();
      const uint64_t da = mkdesc((src ? sb + sB * SLOT : sb + OFF_HOWN + 49152) + rh * 4096, 1024, 128, 0);
      const uint64_t db = mkdesc(sb + sB * SLOT + 8192, 1792, 128, 0);
#pragma unroll
      for (int kk = 0; kk < 2; kk++) wgmma_ss_112<0, 1>(acc, da + kk * 128, db + kk * 224, 1);
      wg_commit();
      if (src < 2) {
        wg_wait<1>();
        if (lane == 0) { mbar_arrive(bars + (B_EMPTY + (src ? 4 : 3)) * 8); if (src == 0) mbar_arrive(bars + (B_EMPTY + 2) * 8); }
      }
    }
    const int t128 = tid & 127;
    if (wg == 0) {
      wg_wait<0>(); keep(acc);
      if (t128 == 0) PROF(wg, 12);
      mbar_wait_cluster(bars + B_RFREE * 8, 0);
      uint32_t rdst, rbar;
      asm volatile("mapa.shared::cluster.u32 %0, %1, %2;" : "=r"(rdst) : "r"(sb + OFF_HOWN + t128 * 16), "r"(kh ^ 1));
      asm volatile("mapa.shared::cluster.u32 %0, %1, %2;" : "=r"(rbar) : "r"(bars + B_RECV * 8), "r"(kh ^ 1));
#pragma unroll
      for (int i = 0; i < 14; i++)
        asm volatile("st.async.weak.shared::cluster.mbarrier::complete_tx::bytes.v4.f32 [%0], {%1,%2,%3,%4}, [%5];"
                     :: "r"(rdst + i * 2048), "f"(acc[4 * i]), "f"(acc[4 * i + 1]), "f"(acc[4 * i + 2]), "f"(acc[4 * i + 3]), "r"(rbar) : "memory");
    } else {
      float spec[2][28];
      if (t128 == 0) PROF(wg, 12);
      mbar_wait(bars + B_PQFULL * 8, 0);
      if (t128 == 0) PROF(wg, 13);
#pragma unroll
      for (int i = 0; i < 4; i++) {
        mbar_wait(bars + (B_FULL + 1 + i) * 8, 1);
        wg_fence();
        const uint64_t da = mkdesc(sb + OFF_PQ + i * 14336, 1024, 1024, 1);
        const uint64_t db = mkdesc(sb + (1 + i) * SLOT, 896, 128, 0);
#pragma unroll
        for (int kk = 0; kk < 7; kk++) wgmma_ss_56<1, 0>(spec[i >> 1], da + kk * 128, db + kk * 112, ((i & 1) | kk) != 0);
        wg_commit();
      }
      const float* gs = reinterpret_cast<const float*>(smem + OFF_G) + w4 * 16 + g;
      const float g0 = gs[0], g1 = gs[8];
      const float o0 = bf16_round(1.0f - g0), o1 = bf16_round(1.0f - g1);
      wg_wait<0>(); keep(acc); keep(spec[0]); keep(spec[1]);
      if (t128 == 0) PROF(wg, 14);
      mbar_wait_cluster(bars + B_RECV * 8, 0);
      if (t128 == 0) PROF(wg, 0);
      float4 o[14];
#pragma unroll
      for (int i = 0; i < 14; i++) o[i] = lds128f(sb + OFF_HOWN + t128 * 16 + i * 2048);
      bar_sync<5, 128>();
      const uint32_t st = sb + OFF_PQ + w4 * 3840;
#pragma unroll
      for (int i = 0; i < 7; i++) {
        uint32_t pk[4];
#pragma unroll
        for (int e = 0; e < 2; e++) {
          const int c = 2 * i + e, si = i * 4 + e;
          pk[2 * e] = pack_bf16(fmaf(acc[4 * c] + o[c].x, o0, g0 * spec[0][si]), fmaf(acc[4 * c + 1] + o[c].y, o0, g0 * spec[1][si]));
          pk[2 * e + 1] = pack_bf16(fmaf(acc[4 * c + 2] + o[c].z, o1, g1 * spec[0][si + 2]), fmaf(acc[4 * c + 3] + o[c].w, o1, g1 * spec[1][si + 2]));
        }
        asm volatile("stmatrix.sync.aligned.m8n8.x4.shared.b16 [%0], {%1,%2,%3,%4};"
                     :: "r"(st + (lane & 15) * 240 + (lane >> 4) * 16 + i * 32), "r"(pk[0]), "r"(pk[1]), "r"(pk[2]), "r"(pk[3]) : "memory");
      }
      __syncwarp();
      if (lane < 28) {
        const int r2 = lane >= 14, cc = lane - r2 * 14;
        unsigned char* ob = reinterpret_cast<unsigned char*>(out) + (size_t)(m * 128 + kh * 64 + w4 * 16 + r2) * (D_ * 2) + n * 224 + cc * 16;
        float4 v[8];
#pragma unroll
        for (int i = 0; i < 8; i++) v[i] = lds128f(st + r2 * 240 + cc * 16 + i * 480);
#pragma unroll
        for (int i = 0; i < 8; i++) stg128(ob + i * (D_ * 4), __float_as_uint(v[i].x), __float_as_uint(v[i].y), __float_as_uint(v[i].z), __float_as_uint(v[i].w));
      }
    }
    if (t128 == 0) { PROF(wg, 15); if (wg) { PROFG(4, 30); PROF(4, 31); } }
  } else {
    asm volatile("setmaxnreg.dec.sync.aligned.u32 72;");
    const int t = tid - 256;
    const int k = bid;
    if (t == 0) PROF(2, 0);
    if (t < 98) {
      int cid = m * 98 + t, kc = cid / 56, nn = cid - kc * 56;
      int d = 112 * n + 8 * (2 * (nn >> 3) + (nn & 1)) + (nn & 6) + kh;
      uint32_t pk[4];
#pragma unroll
      for (int e = 0; e < 4; e++) {
        int kk = 4 * kc + e; float c, s;
        cs448((d * kk) % 448, c, s); s = -s;
        if (kk == 0) s = (float)(kh ? ((d & 2) - 1) : (1 - (d & 2)));
        pk[e] = pack_bf16(c, s);
      }
      stg128(g_G + (size_t)(n * 2 + kh) * G_IMG + cid * 16, pk[0], pk[1], pk[2], pk[3]);
    }
    bar_sync<0, NTHREADS>();
    asm volatile("barrier.cluster.arrive.relaxed.aligned;" ::: "memory");
    mbar_wait(bars + B_XFULL * 8, 0);
    if (t == 0) PROF(2, 8);
    {
      const int c0 = 2 * (t >> 2) - (bid & 1);
      const int ofs = ((bid & 7) + 128 * (bid >> 3) + 32 * (t & 3)) * DF_ + c0;
      uint32_t a[16], b[16];
#pragma unroll
      for (int rd = 0; rd < 4; rd++) {
#pragma unroll
        for (int i = 0; i < 4; i++) {
          if (rd < 3 || t < 68) { a[rd * 4 + i] = ldg32(w_r + ofs + rd * 64 + i * 8 * DF_); b[rd * 4 + i] = ldg32(w_i + ofs + rd * 64 + i * 8 * DF_); }
        }
      }
      uint4 wd[7];
      const unsigned char* wsrc = reinterpret_cast<const unsigned char*>(w_down) + bid * 12544 + (t & 1) * 896 + (t >> 1) * 16;
      if (t < 112) {
#pragma unroll
        for (int i = 0; i < 4; i++) wd[i] = ldg128(wsrc + i * 1792);
      } else if (t == 127) prefetch_l2(reinterpret_cast<const unsigned char*>(w_down) + bid * 12544 + 7168, 5376);
      uint32_t* dst = g_Wt + c0 * S_ + 16 * bid + 4 * (t & 3);
#pragma unroll
      for (int rd = 0; rd < 4; rd++) {
        if (rd < 3 || t < 68) {
          if (rd > 0 || c0 >= 0)
            stg128(dst + rd * 64 * S_, __byte_perm(a[4 * rd], b[4 * rd], 0x5410), __byte_perm(a[4 * rd + 1], b[4 * rd + 1], 0x5410),
                   __byte_perm(a[4 * rd + 2], b[4 * rd + 2], 0x5410), __byte_perm(a[4 * rd + 3], b[4 * rd + 3], 0x5410));
          stg128(dst + (rd * 64 + 1) * S_, __byte_perm(a[4 * rd], b[4 * rd], 0x7632), __byte_perm(a[4 * rd + 1], b[4 * rd + 1], 0x7632),
                 __byte_perm(a[4 * rd + 2], b[4 * rd + 2], 0x7632), __byte_perm(a[4 * rd + 3], b[4 * rd + 3], 0x7632));
        }
      }
      if (t == 0) PROF(2, 9);
      if (t < 112) {
#pragma unroll
        for (int i = 4; i < 7; i++) wd[i] = ldg128(wsrc + i * 1792);
        const int js = bid >> 4, nn = (t >> 1) / 14, cc = (t >> 1) - nn * 14;
        unsigned char* wdst = g_Wd + (size_t)((js >> 2) * 4 + nn) * WD_IMG + (js & 3) * 28 * 1792 + cc * 128 + (t & 1) * 16;
#pragma unroll
        for (int i = 0; i < 7; i++) {
          const int col = 14 * (bid & 15) + 2 * i, grp = col >> 5;
          const int kg = (js & 1) ? (grp ? grp - 1 : 6) : grp;
          stg128(wdst + (kg * 4 + ((col >> 1) & 3)) * 1792 + ((col >> 3) & 3) * 32, wd[i].x, wd[i].y, wd[i].z, wd[i].w);
        }
      }
    }
    bar_sync<3, 128>();
    if (t == 96) { PROF(2, 10); red_release(&g_cnt[4 * 32]); PROF(2, 1); }
    {
      const int row = m * 128 + j * 16 + (t >> 3), l8 = t & 7;
      const uint4* xr = reinterpret_cast<const uint4*>(x + (size_t)row * D_);
      const uint4* gw = reinterpret_cast<const uint4*>(gate_w);
      float sum = 0.f;
      uint4 xv[7], gv[7];
#pragma unroll
      for (int i = 0; i < 7; i++) { xv[i] = ldg128(xr + i * 8 + l8); gv[i] = ldg128(gw + i * 8 + l8); }
#pragma unroll
      for (int i = 0; i < 7; i++) {
        uint4 a = xv[i], b = gv[i];
        uint32_t aa[4] = {a.x, a.y, a.z, a.w}, bb[4] = {b.x, b.y, b.z, b.w};
#pragma unroll
        for (int e = 0; e < 4; e++) {
          uint32_t pr; asm("mul.rn.bf16x2 %0, %1, %2;" : "=r"(pr) : "r"(aa[e]), "r"(bb[e]));
          sum += bf_lo(pr) + bf_hi(pr);
        }
      }
      sum += __shfl_xor_sync(0xffffffffu, sum, 1); sum += __shfl_xor_sync(0xffffffffu, sum, 2); sum += __shfl_xor_sync(0xffffffffu, sum, 4);
      if (l8 == 0) g_gate[row] = bf16_round(1.0f / (1.0f + __expf(-bf16_round(sum))));
    }
    if (t == 0) PROF(2, 11);
    if (k < 113) {
      mbar_wait(bars + (B_XFREE + 1) * 8, 0);
      {
        const uint32_t tw = sb + OFF_TW;
        const float r = (float)(t >> 4), l = (float)(t & 15);
        const float2 a0 = cis((float)(2 * t) / 2048.0f), a1 = cis((float)(2 * t + 1) / 2048.0f);
        const float2 c0 = cis(r * l / 2048.0f), c1 = cis(r * (l + 16.0f) / 2048.0f);
        sts128f(tw + t * 16, a0.x, a0.y, a1.x, a1.y);
        sts128f(tw + 2048 + t * 16, c0.x, c0.y, c1.x, c1.y);
        if (t < 41) {
          const float2 q = cis(t < 16 ? l / 256.0f : (t < 32 ? l / 128.0f : (t < 40 ? l / 64.0f : 0.f)));
          sts128f(tw + 4096 + t * 16, t < 16 ? 1.0f : q.x, t < 16 ? 0.0f : q.y, q.x, q.y);
        }
      }
      if (t == 0) PROF(2, 2);
      mbar_wait(bars + B_XCFULL * 8, 0);
      if (t == 0) PROF(2, 3);
      float2 v[16];
      const uint32_t mre = (k == 112) ? 0u : 0xffffffffu, mim = (k == 0) ? 0u : 0xffff0000u;
#pragma unroll
      for (int jj = 0; jj < 8; jj++) {
        uint2 e = lds64(sb + OFF_EXCH + jj * 1024 + t * 8), o = lds64(sb + OFF_EXCH + 8192 + jj * 1024 + t * 8);
        if (k == 112) { e.x >>= 16; e.y >>= 16; }
        const float e0 = bf_lo(e.x), e1 = __uint_as_float(e.x & mim), e2 = bf_lo(e.y), e3 = __uint_as_float(e.y & mim);
        const float o0 = bf_lo(o.x & mre), o1 = __uint_as_float(o.x & mim), o2 = bf_lo(o.y & mre), o3 = __uint_as_float(o.y & mim);
        v[2 * jj] = make_float2(e0 + o0, e1 + o1); v[2 * jj + 1] = make_float2(e2 + o2, e3 + o3);
        sts128f(sb + OFF_STASH + jj * 2048 + t * 16, e0 - o0, o1 - e1, e2 - o2, o3 - e3);
      }
      bar_sync<3, 128>();
      const float sc = ((k == 0 || k == 112) ? 1.0f : 2.0f) / (float)(S_ * D_);
#pragma unroll 1
      for (int col = 0; col < 2; col++) {
        if (t == 0) PROF(2, 12 + col);
        column(v, sb, t, sb + OFF_WS + col * 8192 + t * 4);
        if (t == 0) PROF(2, 14 + col);
        if (col == 0) {
#pragma unroll
          for (int jj = 0; jj < 8; jj++) {
            const float4 a = lds128f(sb + OFF_STASH + jj * 2048 + t * 16);
            sts128f(sb + OFF_STASH + jj * 2048 + t * 16, v[2 * jj].x * sc, v[2 * jj].y * sc, v[2 * jj + 1].x * sc, v[2 * jj + 1].y * sc);
            v[2 * jj] = make_float2(a.x, a.y); v[2 * jj + 1] = make_float2(a.z, a.w);
          }
        }
      }
      const int pre = (k == 112) ? 1 : 2 * k, pim = (k == 112) ? 1 : 2 * k + 1;
      uint32_t* pq = reinterpret_cast<uint32_t*>(g_PQ) + (t >> 5) * 14336;
      const int ore = pre * 32 + ((((lane >> 2) ^ pre) & 7) << 2) + (lane & 3);
      const int oim = pim * 32 + ((((lane >> 2) ^ pim) & 7) << 2) + (lane & 3);
#pragma unroll
      for (int jj = 0; jj < 8; jj++) {
        float4 a = lds128f(sb + OFF_STASH + jj * 2048 + t * 16);
        uint32_t* pb = pq + jj * 57344;
        uint32_t p_re = pack_bf16(a.y + sc * v[2 * jj].y, a.w + sc * v[2 * jj + 1].y), p_im = pack_bf16(a.x - sc * v[2 * jj].x, a.z - sc * v[2 * jj + 1].x);
        uint32_t q_re = pack_bf16(a.y - sc * v[2 * jj].y, a.w - sc * v[2 * jj + 1].y), q_im = pack_bf16(a.x + sc * v[2 * jj].x, a.z + sc * v[2 * jj + 1].x);
        pb[ore] = p_re;
        if (k != 112) pb[7168 + ore] = q_re;
        if (k != 0) pb[7168 + oim] = q_im;
        if (k != 0 && k != 112) pb[oim] = p_im;
      }
      fence_async_smem();
    }
    bar_sync<3, 128>();
    if (t == 0) { PROF(2, 5); red_release(&g_cnt[5 * 32]); PROF(2, 7); }
    __syncwarp();
    asm volatile("barrier.cluster.wait.aligned;" ::: "memory");
  }
}

typedef CUresult (*EncodeFn)(CUtensorMap*, CUtensorMapDataType, cuuint32_t, void*, const cuuint64_t*, const cuuint64_t*, const cuuint32_t*,
                             const cuuint32_t*, CUtensorMapInterleave, CUtensorMapSwizzle, CUtensorMapL2promotion, CUtensorMapFloatOOBfill);

void make_map(EncodeFn enc, CUtensorMap* tm, const void* base, int cols, int rows, int bc, int br, CUtensorMapSwizzle sw) {
  cuuint64_t gd[2] = {(cuuint64_t)cols, (cuuint64_t)rows};
  cuuint64_t gs[1] = {(cuuint64_t)cols * 2};
  cuuint32_t bd[2] = {(cuuint32_t)bc, (cuuint32_t)br};
  cuuint32_t es[2] = {1, 1};
  enc(tm, CU_TENSOR_MAP_DATA_TYPE_BFLOAT16, 2, const_cast<void*>(base), gd, gs, bd, es, CU_TENSOR_MAP_INTERLEAVE_NONE, sw,
      CU_TENSOR_MAP_L2_PROMOTION_L2_128B, CU_TENSOR_MAP_FLOAT_OOB_FILL_NONE);
}

}

extern "C" void kernel_launch(void* const* d_in, const int* in_sizes, int n_in, void* d_out, int out_size) {
  (void)in_sizes; (void)n_in; (void)out_size;
  const __nv_bfloat16* x = (const __nv_bfloat16*)d_in[0];
  const __nv_bfloat16* w_r = (const __nv_bfloat16*)d_in[1];
  const __nv_bfloat16* w_i = (const __nv_bfloat16*)d_in[2];
  const __nv_bfloat16* w_gate = (const __nv_bfloat16*)d_in[4];
  const __nv_bfloat16* w_up = (const __nv_bfloat16*)d_in[5];
  const __nv_bfloat16* w_down = (const __nv_bfloat16*)d_in[6];
  const __nv_bfloat16* gate_w = (const __nv_bfloat16*)d_in[7];
  static EncodeFn enc = nullptr;
  static bool ok = false;
  if (!enc) {
    cudaDriverEntryPointQueryResult qr;
    cudaGetDriverEntryPoint("cuTensorMapEncodeTiled", (void**)&enc, cudaEnableDefault, &qr);
    cudaFuncSetAttribute(fused_kernel, cudaFuncAttributeMaxDynamicSharedMemorySize, SMEM_BYTES);
    cudaFuncAttributes fa;
    cudaFuncGetAttributes(&fa, fused_kernel);
    ok = (fa.numRegs == 128);
  }
  if (!ok) return;
  CUtensorMap tx, tg, tu, tg32, tu32;
  {
    cuuint64_t gd[3] = {64, (cuuint64_t)S_, 7};
    cuuint64_t gs[2] = {(cuuint64_t)D_ * 2, 128};
    cuuint32_t bd[3] = {64, 64, 7};
    cuuint32_t es[3] = {1, 1, 1};
    enc(&tx, CU_TENSOR_MAP_DATA_TYPE_BFLOAT16, 3, const_cast<__nv_bfloat16*>(x), gd, gs, bd, es, CU_TENSOR_MAP_INTERLEAVE_NONE, CU_TENSOR_MAP_SWIZZLE_128B,
        CU_TENSOR_MAP_L2_PROMOTION_L2_128B, CU_TENSOR_MAP_FLOAT_OOB_FILL_NONE);
  }
  make_map(enc, &tg, w_gate, F_, D_, 64, 64, CU_TENSOR_MAP_SWIZZLE_128B);
  make_map(enc, &tu, w_up, F_, D_, 64, 64, CU_TENSOR_MAP_SWIZZLE_128B);
  make_map(enc, &tg32, w_gate, F_, D_, 32, 128, CU_TENSOR_MAP_SWIZZLE_64B);
  make_map(enc, &tu32, w_up, F_, D_, 32, 128, CU_TENSOR_MAP_SWIZZLE_64B);
  fused_kernel<<<128, NTHREADS, SMEM_BYTES>>>(tx, tg, tu, tg32, tu32, x, w_r, w_i, w_gate, w_up, w_down, gate_w, (__nv_bfloat16*)d_out);
}
```

```cpp
#include <cuda_runtime.h>
#include <cuda_bf16.h>
#include <cuda.h>
#include <stdint.h>

namespace {

constexpr int S_ = 2048, D_ = 448, F_ = 1792, DF_ = 225;
constexpr int NTHREADS = 512;
constexpr int SLOT = 16384, NSLOT = 7;
constexpr int HALF_XR = 57344;
constexpr int OFF_PQ = NSLOT * SLOT;
constexpr int OFF_R = OFF_PQ + HALF_XR;
constexpr int OFF_EXCH = OFF_PQ;
constexpr int OFF_WS = OFF_EXCH + 18432;
constexpr int OFF_TW = OFF_WS + 16384;
constexpr int OFF_MISC = OFF_R + HALF_XR;
constexpr int OFF_G = OFF_MISC;
constexpr int OFF_BAR = OFF_MISC + 512;
constexpr int SMEM_BYTES = OFF_BAR + 512;
constexpr int B_FULL = 0, B_EMPTY = 7, B_XFULL = 14  ;
constexpr int B_XFREE = 16  , B_PUB = 18  , B_RFREE = 23, B_LFREE = 24;
constexpr int B_WDONE = 25  , B_HRDY = 26  ;
constexpr int B_PQFULL = 30, B_RECV = 31, B_WFULL = 32, B_XCFULL = 33, B_PREP = 34, B_PIN = 35, B_RFULL = 36, B_GFULL = 37;

constexpr int WD_IMG = 896 * 112 * 2;
constexpr int G_IMG = 224 * 56 * 2;

__device__ __align__(1024) uint32_t g_Xc[112 * 2 * S_];
__device__ __align__(1024) unsigned char g_H[32 * 56 * 4096];
__device__ __align__(1024) unsigned char g_PQ[32 * HALF_XR];
__device__ __align__(1024) unsigned char g_Wd[8 * WD_IMG];
__device__ __align__(1024) unsigned char g_G[8 * G_IMG];
__device__ __align__(1024) uint2 g_Wt[113 * S_];
__device__ __align__(1024) float g_gate[S_];
__device__ __align__(128) unsigned int g_hflag[128 * 4];
__device__ __align__(128) unsigned int g_ep[128 * 2];
__device__ __align__(128) unsigned int g_cnt[8 * 32];

#define PROF(role, idx) do {} while (0)
#define PROFG(role, idx) do {} while (0)

__device__ __forceinline__ uint32_t s2u(const void* p) { return (uint32_t)__cvta_generic_to_shared(p); }
__device__ __forceinline__ void mbar_init(uint32_t b, int c) { asm volatile("mbarrier.init.shared::cta.b64 [%0], %1;" :: "r"(b), "r"(c) : "memory"); }
__device__ __forceinline__ void mbar_expect(uint32_t b, int bytes) { asm volatile("mbarrier.arrive.expect_tx.shared::cta.b64 _, [%0], %1;" :: "r"(b), "r"(bytes) : "memory"); }
__device__ __forceinline__ void mbar_arrive(uint32_t b) { asm volatile("mbarrier.arrive.shared::cta.b64 _, [%0];" :: "r"(b) : "memory"); }
__device__ __forceinline__ void mbar_wait(uint32_t b, int ph) {
  asm volatile("{\n.reg .pred p;\n.reg .u32 c;\nmov.u32 c, 0;\nL_WAIT:\nmbarrier.try_wait.parity.shared::cta.b64 p, [%0], %1;\n@p bra.uni L_DONE;\n"
               "add.u32 c, c, 1;\nsetp.lt.u32 p, c, 4194304;\n@p bra.uni L_WAIT;\ntrap;\nL_DONE:\n}" :: "r"(b), "r"(ph) : "memory");
}
__device__ __forceinline__ void mbar_wait_cluster(uint32_t b, int ph) {
  asm volatile("{\n.reg .pred p;\n.reg .u32 c;\nmov.u32 c, 0;\nL_WAIT:\nmbarrier.try_wait.parity.acquire.cluster.shared::cta.b64 p, [%0], %1;\n@p bra.uni L_DONE;\n"
               "add.u32 c, c, 1;\nsetp.lt.u32 p, c, 4194304;\n@p bra.uni L_WAIT;\ntrap;\nL_DONE:\n}" :: "r"(b), "r"(ph) : "memory");
}
__device__ __forceinline__ uint32_t ld_acquire(const unsigned int* p) { uint32_t v; asm volatile("ld.acquire.gpu.global.u32 %0, [%1];" : "=r"(v) : "l"(p) : "memory"); return v; }
__device__ __forceinline__ uint32_t ld_relaxed(const unsigned int* p) { uint32_t v; asm volatile("ld.relaxed.gpu.global.u32 %0, [%1];" : "=r"(v) : "l"(p) : "memory"); return v; }
__device__ __forceinline__ void wait_ge(const unsigned int* p, uint32_t target) {
#pragma unroll 1
  for (int i = 0; i < (1 << 22); i++) { if ((int)(ld_acquire(p) - target) >= 0) return; }
  __trap();
}
__device__ __forceinline__ void red_release(unsigned int* p) { asm volatile("red.release.gpu.global.add.u32 [%0], 1;" :: "l"(p) : "memory"); }
__device__ __forceinline__ bool elect() { uint32_t p; asm volatile("{\n.reg .pred p;\nelect.sync _|p, 0xffffffff;\nselp.u32 %0, 1, 0, p;\n}" : "=r"(p)); return p; }
__device__ __forceinline__ void fence_async_smem() { asm volatile("fence.proxy.async.shared::cta;" ::: "memory"); }
__device__ __forceinline__ void fence_async_global() { asm volatile("fence.proxy.async.global;" ::: "memory"); }
template <int ID, int N> __device__ __forceinline__ void bar_sync() { asm volatile("bar.sync %0, %1;" :: "n"(ID), "n"(N) : "memory"); }
template <int ID, int N> __device__ __forceinline__ void bar_arrive() { asm volatile("bar.arrive %0, %1;" :: "n"(ID), "n"(N) : "memory"); }
__device__ __forceinline__ void tma2d(uint32_t dst, const CUtensorMap* tm, int c0, int c1, uint32_t bar) {
  asm volatile("cp.async.bulk.tensor.2d.shared::cluster.global.mbarrier::complete_tx::bytes [%0], [%1, {%3, %4}], [%2];"
               :: "r"(dst), "l"(tm), "r"(bar), "r"(c0), "r"(c1) : "memory");
}
__device__ __forceinline__ void tma3d(uint32_t dst, const CUtensorMap* tm, int c0, int c1, int c2, uint32_t bar) {
  asm volatile("cp.async.bulk.tensor.3d.shared::cluster.global.mbarrier::complete_tx::bytes [%0], [%1, {%3, %4, %5}], [%2];"
               :: "r"(dst), "l"(tm), "r"(bar), "r"(c0), "r"(c1), "r"(c2) : "memory");
}
__device__ __forceinline__ void bulk_g2s(uint32_t dst, const void* src, int bytes, uint32_t bar) {
  asm volatile("cp.async.bulk.shared::cluster.global.mbarrier::complete_tx::bytes [%0], [%1], %2, [%3];"
               :: "r"(dst), "l"(src), "r"(bytes), "r"(bar) : "memory");
}
__device__ __forceinline__ void prefetch_l2(const void* src, int bytes) {
  asm volatile("cp.async.bulk.prefetch.L2.global [%0], %1;" :: "l"(src), "r"(bytes) : "memory");
}
__device__ __forceinline__ uint64_t mkdesc(uint32_t addr, uint32_t lbo, uint32_t sbo, uint32_t mode) {
  return (uint64_t)((addr & 0x3FFFF) >> 4) | ((uint64_t)(lbo >> 4) << 16) | ((uint64_t)(sbo >> 4) << 32) | ((uint64_t)mode << 62);
}
__device__ __forceinline__ void wg_fence() { asm volatile("wgmma.fence.sync.aligned;" ::: "memory"); }
__device__ __forceinline__ void wg_commit() { asm volatile("wgmma.commit_group.sync.aligned;" ::: "memory"); }
template <int N> __device__ __forceinline__ void wg_wait() { asm volatile("wgmma.wait_group.sync.aligned %0;" :: "n"(N) : "memory"); }
template <int N> __device__ __forceinline__ void keep(float (&d)[N]) {
#pragma unroll
  for (int i = 0; i < N; i++) asm volatile("" : "+f"(d[i]) :: "memory");
}
__device__ __forceinline__ uint32_t pack_bf16(float lo, float hi) { uint32_t r; asm("cvt.rn.bf16x2.f32 %0, %1, %2;" : "=r"(r) : "f"(hi), "f"(lo)); return r; }
__device__ __forceinline__ float bf16_round(float v) { return __bfloat162float(__float2bfloat16_rn(v)); }
__device__ __forceinline__ void sts128(uint32_t a, uint32_t x, uint32_t y, uint32_t z, uint32_t w) { asm volatile("st.shared.v4.b32 [%0], {%1,%2,%3,%4};" :: "r"(a), "r"(x), "r"(y), "r"(z), "r"(w) : "memory"); }
__device__ __forceinline__ float4 lds128f(uint32_t a) { float4 v; asm volatile("ld.shared.v4.f32 {%0,%1,%2,%3}, [%4];" : "=f"(v.x), "=f"(v.y), "=f"(v.z), "=f"(v.w) : "r"(a) : "memory"); return v; }

__device__ __forceinline__ uint2 lds64(uint32_t a) { uint2 v; asm volatile("ld.shared.v2.b32 {%0,%1}, [%2];" : "=r"(v.x), "=r"(v.y) : "r"(a) : "memory"); return v; }
__device__ __forceinline__ float bf_lo(uint32_t w) { return __uint_as_float(w << 16); }
__device__ __forceinline__ float bf_hi(uint32_t w) { return __uint_as_float(w & 0xffff0000u); }
__device__ __forceinline__ uint32_t opaque(uint32_t v) { asm volatile("" : "+r"(v)); return v; }
__device__ __forceinline__ uint4 ldg128(const void* p) { uint4 v; asm volatile("ld.global.nc.v4.b32 {%0,%1,%2,%3}, [%4];" : "=r"(v.x), "=r"(v.y), "=r"(v.z), "=r"(v.w) : "l"(p)); return v; }
__device__ __forceinline__ void stg128(void* p, uint32_t x, uint32_t y, uint32_t z, uint32_t w) { asm volatile("st.global.v4.b32 [%0], {%1,%2,%3,%4};" :: "l"(p), "r"(x), "r"(y), "r"(z), "r"(w) : "memory"); }
__device__ __forceinline__ void ldg128_l2(uint32_t (&v)[4], const void* p) { asm volatile("ld.relaxed.gpu.global.v4.b32 {%0,%1,%2,%3}, [%4];" : "=r"(v[0]), "=r"(v[1]), "=r"(v[2]), "=r"(v[3]) : "l"(p) : "memory"); }
__device__ __forceinline__ uint4 lds128(uint32_t a) { uint4 v; asm volatile("ld.shared.v4.b32 {%0,%1,%2,%3}, [%4];" : "=r"(v.x), "=r"(v.y), "=r"(v.z), "=r"(v.w) : "r"(a) : "memory"); return v; }
__device__ __forceinline__ uint32_t lds16(uint32_t a) { uint32_t v; asm volatile("ld.shared.u16 %0, [%1];" : "=r"(v) : "r"(a) : "memory"); return v; }
__device__ __forceinline__ void sts64(uint32_t a, uint32_t x, uint32_t y) { asm volatile("st.shared.v2.b32 [%0], {%1,%2};" :: "r"(a), "r"(x), "r"(y) : "memory"); }
template <int TB> __device__ __forceinline__ void wgmma_rs_128(float (&d)[64], const uint32_t (&a)[4], uint64_t db, int sc) {
  asm volatile("{\n.reg .pred p;\nsetp.ne.b32 p, %69, 0;\n"
    "wgmma.mma_async.sync.aligned.m64n128k16.f32.bf16.bf16 {%0, %1, %2, %3, %4, %5, %6, %7, %8, %9, %10, %11, %12, %13, %14, %15, %16, %17, %18, %19, %20, %21, %22, %23, %24, %25, %26, %27, %28, %29, %30, %31, %32, %33, %34, %35, %36, %37, %38, %39, %40, %41, %42, %43, %44, %45, %46, %47, %48, %49, %50, %51, %52, %53, %54, %55, %56, %57, %58, %59, %60, %61, %62, %63}, {%64, %65, %66, %67}, %68, p, 1, 1, %70;\n}\n"
    : "+f"(d[0]), "+f"(d[1]), "+f"(d[2]), "+f"(d[3]), "+f"(d[4]), "+f"(d[5]), "+f"(d[6]), "+f"(d[7]), "+f"(d[8]), "+f"(d[9]), "+f"(d[10]), "+f"(d[11]), "+f"(d[12]), "+f"(d[13]), "+f"(d[14]), "+f"(d[15]), "+f"(d[16]), "+f"(d[17]), "+f"(d[18]), "+f"(d[19]), "+f"(d[20]), "+f"(d[21]), "+f"(d[22]), "+f"(d[23]), "+f"(d[24]), "+f"(d[25]), "+f"(d[26]), "+f"(d[27]), "+f"(d[28]), "+f"(d[29]), "+f"(d[30]), "+f"(d[31]), "+f"(d[32]), "+f"(d[33]), "+f"(d[34]), "+f"(d[35]), "+f"(d[36]), "+f"(d[37]), "+f"(d[38]), "+f"(d[39]), "+f"(d[40]), "+f"(d[41]), "+f"(d[42]), "+f"(d[43]), "+f"(d[44]), "+f"(d[45]), "+f"(d[46]), "+f"(d[47]), "+f"(d[48]), "+f"(d[49]), "+f"(d[50]), "+f"(d[51]), "+f"(d[52]), "+f"(d[53]), "+f"(d[54]), "+f"(d[55]), "+f"(d[56]), "+f"(d[57]), "+f"(d[58]), "+f"(d[59]), "+f"(d[60]), "+f"(d[61]), "+f"(d[62]), "+f"(d[63])
    : "r"(a[0]), "r"(a[1]), "r"(a[2]), "r"(a[3]), "l"(db), "r"(sc), "n"(TB));
}
template <int TB> __device__ __forceinline__ void wgmma_rs_64(float (&d)[32], const uint32_t (&a)[4], uint64_t db, int sc) {
  asm volatile("{\n.reg .pred p;\nsetp.ne.b32 p, %37, 0;\n"
    "wgmma.mma_async.sync.aligned.m64n64k16.f32.bf16.bf16 {%0, %1, %2, %3, %4, %5, %6, %7, %8, %9, %10, %11, %12, %13, %14, %15, %16, %17, %18, %19, %20, %21, %22, %23, %24, %25, %26, %27, %28, %29, %30, %31}, {%32, %33, %34, %35}, %36, p, 1, 1, %38;\n}\n"
    : "+f"(d[0]), "+f"(d[1]), "+f"(d[2]), "+f"(d[3]), "+f"(d[4]), "+f"(d[5]), "+f"(d[6]), "+f"(d[7]), "+f"(d[8]), "+f"(d[9]), "+f"(d[10]), "+f"(d[11]), "+f"(d[12]), "+f"(d[13]), "+f"(d[14]), "+f"(d[15]), "+f"(d[16]), "+f"(d[17]), "+f"(d[18]), "+f"(d[19]), "+f"(d[20]), "+f"(d[21]), "+f"(d[22]), "+f"(d[23]), "+f"(d[24]), "+f"(d[25]), "+f"(d[26]), "+f"(d[27]), "+f"(d[28]), "+f"(d[29]), "+f"(d[30]), "+f"(d[31])
    : "r"(a[0]), "r"(a[1]), "r"(a[2]), "r"(a[3]), "l"(db), "r"(sc), "n"(TB));
}
template <int TB> __device__ __forceinline__ void wgmma_rs_56(float (&d)[28], const uint32_t (&a)[4], uint64_t db, int sc) {
  asm volatile("{\n.reg .pred p;\nsetp.ne.b32 p, %33, 0;\n"
    "wgmma.mma_async.sync.aligned.m64n56k16.f32.bf16.bf16 {%0, %1, %2, %3, %4, %5, %6, %7, %8, %9, %10, %11, %12, %13, %14, %15, %16, %17, %18, %19, %20, %21, %22, %23, %24, %25, %26, %27}, {%28, %29, %30, %31}, %32, p, 1, 1, %34;\n}\n"
    : "+f"(d[0]), "+f"(d[1]), "+f"(d[2]), "+f"(d[3]), "+f"(d[4]), "+f"(d[5]), "+f"(d[6]), "+f"(d[7]), "+f"(d[8]), "+f"(d[9]), "+f"(d[10]), "+f"(d[11]), "+f"(d[12]), "+f"(d[13]), "+f"(d[14]), "+f"(d[15]), "+f"(d[16]), "+f"(d[17]), "+f"(d[18]), "+f"(d[19]), "+f"(d[20]), "+f"(d[21]), "+f"(d[22]), "+f"(d[23]), "+f"(d[24]), "+f"(d[25]), "+f"(d[26]), "+f"(d[27])
    : "r"(a[0]), "r"(a[1]), "r"(a[2]), "r"(a[3]), "l"(db), "r"(sc), "n"(TB));
}
template <int TB> __device__ __forceinline__ void wgmma_rs_112(float (&d)[56], const uint32_t (&a)[4], uint64_t db, int sc) {
  asm volatile("{\n.reg .pred p;\nsetp.ne.b32 p, %61, 0;\n"
    "wgmma.mma_async.sync.aligned.m64n112k16.f32.bf16.bf16 {%0, %1, %2, %3, %4, %5, %6, %7, %8, %9, %10, %11, %12, %13, %14, %15, %16, %17, %18, %19, %20, %21, %22, %23, %24, %25, %26, %27, %28, %29, %30, %31, %32, %33, %34, %35, %36, %37, %38, %39, %40, %41, %42, %43, %44, %45, %46, %47, %48, %49, %50, %51, %52, %53, %54, %55}, {%56, %57, %58, %59}, %60, p, 1, 1, %62;\n}\n"
    : "+f"(d[0]), "+f"(d[1]), "+f"(d[2]), "+f"(d[3]), "+f"(d[4]), "+f"(d[5]), "+f"(d[6]), "+f"(d[7]), "+f"(d[8]), "+f"(d[9]), "+f"(d[10]), "+f"(d[11]), "+f"(d[12]), "+f"(d[13]), "+f"(d[14]), "+f"(d[15]), "+f"(d[16]), "+f"(d[17]), "+f"(d[18]), "+f"(d[19]), "+f"(d[20]), "+f"(d[21]), "+f"(d[22]), "+f"(d[23]), "+f"(d[24]), "+f"(d[25]), "+f"(d[26]), "+f"(d[27]), "+f"(d[28]), "+f"(d[29]), "+f"(d[30]), "+f"(d[31]), "+f"(d[32]), "+f"(d[33]), "+f"(d[34]), "+f"(d[35]), "+f"(d[36]), "+f"(d[37]), "+f"(d[38]), "+f"(d[39]), "+f"(d[40]), "+f"(d[41]), "+f"(d[42]), "+f"(d[43]), "+f"(d[44]), "+f"(d[45]), "+f"(d[46]), "+f"(d[47]), "+f"(d[48]), "+f"(d[49]), "+f"(d[50]), "+f"(d[51]), "+f"(d[52]), "+f"(d[53]), "+f"(d[54]), "+f"(d[55])
    : "r"(a[0]), "r"(a[1]), "r"(a[2]), "r"(a[3]), "l"(db), "r"(sc), "n"(TB));
}
template <int TA, int TB> __device__ __forceinline__ void wgmma_ss_56(float (&d)[28], uint64_t da, uint64_t db, int sc) {
  asm volatile("{\n.reg .pred p;\nsetp.ne.b32 p, %30, 0;\n"
    "wgmma.mma_async.sync.aligned.m64n56k16.f32.bf16.bf16 {%0, %1, %2, %3, %4, %5, %6, %7, %8, %9, %10, %11, %12, %13, %14, %15, %16, %17, %18, %19, %20, %21, %22, %23, %24, %25, %26, %27}, %28, %29, p, 1, 1, %31, %32;\n}\n"
    : "+f"(d[0]), "+f"(d[1]), "+f"(d[2]), "+f"(d[3]), "+f"(d[4]), "+f"(d[5]), "+f"(d[6]), "+f"(d[7]), "+f"(d[8]), "+f"(d[9]), "+f"(d[10]), "+f"(d[11]), "+f"(d[12]), "+f"(d[13]), "+f"(d[14]), "+f"(d[15]), "+f"(d[16]), "+f"(d[17]), "+f"(d[18]), "+f"(d[19]), "+f"(d[20]), "+f"(d[21]), "+f"(d[22]), "+f"(d[23]), "+f"(d[24]), "+f"(d[25]), "+f"(d[26]), "+f"(d[27])
    : "l"(da), "l"(db), "r"(sc), "n"(TA), "n"(TB));
}

__device__ __forceinline__ void cs448(int idx, float& c, float& s) {
  if (idx > 224) idx -= 448;
  float a = (float)idx * (6.283185307179586f / 448.0f);
  c = __cosf(a); s = __sinf(a);
}
__device__ __forceinline__ uint32_t cis2048(int i) {
  float s, c; __sincosf((float)(i > 1024 ? i - 2048 : i) * (-6.283185307179586f / 2048.0f), &s, &c); return pack_bf16(c, s);
}

typedef __nv_bfloat162 b2;
struct c2 { b2 x, y; };
__device__ __forceinline__ b2 as_b2(uint32_t u) { return *reinterpret_cast<b2*>(&u); }
__device__ __forceinline__ uint32_t as_u(b2 v) { return *reinterpret_cast<uint32_t*>(&v); }
__device__ __forceinline__ c2 mk(b2 x, b2 y) { c2 r; r.x = x; r.y = y; return r; }
__device__ __forceinline__ c2 cmul(c2 a, b2 wr, b2 wi) { return mk(__hfma2(a.x, wr, __hneg2(__hmul2(a.y, wi))), __hfma2(a.x, wi, __hmul2(a.y, wr))); }
__device__ __forceinline__ void fft4(c2& a0, c2& a1, c2& a2, c2& a3) {
  c2 t0 = mk(__hadd2(a0.x, a2.x), __hadd2(a0.y, a2.y)), t1 = mk(__hsub2(a0.x, a2.x), __hsub2(a0.y, a2.y));
  c2 t2 = mk(__hadd2(a1.x, a3.x), __hadd2(a1.y, a3.y)), t3 = mk(__hsub2(a1.x, a3.x), __hsub2(a1.y, a3.y));
  a0 = mk(__hadd2(t0.x, t2.x), __hadd2(t0.y, t2.y)); a2 = mk(__hsub2(t0.x, t2.x), __hsub2(t0.y, t2.y));
  a1 = mk(__hadd2(t1.x, t3.y), __hsub2(t1.y, t3.x)); a3 = mk(__hsub2(t1.x, t3.y), __hadd2(t1.y, t3.x));
}
__device__ __forceinline__ void fft4_s2(c2& a0, c2& a1, c2& a2, c2& a3, b2 r) {
  const b2 nr = __hneg2(r);
  c2 t0 = mk(__hfma2(a2.x, r, a0.x), __hfma2(a2.y, r, a0.y)), t1 = mk(__hfma2(a2.x, nr, a0.x), __hfma2(a2.y, nr, a0.y));
  c2 t2 = mk(__hadd2(a1.x, a3.x), __hadd2(a1.y, a3.y)), t3 = mk(__hsub2(a1.x, a3.x), __hsub2(a1.y, a3.y));
  a0 = mk(__hadd2(t0.x, t2.x), __hadd2(t0.y, t2.y)); a2 = mk(__hsub2(t0.x, t2.x), __hsub2(t0.y, t2.y));
  a1 = mk(__hadd2(t1.x, t3.y), __hsub2(t1.y, t3.x)); a3 = mk(__hsub2(t1.x, t3.y), __hadd2(t1.y, t3.x));
}
__device__ __forceinline__ void fft4_s13(c2& a0, c2& a1, c2& a2, c2& a3, b2 r) {
  const b2 nr = __hneg2(r);
  c2 t0 = mk(__hadd2(a0.x, a2.x), __hadd2(a0.y, a2.y)), t1 = mk(__hsub2(a0.x, a2.x), __hsub2(a0.y, a2.y));
  c2 t2 = mk(__hadd2(a1.x, a3.x), __hadd2(a1.y, a3.y)), t3 = mk(__hsub2(a1.x, a3.x), __hsub2(a1.y, a3.y));
  a0 = mk(__hfma2(t2.x, r, t0.x), __hfma2(t2.y, r, t0.y)); a2 = mk(__hfma2(t2.x, nr, t0.x), __hfma2(t2.y, nr, t0.y));
  a1 = mk(__hfma2(t3.y, r, t1.x), __hfma2(t3.x, nr, t1.y)); a3 = mk(__hfma2(t3.y, nr, t1.x), __hfma2(t3.x, r, t1.y));
}
__device__ __forceinline__ c2 rot1(c2 a) { return mk(__hadd2(a.x, a.y), __hsub2(a.y, a.x)); }
__device__ __forceinline__ c2 rot3(c2 a) { return mk(__hsub2(a.y, a.x), __hneg2(__hadd2(a.x, a.y))); }
__device__ __forceinline__ c2 mul_mi(c2 a) { return mk(a.y, __hneg2(a.x)); }
template <int O> __device__ __forceinline__ void fft8(c2 (&v)[16]) {
  const b2 r = as_b2(0x3F353F35u), nr = as_b2(0xBF35BF35u);
  fft4(v[O], v[O + 4], v[O + 8], v[O + 12]);
  fft4(v[O + 2], v[O + 6], v[O + 10], v[O + 14]);
  const c2 o0 = v[O + 2], o1 = rot1(v[O + 6]), o2 = v[O + 10], o3 = rot1(v[O + 14]);
  const c2 e0 = v[O], e1 = v[O + 4], e2 = v[O + 8], e3 = v[O + 12];
  v[O] = mk(__hadd2(e0.x, o0.x), __hadd2(e0.y, o0.y));              v[O + 8] = mk(__hsub2(e0.x, o0.x), __hsub2(e0.y, o0.y));
  v[O + 2] = mk(__hfma2(o1.x, r, e1.x), __hfma2(o1.y, r, e1.y));    v[O + 10] = mk(__hfma2(o1.x, nr, e1.x), __hfma2(o1.y, nr, e1.y));
  v[O + 4] = mk(__hadd2(e2.x, o2.y), __hsub2(e2.y, o2.x));          v[O + 12] = mk(__hsub2(e2.x, o2.y), __hadd2(e2.y, o2.x));
  v[O + 6] = mk(__hfma2(o3.y, r, e3.x), __hfma2(o3.x, nr, e3.y));   v[O + 14] = mk(__hfma2(o3.y, nr, e3.x), __hfma2(o3.x, r, e3.y));
}
__device__ __forceinline__ void fft16(c2 (&v)[16]) {
  const b2 r = as_b2(0x3F353F35u), c1 = as_b2(0x3F6D3F6Du), s1 = as_b2(0x3EC43EC4u), nc1 = as_b2(0xBF6DBF6Du), ns1 = as_b2(0xBEC4BEC4u);
#pragma unroll
  for (int a = 0; a < 4; a++) fft4(v[a], v[a + 4], v[a + 8], v[a + 12]);
  v[5] = cmul(v[5], c1, ns1); v[6] = rot1(v[6]); v[7] = cmul(v[7], s1, nc1);
  v[9] = rot1(v[9]); v[10] = mul_mi(v[10]); v[11] = rot3(v[11]);
  v[13] = cmul(v[13], s1, nc1); v[14] = rot3(v[14]); v[15] = cmul(v[15], nc1, s1);
  fft4(v[0], v[1], v[2], v[3]); fft4_s2(v[4], v[5], v[6], v[7], r); fft4_s13(v[8], v[9], v[10], v[11], r); fft4_s2(v[12], v[13], v[14], v[15], r);
  c2 t;
  t = v[1]; v[1] = v[4]; v[4] = t;  t = v[2]; v[2] = v[8]; v[8] = t;  t = v[3]; v[3] = v[12]; v[12] = t;
  t = v[6]; v[6] = v[9]; v[9] = t;  t = v[7]; v[7] = v[13]; v[13] = t; t = v[11]; v[11] = v[14]; v[14] = t;
}

__device__ __forceinline__ void columns(c2 (&v)[16], uint32_t sb, int t) {
  const int l16 = t & 15;
  const uint32_t row = sb + OFF_EXCH + (t >> 4) * 2304;
  const uint32_t pos = sb + OFF_EXCH + (t >> 3) * 144 + (t & 7) * 16;
#pragma unroll 1
  for (int ps = 0; ps < 6; ps++) {
    if (ps == 0 || ps == 5) { fft8<0>(v); fft8<1>(v); } else fft16(v);
    if (ps == 5) break;
    if (ps == 2) {
      const uint32_t ws = sb + OFF_WS + (l16 >> 1) * 128 + ((((t >> 4) + (l16 >> 1)) & 7) * 2 + (l16 & 1)) * 8;
      mbar_wait(sb + OFF_BAR + B_WFULL * 8, 0);
#pragma unroll
      for (int q = 0; q < 16; q++) {
        const uint2 w = lds64(ws + q * 1024);
        const c2 z = cmul(v[q], as_b2(w.x), as_b2(w.y));
        v[q] = mk(z.y, z.x);
      }
      continue;
    }
    {
      const bool full = ps == 0 || ps == 4;
      const uint32_t tw = sb + OFF_TW + (full ? ps * 2048 + t * 16 : 16384 + l16 * 16);
      const uint32_t st = full ? 2048 : 256;
#pragma unroll
      for (int i = 0; i < 4; i++) {
        const uint4 w4 = lds128(tw + i * st);
        const uint32_t w[4] = {w4.x, w4.y, w4.z, w4.w};
#pragma unroll
        for (int e = 0; e < 4; e++) v[4 * i + e] = cmul(v[4 * i + e], __low2bfloat162(as_b2(w[e])), __high2bfloat162(as_b2(w[e])));
      }
    }
    if (ps == 0) {
      bar_sync<3, 128>();
#pragma unroll
      for (int q = 0; q < 8; q++) sts128(pos + q * 2304, as_u(v[2 * q].x), as_u(v[2 * q].y), as_u(v[2 * q + 1].x), as_u(v[2 * q + 1].y));
      bar_sync<3, 128>();
#pragma unroll
      for (int q = 0; q < 16; q++) { const uint2 a = lds64(row + q * 144 + l16 * 8); v[q] = mk(as_b2(a.x), as_b2(a.y)); }
    } else {
      __syncwarp();
#pragma unroll
      for (int q = 0; q < 16; q++) sts64(row + q * 144 + l16 * 8, as_u(v[q].x), as_u(v[q].y));
      if (ps == 4) bar_sync<3, 128>(); else __syncwarp();
      const uint32_t src = ps == 4 ? pos : row + l16 * 144, st = ps == 4 ? 2304 : 16;
#pragma unroll
      for (int q = 0; q < 8; q++) { const uint4 a = lds128(src + q * st); v[2 * q] = mk(as_b2(a.x), as_b2(a.y)); v[2 * q + 1] = mk(as_b2(a.z), as_b2(a.w)); }
    }
  }
}

template <int NH> __device__ __forceinline__ void h_epilogue(float (&acc)[NH * 8], unsigned char* gdst) {
#pragma unroll
  for (int c = 0; c < NH / 2; c++) {
    uint32_t pk[4];
#pragma unroll
    for (int i = 0; i < 4; i++) {
      float hv[2];
#pragma unroll
      for (int e = 0; e < 2; e++) {
        float hg = 0.5f * acc[c * 8 + i * 2 + e], up = acc[NH * 4 + c * 8 + i * 2 + e];
        float th; asm("tanh.approx.f32 %0, %1;" : "=f"(th) : "f"(hg));
        hv[e] = fmaf(hg, th, hg) * up;
      }
      pk[i] = pack_bf16(hv[0], hv[1]);
    }
    stg128(gdst + c * 4096, pk[0], pk[1], pk[2], pk[3]);
  }
}

#define LA2 5
#define LEAD1 2

__global__ void __cluster_dims__(2, 1, 1) __launch_bounds__(NTHREADS, 1)
fused_kernel(const __grid_constant__ CUtensorMap tm_x, const __grid_constant__ CUtensorMap tm_g, const __grid_constant__ CUtensorMap tm_u,
             const __grid_constant__ CUtensorMap tm_g32, const __grid_constant__ CUtensorMap tm_u32,
             const __nv_bfloat16* __restrict__ w_r, const __nv_bfloat16* __restrict__ w_i,
             const __nv_bfloat16* __restrict__ w_gate, const __nv_bfloat16* __restrict__ w_up,
             const __nv_bfloat16* __restrict__ w_down, const __nv_bfloat16* __restrict__ gate_w, __nv_bfloat16* __restrict__ out) {
  extern __shared__ __align__(1024) unsigned char smem[];
  const uint32_t sb = s2u(smem);
  const uint32_t bars = sb + OFF_BAR;
  const int tid = threadIdx.x, warp = __shfl_sync(0xffffffffu, tid >> 5, 0), lane = tid & 31;
  const int cl = blockIdx.x >> 1, kh = blockIdx.x & 1;
  const int n = cl < 4 ? cl : (cl < 36 ? (cl - 4) >> 3 : (cl - 36) / 7);
  const int m = cl < 4 ? 15 : (cl < 36 ? (cl - 4) & 7 : cl - 28 - 7 * n);
  const int j = kh * 4 + n, bid = m * 8 + n * 2 + kh;

  if (warp >= 12) {
    asm volatile("setmaxnreg.dec.sync.aligned.u32 24;");
    const int c64 = 224 * j + (j & 1) * 32;
    if (warp == 13) {
      if (elect()) {
        PROFG(4, 0); PROF(4, 1);
        mbar_init(bars + B_XFULL * 8, 1); mbar_init(bars + (B_XFULL + 1) * 8, 1);
        fence_async_smem();
#pragma unroll
        for (int w = 0; w < 2; w++) {
          mbar_expect(bars + (B_XFULL + w) * 8, HALF_XR);
          tma3d(sb + OFF_PQ + w * HALF_XR, &tm_x, 0, m * 128 + (w ^ kh ^ 1) * 64, 0, bars + (B_XFULL + w) * 8);
        }
      }
    } else if (warp == 12) {
      if (lane < NSLOT) mbar_init(bars + (B_FULL + lane) * 8, 1);
      fence_async_smem();
      __syncwarp();
#pragma unroll 1
      for (int i = 0; i < 6; i++) {
        if (elect()) {
          const uint32_t fb = bars + (B_FULL + i) * 8;
          mbar_expect(fb, SLOT);
          tma2d(sb + i * SLOT, &tm_g, c64, i * 64, fb);
          tma2d(sb + i * SLOT + 8192, &tm_u, c64, i * 64, fb);
        }
      }
      if (lane == 0) PROF(3, 3);
    } else if (warp == 14) {
      if (lane < NSLOT) mbar_init(bars + (B_EMPTY + lane) * 8, 8);
      else if (lane < 29) { const int i = B_XFREE - NSLOT + lane; mbar_init(bars + i * 8, i >= B_PQFULL ? 1 : (i >= B_HRDY ? 3 : ((i == B_XFREE || i == B_WDONE) ? 4 : 8))); }
      asm volatile("fence.mbarrier_init.release.cluster;" ::: "memory");
      __syncwarp();
      if (lane == 0) mbar_expect(bars + B_RECV * 8, 64 * 112 * 4);
    }
    bar_sync<0, NTHREADS>();
    asm volatile("barrier.cluster.arrive.relaxed.aligned;" ::: "memory");
    if (warp == 12) {
      int slot = 6, ph = 1;
      auto wait_slot = [&]() { mbar_wait(bars + (B_EMPTY + slot) * 8, ph ^ (slot == 6)); };
      auto adv = [&]() { if (++slot == NSLOT) { slot = 0; ph ^= 1; } };
      const int c32 = 224 * j + ((j & 1) ? 0 : 192);
#pragma unroll 1
      for (int i = 6; i < 25; i++) {
        wait_slot();
        if (elect()) {
          const uint32_t dst = sb + slot * SLOT, fb = bars + (B_FULL + slot) * 8;
          const bool last = i >= 21;
          const int cc = last ? c32 : c64 + 64 * (i / 7), rr = last ? slot * 128 : slot * 64;
          mbar_expect(fb, SLOT);
          tma2d(dst, last ? &tm_g32 : &tm_g, cc, rr, fb);
          tma2d(dst + 8192, last ? &tm_u32 : &tm_u, cc, rr, fb);
        }
        adv();
      }
      if (lane == 0) PROF(3, 0);
      mbar_wait(bars + B_PREP * 8, 0);
      if (lane == 0) PROF(3, 1);
#pragma unroll 1
      for (int i = 4; i < 16; i++) {
        if (lane == 0) PROF(3, 16 + i);
        wait_slot();
        if (elect()) {
          const int bytes = i < 14 ? 14336 : G_IMG / 2;
          const unsigned char* src = i < 14 ? g_Wd + (size_t)j * WD_IMG + i * 14336 : g_G + (size_t)(n * 4 + i - 12) * (G_IMG / 2);
          mbar_expect(bars + (B_FULL + slot) * 8, bytes);
          bulk_g2s(sb + slot * SLOT, src, bytes, bars + (B_FULL + slot) * 8);
        }
        adv();
      }
      if (lane == 0) PROF(3, 2);
    } else if (warp == 13) {
      mbar_wait(bars + B_XFULL * 8, 0);
      if (elect()) {
        PROF(4, 2);
        prefetch_l2(reinterpret_cast<const unsigned char*>(w_r) + bid * 7200, 7200);
        prefetch_l2(reinterpret_cast<const unsigned char*>(w_i) + bid * 7200, 7200);
        prefetch_l2(reinterpret_cast<const unsigned char*>(w_down) + bid * 12544, 12544);
        prefetch_l2(reinterpret_cast<const unsigned char*>(w_gate) + bid * 12544, 12544);
        prefetch_l2(reinterpret_cast<const unsigned char*>(w_up) + bid * 12544, 12544);
      }
#pragma unroll 1
      for (int u = 0; u < 5; u++) {
        mbar_wait(bars + (B_PUB + u) * 8, 0);
        if (lane == 0) {
          PROF(4, 8 + u);
          red_release(u == 0 ? &g_cnt[(j >> 1) * 32] : &g_hflag[bid * 4 + u - 1]);
          PROF(4, 16 + u);
        }
        __syncwarp();
      }
      mbar_wait(bars + B_LFREE * 8, 0);
      if (elect()) {
        mbar_expect(bars + B_GFULL * 8, G_IMG);
        bulk_g2s(sb + OFF_R + 28672, g_G + (size_t)(n * 2) * G_IMG, G_IMG, bars + B_GFULL * 8);
      }
    } else if (warp == 14) {
      const uint32_t epoch = ld_relaxed(&g_ep[bid * 2]);
      if (lane < 13) {
        const unsigned int* fp = lane < 12 ? &g_hflag[(m * 8 + ((n + 1 + (lane >> 2)) & 3) * 2 + kh) * 4 + (lane & 3)] : &g_cnt[4 * 32];
        const uint32_t tgt = lane < 12 ? epoch + 1 : (epoch + 1) * 128;
        const uint32_t rb = bars + (lane < 12 ? B_HRDY + (lane & 3) : B_PREP) * 8;
        bool done = false;
#pragma unroll 1
        for (int i = 0; i < (1 << 20); i++) {
          if (!done && (int)(ld_acquire(fp) - tgt) >= 0) { fence_async_global(); mbar_arrive(rb); done = true; PROF(5, lane); }
          if (__all_sync(0x1fff, done)) break;
        }
        if (!done) __trap();
        if (lane == 0) g_ep[bid * 2] = epoch + 1;
      }
    } else {
      const uint32_t epoch = ld_relaxed(&g_ep[bid * 2 + 1]);
      mbar_wait(bars + B_XFREE * 8, 0);
      if (elect()) {
        mbar_expect(bars + B_PIN * 8, 14400 + 12544);
        bulk_g2s(sb + OFF_EXCH, reinterpret_cast<const unsigned char*>(w_down) + bid * 12544, 12544, bars + B_PIN * 8);
        bulk_g2s(sb + OFF_WS, reinterpret_cast<const unsigned char*>(w_r) + bid * 7200, 7200, bars + B_PIN * 8);
        bulk_g2s(sb + OFF_WS + 7200, reinterpret_cast<const unsigned char*>(w_i) + bid * 7200, 7200, bars + B_PIN * 8);
      }
      if (bid < 113) {
        const int sl = (bid == 112) ? 0 : bid;
        wait_ge(&g_cnt[((sl & 1) + 2 * ((sl >> 1) / 28)) * 32], (epoch + 1) * 32);
        fence_async_global();
        mbar_wait(bars + B_WDONE * 8, 0);
        if (elect()) {
          PROF(5, 16);
          mbar_expect(bars + B_XCFULL * 8, 16384);
          bulk_g2s(sb + OFF_EXCH, g_Xc + sl * 2 * S_, 16384, bars + B_XCFULL * 8);
        }
      }
      mbar_wait(bars + B_PREP * 8, 0);
      mbar_wait(bars + (B_XFREE + 1) * 8, 0);
      if (elect()) {
        if (bid < 113) {
          mbar_expect(bars + B_WFULL * 8, 16384);
          bulk_g2s(sb + OFF_WS, g_Wt + bid * S_, 16384, bars + B_WFULL * 8);
        }
        mbar_expect(bars + B_RFULL * 8, HALF_XR);
        bulk_g2s(sb + OFF_R, g_Wd + (size_t)j * WD_IMG, HALF_XR, bars + B_RFULL * 8);
        PROF(5, 17);
      }
      wait_ge(&g_cnt[5 * 32], (epoch + 1) * 128);
      fence_async_global();
      if (elect()) {
        PROF(5, 18);
        mbar_expect(bars + B_PQFULL * 8, HALF_XR + 256);
        const unsigned char* src = g_PQ + (size_t)(m * 2 + kh) * HALF_XR;
        bulk_g2s(sb + OFF_PQ, src, 28672, bars + B_PQFULL * 8);
        bulk_g2s(sb + OFF_PQ + 28672, src + 28672, 28672, bars + B_PQFULL * 8);
        bulk_g2s(sb + OFF_G, g_gate + m * 128 + kh * 64, 256, bars + B_PQFULL * 8);
        g_ep[bid * 2 + 1] = epoch + 1;
      }
    }
    __syncwarp();
    asm volatile("barrier.cluster.wait.aligned;" ::: "memory");
  } else if (warp < 8) {
    asm volatile("setmaxnreg.inc.sync.aligned.u32 208;");
    const int wg = warp >> 2, w4 = warp & 3, g = lane >> 2, t = lane & 3;
    const int rh = wg ^ kh ^ 1;
    const int p = j & 1, r = (j >> 1) & 1, hh = j >> 2;
#pragma unroll 1
    for (int it = tid; it < 392; it += 256) {
      int kc = it / 28, sg = it - kc * 28;
      int k = 2 * (28 * hh + sg) + r;
      float c[8], s[8];
#pragma unroll
      for (int q = 0; q < 8; q++) {
        int d = 16 * kc + 8 * (q & 1) + 2 * (q >> 1) + p;
        cs448((d * k) % 448, c[q], s[q]);
        s[q] = -s[q];
        if (k == 0) s[q] = (float)(p ? ((d & 2) - 1) : (1 - (d & 2)));
      }
      uint32_t a = sb + 6 * SLOT + (kc * 56 + 2 * sg) * 16;
      sts128(a, pack_bf16(c[0], c[1]), pack_bf16(c[2], c[3]), pack_bf16(c[4], c[5]), pack_bf16(c[6], c[7]));
      sts128(a + 16, pack_bf16(s[0], s[1]), pack_bf16(s[2], s[3]), pack_bf16(s[4], s[5]), pack_bf16(s[6], s[7]));
    }
    fence_async_smem();
    bar_sync<0, NTHREADS>();
    asm volatile("barrier.cluster.arrive.relaxed.aligned;" ::: "memory");
    if ((tid & 127) == 0) PROF(wg, 1);

    uint32_t xa[28][4];
    {
      const uint32_t xb = sb + OFF_PQ + wg * HALF_XR + (w4 * 16 + (lane & 15)) * 128;
      mbar_wait(bars + (B_XFULL + wg) * 8, 0);
      if ((tid & 127) == 0) PROF(wg, 2);
#pragma unroll
      for (int kb = 0; kb < 7; kb++) {
#pragma unroll
        for (int kk = 0; kk < 4; kk++) {
          uint32_t a = xb + kb * 8192 + (((2 * kk + (lane >> 4)) ^ (lane & 7)) << 4);
          asm volatile("ldmatrix.sync.aligned.m8n8.x4.shared.b16 {%0,%1,%2,%3}, [%4];"
                       : "=r"(xa[kb * 4 + kk][0]), "=r"(xa[kb * 4 + kk][1]), "=r"(xa[kb * 4 + kk][2]), "=r"(xa[kb * 4 + kk][3]) : "r"(a) : "memory");
        }
      }
    }
    {
      uint32_t ad[7][4];
      const uint32_t sel = p ? 0x7632 : 0x5410;
      const uint32_t sgn = r ? 0xBF80BF80u : 0x3F803F80u;
#pragma unroll
      for (int jj = 0; jj < 7; jj++) {
#pragma unroll
        for (int i = 0; i < 4; i++) {
          int ks = 2 * jj + (i >> 1), rr = i & 1;
          uint32_t lo = __byte_perm(xa[ks][rr], xa[ks][rr + 2], sel);
          uint32_t hi = __byte_perm(xa[ks + 14][rr], xa[ks + 14][rr + 2], sel);
          asm("fma.rn.bf16x2 %0, %1, %2, %3;" : "=r"(ad[jj][i]) : "r"(hi), "r"(sgn), "r"(lo));
        }
      }
      fence_async_smem();
      __syncwarp();
      if (lane == 0) mbar_arrive(bars + (B_XFREE + wg) * 8);
      float acc[28];
      wg_fence();
      uint64_t db = mkdesc(sb + 6 * SLOT, 896, 128, 0);
#pragma unroll
      for (int jj = 0; jj < 7; jj++) wgmma_rs_56<0>(acc, ad[jj], db + jj * 112, jj != 0);
      wg_commit();
      wg_wait<0>(); keep(acc);
      if (lane == 0) mbar_arrive(bars + (B_EMPTY + 6) * 8);
      uint32_t* xc = g_Xc + (size_t)((2 * (28 * hh + t) + r) * 2 + p) * S_ + m * 128 + rh * 64 + w4 * 16 + g;
#pragma unroll
      for (int i = 0; i < 7; i++) {
        xc[i * 16 * S_] = pack_bf16(acc[4 * i], acc[4 * i + 1]);
        xc[i * 16 * S_ + 8] = pack_bf16(acc[4 * i + 2], acc[4 * i + 3]);
      }
      __syncwarp();
      if (lane == 0) mbar_arrive(bars + B_PUB * 8);
    }
    if ((tid & 127) == 0) PROF(wg, 3);
    unsigned char* const hbase = g_H + (size_t)(m * 2 + kh) * (56 * 4096) + rh * 2048 + (tid & 127) * 16;
#pragma unroll 1
    for (int u = 0; u < 3; u++) {
      float acc[64];
      if (wg == 1) { if (u & 1) bar_sync<6, 256>(); else bar_sync<2, 256>(); }
      const uint32_t sbu = opaque(sb);
#pragma unroll
      for (int kb = 0; kb < 7; kb++) {
        mbar_wait(sbu + OFF_BAR + (B_FULL + kb) * 8, u & 1);
        wg_fence();
        uint64_t db = mkdesc(sbu + kb * SLOT, 8192, 1024, 1);
#pragma unroll
        for (int kk = 0; kk < 4; kk++) wgmma_rs_128<1>(acc, xa[kb * 4 + kk], db + kk * 128, (kb | kk) != 0);
        wg_commit();
        if (kb == LEAD1 && wg == 0) { if (u & 1) bar_arrive<6, 256>(); else bar_arrive<2, 256>(); }
        if (kb > 0) { wg_wait<1>(); if (lane == 0) mbar_arrive(sbu + OFF_BAR + (B_EMPTY + kb - 1) * 8); }
      }
      wg_wait<0>(); keep(acc);
      if (lane == 0) mbar_arrive(sbu + OFF_BAR + (B_EMPTY + 6) * 8);
      if ((tid & 127) == 0) PROF(wg, 4 + 2 * u);
      h_epilogue<8>(acc, hbase + (u * 16 + n * 4) * 4096);
      __syncwarp();
      if (lane == 0) mbar_arrive(sbu + OFF_BAR + (B_PUB + 1 + u) * 8);
      if ((tid & 127) == 0) PROF(wg, 5 + 2 * u);
    }
    {
      float acc[32];
      uint32_t pre[8][4];
      const uint32_t zero = opaque(0);
      mbar_wait(bars + B_HRDY * 8, 0);
#pragma unroll
      for (int i = 0; i < 8; i++) ldg128_l2(pre[i], hbase + i * 4096);
      if (wg == 1) bar_sync<6, 256>();
      const uint32_t sbu = opaque(sb);
#pragma unroll
      for (int it = 0; it < 4; it++) {
        mbar_wait(sbu + OFF_BAR + (B_FULL + it) * 8, 1);
        wg_fence();
        uint64_t db = mkdesc(sbu + it * SLOT, 8192, 512, 2);
#pragma unroll
        for (int kk = 0; kk < 8; kk++) if (it * 8 + kk < 28) wgmma_rs_64<1>(acc, xa[it * 8 + kk], db + kk * 64, (it | kk) != 0);
        wg_commit();
        if (it == LEAD1 && wg == 0) bar_arrive<6, 256>();
        if (it > 0) { wg_wait<1>(); if (lane == 0) mbar_arrive(sbu + OFF_BAR + (B_EMPTY + it - 1) * 8); }
      }
      wg_wait<0>(); keep(acc);
      if (lane == 0) mbar_arrive(sbu + OFF_BAR + (B_EMPTY + 3) * 8);
      if ((tid & 127) == 0) PROF(wg, 10);
#pragma unroll
      for (int i = 0; i < 32; i++) xa[i >> 2][i & 3] = i < 8 ? pre[i >> 2][i & 3] : pre[i >> 2][i & 3] ^ zero;
      if (LA2 > 4) mbar_wait(bars + (B_HRDY + 1) * 8, 0);
#pragma unroll
      for (int i = 8; i < 4 * LA2; i++) ldg128_l2(xa[i], hbase + i * 4096);
      h_epilogue<4>(acc, hbase + (48 + n * 2) * 4096);
      __syncwarp();
      if (lane == 0) mbar_arrive(sbu + OFF_BAR + (B_PUB + 4) * 8);
    }
    asm volatile("barrier.cluster.wait.aligned;" ::: "memory");
    if ((tid & 127) == 0) PROF(wg, 11);

    float acc[56];
    if (wg == 1) bar_sync<2, 256>();
#pragma unroll 1
    for (int it = 0; it < 2; it++) {
#pragma unroll
      for (int e = 0; e < 7; e++) {
        if ((tid & 127) == 0) PROF(wg, 16 + it * 7 + e);
        const bool inr = e < 4 && it == 0;
        if (e >= 4 || it == 1) mbar_wait(bars + (B_FULL + e) * 8, e < 4 ? 0 : it ^ 1);
        else if (e == 0) mbar_wait(bars + B_RFULL * 8, 0);
        wg_fence();
        const uint64_t db = mkdesc(inr ? sb + OFF_R + e * 14336 : sb + e * SLOT, 1792, 128, 0);
#pragma unroll
        for (int kk = 0; kk < 4; kk++) wgmma_rs_112<1>(acc, xa[e * 4 + kk], db + kk * 224, (e | kk) ? 1 : it);
        wg_commit();
        if (e == 1 && it == 0 && wg == 0) bar_arrive<2, 256>();
        if (it == 0 || e + LA2 < 7) {
          const int nb = it * 7 + e + LA2;
          if ((e + LA2) % 4 == 0 || (e + LA2 + 7) % 4 == 0) { if ((nb & 3) == 0) mbar_wait(bars + (B_HRDY + (nb >> 2)) * 8, 0); }
#pragma unroll
          for (int kk = 0; kk < 4; kk++) ldg128_l2(xa[((e + LA2) % 7) * 4 + kk], hbase + (nb * 4 + kk) * 4096);
        }
        wg_wait<1>();
        if (lane == 0) {
          if (it == 0 ? e >= 5 : e <= 2) mbar_arrive(bars + (B_EMPTY + (e + 6) % 7) * 8);
          if (e == 4 && it == 0) {
            mbar_arrive(bars + B_LFREE * 8);
            asm volatile("{\n.reg .b32 ra;\nmapa.shared::cluster.u32 ra, %0, %1;\nmbarrier.arrive.relaxed.cluster.shared::cluster.b64 _, [ra];\n}"
                         :: "r"(bars + B_RFREE * 8), "r"(kh ^ 1) : "memory");
          }
        }
      }
    }
    const int t128 = tid & 127;
    wg_wait<0>(); keep(acc);
    if (wg == 0) {
      if (t128 == 0) PROF(wg, 12);
      mbar_wait_cluster(bars + B_RFREE * 8, 0);
      uint32_t rdst, rbar;
      asm volatile("mapa.shared::cluster.u32 %0, %1, %2;" : "=r"(rdst) : "r"(sb + OFF_R + t128 * 16), "r"(kh ^ 1));
      asm volatile("mapa.shared::cluster.u32 %0, %1, %2;" : "=r"(rbar) : "r"(bars + B_RECV * 8), "r"(kh ^ 1));
#pragma unroll
      for (int i = 0; i < 14; i++)
        asm volatile("st.async.weak.shared::cluster.mbarrier::complete_tx::bytes.v4.f32 [%0], {%1,%2,%3,%4}, [%5];"
                     :: "r"(rdst + i * 2048), "f"(acc[4 * i]), "f"(acc[4 * i + 1]), "f"(acc[4 * i + 2]), "f"(acc[4 * i + 3]), "r"(rbar) : "memory");
    } else {
      float spec[2][28];
      if (t128 == 0) PROF(wg, 12);
      mbar_wait(bars + B_PQFULL * 8, 0);
      if (t128 == 0) PROF(wg, 13);
#pragma unroll
      for (int i = 0; i < 4; i++) {
        if (i == 0) mbar_wait(bars + B_GFULL * 8, 0);
        if (i >= 2) mbar_wait(bars + (B_FULL + i - 2) * 8, 1);
        wg_fence();
        const uint64_t da = mkdesc(sb + OFF_PQ + i * 14336, 1024, 1024, 1);
        const uint64_t db = mkdesc(i < 2 ? sb + OFF_R + 28672 + i * (G_IMG / 2) : sb + (i - 2) * SLOT, 896, 128, 0);
#pragma unroll
        for (int kk = 0; kk < 7; kk++) wgmma_ss_56<1, 0>(spec[i >> 1], da + kk * 128, db + kk * 112, ((i & 1) | kk) != 0);
        wg_commit();
      }
      const float* gs = reinterpret_cast<const float*>(smem + OFF_G) + w4 * 16 + g;
      const float o0 = bf16_round(1.0f - gs[0]), o1 = bf16_round(1.0f - gs[8]);
      const float g0 = gs[0] * (1.0f / (float)(S_ * D_)), g1 = gs[8] * (1.0f / (float)(S_ * D_));
      wg_wait<0>(); keep(spec[0]); keep(spec[1]);
      if (t128 == 0) PROF(wg, 14);
      mbar_wait_cluster(bars + B_RECV * 8, 0);
      if (t128 == 0) PROF(wg, 0);
      float4 o[14];
#pragma unroll
      for (int i = 0; i < 14; i++) o[i] = lds128f(sb + OFF_R + t128 * 16 + i * 2048);
      bar_sync<5, 128>();
      const uint32_t st = sb + OFF_PQ + w4 * 3840;
#pragma unroll
      for (int i = 0; i < 7; i++) {
        uint32_t pk[4];
#pragma unroll
        for (int e = 0; e < 2; e++) {
          const int c = 2 * i + e, si = i * 4 + e;
          pk[2 * e] = pack_bf16(fmaf(acc[4 * c] + o[c].x, o0, g0 * spec[0][si]), fmaf(acc[4 * c + 1] + o[c].y, o0, g0 * spec[1][si]));
          pk[2 * e + 1] = pack_bf16(fmaf(acc[4 * c + 2] + o[c].z, o1, g1 * spec[0][si + 2]), fmaf(acc[4 * c + 3] + o[c].w, o1, g1 * spec[1][si + 2]));
        }
        asm volatile("stmatrix.sync.aligned.m8n8.x4.shared.b16 [%0], {%1,%2,%3,%4};"
                     :: "r"(st + (lane & 15) * 240 + (lane >> 4) * 16 + i * 32), "r"(pk[0]), "r"(pk[1]), "r"(pk[2]), "r"(pk[3]) : "memory");
      }
      __syncwarp();
      if (lane < 28) {
        const int r2 = lane >= 14, cc = lane - r2 * 14;
        unsigned char* ob = reinterpret_cast<unsigned char*>(out) + (size_t)(m * 128 + kh * 64 + w4 * 16 + r2) * (D_ * 2) + n * 224 + cc * 16;
        float4 v[8];
#pragma unroll
        for (int i = 0; i < 8; i++) v[i] = lds128f(st + r2 * 240 + cc * 16 + i * 480);
#pragma unroll
        for (int i = 0; i < 8; i++) stg128(ob + i * (D_ * 4), __float_as_uint(v[i].x), __float_as_uint(v[i].y), __float_as_uint(v[i].z), __float_as_uint(v[i].w));
      }
    }
    if (t128 == 0) { PROF(wg, 15); if (wg) { PROFG(4, 30); PROF(4, 31); } }
  } else {
    asm volatile("setmaxnreg.dec.sync.aligned.u32 72;");
    const int t = tid - 256;
    const int k = bid;
    if (t == 0) PROF(2, 0);
    uint4 gv[7];
#pragma unroll
    for (int i = 0; i < 7; i++) gv[i] = ldg128(reinterpret_cast<const uint4*>(gate_w) + i * 8 + (t & 7));
    if (t < 98) {
      int cid = m * 98 + t, kc = cid / 56, nn = cid - kc * 56;
      int d = 112 * n + 8 * (2 * (nn >> 3) + (nn & 1)) + (nn & 6) + kh;
      uint32_t pk[4];
#pragma unroll
      for (int e = 0; e < 4; e++) {
        int kk = 4 * kc + e; float c, s;
        cs448((d * kk) % 448, c, s); c *= 2.0f; s *= -2.0f;
        if (kk == 0) { c = 1.0f; s = (float)(kh ? ((d & 2) - 1) : (1 - (d & 2))); }
        pk[e] = pack_bf16(c, s);
      }
      stg128(g_G + (size_t)(n * 2 + kh) * G_IMG + cid * 16, pk[0], pk[1], pk[2], pk[3]);
    }
    bar_sync<0, NTHREADS>();
    asm volatile("barrier.cluster.arrive.relaxed.aligned;" ::: "memory");
    mbar_wait(bars + B_XFREE * 8, 0);
    if (t == 0) PROF(2, 8);
    if (k < 113) {
#pragma unroll 1
      for (int i = 0; i < 4; i++) {
        const int q = 2 * i, rl = (t >> 4) * ((t & 15) + 64 * i), r16 = (t >> 4) * 16;
        sts128(sb + OFF_TW + i * 2048 + t * 16, cis2048(2 * t * q), cis2048((2 * t + 1) * q), cis2048(2 * t * (q + 1)), cis2048((2 * t + 1) * (q + 1)));
        sts128(sb + OFF_TW + 8192 + i * 2048 + t * 16, cis2048(rl), cis2048(rl + r16), cis2048(rl + 2 * r16), cis2048(rl + 3 * r16));
      }
      const int l = (t >> 1) & 15, jj = (t >> 5) * 4 + (t & 1) * 2;
      sts64(sb + OFF_TW + 16384 + t * 8, cis2048(8 * l * jj), cis2048(8 * l * (jj + 1)));
    }
    if (t == 0) PROF(2, 9);
    {
      const int row = n * 16 + (t >> 3), l8 = t & 7;
      mbar_wait(bars + (B_XFULL + 1) * 8, 0);
      float sum = 0.f;
#pragma unroll
      for (int i = 0; i < 7; i++) {
        const uint4 a = lds128(sb + OFF_R + i * 8192 + row * 128 + ((l8 ^ (row & 7)) << 4));
        const uint32_t aa[4] = {a.x, a.y, a.z, a.w}, bb[4] = {gv[i].x, gv[i].y, gv[i].z, gv[i].w};
#pragma unroll
        for (int e = 0; e < 4; e++) {
          const uint32_t pr = as_u(__hmul2(as_b2(aa[e]), as_b2(bb[e])));
          sum += bf_lo(pr) + bf_hi(pr);
        }
      }
      fence_async_smem();
      sum += __shfl_xor_sync(0xffffffffu, sum, 1); sum += __shfl_xor_sync(0xffffffffu, sum, 2); sum += __shfl_xor_sync(0xffffffffu, sum, 4);
      if (lane == 0) mbar_arrive(bars + (B_XFREE + 1) * 8);
      if (l8 == 0) g_gate[m * 128 + kh * 64 + row] = bf16_round(__fdividef(1.0f, 1.0f + __expf(-bf16_round(sum))));
    }
    if (t == 0) PROF(2, 11);
    mbar_wait(bars + B_PIN * 8, 0);
    if (t == 0) PROF(2, 4);
    {
      if (t < 112) {
        const int js = bid >> 4, nn = (t >> 1) / 14, cc = (t >> 1) - nn * 14;
        unsigned char* wdst = g_Wd + (size_t)((js >> 2) * 4 + nn) * WD_IMG + cc * 128 + (t & 1) * 16;
#pragma unroll 1
        for (int i = 0; i < 7; i++) {
          const uint4 v = lds128(sb + OFF_EXCH + i * 1792 + (t & 1) * 896 + (t >> 1) * 16);
          int col = 14 * (bid & 15) + 2 * i - (js & 1) * 32;
          if (col < 0) col += 224;
          const int kpos = col < 192 ? (col >> 6) * 256 + (js & 3) * 64 + (col & 63) : 576 + (js & 3) * 32 + col;
          stg128(wdst + (kpos >> 3) * 1792 + (kpos & 7) * 16, v.x, v.y, v.z, v.w);
        }
      }
      fence_async_smem();
      __syncwarp();
      if (lane == 0) mbar_arrive(bars + B_WDONE * 8);
      const uint32_t wrow = sb + OFF_WS + (((t & 7) - bid) & 7) * 450;
#pragma unroll 2
      for (int kk = t >> 3; kk < 113; kk += 16) {
        const uint32_t a = wrow + kk * 2, c = wrow + 448 - kk * 2;
        const uint32_t r0 = lds16(a) | (lds16(c) << 16), i0 = lds16(a + 7200) | (lds16(c + 7200) << 16);
        const uint32_t r1 = lds16(a + 3600) | (lds16(c + 3600) << 16), i1 = lds16(a + 10800) | (lds16(c + 10800) << 16);
        stg128(g_Wt + kk * S_ + 16 * bid + 2 * (t & 7), r0, i0, r1, i1);
      }
      fence_async_smem();
    }
    bar_sync<3, 128>();
    if (t == 96) { PROF(2, 10); red_release(&g_cnt[4 * 32]); PROF(2, 1); }
    if (k < 113) {
      if (t == 0) PROF(2, 2);
      mbar_wait(bars + B_XCFULL * 8, 0);
      if (t == 0) PROF(2, 3);
      c2 v[16];
      const uint32_t se = k == 0 ? 0x4410 : (k == 112 ? 0x4432 : 0x3210), so = k == 0 ? 0x4410 : (k == 112 ? 0x3244 : 0x3210);
#pragma unroll
      for (int jj = 0; jj < 8; jj++) {
        const uint2 e2 = lds64(sb + OFF_EXCH + jj * 1024 + t * 8), o2 = lds64(sb + OFF_EXCH + 8192 + jj * 1024 + t * 8);
#pragma unroll
        for (int h = 0; h < 2; h++) {
          const b2 e = as_b2(__byte_perm(h ? e2.y : e2.x, 0, se)), o = as_b2(__byte_perm(h ? o2.y : o2.x, 0, so));
          const uint32_t s = as_u(__hadd2(e, o)), d = as_u(__hsub2(e, o)) ^ 0x80000000u;
          v[2 * jj + h] = mk(as_b2(__byte_perm(s, d, 0x5410)), as_b2(__byte_perm(s, d, 0x7632)));
        }
      }
      if (t == 0) PROF(2, 12);
      columns(v, sb, t);
      if (t == 0) PROF(2, 14);
      const int pre = (k == 112) ? 1 : 2 * k, pim = (k == 112) ? 1 : 2 * k + 1;
      uint32_t* pq = reinterpret_cast<uint32_t*>(g_PQ) + (t >> 5) * 14336;
      uint32_t* pr = pq + pre * 32 + ((((lane >> 2) ^ pre) & 7) << 2) + (lane & 3);
      uint32_t* pi = pq + pim * 32 + ((((lane >> 2) ^ pim) & 7) << 2) + (lane & 3);
#pragma unroll
      for (int jj = 0; jj < 8; jj++) {
        const b2 ar = as_b2(__byte_perm(as_u(v[2 * jj].y), as_u(v[2 * jj + 1].y), 0x5410)), br = as_b2(__byte_perm(as_u(v[2 * jj].y), as_u(v[2 * jj + 1].y), 0x7632));
        const b2 ai = as_b2(__byte_perm(as_u(v[2 * jj].x), as_u(v[2 * jj + 1].x), 0x5410)), bi = as_b2(__byte_perm(as_u(v[2 * jj].x), as_u(v[2 * jj + 1].x), 0x7632));
        pr[jj * 57344] = as_u(__hadd2(ar, br));
        if (k != 112) pr[jj * 57344 + 7168] = as_u(__hsub2(ar, br));
        if (k != 0) pi[jj * 57344 + 7168] = as_u(__hadd2(ai, bi));
        if (k != 0 && k != 112) pi[jj * 57344] = as_u(__hsub2(ai, bi));
      }
      fence_async_smem();
    }
    bar_sync<3, 128>();
    if (t == 0) { PROF(2, 5); red_release(&g_cnt[5 * 32]); PROF(2, 7); }
    __syncwarp();
    asm volatile("barrier.cluster.wait.aligned;" ::: "memory");
  }
}

typedef CUresult (*EncodeFn)(CUtensorMap*, CUtensorMapDataType, cuuint32_t, void*, const cuuint64_t*, const cuuint64_t*, const cuuint32_t*,
                             const cuuint32_t*, CUtensorMapInterleave, CUtensorMapSwizzle, CUtensorMapL2promotion, CUtensorMapFloatOOBfill);

void make_map(EncodeFn enc, CUtensorMap* tm, const void* base, int cols, int rows, int bc, int br, CUtensorMapSwizzle sw) {
  cuuint64_t gd[2] = {(cuuint64_t)cols, (cuuint64_t)rows};
  cuuint64_t gs[1] = {(cuuint64_t)cols * 2};
  cuuint32_t bd[2] = {(cuuint32_t)bc, (cuuint32_t)br};
  cuuint32_t es[2] = {1, 1};
  enc(tm, CU_TENSOR_MAP_DATA_TYPE_BFLOAT16, 2, const_cast<void*>(base), gd, gs, bd, es, CU_TENSOR_MAP_INTERLEAVE_NONE, sw,
      CU_TENSOR_MAP_L2_PROMOTION_L2_128B, CU_TENSOR_MAP_FLOAT_OOB_FILL_NONE);
}

}

extern "C" void kernel_launch(void* const* d_in, const int* in_sizes, int n_in, void* d_out, int out_size) {
  (void)in_sizes; (void)n_in; (void)out_size;
  const __nv_bfloat16* x = (const __nv_bfloat16*)d_in[0];
  const __nv_bfloat16* w_r = (const __nv_bfloat16*)d_in[1];
  const __nv_bfloat16* w_i = (const __nv_bfloat16*)d_in[2];
  const __nv_bfloat16* w_gate = (const __nv_bfloat16*)d_in[4];
  const __nv_bfloat16* w_up = (const __nv_bfloat16*)d_in[5];
  const __nv_bfloat16* w_down = (const __nv_bfloat16*)d_in[6];
  const __nv_bfloat16* gate_w = (const __nv_bfloat16*)d_in[7];
  static EncodeFn enc = nullptr;
  static bool ok = false;
  if (!enc) {
    cudaDriverEntryPointQueryResult qr;
    cudaGetDriverEntryPoint("cuTensorMapEncodeTiled", (void**)&enc, cudaEnableDefault, &qr);
    cudaFuncSetAttribute(fused_kernel, cudaFuncAttributeMaxDynamicSharedMemorySize, SMEM_BYTES);
    cudaFuncAttributes fa;
    cudaFuncGetAttributes(&fa, fused_kernel);
    ok = (fa.numRegs == 128);
  }
  if (!ok) return;
  CUtensorMap tx, tg, tu, tg32, tu32;
  {
    cuuint64_t gd[3] = {64, (cuuint64_t)S_, 7};
    cuuint64_t gs[2] = {(cuuint64_t)D_ * 2, 128};
    cuuint32_t bd[3] = {64, 64, 7};
    cuuint32_t es[3] = {1, 1, 1};
    enc(&tx, CU_TENSOR_MAP_DATA_TYPE_BFLOAT16, 3, const_cast<__nv_bfloat16*>(x), gd, gs, bd, es, CU_TENSOR_MAP_INTERLEAVE_NONE, CU_TENSOR_MAP_SWIZZLE_128B,
        CU_TENSOR_MAP_L2_PROMOTION_L2_128B, CU_TENSOR_MAP_FLOAT_OOB_FILL_NONE);
  }
  make_map(enc, &tg, w_gate, F_, D_, 64, 64, CU_TENSOR_MAP_SWIZZLE_128B);
  make_map(enc, &tu, w_up, F_, D_, 64, 64, CU_TENSOR_MAP_SWIZZLE_128B);
  make_map(enc, &tg32, w_gate, F_, D_, 32, 128, CU_TENSOR_MAP_SWIZZLE_64B);
  make_map(enc, &tu32, w_up, F_, D_, 32, 128, CU_TENSOR_MAP_SWIZZLE_64B);
  fused_kernel<<<128, NTHREADS, SMEM_BYTES>>>(tx, tg, tu, tg32, tu32, w_r, w_i, w_gate, w_up, w_down, gate_w, (__nv_bfloat16*)d_out);
}
```

```cpp
#include <cuda_runtime.h>
#include <cuda_bf16.h>
#include <cuda.h>
#include <stdint.h>

namespace {

constexpr int S_ = 2048, D_ = 448, F_ = 1792;
constexpr int NTHREADS = 512;
constexpr int SLOT = 16384, NSLOT = 7;
constexpr int HALF_XR = 57344;
constexpr int OFF_PQ = NSLOT * SLOT;
constexpr int OFF_R = OFF_PQ + HALF_XR;
constexpr int OFF_EXCH = OFF_PQ;
constexpr int OFF_WS = OFF_EXCH + 18432;
constexpr int OFF_TW = OFF_WS + 16384;
constexpr int OFF_MISC = OFF_R + HALF_XR;
constexpr int OFF_G = OFF_MISC;
constexpr int OFF_BAR = OFF_MISC + 512;
constexpr int SMEM_BYTES = OFF_BAR + 512;
constexpr int B_FULL = 0, B_EMPTY = 7, B_XFULL = 14  ;
constexpr int B_XFREE = 16  , B_PUBX = 18, B_RFREE = 19, B_LFREE = 20;
constexpr int B_PUB = 21  , B_HRDY = 29  ;
constexpr int B_PQFULL = 37, B_RECV = 38, B_WFULL = 39, B_XCFULL = 40, B_PREP = 41, B_PREPW = 42, B_PIN = 43, B_RFULL = 44, B_GFULL = 45, B_END = 46;

constexpr int WD_IMG = 896 * 112 * 2;
constexpr int G_IMG = 224 * 56 * 2;

__device__ __align__(1024) uint32_t g_Xc[112 * 2 * S_];
__device__ __align__(1024) unsigned char g_H[32 * 56 * 4096];
__device__ __align__(1024) unsigned char g_PQ[32 * HALF_XR];
__device__ __align__(1024) unsigned char g_Wd[8 * WD_IMG];
__device__ __align__(1024) unsigned char g_G[8 * G_IMG];
__device__ __align__(1024) uint2 g_Wt[113 * S_];
__device__ __align__(1024) float g_gate[S_];
__device__ __align__(128) unsigned int g_hflag[128 * 8];
__device__ __align__(128) unsigned int g_ep[128 * 2];
__device__ __align__(128) unsigned int g_cnt[8 * 32];

#define PROF(role, idx) do {} while (0)
#define PROFG(role, idx) do {} while (0)

__device__ __forceinline__ uint32_t s2u(const void* p) { return (uint32_t)__cvta_generic_to_shared(p); }
__device__ __forceinline__ void mbar_init(uint32_t b, int c) { asm volatile("mbarrier.init.shared::cta.b64 [%0], %1;" :: "r"(b), "r"(c) : "memory"); }
__device__ __forceinline__ void mbar_expect(uint32_t b, int bytes) { asm volatile("mbarrier.arrive.expect_tx.shared::cta.b64 _, [%0], %1;" :: "r"(b), "r"(bytes) : "memory"); }
__device__ __forceinline__ void mbar_arrive(uint32_t b) { asm volatile("mbarrier.arrive.shared::cta.b64 _, [%0];" :: "r"(b) : "memory"); }
__device__ __forceinline__ void mbar_wait(uint32_t b, int ph) {
  asm volatile("{\n.reg .pred p;\n.reg .u32 c;\nmov.u32 c, 0;\nL_WAIT:\nmbarrier.try_wait.parity.shared::cta.b64 p, [%0], %1;\n@p bra.uni L_DONE;\n"
               "add.u32 c, c, 1;\nsetp.lt.u32 p, c, 4194304;\n@p bra.uni L_WAIT;\ntrap;\nL_DONE:\n}" :: "r"(b), "r"(ph) : "memory");
}
__device__ __forceinline__ void mbar_wait_cluster(uint32_t b, int ph) {
  asm volatile("{\n.reg .pred p;\n.reg .u32 c;\nmov.u32 c, 0;\nL_WAIT:\nmbarrier.try_wait.parity.acquire.cluster.shared::cta.b64 p, [%0], %1;\n@p bra.uni L_DONE;\n"
               "add.u32 c, c, 1;\nsetp.lt.u32 p, c, 4194304;\n@p bra.uni L_WAIT;\ntrap;\nL_DONE:\n}" :: "r"(b), "r"(ph) : "memory");
}
__device__ __forceinline__ uint32_t ld_acquire(const unsigned int* p) { uint32_t v; asm volatile("ld.acquire.gpu.global.u32 %0, [%1];" : "=r"(v) : "l"(p) : "memory"); return v; }
__device__ __forceinline__ uint32_t ld_relaxed(const unsigned int* p) { uint32_t v; asm volatile("ld.relaxed.gpu.global.u32 %0, [%1];" : "=r"(v) : "l"(p) : "memory"); return v; }
__device__ __forceinline__ void wait_ge(const unsigned int* p, uint32_t target) {
#pragma unroll 1
  for (int i = 0; i < (1 << 22); i++) { if ((int)(ld_acquire(p) - target) >= 0) return; }
  __trap();
}
__device__ __forceinline__ void red_release(unsigned int* p) { asm volatile("red.release.gpu.global.add.u32 [%0], 1;" :: "l"(p) : "memory"); }
__device__ __forceinline__ bool elect() { uint32_t p; asm volatile("{\n.reg .pred p;\nelect.sync _|p, 0xffffffff;\nselp.u32 %0, 1, 0, p;\n}" : "=r"(p)); return p; }
__device__ __forceinline__ void fence_async_smem() { asm volatile("fence.proxy.async.shared::cta;" ::: "memory"); }
__device__ __forceinline__ void fence_async_global() { asm volatile("fence.proxy.async.global;" ::: "memory"); }
template <int ID, int N> __device__ __forceinline__ void bar_sync() { asm volatile("bar.sync %0, %1;" :: "n"(ID), "n"(N) : "memory"); }
template <int ID, int N> __device__ __forceinline__ void bar_arrive() { asm volatile("bar.arrive %0, %1;" :: "n"(ID), "n"(N) : "memory"); }
__device__ __forceinline__ void tma2d(uint32_t dst, const CUtensorMap* tm, int c0, int c1, uint32_t bar) {
  asm volatile("cp.async.bulk.tensor.2d.shared::cluster.global.mbarrier::complete_tx::bytes [%0], [%1, {%3, %4}], [%2];"
               :: "r"(dst), "l"(tm), "r"(bar), "r"(c0), "r"(c1) : "memory");
}
__device__ __forceinline__ void tma3d(uint32_t dst, const CUtensorMap* tm, int c0, int c1, int c2, uint32_t bar) {
  asm volatile("cp.async.bulk.tensor.3d.shared::cluster.global.mbarrier::complete_tx::bytes [%0], [%1, {%3, %4, %5}], [%2];"
               :: "r"(dst), "l"(tm), "r"(bar), "r"(c0), "r"(c1), "r"(c2) : "memory");
}
__device__ __forceinline__ void bulk_g2s(uint32_t dst, const void* src, int bytes, uint32_t bar) {
  asm volatile("cp.async.bulk.shared::cluster.global.mbarrier::complete_tx::bytes [%0], [%1], %2, [%3];"
               :: "r"(dst), "l"(src), "r"(bytes), "r"(bar) : "memory");
}
__device__ __forceinline__ void prefetch_l2(const void* src, int bytes) {
  asm volatile("cp.async.bulk.prefetch.L2.global [%0], %1;" :: "l"(src), "r"(bytes) : "memory");
}
__device__ __forceinline__ uint64_t mkdesc(uint32_t addr, uint32_t lbo, uint32_t sbo, uint32_t mode) {
  return (uint64_t)((addr & 0x3FFFF) >> 4) | ((uint64_t)(lbo >> 4) << 16) | ((uint64_t)(sbo >> 4) << 32) | ((uint64_t)mode << 62);
}
__device__ __forceinline__ void wg_fence() { asm volatile("wgmma.fence.sync.aligned;" ::: "memory"); }
__device__ __forceinline__ void wg_commit() { asm volatile("wgmma.commit_group.sync.aligned;" ::: "memory"); }
template <int N> __device__ __forceinline__ void wg_wait() { asm volatile("wgmma.wait_group.sync.aligned %0;" :: "n"(N) : "memory"); }
template <int N> __device__ __forceinline__ void keep(float (&d)[N]) {
#pragma unroll
  for (int i = 0; i < N; i++) asm volatile("" : "+f"(d[i]) :: "memory");
}
__device__ __forceinline__ uint32_t pack_bf16(float lo, float hi) { uint32_t r; asm("cvt.rn.bf16x2.f32 %0, %1, %2;" : "=r"(r) : "f"(hi), "f"(lo)); return r; }
__device__ __forceinline__ float bf16_round(float v) { return __bfloat162float(__float2bfloat16_rn(v)); }
__device__ __forceinline__ void sts128(uint32_t a, uint32_t x, uint32_t y, uint32_t z, uint32_t w) { asm volatile("st.shared.v4.b32 [%0], {%1,%2,%3,%4};" :: "r"(a), "r"(x), "r"(y), "r"(z), "r"(w) : "memory"); }
__device__ __forceinline__ float4 lds128f(uint32_t a) { float4 v; asm volatile("ld.shared.v4.f32 {%0,%1,%2,%3}, [%4];" : "=f"(v.x), "=f"(v.y), "=f"(v.z), "=f"(v.w) : "r"(a) : "memory"); return v; }

__device__ __forceinline__ uint2 lds64(uint32_t a) { uint2 v; asm volatile("ld.shared.v2.b32 {%0,%1}, [%2];" : "=r"(v.x), "=r"(v.y) : "r"(a) : "memory"); return v; }
__device__ __forceinline__ float bf_lo(uint32_t w) { return __uint_as_float(w << 16); }
__device__ __forceinline__ float bf_hi(uint32_t w) { return __uint_as_float(w & 0xffff0000u); }
__device__ __forceinline__ uint32_t opaque(uint32_t v) { asm volatile("" : "+r"(v)); return v; }
__device__ __forceinline__ uint4 ldg128(const void* p) { uint4 v; asm volatile("ld.global.nc.v4.b32 {%0,%1,%2,%3}, [%4];" : "=r"(v.x), "=r"(v.y), "=r"(v.z), "=r"(v.w) : "l"(p)); return v; }
__device__ __forceinline__ void stg128(void* p, uint32_t x, uint32_t y, uint32_t z, uint32_t w) { asm volatile("st.global.v4.b32 [%0], {%1,%2,%3,%4};" :: "l"(p), "r"(x), "r"(y), "r"(z), "r"(w) : "memory"); }
__device__ __forceinline__ void ldg128_l2(uint32_t (&v)[4], const void* p) { asm volatile("ld.relaxed.gpu.global.v4.b32 {%0,%1,%2,%3}, [%4];" : "=r"(v[0]), "=r"(v[1]), "=r"(v[2]), "=r"(v[3]) : "l"(p) : "memory"); }
__device__ __forceinline__ uint4 lds128(uint32_t a) { uint4 v; asm volatile("ld.shared.v4.b32 {%0,%1,%2,%3}, [%4];" : "=r"(v.x), "=r"(v.y), "=r"(v.z), "=r"(v.w) : "r"(a) : "memory"); return v; }
__device__ __forceinline__ uint32_t lds16(uint32_t a) { uint32_t v; asm volatile("ld.shared.u16 %0, [%1];" : "=r"(v) : "r"(a) : "memory"); return v; }
__device__ __forceinline__ void sts64(uint32_t a, uint32_t x, uint32_t y) { asm volatile("st.shared.v2.b32 [%0], {%1,%2};" :: "r"(a), "r"(x), "r"(y) : "memory"); }
template <int TB> __device__ __forceinline__ void wgmma_rs_128(float (&d)[64], const uint32_t (&a)[4], uint64_t db, int sc) {
  asm volatile("{\n.reg .pred p;\nsetp.ne.b32 p, %69, 0;\n"
    "wgmma.mma_async.sync.aligned.m64n128k16.f32.bf16.bf16 {%0, %1, %2, %3, %4, %5, %6, %7, %8, %9, %10, %11, %12, %13, %14, %15, %16, %17, %18, %19, %20, %21, %22, %23, %24, %25, %26, %27, %28, %29, %30, %31, %32, %33, %34, %35, %36, %37, %38, %39, %40, %41, %42, %43, %44, %45, %46, %47, %48, %49, %50, %51, %52, %53, %54, %55, %56, %57, %58, %59, %60, %61, %62, %63}, {%64, %65, %66, %67}, %68, p, 1, 1, %70;\n}\n"
    : "+f"(d[0]), "+f"(d[1]), "+f"(d[2]), "+f"(d[3]), "+f"(d[4]), "+f"(d[5]), "+f"(d[6]), "+f"(d[7]), "+f"(d[8]), "+f"(d[9]), "+f"(d[10]), "+f"(d[11]), "+f"(d[12]), "+f"(d[13]), "+f"(d[14]), "+f"(d[15]), "+f"(d[16]), "+f"(d[17]), "+f"(d[18]), "+f"(d[19]), "+f"(d[20]), "+f"(d[21]), "+f"(d[22]), "+f"(d[23]), "+f"(d[24]), "+f"(d[25]), "+f"(d[26]), "+f"(d[27]), "+f"(d[28]), "+f"(d[29]), "+f"(d[30]), "+f"(d[31]), "+f"(d[32]), "+f"(d[33]), "+f"(d[34]), "+f"(d[35]), "+f"(d[36]), "+f"(d[37]), "+f"(d[38]), "+f"(d[39]), "+f"(d[40]), "+f"(d[41]), "+f"(d[42]), "+f"(d[43]), "+f"(d[44]), "+f"(d[45]), "+f"(d[46]), "+f"(d[47]), "+f"(d[48]), "+f"(d[49]), "+f"(d[50]), "+f"(d[51]), "+f"(d[52]), "+f"(d[53]), "+f"(d[54]), "+f"(d[55]), "+f"(d[56]), "+f"(d[57]), "+f"(d[58]), "+f"(d[59]), "+f"(d[60]), "+f"(d[61]), "+f"(d[62]), "+f"(d[63])
    : "r"(a[0]), "r"(a[1]), "r"(a[2]), "r"(a[3]), "l"(db), "r"(sc), "n"(TB));
}
template <int TB> __device__ __forceinline__ void wgmma_rs_64(float (&d)[32], const uint32_t (&a)[4], uint64_t db, int sc) {
  asm volatile("{\n.reg .pred p;\nsetp.ne.b32 p, %37, 0;\n"
    "wgmma.mma_async.sync.aligned.m64n64k16.f32.bf16.bf16 {%0, %1, %2, %3, %4, %5, %6, %7, %8, %9, %10, %11, %12, %13, %14, %15, %16, %17, %18, %19, %20, %21, %22, %23, %24, %25, %26, %27, %28, %29, %30, %31}, {%32, %33, %34, %35}, %36, p, 1, 1, %38;\n}\n"
    : "+f"(d[0]), "+f"(d[1]), "+f"(d[2]), "+f"(d[3]), "+f"(d[4]), "+f"(d[5]), "+f"(d[6]), "+f"(d[7]), "+f"(d[8]), "+f"(d[9]), "+f"(d[10]), "+f"(d[11]), "+f"(d[12]), "+f"(d[13]), "+f"(d[14]), "+f"(d[15]), "+f"(d[16]), "+f"(d[17]), "+f"(d[18]), "+f"(d[19]), "+f"(d[20]), "+f"(d[21]), "+f"(d[22]), "+f"(d[23]), "+f"(d[24]), "+f"(d[25]), "+f"(d[26]), "+f"(d[27]), "+f"(d[28]), "+f"(d[29]), "+f"(d[30]), "+f"(d[31])
    : "r"(a[0]), "r"(a[1]), "r"(a[2]), "r"(a[3]), "l"(db), "r"(sc), "n"(TB));
}
template <int TB> __device__ __forceinline__ void wgmma_rs_56(float (&d)[28], const uint32_t (&a)[4], uint64_t db, int sc) {
  asm volatile("{\n.reg .pred p;\nsetp.ne.b32 p, %33, 0;\n"
    "wgmma.mma_async.sync.aligned.m64n56k16.f32.bf16.bf16 {%0, %1, %2, %3, %4, %5, %6, %7, %8, %9, %10, %11, %12, %13, %14, %15, %16, %17, %18, %19, %20, %21, %22, %23, %24, %25, %26, %27}, {%28, %29, %30, %31}, %32, p, 1, 1, %34;\n}\n"
    : "+f"(d[0]), "+f"(d[1]), "+f"(d[2]), "+f"(d[3]), "+f"(d[4]), "+f"(d[5]), "+f"(d[6]), "+f"(d[7]), "+f"(d[8]), "+f"(d[9]), "+f"(d[10]), "+f"(d[11]), "+f"(d[12]), "+f"(d[13]), "+f"(d[14]), "+f"(d[15]), "+f"(d[16]), "+f"(d[17]), "+f"(d[18]), "+f"(d[19]), "+f"(d[20]), "+f"(d[21]), "+f"(d[22]), "+f"(d[23]), "+f"(d[24]), "+f"(d[25]), "+f"(d[26]), "+f"(d[27])
    : "r"(a[0]), "r"(a[1]), "r"(a[2]), "r"(a[3]), "l"(db), "r"(sc), "n"(TB));
}
template <int TB> __device__ __forceinline__ void wgmma_rs_112(float (&d)[56], const uint32_t (&a)[4], uint64_t db, int sc) {
  asm volatile("{\n.reg .pred p;\nsetp.ne.b32 p, %61, 0;\n"
    "wgmma.mma_async.sync.aligned.m64n112k16.f32.bf16.bf16 {%0, %1, %2, %3, %4, %5, %6, %7, %8, %9, %10, %11, %12, %13, %14, %15, %16, %17, %18, %19, %20, %21, %22, %23, %24, %25, %26, %27, %28, %29, %30, %31, %32, %33, %34, %35, %36, %37, %38, %39, %40, %41, %42, %43, %44, %45, %46, %47, %48, %49, %50, %51, %52, %53, %54, %55}, {%56, %57, %58, %59}, %60, p, 1, 1, %62;\n}\n"
    : "+f"(d[0]), "+f"(d[1]), "+f"(d[2]), "+f"(d[3]), "+f"(d[4]), "+f"(d[5]), "+f"(d[6]), "+f"(d[7]), "+f"(d[8]), "+f"(d[9]), "+f"(d[10]), "+f"(d[11]), "+f"(d[12]), "+f"(d[13]), "+f"(d[14]), "+f"(d[15]), "+f"(d[16]), "+f"(d[17]), "+f"(d[18]), "+f"(d[19]), "+f"(d[20]), "+f"(d[21]), "+f"(d[22]), "+f"(d[23]), "+f"(d[24]), "+f"(d[25]), "+f"(d[26]), "+f"(d[27]), "+f"(d[28]), "+f"(d[29]), "+f"(d[30]), "+f"(d[31]), "+f"(d[32]), "+f"(d[33]), "+f"(d[34]), "+f"(d[35]), "+f"(d[36]), "+f"(d[37]), "+f"(d[38]), "+f"(d[39]), "+f"(d[40]), "+f"(d[41]), "+f"(d[42]), "+f"(d[43]), "+f"(d[44]), "+f"(d[45]), "+f"(d[46]), "+f"(d[47]), "+f"(d[48]), "+f"(d[49]), "+f"(d[50]), "+f"(d[51]), "+f"(d[52]), "+f"(d[53]), "+f"(d[54]), "+f"(d[55])
    : "r"(a[0]), "r"(a[1]), "r"(a[2]), "r"(a[3]), "l"(db), "r"(sc), "n"(TB));
}
template <int TA, int TB> __device__ __forceinline__ void wgmma_ss_56(float (&d)[28], uint64_t da, uint64_t db, int sc) {
  asm volatile("{\n.reg .pred p;\nsetp.ne.b32 p, %30, 0;\n"
    "wgmma.mma_async.sync.aligned.m64n56k16.f32.bf16.bf16 {%0, %1, %2, %3, %4, %5, %6, %7, %8, %9, %10, %11, %12, %13, %14, %15, %16, %17, %18, %19, %20, %21, %22, %23, %24, %25, %26, %27}, %28, %29, p, 1, 1, %31, %32;\n}\n"
    : "+f"(d[0]), "+f"(d[1]), "+f"(d[2]), "+f"(d[3]), "+f"(d[4]), "+f"(d[5]), "+f"(d[6]), "+f"(d[7]), "+f"(d[8]), "+f"(d[9]), "+f"(d[10]), "+f"(d[11]), "+f"(d[12]), "+f"(d[13]), "+f"(d[14]), "+f"(d[15]), "+f"(d[16]), "+f"(d[17]), "+f"(d[18]), "+f"(d[19]), "+f"(d[20]), "+f"(d[21]), "+f"(d[22]), "+f"(d[23]), "+f"(d[24]), "+f"(d[25]), "+f"(d[26]), "+f"(d[27])
    : "l"(da), "l"(db), "r"(sc), "n"(TA), "n"(TB));
}

__device__ __forceinline__ uint32_t cis(float a) { return pack_bf16(__cosf(a), __sinf(a)); }

typedef __nv_bfloat162 b2;
struct c2 { b2 x, y; };
__device__ __forceinline__ b2 as_b2(uint32_t u) { return *reinterpret_cast<b2*>(&u); }
__device__ __forceinline__ uint32_t as_u(b2 v) { return *reinterpret_cast<uint32_t*>(&v); }
__device__ __forceinline__ c2 mk(b2 x, b2 y) { c2 r; r.x = x; r.y = y; return r; }
__device__ __forceinline__ c2 cmul(c2 a, b2 wr, b2 wi) { return mk(__hfma2(a.x, wr, __hneg2(__hmul2(a.y, wi))), __hfma2(a.x, wi, __hmul2(a.y, wr))); }
__device__ __forceinline__ void fft4(c2& a0, c2& a1, c2& a2, c2& a3) {
  c2 t0 = mk(__hadd2(a0.x, a2.x), __hadd2(a0.y, a2.y)), t1 = mk(__hsub2(a0.x, a2.x), __hsub2(a0.y, a2.y));
  c2 t2 = mk(__hadd2(a1.x, a3.x), __hadd2(a1.y, a3.y)), t3 = mk(__hsub2(a1.x, a3.x), __hsub2(a1.y, a3.y));
  a0 = mk(__hadd2(t0.x, t2.x), __hadd2(t0.y, t2.y)); a2 = mk(__hsub2(t0.x, t2.x), __hsub2(t0.y, t2.y));
  a1 = mk(__hadd2(t1.x, t3.y), __hsub2(t1.y, t3.x)); a3 = mk(__hsub2(t1.x, t3.y), __hadd2(t1.y, t3.x));
}
__device__ __forceinline__ void fft4_s2(c2& a0, c2& a1, c2& a2, c2& a3, b2 r) {
  const b2 nr = __hneg2(r);
  c2 t0 = mk(__hfma2(a2.x, r, a0.x), __hfma2(a2.y, r, a0.y)), t1 = mk(__hfma2(a2.x, nr, a0.x), __hfma2(a2.y, nr, a0.y));
  c2 t2 = mk(__hadd2(a1.x, a3.x), __hadd2(a1.y, a3.y)), t3 = mk(__hsub2(a1.x, a3.x), __hsub2(a1.y, a3.y));
  a0 = mk(__hadd2(t0.x, t2.x), __hadd2(t0.y, t2.y)); a2 = mk(__hsub2(t0.x, t2.x), __hsub2(t0.y, t2.y));
  a1 = mk(__hadd2(t1.x, t3.y), __hsub2(t1.y, t3.x)); a3 = mk(__hsub2(t1.x, t3.y), __hadd2(t1.y, t3.x));
}
__device__ __forceinline__ void fft4_s13(c2& a0, c2& a1, c2& a2, c2& a3, b2 r) {
  const b2 nr = __hneg2(r);
  c2 t0 = mk(__hadd2(a0.x, a2.x), __hadd2(a0.y, a2.y)), t1 = mk(__hsub2(a0.x, a2.x), __hsub2(a0.y, a2.y));
  c2 t2 = mk(__hadd2(a1.x, a3.x), __hadd2(a1.y, a3.y)), t3 = mk(__hsub2(a1.x, a3.x), __hsub2(a1.y, a3.y));
  a0 = mk(__hfma2(t2.x, r, t0.x), __hfma2(t2.y, r, t0.y)); a2 = mk(__hfma2(t2.x, nr, t0.x), __hfma2(t2.y, nr, t0.y));
  a1 = mk(__hfma2(t3.y, r, t1.x), __hfma2(t3.x, nr, t1.y)); a3 = mk(__hfma2(t3.y, nr, t1.x), __hfma2(t3.x, r, t1.y));
}
__device__ __forceinline__ c2 rot1(c2 a) { return mk(__hadd2(a.x, a.y), __hsub2(a.y, a.x)); }
__device__ __forceinline__ c2 rot3(c2 a) { return mk(__hsub2(a.y, a.x), __hneg2(__hadd2(a.x, a.y))); }
__device__ __forceinline__ c2 mul_mi(c2 a) { return mk(a.y, __hneg2(a.x)); }
template <int O> __device__ __forceinline__ void fft8(c2 (&v)[16]) {
  const b2 r = as_b2(0x3F353F35u), nr = as_b2(0xBF35BF35u);
  fft4(v[O], v[O + 4], v[O + 8], v[O + 12]);
  fft4(v[O + 2], v[O + 6], v[O + 10], v[O + 14]);
  const c2 o0 = v[O + 2], o1 = rot1(v[O + 6]), o2 = v[O + 10], o3 = rot1(v[O + 14]);
  const c2 e0 = v[O], e1 = v[O + 4], e2 = v[O + 8], e3 = v[O + 12];
  v[O] = mk(__hadd2(e0.x, o0.x), __hadd2(e0.y, o0.y));              v[O + 8] = mk(__hsub2(e0.x, o0.x), __hsub2(e0.y, o0.y));
  v[O + 2] = mk(__hfma2(o1.x, r, e1.x), __hfma2(o1.y, r, e1.y));    v[O + 10] = mk(__hfma2(o1.x, nr, e1.x), __hfma2(o1.y, nr, e1.y));
  v[O + 4] = mk(__hadd2(e2.x, o2.y), __hsub2(e2.y, o2.x));          v[O + 12] = mk(__hsub2(e2.x, o2.y), __hadd2(e2.y, o2.x));
  v[O + 6] = mk(__hfma2(o3.y, r, e3.x), __hfma2(o3.x, nr, e3.y));   v[O + 14] = mk(__hfma2(o3.y, nr, e3.x), __hfma2(o3.x, r, e3.y));
}
__device__ __forceinline__ void fft16(c2 (&v)[16]) {
  const b2 r = as_b2(0x3F353F35u), c1 = as_b2(0x3F6D3F6Du), s1 = as_b2(0x3EC43EC4u), nc1 = as_b2(0xBF6DBF6Du), ns1 = as_b2(0xBEC4BEC4u);
#pragma unroll
  for (int a = 0; a < 4; a++) fft4(v[a], v[a + 4], v[a + 8], v[a + 12]);
  v[5] = cmul(v[5], c1, ns1); v[6] = rot1(v[6]); v[7] = cmul(v[7], s1, nc1);
  v[9] = rot1(v[9]); v[10] = mul_mi(v[10]); v[11] = rot3(v[11]);
  v[13] = cmul(v[13], s1, nc1); v[14] = rot3(v[14]); v[15] = cmul(v[15], nc1, s1);
  fft4(v[0], v[1], v[2], v[3]); fft4_s2(v[4], v[5], v[6], v[7], r); fft4_s13(v[8], v[9], v[10], v[11], r); fft4_s2(v[12], v[13], v[14], v[15], r);
  c2 t;
  t = v[1]; v[1] = v[4]; v[4] = t;  t = v[2]; v[2] = v[8]; v[8] = t;  t = v[3]; v[3] = v[12]; v[12] = t;
  t = v[6]; v[6] = v[9]; v[9] = t;  t = v[7]; v[7] = v[13]; v[13] = t; t = v[11]; v[11] = v[14]; v[14] = t;
}

__device__ __forceinline__ void columns(c2 (&v)[16], uint32_t sb, int t) {
  const int l16 = t & 15;
  const uint32_t row = sb + OFF_EXCH + (t >> 4) * 2304;
  const uint32_t pos = sb + OFF_EXCH + (t >> 3) * 144 + (t & 7) * 16;
#pragma unroll 1
  for (int ps = 0; ps < 6; ps++) {
    if (ps == 0 || ps == 5) { fft8<0>(v); fft8<1>(v); } else fft16(v);
    if (ps == 5) break;
    if (ps == 2) {
      const uint32_t ws = sb + OFF_WS + (l16 >> 1) * 128 + ((((t >> 4) + (l16 >> 1)) & 7) * 2 + (l16 & 1)) * 8;
      mbar_wait(sb + OFF_BAR + B_WFULL * 8, 0);
#pragma unroll
      for (int q = 0; q < 16; q++) {
        const uint2 w = lds64(ws + q * 1024);
        const c2 z = cmul(v[q], as_b2(w.x), as_b2(w.y));
        v[q] = mk(z.y, z.x);
      }
      continue;
    }
    {
      const bool full = ps == 0 || ps == 4;
      const uint32_t tw = sb + OFF_TW + (full ? ps * 2048 + t * 16 : 16384 + l16 * 16);
      const uint32_t st = full ? 2048 : 256;
#pragma unroll
      for (int i = 0; i < 4; i++) {
        const uint4 w4 = lds128(tw + i * st);
        const uint32_t w[4] = {w4.x, w4.y, w4.z, w4.w};
#pragma unroll
        for (int e = 0; e < 4; e++) v[4 * i + e] = cmul(v[4 * i + e], __low2bfloat162(as_b2(w[e])), __high2bfloat162(as_b2(w[e])));
      }
    }
    if (ps == 0) {
      bar_sync<3, 128>();
#pragma unroll
      for (int q = 0; q < 8; q++) sts128(pos + q * 2304, as_u(v[2 * q].x), as_u(v[2 * q].y), as_u(v[2 * q + 1].x), as_u(v[2 * q + 1].y));
      bar_sync<3, 128>();
#pragma unroll
      for (int q = 0; q < 16; q++) { const uint2 a = lds64(row + q * 144 + l16 * 8); v[q] = mk(as_b2(a.x), as_b2(a.y)); }
    } else {
      __syncwarp();
#pragma unroll
      for (int q = 0; q < 16; q++) sts64(row + q * 144 + l16 * 8, as_u(v[q].x), as_u(v[q].y));
      if (ps == 4) bar_sync<3, 128>(); else __syncwarp();
      const uint32_t src = ps == 4 ? pos : row + l16 * 144, st = ps == 4 ? 2304 : 16;
#pragma unroll
      for (int q = 0; q < 8; q++) { const uint4 a = lds128(src + q * st); v[2 * q] = mk(as_b2(a.x), as_b2(a.y)); v[2 * q + 1] = mk(as_b2(a.z), as_b2(a.w)); }
    }
  }
}

template <int NH> __device__ __forceinline__ void h_epilogue(float (&acc)[NH * 8], unsigned char* gdst) {
#pragma unroll
  for (int c = 0; c < NH / 2; c++) {
    uint32_t pk[4];
#pragma unroll
    for (int i = 0; i < 4; i++) {
      float hv[2];
#pragma unroll
      for (int e = 0; e < 2; e++) {
        float hg = 0.5f * acc[c * 8 + i * 2 + e], up = acc[NH * 4 + c * 8 + i * 2 + e];
        float th; asm("tanh.approx.f32 %0, %1;" : "=f"(th) : "f"(hg));
        hv[e] = fmaf(hg, th, hg) * up;
      }
      pk[i] = pack_bf16(hv[0], hv[1]);
    }
    stg128(gdst + c * 4096, pk[0], pk[1], pk[2], pk[3]);
  }
}

#define LA2 5
#define LEAD1 3

__global__ void __cluster_dims__(2, 1, 1) __launch_bounds__(NTHREADS, 1)
fused_kernel(const __grid_constant__ CUtensorMap tm_x, const __grid_constant__ CUtensorMap tm_g, const __grid_constant__ CUtensorMap tm_u,
             const __grid_constant__ CUtensorMap tm_g32, const __grid_constant__ CUtensorMap tm_u32,
             const __nv_bfloat16* __restrict__ w_r, const __nv_bfloat16* __restrict__ w_i,
             const __nv_bfloat16* __restrict__ w_gate, const __nv_bfloat16* __restrict__ w_up,
             const __nv_bfloat16* __restrict__ w_down, const __nv_bfloat16* __restrict__ gate_w, __nv_bfloat16* __restrict__ out) {
  extern __shared__ __align__(1024) unsigned char smem[];
  const uint32_t sb = s2u(smem);
  const uint32_t bars = sb + OFF_BAR;
  const int tid = threadIdx.x, warp = __shfl_sync(0xffffffffu, tid >> 5, 0), lane = tid & 31;
  const int cl = blockIdx.x >> 1, kh = blockIdx.x & 1;
  const int n = cl < 4 ? cl : (cl < 36 ? (cl - 4) >> 3 : (cl - 36) / 7);
  const int m = cl < 4 ? 15 : (cl < 36 ? (cl - 4) & 7 : cl - 28 - 7 * n);
  const int j = kh * 4 + n, bid = m * 8 + n * 2 + kh;

  if (warp >= 12) {
    asm volatile("setmaxnreg.dec.sync.aligned.u32 24;");
    const int c64 = 224 * j + (j & 1) * 32;
    if (warp == 13) {
      if (elect()) {
        PROFG(4, 0); PROF(4, 1);
        mbar_init(bars + B_XFULL * 8, 1); mbar_init(bars + (B_XFULL + 1) * 8, 1);
        fence_async_smem();
#pragma unroll
        for (int w = 0; w < 2; w++) {
          mbar_expect(bars + (B_XFULL + w) * 8, HALF_XR);
          tma3d(sb + OFF_PQ + w * HALF_XR, &tm_x, 0, m * 128 + (w ^ kh ^ 1) * 64, 0, bars + (B_XFULL + w) * 8);
        }
      }
    } else if (warp == 12) {
      if (lane < NSLOT) mbar_init(bars + (B_FULL + lane) * 8, 1);
      fence_async_smem();
      __syncwarp();
#pragma unroll 1
      for (int i = 0; i < 6; i++) {
        if (elect()) {
          const uint32_t fb = bars + (B_FULL + i) * 8;
          mbar_expect(fb, SLOT);
          tma2d(sb + i * SLOT, &tm_g, c64, i * 64, fb);
          tma2d(sb + i * SLOT + 8192, &tm_u, c64, i * 64, fb);
        }
      }
      if (lane == 0) PROF(3, 3);
    } else if (warp == 14) {
      if (lane < NSLOT) mbar_init(bars + (B_EMPTY + lane) * 8, 8);
      const int i = B_XFREE + lane;
      if (i < B_END) mbar_init(bars + i * 8, i >= B_PQFULL ? 1 : (i >= B_HRDY ? 3 : ((i == B_XFREE || i >= B_PUB) ? 4 : 8)));
      asm volatile("fence.mbarrier_init.release.cluster;" ::: "memory");
      __syncwarp();
      if (lane == 0) mbar_expect(bars + B_RECV * 8, 64 * 112 * 4);
    } else if (elect()) {
      prefetch_l2(reinterpret_cast<const unsigned char*>(w_r) + bid * 7200, 7200);
      prefetch_l2(reinterpret_cast<const unsigned char*>(w_i) + bid * 7200, 7200);
    }
    bar_sync<0, NTHREADS>();
    asm volatile("barrier.cluster.arrive.relaxed.aligned;" ::: "memory");
    if (warp == 12) {
      int slot = 6, ph = 1;
      auto wait_slot = [&]() { mbar_wait(bars + (B_EMPTY + slot) * 8, ph ^ (slot == 6)); };
      auto adv = [&]() { if (++slot == NSLOT) { slot = 0; ph ^= 1; } };
      const int c32 = 224 * j + ((j & 1) ? 0 : 192);
#pragma unroll 1
      for (int i = 6; i < 25; i++) {
        wait_slot();
        if (elect()) {
          const uint32_t dst = sb + slot * SLOT, fb = bars + (B_FULL + slot) * 8;
          const bool last = i >= 21;
          const int cc = last ? c32 : c64 + 64 * (i / 7), rr = last ? slot * 128 : slot * 64;
          mbar_expect(fb, SLOT);
          tma2d(dst, last ? &tm_g32 : &tm_g, cc, rr, fb);
          tma2d(dst + 8192, last ? &tm_u32 : &tm_u, cc, rr, fb);
        }
        adv();
      }
      if (lane == 0) PROF(3, 0);
      mbar_wait(bars + B_PREP * 8, 0);
      if (lane == 0) PROF(3, 1);
#pragma unroll 1
      for (int i = 4; i < 16; i++) {
        if (lane == 0) PROF(3, 16 + i);
        wait_slot();
        if (elect()) {
          const int bytes = i < 14 ? 14336 : G_IMG / 2;
          const unsigned char* src = i < 14 ? g_Wd + (size_t)j * WD_IMG + i * 14336 : g_G + (size_t)(n * 4 + i - 12) * (G_IMG / 2);
          mbar_expect(bars + (B_FULL + slot) * 8, bytes);
          bulk_g2s(sb + slot * SLOT, src, bytes, bars + (B_FULL + slot) * 8);
        }
        adv();
      }
      if (lane == 0) PROF(3, 2);
    } else if (warp == 13) {
#pragma unroll 1
      for (int u = -1; u < 8; u++) {
        mbar_wait(bars + (u < 0 ? B_PUBX : B_PUB + u) * 8, 0);
        if (lane == 0) {
          PROF(4, 9 + u);
          red_release(u < 0 ? &g_cnt[(j >> 1) * 32] : &g_hflag[bid * 8 + u]);
          PROF(4, 19 + u);
        }
        __syncwarp();
      }
      mbar_wait(bars + B_LFREE * 8, 0);
      if (elect()) {
        mbar_expect(bars + B_GFULL * 8, G_IMG);
        bulk_g2s(sb + OFF_R + 28672, g_G + (size_t)(n * 2) * G_IMG, G_IMG, bars + B_GFULL * 8);
      }
    } else if (warp == 14) {
      const uint32_t epoch = ld_relaxed(&g_ep[bid * 2]);
      if (lane < 26) {
        const unsigned int* fp = lane < 24 ? &g_hflag[(m * 8 + ((n + 1 + (lane >> 3)) & 3) * 2 + kh) * 8 + (lane & 7)] : &g_cnt[(lane * 2 - 44) * 32];
        const uint32_t tgt = lane < 24 ? epoch + 1 : (epoch + 1) * 128;
        const uint32_t rb = bars + (lane < 24 ? B_HRDY + (lane & 7) : B_PREP - 24 + lane) * 8;
        bool done = false;
#pragma unroll 1
        for (int i = 0; i < (1 << 20); i++) {
          if (!done && (int)(ld_acquire(fp) - tgt) >= 0) { fence_async_global(); mbar_arrive(rb); done = true; if (lane < 8 || lane >= 24) PROF(5, lane & 15); }
          if (__all_sync(0x3ffffff, done)) break;
        }
        if (!done) __trap();
        if (lane == 0) g_ep[bid * 2] = epoch + 1;
      }
    } else {
      const uint32_t epoch = ld_relaxed(&g_ep[bid * 2 + 1]);
      mbar_wait(bars + B_XFREE * 8, 0);
      if (elect()) {
        mbar_expect(bars + B_PIN * 8, 14400);
        bulk_g2s(sb + OFF_WS, reinterpret_cast<const unsigned char*>(w_r) + bid * 7200, 7200, bars + B_PIN * 8);
        bulk_g2s(sb + OFF_WS + 7200, reinterpret_cast<const unsigned char*>(w_i) + bid * 7200, 7200, bars + B_PIN * 8);
        prefetch_l2(reinterpret_cast<const unsigned char*>(w_gate) + bid * 12544, 12544);
        prefetch_l2(reinterpret_cast<const unsigned char*>(w_up) + bid * 12544, 12544);
      }
      mbar_wait(bars + (B_XFREE + 1) * 8, 0);
      if (elect()) {
        mbar_expect(bars + B_RFULL * 8, 12544);
        bulk_g2s(sb + OFF_R, reinterpret_cast<const unsigned char*>(w_down) + bid * 12544, 12544, bars + B_RFULL * 8);
      }
      if (bid < 113) {
        const int sl = (bid == 112) ? 0 : bid;
        wait_ge(&g_cnt[((sl & 1) + 2 * ((sl >> 1) / 28)) * 32], (epoch + 1) * 32);
        fence_async_global();
        if (elect()) {
          PROF(5, 16);
          mbar_expect(bars + B_XCFULL * 8, 16384);
          bulk_g2s(sb + OFF_EXCH, g_Xc + sl * 2 * S_, 16384, bars + B_XCFULL * 8);
        }
        mbar_wait(bars + B_PREPW * 8, 0);
        if (elect()) {
          mbar_expect(bars + B_WFULL * 8, 16384);
          bulk_g2s(sb + OFF_WS, g_Wt + bid * S_, 16384, bars + B_WFULL * 8);
          PROF(5, 17);
        }
      }
      mbar_wait(bars + B_PREP * 8, 0);
      if (elect()) {
        mbar_expect(bars + B_RFULL * 8, HALF_XR);
        bulk_g2s(sb + OFF_R, g_Wd + (size_t)j * WD_IMG, HALF_XR, bars + B_RFULL * 8);
        PROF(5, 19);
      }
      wait_ge(&g_cnt[5 * 32], (epoch + 1) * 128);
      fence_async_global();
      if (elect()) {
        PROF(5, 18);
        mbar_expect(bars + B_PQFULL * 8, HALF_XR + 256);
        const unsigned char* src = g_PQ + (size_t)(m * 2 + kh) * HALF_XR;
        bulk_g2s(sb + OFF_PQ, src, 28672, bars + B_PQFULL * 8);
        bulk_g2s(sb + OFF_PQ + 28672, src + 28672, 28672, bars + B_PQFULL * 8);
        bulk_g2s(sb + OFF_G, g_gate + m * 128 + kh * 64, 256, bars + B_PQFULL * 8);
        g_ep[bid * 2 + 1] = epoch + 1;
      }
    }
    __syncwarp();
    asm volatile("barrier.cluster.wait.aligned;" ::: "memory");
  } else if (warp < 8) {
    asm volatile("setmaxnreg.inc.sync.aligned.u32 208;");
    const int wg = warp >> 2, w4 = warp & 3, g = lane >> 2, t = lane & 3;
    const int rh = wg ^ kh ^ 1;
    const int p = j & 1, r = (j >> 1) & 1, hh = j >> 2;
    if ((tid & 127) == 0) PROF(wg, 30);
#pragma unroll 1
    for (int it = tid; it < 392; it += 256) {
      const int kc = it / 28, sg = it - kc * 28;
      const int k = 2 * (28 * hh + sg) + r;
      const float kf = (float)k * (-6.283185307179586f / 448.0f), a0 = (float)(16 * kc + p) * kf;
      uint32_t c[4], s[4];
#pragma unroll
      for (int q = 0; q < 4; q++) {
        const float a1 = fmaf((float)(2 * q), kf, a0), a2 = fmaf((float)(2 * q + 8), kf, a0);
        c[q] = pack_bf16(__cosf(a1), __cosf(a2)); s[q] = pack_bf16(__sinf(a1), __sinf(a2));
        if (k == 0) s[q] = ((q ^ p) & 1) ? 0xBF80BF80u : 0x3F803F80u;
      }
      const uint32_t a = sb + 6 * SLOT + (kc * 56 + 2 * sg) * 16;
      sts128(a, c[0], c[1], c[2], c[3]);
      sts128(a + 16, s[0], s[1], s[2], s[3]);
    }
    if ((tid & 127) == 0) PROF(wg, 31);
    fence_async_smem();
    bar_sync<0, NTHREADS>();
    asm volatile("barrier.cluster.arrive.relaxed.aligned;" ::: "memory");
    if ((tid & 127) == 0) PROF(wg, 1);

    uint32_t xa[28][4];
    {
      const uint32_t xb = sb + OFF_PQ + wg * HALF_XR + (w4 * 16 + (lane & 15)) * 128;
      mbar_wait(bars + (B_XFULL + wg) * 8, 0);
      if ((tid & 127) == 0) PROF(wg, 2);
#pragma unroll
      for (int kb = 0; kb < 7; kb++) {
#pragma unroll
        for (int kk = 0; kk < 4; kk++) {
          uint32_t a = xb + kb * 8192 + (((2 * kk + (lane >> 4)) ^ (lane & 7)) << 4);
          asm volatile("ldmatrix.sync.aligned.m8n8.x4.shared.b16 {%0,%1,%2,%3}, [%4];"
                       : "=r"(xa[kb * 4 + kk][0]), "=r"(xa[kb * 4 + kk][1]), "=r"(xa[kb * 4 + kk][2]), "=r"(xa[kb * 4 + kk][3]) : "r"(a) : "memory");
        }
      }
    }
    {
      uint32_t ad[7][4];
      const uint32_t sel = p ? 0x7632 : 0x5410;
      const uint32_t sgn = r ? 0xBF80BF80u : 0x3F803F80u;
#pragma unroll
      for (int jj = 0; jj < 7; jj++) {
#pragma unroll
        for (int i = 0; i < 4; i++) {
          int ks = 2 * jj + (i >> 1), rr = i & 1;
          uint32_t lo = __byte_perm(xa[ks][rr], xa[ks][rr + 2], sel);
          uint32_t hi = __byte_perm(xa[ks + 14][rr], xa[ks + 14][rr + 2], sel);
          asm("fma.rn.bf16x2 %0, %1, %2, %3;" : "=r"(ad[jj][i]) : "r"(hi), "r"(sgn), "r"(lo));
        }
      }
      __syncwarp();
      if (lane == 0) mbar_arrive(bars + (B_XFREE + wg) * 8);
      float acc[28];
      wg_fence();
      uint64_t db = mkdesc(sb + 6 * SLOT, 896, 128, 0);
#pragma unroll
      for (int jj = 0; jj < 7; jj++) wgmma_rs_56<0>(acc, ad[jj], db + jj * 112, jj != 0);
      wg_commit();
      wg_wait<0>(); keep(acc);
      if (lane == 0) mbar_arrive(bars + (B_EMPTY + 6) * 8);
      uint32_t* xc = g_Xc + (size_t)((2 * (28 * hh + t) + r) * 2 + p) * S_ + m * 128 + rh * 64 + w4 * 16 + g;
#pragma unroll
      for (int i = 0; i < 7; i++) {
        xc[i * 16 * S_] = pack_bf16(acc[4 * i], acc[4 * i + 1]);
        xc[i * 16 * S_ + 8] = pack_bf16(acc[4 * i + 2], acc[4 * i + 3]);
      }
      __syncwarp();
      if (lane == 0) mbar_arrive(bars + B_PUBX * 8);
    }
    if ((tid & 127) == 0) PROF(wg, 3);
    const uint32_t hrdy = bars + (B_HRDY + wg) * 8;
    unsigned char* const hbase = g_H + (size_t)(m * 2 + kh) * (56 * 4096) + rh * 2048 + (tid & 127) * 16;
#pragma unroll 1
    for (int u = 0; u < 3; u++) {
      float acc[64];
      if (wg == 1) { if (u & 1) bar_sync<6, 256>(); else bar_sync<2, 256>(); }
      const uint32_t sbu = opaque(sb);
#pragma unroll
      for (int kb = 0; kb < 7; kb++) {
        mbar_wait(sbu + OFF_BAR + (B_FULL + kb) * 8, u & 1);
        wg_fence();
        uint64_t db = mkdesc(sbu + kb * SLOT, 8192, 1024, 1);
#pragma unroll
        for (int kk = 0; kk < 4; kk++) wgmma_rs_128<1>(acc, xa[kb * 4 + kk], db + kk * 128, (kb | kk) != 0);
        wg_commit();
        if (kb == LEAD1 && wg == 0) { if (u & 1) bar_arrive<6, 256>(); else bar_arrive<2, 256>(); }
        if (kb > 0) { wg_wait<1>(); if (lane == 0) mbar_arrive(sbu + OFF_BAR + (B_EMPTY + kb - 1) * 8); }
      }
      wg_wait<0>(); keep(acc);
      if (lane == 0) mbar_arrive(sbu + OFF_BAR + (B_EMPTY + 6) * 8);
      if ((tid & 127) == 0) PROF(wg, 4 + 2 * u);
      h_epilogue<8>(acc, hbase + (u * 16 + n * 4) * 4096);
      __syncwarp();
      if (lane == 0) mbar_arrive(sbu + OFF_BAR + (B_PUB + 2 * u + wg) * 8);
      if ((tid & 127) == 0) PROF(wg, 5 + 2 * u);
    }
    {
      float acc[32];
      if (wg == 1) bar_sync<6, 256>();
      const uint32_t sbu = opaque(sb);
#pragma unroll
      for (int it = 0; it < 4; it++) {
        mbar_wait(sbu + OFF_BAR + (B_FULL + it) * 8, 1);
        wg_fence();
        uint64_t db = mkdesc(sbu + it * SLOT, 8192, 512, 2);
#pragma unroll
        for (int kk = 0; kk < 8; kk++) if (it * 8 + kk < 28) wgmma_rs_64<1>(acc, xa[it * 8 + kk], db + kk * 64, (it | kk) != 0);
        wg_commit();
        if (it == 2 && wg == 0) bar_arrive<6, 256>();
        if (it > 0) {
          wg_wait<1>();
          if (lane == 0) mbar_arrive(sbu + OFF_BAR + (B_EMPTY + it - 1) * 8);
          if (it != 2) mbar_wait(hrdy + (it >> 1) * 16, 0);
#pragma unroll
          for (int i = it * 8 - 8; i < it * 8; i++) if (i < 4 * LA2) ldg128_l2(xa[i], hbase + i * 4096);
        }
      }
      wg_wait<0>(); keep(acc);
      if (lane == 0) mbar_arrive(sbu + OFF_BAR + (B_EMPTY + 3) * 8);
      if ((tid & 127) == 0) PROF(wg, 10);
      h_epilogue<4>(acc, hbase + (48 + n * 2) * 4096);
      __syncwarp();
      if (lane == 0) mbar_arrive(sbu + OFF_BAR + (B_PUB + 6 + wg) * 8);
    }
    asm volatile("barrier.cluster.wait.aligned;" ::: "memory");
    if ((tid & 127) == 0) PROF(wg, 11);

    float acc[56];
    if (wg == 1) bar_sync<2, 256>();
#pragma unroll 1
    for (int it = 0; it < 2; it++) {
#pragma unroll
      for (int e = 0; e < 7; e++) {
        if ((tid & 127) == 0) PROF(wg, 16 + it * 7 + e);
        const bool inr = e < 4 && it == 0;
        if (e >= 4 || it == 1) mbar_wait(bars + (B_FULL + e) * 8, e < 4 ? 0 : it ^ 1);
        else if (e == 0) mbar_wait(bars + B_RFULL * 8, 1);
        wg_fence();
        const uint64_t db = mkdesc(inr ? sb + OFF_R + e * 14336 : sb + e * SLOT, 1792, 128, 0);
#pragma unroll
        for (int kk = 0; kk < 4; kk++) wgmma_rs_112<1>(acc, xa[e * 4 + kk], db + kk * 224, (e | kk) ? 1 : it);
        wg_commit();
        if (e == 1 && it == 0 && wg == 0) bar_arrive<2, 256>();
        if (it == 0 || e + LA2 < 7) {
          const int nb = it * 7 + e + LA2;
          if ((e + LA2) % 4 == 0 || (e + LA2 + 7) % 4 == 0) { if ((nb & 3) == 0) mbar_wait(hrdy + nb * 4, 0); }
#pragma unroll
          for (int kk = 0; kk < 4; kk++) ldg128_l2(xa[((e + LA2) % 7) * 4 + kk], hbase + (nb * 4 + kk) * 4096);
        }
        wg_wait<1>();
        if (lane == 0) {
          if (it == 0 ? e >= 5 : e <= 2) mbar_arrive(bars + (B_EMPTY + (e + 6) % 7) * 8);
          if (e == 4 && it == 0) {
            mbar_arrive(bars + B_LFREE * 8);
            asm volatile("{\n.reg .b32 ra;\nmapa.shared::cluster.u32 ra, %0, %1;\nmbarrier.arrive.relaxed.cluster.shared::cluster.b64 _, [ra];\n}"
                         :: "r"(bars + B_RFREE * 8), "r"(kh ^ 1) : "memory");
          }
        }
      }
    }
    const int t128 = tid & 127;
    wg_wait<0>(); keep(acc);
    if (wg == 0) {
      if (t128 == 0) PROF(wg, 12);
      mbar_wait_cluster(bars + B_RFREE * 8, 0);
      uint32_t rdst, rbar;
      asm volatile("mapa.shared::cluster.u32 %0, %1, %2;" : "=r"(rdst) : "r"(sb + OFF_R + t128 * 16), "r"(kh ^ 1));
      asm volatile("mapa.shared::cluster.u32 %0, %1, %2;" : "=r"(rbar) : "r"(bars + B_RECV * 8), "r"(kh ^ 1));
#pragma unroll
      for (int i = 0; i < 14; i++)
        asm volatile("st.async.weak.shared::cluster.mbarrier::complete_tx::bytes.v4.f32 [%0], {%1,%2,%3,%4}, [%5];"
                     :: "r"(rdst + i * 2048), "f"(acc[4 * i]), "f"(acc[4 * i + 1]), "f"(acc[4 * i + 2]), "f"(acc[4 * i + 3]), "r"(rbar) : "memory");
    } else {
      float spec[2][28];
      if (t128 == 0) PROF(wg, 12);
      mbar_wait(bars + B_PQFULL * 8, 0);
      if (t128 == 0) PROF(wg, 13);
#pragma unroll
      for (int i = 0; i < 4; i++) {
        if (i == 0) mbar_wait(bars + B_GFULL * 8, 0);
        if (i >= 2) mbar_wait(bars + (B_FULL + i - 2) * 8, 1);
        wg_fence();
        const uint64_t da = mkdesc(sb + OFF_PQ + i * 14336, 1024, 1024, 1);
        const uint64_t db = mkdesc(i < 2 ? sb + OFF_R + 28672 + i * (G_IMG / 2) : sb + (i - 2) * SLOT, 896, 128, 0);
#pragma unroll
        for (int kk = 0; kk < 7; kk++) wgmma_ss_56<1, 0>(spec[i >> 1], da + kk * 128, db + kk * 112, ((i & 1) | kk) != 0);
        wg_commit();
      }
      const float* gs = reinterpret_cast<const float*>(smem + OFF_G) + w4 * 16 + g;
      const float o0 = bf16_round(1.0f - gs[0]), o1 = bf16_round(1.0f - gs[8]);
      const float g0 = gs[0] * (1.0f / (float)(S_ * D_)), g1 = gs[8] * (1.0f / (float)(S_ * D_));
      wg_wait<0>(); keep(spec[0]); keep(spec[1]);
      if (t128 == 0) PROF(wg, 14);
      mbar_wait_cluster(bars + B_RECV * 8, 0);
      if (t128 == 0) PROF(wg, 0);
      float4 o[14];
#pragma unroll
      for (int i = 0; i < 14; i++) o[i] = lds128f(sb + OFF_R + t128 * 16 + i * 2048);
      bar_sync<5, 128>();
      const uint32_t st = sb + OFF_PQ + w4 * 3840;
#pragma unroll
      for (int i = 0; i < 7; i++) {
        uint32_t pk[4];
#pragma unroll
        for (int e = 0; e < 2; e++) {
          const int c = 2 * i + e, si = i * 4 + e;
          pk[2 * e] = pack_bf16(fmaf(acc[4 * c] + o[c].x, o0, g0 * spec[0][si]), fmaf(acc[4 * c + 1] + o[c].y, o0, g0 * spec[1][si]));
          pk[2 * e + 1] = pack_bf16(fmaf(acc[4 * c + 2] + o[c].z, o1, g1 * spec[0][si + 2]), fmaf(acc[4 * c + 3] + o[c].w, o1, g1 * spec[1][si + 2]));
        }
        asm volatile("stmatrix.sync.aligned.m8n8.x4.shared.b16 [%0], {%1,%2,%3,%4};"
                     :: "r"(st + (lane & 15) * 240 + (lane >> 4) * 16 + i * 32), "r"(pk[0]), "r"(pk[1]), "r"(pk[2]), "r"(pk[3]) : "memory");
      }
      __syncwarp();
      if (lane < 28) {
        const int r2 = lane >= 14, cc = lane - r2 * 14;
        unsigned char* ob = reinterpret_cast<unsigned char*>(out) + (size_t)(m * 128 + kh * 64 + w4 * 16 + r2) * (D_ * 2) + n * 224 + cc * 16;
        float4 v[8];
#pragma unroll
        for (int i = 0; i < 8; i++) v[i] = lds128f(st + r2 * 240 + cc * 16 + i * 480);
#pragma unroll
        for (int i = 0; i < 8; i++) stg128(ob + i * (D_ * 4), __float_as_uint(v[i].x), __float_as_uint(v[i].y), __float_as_uint(v[i].z), __float_as_uint(v[i].w));
      }
    }
    if (t128 == 0) { PROF(wg, 15); if (wg) { PROFG(4, 30); PROF(4, 31); } }
  } else {
    asm volatile("setmaxnreg.dec.sync.aligned.u32 72;");
    const int t = tid - 256;
    const int k = bid;
    if (t == 0) PROF(2, 0);
    uint4 gv[7];
#pragma unroll
    for (int i = 0; i < 7; i++) gv[i] = ldg128(reinterpret_cast<const uint4*>(gate_w) + i * 8 + (t & 7));
    if (t < 98) {
      int cid = m * 98 + t, kc = cid / 56, nn = cid - kc * 56;
      int d = 112 * n + 8 * (2 * (nn >> 3) + (nn & 1)) + (nn & 6) + kh;
      int dr = d > 224 ? d - 448 : d;
      const float df = (float)dr * (-6.283185307179586f / 448.0f);
      uint32_t pk[4];
#pragma unroll
      for (int e = 0; e < 4; e++) {
        const float a = (float)(4 * kc + e) * df;
        pk[e] = pack_bf16(2.0f * __cosf(a), 2.0f * __sinf(a));
      }
      if (kc == 0) pk[0] = (((d >> 1) ^ kh) & 1) ? 0xBF803F80u : 0x3F803F80u;
      stg128(g_G + (size_t)(n * 2 + kh) * G_IMG + cid * 16, pk[0], pk[1], pk[2], pk[3]);
    }
    bar_sync<0, NTHREADS>();
    asm volatile("barrier.cluster.arrive.relaxed.aligned;" ::: "memory");
    {
      const int row = n * 16 + (t >> 3), l8 = t & 7;
      mbar_wait(bars + (B_XFULL + 1) * 8, 0);
      float sum = 0.f;
#pragma unroll
      for (int i = 0; i < 7; i++) {
        const uint4 a = lds128(sb + OFF_R + i * 8192 + row * 128 + ((l8 ^ (row & 7)) << 4));
        const uint32_t aa[4] = {a.x, a.y, a.z, a.w}, bb[4] = {gv[i].x, gv[i].y, gv[i].z, gv[i].w};
#pragma unroll
        for (int e = 0; e < 4; e++) {
          const uint32_t pr = as_u(__hmul2(as_b2(aa[e]), as_b2(bb[e])));
          sum += bf_lo(pr) + bf_hi(pr);
        }
      }
      sum += __shfl_xor_sync(0xffffffffu, sum, 1); sum += __shfl_xor_sync(0xffffffffu, sum, 2); sum += __shfl_xor_sync(0xffffffffu, sum, 4);
      if (lane == 0) mbar_arrive(bars + (B_XFREE + 1) * 8);
      if (l8 == 0) g_gate[m * 128 + kh * 64 + row] = bf16_round(__fdividef(1.0f, 1.0f + __expf(-bf16_round(sum))));
    }
    if (t == 0) PROF(2, 11);
    mbar_wait(bars + B_XFREE * 8, 0);
    if (k < 113) {
      const float u = -6.283185307179586f / 2048.0f, t2 = (float)(2 * t) * u, rr = (float)(t >> 4) * u;
#pragma unroll 1
      for (int i = 0; i < 4; i++) {
        const float q = (float)(2 * i), l = (float)((t & 15) + 64 * i);
        sts128(sb + OFF_TW + i * 2048 + t * 16, cis(t2 * q), cis((t2 + u) * q), cis(t2 * (q + 1.0f)), cis((t2 + u) * (q + 1.0f)));
        sts128(sb + OFF_TW + 8192 + i * 2048 + t * 16, cis(rr * l), cis(rr * (l + 16.0f)), cis(rr * (l + 32.0f)), cis(rr * (l + 48.0f)));
      }
      const float l = (float)((t >> 1) & 15) * (8.0f * u), jj = (float)((t >> 5) * 4 + (t & 1) * 2);
      sts64(sb + OFF_TW + 16384 + t * 8, cis(l * jj), cis(l * (jj + 1.0f)));
    }
    if (t == 0) PROF(2, 9);
    mbar_wait(bars + B_PIN * 8, 0);
    if (t == 0) PROF(2, 4);
    {
      const uint32_t wa = sb + OFF_WS + (((t & 7) - bid) & 7) * 450 + (t >> 3) * 2, wc = wa + 448 - (t >> 3) * 4;
      uint2* dst = g_Wt + (t >> 3) * S_ + 16 * bid + 2 * (t & 7);
#pragma unroll 1
      for (int h = 0; h < 2; h++) {
        uint32_t w[4][8];
#pragma unroll
        for (int i = 0; i < 4; i++) {
#pragma unroll
          for (int e = 0; e < 4; e++) { w[i][2 * e] = lds16(wa + h * 128 + i * 32 + e * 3600); w[i][2 * e + 1] = lds16(wc - h * 128 - i * 32 + e * 3600); }
        }
#pragma unroll
        for (int i = 0; i < 4; i++)
          if (i < 3 || h == 0 || t < 8)
            stg128(dst + (h * 64 + i * 16) * S_, __byte_perm(w[i][0], w[i][1], 0x5410), __byte_perm(w[i][4], w[i][5], 0x5410), __byte_perm(w[i][2], w[i][3], 0x5410), __byte_perm(w[i][6], w[i][7], 0x5410));
      }
    }
    bar_sync<3, 128>();
    if (t == 64) { PROF(2, 6); red_release(&g_cnt[6 * 32]); PROF(2, 8); }
    mbar_wait(bars + B_RFULL * 8, 0);
    if (t < 112) {
      const int js = bid >> 4, nn = (t >> 1) / 14, cc = (t >> 1) - nn * 14;
      unsigned char* wdst = g_Wd + (size_t)((js >> 2) * 4 + nn) * WD_IMG + cc * 128 + (t & 1) * 16;
      uint4 v[7];
#pragma unroll
      for (int i = 0; i < 7; i++) v[i] = lds128(sb + OFF_R + i * 1792 + (t & 1) * 896 + (t >> 1) * 16);
#pragma unroll
      for (int i = 0; i < 7; i++) {
        int col = 14 * (bid & 15) + 2 * i - (js & 1) * 32;
        if (col < 0) col += 224;
        const int kpos = col < 192 ? (col >> 6) * 256 + (js & 3) * 64 + (col & 63) : 576 + (js & 3) * 32 + col;
        stg128(wdst + (kpos >> 3) * 1792 + (kpos & 7) * 16, v[i].x, v[i].y, v[i].z, v[i].w);
      }
    }
    bar_sync<3, 128>();
    if (t == 96) { PROF(2, 10); red_release(&g_cnt[4 * 32]); PROF(2, 1); }
    if (k < 113) {
      if (t == 0) PROF(2, 2);
      mbar_wait(bars + B_XCFULL * 8, 0);
      if (t == 0) PROF(2, 3);
      c2 v[16];
      const uint32_t se = k == 0 ? 0x4410 : (k == 112 ? 0x4432 : 0x3210), so = k == 0 ? 0x4410 : (k == 112 ? 0x3244 : 0x3210);
#pragma unroll
      for (int jj = 0; jj < 8; jj++) {
        const uint2 e2 = lds64(sb + OFF_EXCH + jj * 1024 + t * 8), o2 = lds64(sb + OFF_EXCH + 8192 + jj * 1024 + t * 8);
#pragma unroll
        for (int h = 0; h < 2; h++) {
          const b2 e = as_b2(__byte_perm(h ? e2.y : e2.x, 0, se)), o = as_b2(__byte_perm(h ? o2.y : o2.x, 0, so));
          const uint32_t s = as_u(__hadd2(e, o)), d = as_u(__hsub2(e, o)) ^ 0x80000000u;
          v[2 * jj + h] = mk(as_b2(__byte_perm(s, d, 0x5410)), as_b2(__byte_perm(s, d, 0x7632)));
        }
      }
      if (t == 0) PROF(2, 12);
      columns(v, sb, t);
      if (t == 0) PROF(2, 14);
      const int pre = (k == 112) ? 1 : 2 * k, pim = (k == 112) ? 1 : 2 * k + 1;
      uint32_t* pq = reinterpret_cast<uint32_t*>(g_PQ) + (t >> 5) * 14336;
      uint32_t* pr = pq + pre * 32 + ((((lane >> 2) ^ pre) & 7) << 2) + (lane & 3);
      uint32_t* pi = pq + pim * 32 + ((((lane >> 2) ^ pim) & 7) << 2) + (lane & 3);
#pragma unroll
      for (int jj = 0; jj < 8; jj++) {
        const b2 ar = as_b2(__byte_perm(as_u(v[2 * jj].y), as_u(v[2 * jj + 1].y), 0x5410)), br = as_b2(__byte_perm(as_u(v[2 * jj].y), as_u(v[2 * jj + 1].y), 0x7632));
        const b2 ai = as_b2(__byte_perm(as_u(v[2 * jj].x), as_u(v[2 * jj + 1].x), 0x5410)), bi = as_b2(__byte_perm(as_u(v[2 * jj].x), as_u(v[2 * jj + 1].x), 0x7632));
        pr[jj * 57344] = as_u(__hadd2(ar, br));
        if (k != 112) pr[jj * 57344 + 7168] = as_u(__hsub2(ar, br));
        if (k != 0) pi[jj * 57344 + 7168] = as_u(__hadd2(ai, bi));
        if (k != 0 && k != 112) pi[jj * 57344] = as_u(__hsub2(ai, bi));
      }
      fence_async_smem();
    }
    bar_sync<3, 128>();
    if (t == 0) { PROF(2, 5); red_release(&g_cnt[5 * 32]); PROF(2, 7); }
    __syncwarp();
    asm volatile("barrier.cluster.wait.aligned;" ::: "memory");
  }
}

typedef CUresult (*EncodeFn)(CUtensorMap*, CUtensorMapDataType, cuuint32_t, void*, const cuuint64_t*, const cuuint64_t*, const cuuint32_t*,
                             const cuuint32_t*, CUtensorMapInterleave, CUtensorMapSwizzle, CUtensorMapL2promotion, CUtensorMapFloatOOBfill);

void make_map(EncodeFn enc, CUtensorMap* tm, const void* base, int cols, int rows, int bc, int br, CUtensorMapSwizzle sw) {
  cuuint64_t gd[2] = {(cuuint64_t)cols, (cuuint64_t)rows};
  cuuint64_t gs[1] = {(cuuint64_t)cols * 2};
  cuuint32_t bd[2] = {(cuuint32_t)bc, (cuuint32_t)br};
  cuuint32_t es[2] = {1, 1};
  enc(tm, CU_TENSOR_MAP_DATA_TYPE_BFLOAT16, 2, const_cast<void*>(base), gd, gs, bd, es, CU_TENSOR_MAP_INTERLEAVE_NONE, sw,
      CU_TENSOR_MAP_L2_PROMOTION_L2_128B, CU_TENSOR_MAP_FLOAT_OOB_FILL_NONE);
}

}

extern "C" void kernel_launch(void* const* d_in, const int* in_sizes, int n_in, void* d_out, int out_size) {
  (void)in_sizes; (void)n_in; (void)out_size;
  const __nv_bfloat16* x = (const __nv_bfloat16*)d_in[0];
  const __nv_bfloat16* w_r = (const __nv_bfloat16*)d_in[1];
  const __nv_bfloat16* w_i = (const __nv_bfloat16*)d_in[2];
  const __nv_bfloat16* w_gate = (const __nv_bfloat16*)d_in[4];
  const __nv_bfloat16* w_up = (const __nv_bfloat16*)d_in[5];
  const __nv_bfloat16* w_down = (const __nv_bfloat16*)d_in[6];
  const __nv_bfloat16* gate_w = (const __nv_bfloat16*)d_in[7];
  static EncodeFn enc = nullptr;
  static bool ok = false;
  if (!enc) {
    cudaDriverEntryPointQueryResult qr;
    cudaGetDriverEntryPoint("cuTensorMapEncodeTiled", (void**)&enc, cudaEnableDefault, &qr);
    cudaFuncSetAttribute(fused_kernel, cudaFuncAttributeMaxDynamicSharedMemorySize, SMEM_BYTES);
    cudaFuncAttributes fa;
    cudaFuncGetAttributes(&fa, fused_kernel);
    ok = (fa.numRegs == 128);
  }
  if (!ok) return;
  CUtensorMap tx, tg, tu, tg32, tu32;
  {
    cuuint64_t gd[3] = {64, (cuuint64_t)S_, 7};
    cuuint64_t gs[2] = {(cuuint64_t)D_ * 2, 128};
    cuuint32_t bd[3] = {64, 64, 7};
    cuuint32_t es[3] = {1, 1, 1};
    enc(&tx, CU_TENSOR_MAP_DATA_TYPE_BFLOAT16, 3, const_cast<__nv_bfloat16*>(x), gd, gs, bd, es, CU_TENSOR_MAP_INTERLEAVE_NONE, CU_TENSOR_MAP_SWIZZLE_128B,
        CU_TENSOR_MAP_L2_PROMOTION_L2_128B, CU_TENSOR_MAP_FLOAT_OOB_FILL_NONE);
  }
  make_map(enc, &tg, w_gate, F_, D_, 64, 64, CU_TENSOR_MAP_SWIZZLE_128B);
  make_map(enc, &tu, w_up, F_, D_, 64, 64, CU_TENSOR_MAP_SWIZZLE_128B);
  make_map(enc, &tg32, w_gate, F_, D_, 32, 128, CU_TENSOR_MAP_SWIZZLE_64B);
  make_map(enc, &tu32, w_up, F_, D_, 32, 128, CU_TENSOR_MAP_SWIZZLE_64B);
  fused_kernel<<<128, NTHREADS, SMEM_BYTES>>>(tx, tg, tu, tg32, tu32, w_r, w_i, w_gate, w_up, w_down, gate_w, (__nv_bfloat16*)d_out);
}
```

```cpp
#include <cuda_runtime.h>
#include <cuda_bf16.h>
#include <cuda.h>
#include <stdint.h>

namespace {

constexpr int S_ = 2048, D_ = 448, F_ = 1792;
constexpr int NTHREADS = 512;
constexpr int SLOT = 16384, NSLOT = 7;
constexpr int HALF_XR = 57344;
constexpr int OFF_PQ = NSLOT * SLOT;
constexpr int OFF_R = OFF_PQ + HALF_XR;
constexpr int OFF_EXCH = OFF_PQ;
constexpr int OFF_WS = OFF_EXCH + 18432;
constexpr int OFF_TW = OFF_WS + 16384;
constexpr int OFF_MISC = OFF_R + HALF_XR;
constexpr int OFF_G = OFF_MISC;
constexpr int OFF_BAR = OFF_MISC + 512;
constexpr int SMEM_BYTES = OFF_BAR + 512;
constexpr int B_FULL = 0, B_EMPTY = 7, B_XFULL = 14  ;
constexpr int B_XFREE = 16  , B_PUBX = 18, B_RFREE = 19, B_LFREE = 20;
constexpr int B_PUBW = 21, B_PUBD = 22;
constexpr int B_PQFULL = 23, B_RECV = 24, B_WFULL = 25, B_XCFULL = 26, B_PREP = 27, B_PREPW = 28, B_RFULL = 29, B_GFULL = 30, B_END = 31, B_PIN = 31;

constexpr int WD_IMG = 896 * 112 * 2;
constexpr int G_IMG = 224 * 56 * 2;

__device__ __align__(1024) uint32_t g_Xc[112 * 2 * S_];
constexpr int H_IMG = 32 * 56 * 4096;
__device__ __align__(1024) unsigned char g_H[2 * H_IMG];
__device__ __align__(1024) unsigned char g_PQ[32 * HALF_XR];
__device__ __align__(1024) unsigned char g_Wd[8 * WD_IMG];
__device__ __align__(1024) unsigned char g_G[8 * G_IMG];
__device__ __align__(1024) uint2 g_Wt[113 * S_];
__device__ __align__(1024) float g_gate[S_];
__device__ __align__(128) unsigned int g_ep[128];
__device__ __align__(128) unsigned int g_cnt[8 * 32];

#define PROF(role, idx) do {} while (0)
#define PROFG(role, idx) do {} while (0)

__device__ __forceinline__ uint32_t s2u(const void* p) { return (uint32_t)__cvta_generic_to_shared(p); }
__device__ __forceinline__ void mbar_init(uint32_t b, int c) { asm volatile("mbarrier.init.shared::cta.b64 [%0], %1;" :: "r"(b), "r"(c) : "memory"); }
__device__ __forceinline__ void mbar_expect(uint32_t b, int bytes) { asm volatile("mbarrier.arrive.expect_tx.shared::cta.b64 _, [%0], %1;" :: "r"(b), "r"(bytes) : "memory"); }
__device__ __forceinline__ void mbar_arrive(uint32_t b) { asm volatile("mbarrier.arrive.shared::cta.b64 _, [%0];" :: "r"(b) : "memory"); }
__device__ __forceinline__ void mbar_wait(uint32_t b, int ph) {
  asm volatile("{\n.reg .pred p;\n.reg .u32 c;\nmov.u32 c, 0;\nL_WAIT:\nmbarrier.try_wait.parity.shared::cta.b64 p, [%0], %1;\n@p bra.uni L_DONE;\n"
               "add.u32 c, c, 1;\nsetp.lt.u32 p, c, 4194304;\n@p bra.uni L_WAIT;\ntrap;\nL_DONE:\n}" :: "r"(b), "r"(ph) : "memory");
}
__device__ __forceinline__ void mbar_wait_cluster(uint32_t b, int ph) {
  asm volatile("{\n.reg .pred p;\n.reg .u32 c;\nmov.u32 c, 0;\nL_WAIT:\nmbarrier.try_wait.parity.acquire.cluster.shared::cta.b64 p, [%0], %1;\n@p bra.uni L_DONE;\n"
               "add.u32 c, c, 1;\nsetp.lt.u32 p, c, 4194304;\n@p bra.uni L_WAIT;\ntrap;\nL_DONE:\n}" :: "r"(b), "r"(ph) : "memory");
}
__device__ __forceinline__ uint32_t ld_acquire(const unsigned int* p) { uint32_t v; asm volatile("ld.acquire.gpu.global.u32 %0, [%1];" : "=r"(v) : "l"(p) : "memory"); return v; }
__device__ __forceinline__ uint32_t ld_relaxed(const unsigned int* p) { uint32_t v; asm volatile("ld.relaxed.gpu.global.u32 %0, [%1];" : "=r"(v) : "l"(p) : "memory"); return v; }
__device__ __forceinline__ void wait_ge(const unsigned int* p, uint32_t target) {
#pragma unroll 1
  for (int i = 0; i < (1 << 22); i++) { if ((int)(ld_acquire(p) - target) >= 0) return; }
  __trap();
}
__device__ __forceinline__ void red_release(unsigned int* p) { asm volatile("red.release.gpu.global.add.u32 [%0], 1;" :: "l"(p) : "memory"); }
__device__ __forceinline__ void red_relaxed(unsigned int* p) { asm volatile("red.relaxed.gpu.global.add.u32 [%0], 1;" :: "l"(p) : "memory"); }
__device__ __forceinline__ bool elect() { uint32_t p; asm volatile("{\n.reg .pred p;\nelect.sync _|p, 0xffffffff;\nselp.u32 %0, 1, 0, p;\n}" : "=r"(p)); return p; }
__device__ __forceinline__ void fence_async_smem() { asm volatile("fence.proxy.async.shared::cta;" ::: "memory"); }
__device__ __forceinline__ void fence_async_global() { asm volatile("fence.proxy.async.global;" ::: "memory"); }
template <int ID, int N> __device__ __forceinline__ void bar_sync() { asm volatile("bar.sync %0, %1;" :: "n"(ID), "n"(N) : "memory"); }
template <int ID, int N> __device__ __forceinline__ void bar_arrive() { asm volatile("bar.arrive %0, %1;" :: "n"(ID), "n"(N) : "memory"); }
__device__ __forceinline__ void tma2d(uint32_t dst, const CUtensorMap* tm, int c0, int c1, uint32_t bar) {
  asm volatile("cp.async.bulk.tensor.2d.shared::cluster.global.mbarrier::complete_tx::bytes [%0], [%1, {%3, %4}], [%2];"
               :: "r"(dst), "l"(tm), "r"(bar), "r"(c0), "r"(c1) : "memory");
}
__device__ __forceinline__ void tma3d(uint32_t dst, const CUtensorMap* tm, int c0, int c1, int c2, uint32_t bar) {
  asm volatile("cp.async.bulk.tensor.3d.shared::cluster.global.mbarrier::complete_tx::bytes [%0], [%1, {%3, %4, %5}], [%2];"
               :: "r"(dst), "l"(tm), "r"(bar), "r"(c0), "r"(c1), "r"(c2) : "memory");
}
__device__ __forceinline__ void bulk_g2s(uint32_t dst, const void* src, int bytes, uint32_t bar) {
  asm volatile("cp.async.bulk.shared::cluster.global.mbarrier::complete_tx::bytes [%0], [%1], %2, [%3];"
               :: "r"(dst), "l"(src), "r"(bytes), "r"(bar) : "memory");
}
__device__ __forceinline__ void prefetch_l2(const void* src, int bytes) {
  asm volatile("cp.async.bulk.prefetch.L2.global [%0], %1;" :: "l"(src), "r"(bytes) : "memory");
}
__device__ __forceinline__ void prefetch_tma2d(const CUtensorMap* tm, int c0, int c1) {
  asm volatile("cp.async.bulk.prefetch.tensor.2d.L2.global [%0, {%1, %2}];" :: "l"(tm), "r"(c0), "r"(c1) : "memory");
}
__device__ __forceinline__ uint64_t mkdesc(uint32_t addr, uint32_t lbo, uint32_t sbo, uint32_t mode) {
  return (uint64_t)((addr & 0x3FFFF) >> 4) | ((uint64_t)(lbo >> 4) << 16) | ((uint64_t)(sbo >> 4) << 32) | ((uint64_t)mode << 62);
}
__device__ __forceinline__ void wg_fence() { asm volatile("wgmma.fence.sync.aligned;" ::: "memory"); }
__device__ __forceinline__ void wg_commit() { asm volatile("wgmma.commit_group.sync.aligned;" ::: "memory"); }
template <int N> __device__ __forceinline__ void wg_wait() { asm volatile("wgmma.wait_group.sync.aligned %0;" :: "n"(N) : "memory"); }
template <int N> __device__ __forceinline__ void keep(float (&d)[N]) {
#pragma unroll
  for (int i = 0; i < N; i++) asm volatile("" : "+f"(d[i]) :: "memory");
}
__device__ __forceinline__ uint32_t pack_bf16(float lo, float hi) { uint32_t r; asm("cvt.rn.bf16x2.f32 %0, %1, %2;" : "=r"(r) : "f"(hi), "f"(lo)); return r; }
__device__ __forceinline__ float bf16_round(float v) { return __bfloat162float(__float2bfloat16_rn(v)); }
__device__ __forceinline__ void sts128(uint32_t a, uint32_t x, uint32_t y, uint32_t z, uint32_t w) { asm volatile("st.shared.v4.b32 [%0], {%1,%2,%3,%4};" :: "r"(a), "r"(x), "r"(y), "r"(z), "r"(w) : "memory"); }
__device__ __forceinline__ float4 lds128f(uint32_t a) { float4 v; asm volatile("ld.shared.v4.f32 {%0,%1,%2,%3}, [%4];" : "=f"(v.x), "=f"(v.y), "=f"(v.z), "=f"(v.w) : "r"(a) : "memory"); return v; }

__device__ __forceinline__ uint2 lds64(uint32_t a) { uint2 v; asm volatile("ld.shared.v2.b32 {%0,%1}, [%2];" : "=r"(v.x), "=r"(v.y) : "r"(a) : "memory"); return v; }
__device__ __forceinline__ float bf_lo(uint32_t w) { return __uint_as_float(w << 16); }
__device__ __forceinline__ float bf_hi(uint32_t w) { return __uint_as_float(w & 0xffff0000u); }
__device__ __forceinline__ uint32_t opaque(uint32_t v) { asm volatile("" : "+r"(v)); return v; }
__device__ __forceinline__ uint4 ldg128(const void* p) { uint4 v; asm volatile("ld.global.nc.v4.b32 {%0,%1,%2,%3}, [%4];" : "=r"(v.x), "=r"(v.y), "=r"(v.z), "=r"(v.w) : "l"(p)); return v; }
__device__ __forceinline__ void stg128(void* p, uint32_t x, uint32_t y, uint32_t z, uint32_t w) { asm volatile("st.global.v4.b32 [%0], {%1,%2,%3,%4};" :: "l"(p), "r"(x), "r"(y), "r"(z), "r"(w) : "memory"); }
__device__ __forceinline__ void stg128_l2(void* p, uint32_t x, uint32_t y, uint32_t z, uint32_t w) { asm volatile("st.relaxed.gpu.global.v4.b32 [%0], {%1,%2,%3,%4};" :: "l"(p), "r"(x), "r"(y), "r"(z), "r"(w) : "memory"); }
__device__ __forceinline__ void ldg128_l2(uint32_t (&v)[4], const void* p) { asm volatile("ld.relaxed.gpu.global.v4.b32 {%0,%1,%2,%3}, [%4];" : "=r"(v[0]), "=r"(v[1]), "=r"(v[2]), "=r"(v[3]) : "l"(p) : "memory"); }
__device__ __forceinline__ uint4 lds128(uint32_t a) { uint4 v; asm volatile("ld.shared.v4.b32 {%0,%1,%2,%3}, [%4];" : "=r"(v.x), "=r"(v.y), "=r"(v.z), "=r"(v.w) : "r"(a) : "memory"); return v; }
__device__ __forceinline__ uint32_t lds16(uint32_t a) { uint32_t v; asm volatile("ld.shared.u16 %0, [%1];" : "=r"(v) : "r"(a) : "memory"); return v; }
__device__ __forceinline__ void sts64(uint32_t a, uint32_t x, uint32_t y) { asm volatile("st.shared.v2.b32 [%0], {%1,%2};" :: "r"(a), "r"(x), "r"(y) : "memory"); }
template <int TB> __device__ __forceinline__ void wgmma_rs_128(float (&d)[64], const uint32_t (&a)[4], uint64_t db, int sc) {
  asm volatile("{\n.reg .pred p;\nsetp.ne.b32 p, %69, 0;\n"
    "wgmma.mma_async.sync.aligned.m64n128k16.f32.bf16.bf16 {%0, %1, %2, %3, %4, %5, %6, %7, %8, %9, %10, %11, %12, %13, %14, %15, %16, %17, %18, %19, %20, %21, %22, %23, %24, %25, %26, %27, %28, %29, %30, %31, %32, %33, %34, %35, %36, %37, %38, %39, %40, %41, %42, %43, %44, %45, %46, %47, %48, %49, %50, %51, %52, %53, %54, %55, %56, %57, %58, %59, %60, %61, %62, %63}, {%64, %65, %66, %67}, %68, p, 1, 1, %70;\n}\n"
    : "+f"(d[0]), "+f"(d[1]), "+f"(d[2]), "+f"(d[3]), "+f"(d[4]), "+f"(d[5]), "+f"(d[6]), "+f"(d[7]), "+f"(d[8]), "+f"(d[9]), "+f"(d[10]), "+f"(d[11]), "+f"(d[12]), "+f"(d[13]), "+f"(d[14]), "+f"(d[15]), "+f"(d[16]), "+f"(d[17]), "+f"(d[18]), "+f"(d[19]), "+f"(d[20]), "+f"(d[21]), "+f"(d[22]), "+f"(d[23]), "+f"(d[24]), "+f"(d[25]), "+f"(d[26]), "+f"(d[27]), "+f"(d[28]), "+f"(d[29]), "+f"(d[30]), "+f"(d[31]), "+f"(d[32]), "+f"(d[33]), "+f"(d[34]), "+f"(d[35]), "+f"(d[36]), "+f"(d[37]), "+f"(d[38]), "+f"(d[39]), "+f"(d[40]), "+f"(d[41]), "+f"(d[42]), "+f"(d[43]), "+f"(d[44]), "+f"(d[45]), "+f"(d[46]), "+f"(d[47]), "+f"(d[48]), "+f"(d[49]), "+f"(d[50]), "+f"(d[51]), "+f"(d[52]), "+f"(d[53]), "+f"(d[54]), "+f"(d[55]), "+f"(d[56]), "+f"(d[57]), "+f"(d[58]), "+f"(d[59]), "+f"(d[60]), "+f"(d[61]), "+f"(d[62]), "+f"(d[63])
    : "r"(a[0]), "r"(a[1]), "r"(a[2]), "r"(a[3]), "l"(db), "r"(sc), "n"(TB));
}
template <int TB> __device__ __forceinline__ void wgmma_rs_64(float (&d)[32], const uint32_t (&a)[4], uint64_t db, int sc) {
  asm volatile("{\n.reg .pred p;\nsetp.ne.b32 p, %37, 0;\n"
    "wgmma.mma_async.sync.aligned.m64n64k16.f32.bf16.bf16 {%0, %1, %2, %3, %4, %5, %6, %7, %8, %9, %10, %11, %12, %13, %14, %15, %16, %17, %18, %19, %20, %21, %22, %23, %24, %25, %26, %27, %28, %29, %30, %31}, {%32, %33, %34, %35}, %36, p, 1, 1, %38;\n}\n"
    : "+f"(d[0]), "+f"(d[1]), "+f"(d[2]), "+f"(d[3]), "+f"(d[4]), "+f"(d[5]), "+f"(d[6]), "+f"(d[7]), "+f"(d[8]), "+f"(d[9]), "+f"(d[10]), "+f"(d[11]), "+f"(d[12]), "+f"(d[13]), "+f"(d[14]), "+f"(d[15]), "+f"(d[16]), "+f"(d[17]), "+f"(d[18]), "+f"(d[19]), "+f"(d[20]), "+f"(d[21]), "+f"(d[22]), "+f"(d[23]), "+f"(d[24]), "+f"(d[25]), "+f"(d[26]), "+f"(d[27]), "+f"(d[28]), "+f"(d[29]), "+f"(d[30]), "+f"(d[31])
    : "r"(a[0]), "r"(a[1]), "r"(a[2]), "r"(a[3]), "l"(db), "r"(sc), "n"(TB));
}
template <int TB> __device__ __forceinline__ void wgmma_rs_56(float (&d)[28], const uint32_t (&a)[4], uint64_t db, int sc) {
  asm volatile("{\n.reg .pred p;\nsetp.ne.b32 p, %33, 0;\n"
    "wgmma.mma_async.sync.aligned.m64n56k16.f32.bf16.bf16 {%0, %1, %2, %3, %4, %5, %6, %7, %8, %9, %10, %11, %12, %13, %14, %15, %16, %17, %18, %19, %20, %21, %22, %23, %24, %25, %26, %27}, {%28, %29, %30, %31}, %32, p, 1, 1, %34;\n}\n"
    : "+f"(d[0]), "+f"(d[1]), "+f"(d[2]), "+f"(d[3]), "+f"(d[4]), "+f"(d[5]), "+f"(d[6]), "+f"(d[7]), "+f"(d[8]), "+f"(d[9]), "+f"(d[10]), "+f"(d[11]), "+f"(d[12]), "+f"(d[13]), "+f"(d[14]), "+f"(d[15]), "+f"(d[16]), "+f"(d[17]), "+f"(d[18]), "+f"(d[19]), "+f"(d[20]), "+f"(d[21]), "+f"(d[22]), "+f"(d[23]), "+f"(d[24]), "+f"(d[25]), "+f"(d[26]), "+f"(d[27])
    : "r"(a[0]), "r"(a[1]), "r"(a[2]), "r"(a[3]), "l"(db), "r"(sc), "n"(TB));
}
template <int TB> __device__ __forceinline__ void wgmma_rs_112(float (&d)[56], const uint32_t (&a)[4], uint64_t db, int sc) {
  asm volatile("{\n.reg .pred p;\nsetp.ne.b32 p, %61, 0;\n"
    "wgmma.mma_async.sync.aligned.m64n112k16.f32.bf16.bf16 {%0, %1, %2, %3, %4, %5, %6, %7, %8, %9, %10, %11, %12, %13, %14, %15, %16, %17, %18, %19, %20, %21, %22, %23, %24, %25, %26, %27, %28, %29, %30, %31, %32, %33, %34, %35, %36, %37, %38, %39, %40, %41, %42, %43, %44, %45, %46, %47, %48, %49, %50, %51, %52, %53, %54, %55}, {%56, %57, %58, %59}, %60, p, 1, 1, %62;\n}\n"
    : "+f"(d[0]), "+f"(d[1]), "+f"(d[2]), "+f"(d[3]), "+f"(d[4]), "+f"(d[5]), "+f"(d[6]), "+f"(d[7]), "+f"(d[8]), "+f"(d[9]), "+f"(d[10]), "+f"(d[11]), "+f"(d[12]), "+f"(d[13]), "+f"(d[14]), "+f"(d[15]), "+f"(d[16]), "+f"(d[17]), "+f"(d[18]), "+f"(d[19]), "+f"(d[20]), "+f"(d[21]), "+f"(d[22]), "+f"(d[23]), "+f"(d[24]), "+f"(d[25]), "+f"(d[26]), "+f"(d[27]), "+f"(d[28]), "+f"(d[29]), "+f"(d[30]), "+f"(d[31]), "+f"(d[32]), "+f"(d[33]), "+f"(d[34]), "+f"(d[35]), "+f"(d[36]), "+f"(d[37]), "+f"(d[38]), "+f"(d[39]), "+f"(d[40]), "+f"(d[41]), "+f"(d[42]), "+f"(d[43]), "+f"(d[44]), "+f"(d[45]), "+f"(d[46]), "+f"(d[47]), "+f"(d[48]), "+f"(d[49]), "+f"(d[50]), "+f"(d[51]), "+f"(d[52]), "+f"(d[53]), "+f"(d[54]), "+f"(d[55])
    : "r"(a[0]), "r"(a[1]), "r"(a[2]), "r"(a[3]), "l"(db), "r"(sc), "n"(TB));
}
template <int TA, int TB> __device__ __forceinline__ void wgmma_ss_56(float (&d)[28], uint64_t da, uint64_t db, int sc) {
  asm volatile("{\n.reg .pred p;\nsetp.ne.b32 p, %30, 0;\n"
    "wgmma.mma_async.sync.aligned.m64n56k16.f32.bf16.bf16 {%0, %1, %2, %3, %4, %5, %6, %7, %8, %9, %10, %11, %12, %13, %14, %15, %16, %17, %18, %19, %20, %21, %22, %23, %24, %25, %26, %27}, %28, %29, p, 1, 1, %31, %32;\n}\n"
    : "+f"(d[0]), "+f"(d[1]), "+f"(d[2]), "+f"(d[3]), "+f"(d[4]), "+f"(d[5]), "+f"(d[6]), "+f"(d[7]), "+f"(d[8]), "+f"(d[9]), "+f"(d[10]), "+f"(d[11]), "+f"(d[12]), "+f"(d[13]), "+f"(d[14]), "+f"(d[15]), "+f"(d[16]), "+f"(d[17]), "+f"(d[18]), "+f"(d[19]), "+f"(d[20]), "+f"(d[21]), "+f"(d[22]), "+f"(d[23]), "+f"(d[24]), "+f"(d[25]), "+f"(d[26]), "+f"(d[27])
    : "l"(da), "l"(db), "r"(sc), "n"(TA), "n"(TB));
}

__device__ __forceinline__ uint32_t cis(float a) { return pack_bf16(__cosf(a), __sinf(a)); }

typedef __nv_bfloat162 b2;
struct c2 { b2 x, y; };
__device__ __forceinline__ b2 as_b2(uint32_t u) { return *reinterpret_cast<b2*>(&u); }
__device__ __forceinline__ uint32_t as_u(b2 v) { return *reinterpret_cast<uint32_t*>(&v); }
__device__ __forceinline__ c2 mk(b2 x, b2 y) { c2 r; r.x = x; r.y = y; return r; }
__device__ __forceinline__ c2 cmul(c2 a, b2 wr, b2 wi) { return mk(__hfma2(a.x, wr, __hneg2(__hmul2(a.y, wi))), __hfma2(a.x, wi, __hmul2(a.y, wr))); }
__device__ __forceinline__ void fft4(c2& a0, c2& a1, c2& a2, c2& a3) {
  c2 t0 = mk(__hadd2(a0.x, a2.x), __hadd2(a0.y, a2.y)), t1 = mk(__hsub2(a0.x, a2.x), __hsub2(a0.y, a2.y));
  c2 t2 = mk(__hadd2(a1.x, a3.x), __hadd2(a1.y, a3.y)), t3 = mk(__hsub2(a1.x, a3.x), __hsub2(a1.y, a3.y));
  a0 = mk(__hadd2(t0.x, t2.x), __hadd2(t0.y, t2.y)); a2 = mk(__hsub2(t0.x, t2.x), __hsub2(t0.y, t2.y));
  a1 = mk(__hadd2(t1.x, t3.y), __hsub2(t1.y, t3.x)); a3 = mk(__hsub2(t1.x, t3.y), __hadd2(t1.y, t3.x));
}
__device__ __forceinline__ void fft4_s2(c2& a0, c2& a1, c2& a2, c2& a3, b2 r) {
  const b2 nr = __hneg2(r);
  c2 t0 = mk(__hfma2(a2.x, r, a0.x), __hfma2(a2.y, r, a0.y)), t1 = mk(__hfma2(a2.x, nr, a0.x), __hfma2(a2.y, nr, a0.y));
  c2 t2 = mk(__hadd2(a1.x, a3.x), __hadd2(a1.y, a3.y)), t3 = mk(__hsub2(a1.x, a3.x), __hsub2(a1.y, a3.y));
  a0 = mk(__hadd2(t0.x, t2.x), __hadd2(t0.y, t2.y)); a2 = mk(__hsub2(t0.x, t2.x), __hsub2(t0.y, t2.y));
  a1 = mk(__hadd2(t1.x, t3.y), __hsub2(t1.y, t3.x)); a3 = mk(__hsub2(t1.x, t3.y), __hadd2(t1.y, t3.x));
}
__device__ __forceinline__ void fft4_s13(c2& a0, c2& a1, c2& a2, c2& a3, b2 r) {
  const b2 nr = __hneg2(r);
  c2 t0 = mk(__hadd2(a0.x, a2.x), __hadd2(a0.y, a2.y)), t1 = mk(__hsub2(a0.x, a2.x), __hsub2(a0.y, a2.y));
  c2 t2 = mk(__hadd2(a1.x, a3.x), __hadd2(a1.y, a3.y)), t3 = mk(__hsub2(a1.x, a3.x), __hsub2(a1.y, a3.y));
  a0 = mk(__hfma2(t2.x, r, t0.x), __hfma2(t2.y, r, t0.y)); a2 = mk(__hfma2(t2.x, nr, t0.x), __hfma2(t2.y, nr, t0.y));
  a1 = mk(__hfma2(t3.y, r, t1.x), __hfma2(t3.x, nr, t1.y)); a3 = mk(__hfma2(t3.y, nr, t1.x), __hfma2(t3.x, r, t1.y));
}
__device__ __forceinline__ c2 rot1(c2 a) { return mk(__hadd2(a.x, a.y), __hsub2(a.y, a.x)); }
__device__ __forceinline__ c2 rot3(c2 a) { return mk(__hsub2(a.y, a.x), __hneg2(__hadd2(a.x, a.y))); }
__device__ __forceinline__ c2 mul_mi(c2 a) { return mk(a.y, __hneg2(a.x)); }
template <int O> __device__ __forceinline__ void fft8(c2 (&v)[16]) {
  const b2 r = as_b2(0x3F353F35u), nr = as_b2(0xBF35BF35u);
  fft4(v[O], v[O + 4], v[O + 8], v[O + 12]);
  fft4(v[O + 2], v[O + 6], v[O + 10], v[O + 14]);
  const c2 o0 = v[O + 2], o1 = rot1(v[O + 6]), o2 = v[O + 10], o3 = rot1(v[O + 14]);
  const c2 e0 = v[O], e1 = v[O + 4], e2 = v[O + 8], e3 = v[O + 12];
  v[O] = mk(__hadd2(e0.x, o0.x), __hadd2(e0.y, o0.y));              v[O + 8] = mk(__hsub2(e0.x, o0.x), __hsub2(e0.y, o0.y));
  v[O + 2] = mk(__hfma2(o1.x, r, e1.x), __hfma2(o1.y, r, e1.y));    v[O + 10] = mk(__hfma2(o1.x, nr, e1.x), __hfma2(o1.y, nr, e1.y));
  v[O + 4] = mk(__hadd2(e2.x, o2.y), __hsub2(e2.y, o2.x));          v[O + 12] = mk(__hsub2(e2.x, o2.y), __hadd2(e2.y, o2.x));
  v[O + 6] = mk(__hfma2(o3.y, r, e3.x), __hfma2(o3.x, nr, e3.y));   v[O + 14] = mk(__hfma2(o3.y, nr, e3.x), __hfma2(o3.x, r, e3.y));
}
__device__ __forceinline__ void fft16(c2 (&v)[16]) {
  const b2 r = as_b2(0x3F353F35u), c1 = as_b2(0x3F6D3F6Du), s1 = as_b2(0x3EC43EC4u), nc1 = as_b2(0xBF6DBF6Du), ns1 = as_b2(0xBEC4BEC4u);
#pragma unroll
  for (int a = 0; a < 4; a++) fft4(v[a], v[a + 4], v[a + 8], v[a + 12]);
  v[5] = cmul(v[5], c1, ns1); v[6] = rot1(v[6]); v[7] = cmul(v[7], s1, nc1);
  v[9] = rot1(v[9]); v[10] = mul_mi(v[10]); v[11] = rot3(v[11]);
  v[13] = cmul(v[13], s1, nc1); v[14] = rot3(v[14]); v[15] = cmul(v[15], nc1, s1);
  fft4(v[0], v[1], v[2], v[3]); fft4_s2(v[4], v[5], v[6], v[7], r); fft4_s13(v[8], v[9], v[10], v[11], r); fft4_s2(v[12], v[13], v[14], v[15], r);
  c2 t;
  t = v[1]; v[1] = v[4]; v[4] = t;  t = v[2]; v[2] = v[8]; v[8] = t;  t = v[3]; v[3] = v[12]; v[12] = t;
  t = v[6]; v[6] = v[9]; v[9] = t;  t = v[7]; v[7] = v[13]; v[13] = t; t = v[11]; v[11] = v[14]; v[14] = t;
}

__device__ __forceinline__ void columns(c2 (&v)[16], uint32_t sb, int t) {
  const int l16 = t & 15;
  const uint32_t row = sb + OFF_EXCH + (t >> 4) * 2304;
  const uint32_t pos = sb + OFF_EXCH + (t >> 3) * 144 + (t & 7) * 16;
#pragma unroll 1
  for (int ps = 0; ps < 6; ps++) {
    if (ps == 0 || ps == 5) { fft8<0>(v); fft8<1>(v); } else fft16(v);
    if (ps == 5) break;
    if (ps == 2) {
      const uint32_t ws = sb + OFF_WS + (l16 >> 1) * 128 + ((((t >> 4) + (l16 >> 1)) & 7) * 2 + (l16 & 1)) * 8;
      mbar_wait(sb + OFF_BAR + B_WFULL * 8, 0);
#pragma unroll
      for (int q = 0; q < 16; q++) {
        const uint2 w = lds64(ws + q * 1024);
        const c2 z = cmul(v[q], as_b2(w.x), as_b2(w.y));
        v[q] = mk(z.y, z.x);
      }
      continue;
    }
    {
      const bool full = ps == 0 || ps == 4;
      const uint32_t tw = sb + OFF_TW + (full ? ps * 2048 + t * 16 : 16384 + l16 * 16);
      const uint32_t st = full ? 2048 : 256;
#pragma unroll
      for (int i = 0; i < 4; i++) {
        const uint4 w4 = lds128(tw + i * st);
        const uint32_t w[4] = {w4.x, w4.y, w4.z, w4.w};
#pragma unroll
        for (int e = 0; e < 4; e++) v[4 * i + e] = cmul(v[4 * i + e], __low2bfloat162(as_b2(w[e])), __high2bfloat162(as_b2(w[e])));
      }
    }
    if (ps == 0) {
      bar_sync<3, 128>();
#pragma unroll
      for (int q = 0; q < 8; q++) sts128(pos + q * 2304, as_u(v[2 * q].x), as_u(v[2 * q].y), as_u(v[2 * q + 1].x), as_u(v[2 * q + 1].y));
      bar_sync<3, 128>();
#pragma unroll
      for (int q = 0; q < 16; q++) { const uint2 a = lds64(row + q * 144 + l16 * 8); v[q] = mk(as_b2(a.x), as_b2(a.y)); }
    } else {
      __syncwarp();
#pragma unroll
      for (int q = 0; q < 16; q++) sts64(row + q * 144 + l16 * 8, as_u(v[q].x), as_u(v[q].y));
      if (ps == 4) bar_sync<3, 128>(); else __syncwarp();
      const uint32_t src = ps == 4 ? pos : row + l16 * 144, st = ps == 4 ? 2304 : 16;
#pragma unroll
      for (int q = 0; q < 8; q++) { const uint4 a = lds128(src + q * st); v[2 * q] = mk(as_b2(a.x), as_b2(a.y)); v[2 * q + 1] = mk(as_b2(a.z), as_b2(a.w)); }
    }
  }
}

template <int NH> __device__ __forceinline__ void h_epilogue(float (&acc)[NH * 8], unsigned char* gdst) {
#pragma unroll
  for (int c = 0; c < NH / 2; c++) {
    uint32_t pk[4];
#pragma unroll
    for (int i = 0; i < 4; i++) {
      float hv[2];
#pragma unroll
      for (int e = 0; e < 2; e++) {
        float hg = 0.5f * acc[c * 8 + i * 2 + e], up = acc[NH * 4 + c * 8 + i * 2 + e];
        float th; asm("tanh.approx.f32 %0, %1;" : "=f"(th) : "f"(hg));
        hv[e] = fmaf(hg, th, hg) * up;
      }
      pk[i] = pack_bf16(hv[0], hv[1]);
    }
    stg128_l2(gdst + c * 4096, max(pk[0], 1u), pk[1], pk[2], pk[3]);
  }
}

__device__ __forceinline__ void frag_ready(uint32_t (&a)[4], uint32_t (&b)[4], uint32_t (&c)[4], uint32_t (&d)[4], const unsigned char* p) {
  asm volatile("{\n.reg .pred p;\n.reg .u32 c, m;\nmov.u32 c, 0;\nL_TRY:\n"
               "min.u32 m, %0, %4;\nmin.u32 m, m, %8;\nmin.u32 m, m, %12;\nsetp.eq.u32 p, m, 0;\n"
               "vote.sync.any.pred p, p, 0xffffffff;\n@!p bra.uni L_OK;\n"
               "ld.relaxed.gpu.global.v4.b32 {%0,%1,%2,%3}, [%16];\nld.relaxed.gpu.global.v4.b32 {%4,%5,%6,%7}, [%16+4096];\n"
               "ld.relaxed.gpu.global.v4.b32 {%8,%9,%10,%11}, [%16+8192];\nld.relaxed.gpu.global.v4.b32 {%12,%13,%14,%15}, [%16+12288];\n"
               "add.u32 c, c, 1;\nsetp.lt.u32 p, c, 262144;\n@p bra.uni L_TRY;\ntrap;\nL_OK:\n}"
               : "+r"(a[0]), "+r"(a[1]), "+r"(a[2]), "+r"(a[3]), "+r"(b[0]), "+r"(b[1]), "+r"(b[2]), "+r"(b[3]),
                 "+r"(c[0]), "+r"(c[1]), "+r"(c[2]), "+r"(c[3]), "+r"(d[0]), "+r"(d[1]), "+r"(d[2]), "+r"(d[3])
               : "l"(p) : "memory");
}

#define LA2 5
#define LEAD1 3

__global__ void __cluster_dims__(2, 1, 1) __launch_bounds__(NTHREADS, 1)
fused_kernel(const __grid_constant__ CUtensorMap tm_x, const __grid_constant__ CUtensorMap tm_g, const __grid_constant__ CUtensorMap tm_u,
             const __grid_constant__ CUtensorMap tm_g32, const __grid_constant__ CUtensorMap tm_u32,
             const __nv_bfloat16* __restrict__ w_r, const __nv_bfloat16* __restrict__ w_i,
             const __nv_bfloat16* __restrict__ w_gate, const __nv_bfloat16* __restrict__ w_up,
             const __nv_bfloat16* __restrict__ w_down, const __nv_bfloat16* __restrict__ gate_w, __nv_bfloat16* __restrict__ out) {
  extern __shared__ __align__(1024) unsigned char smem[];
  const uint32_t sb = s2u(smem);
  const uint32_t bars = sb + OFF_BAR;
  const int tid = threadIdx.x, warp = __shfl_sync(0xffffffffu, tid >> 5, 0), lane = tid & 31;
  const int cl = blockIdx.x >> 1, kh = blockIdx.x & 1;
  const int n = cl < 4 ? cl : (cl < 36 ? (cl - 4) >> 3 : (cl - 36) / 7);
  const int m = cl < 4 ? 15 : (cl < 36 ? (cl - 4) & 7 : cl - 28 - 7 * n);
  const int j = kh * 4 + n, bid = m * 8 + n * 2 + kh;

  if (warp >= 12) {
    asm volatile("setmaxnreg.dec.sync.aligned.u32 24;");
    const int c64 = 224 * j + (j & 1) * 32;
    uint32_t epoch = 0;
    if (warp == 13) {
      if (lane < 2) mbar_init(bars + (B_XFULL + lane) * 8, 1);
    } else if (warp == 12) {
      if (lane < NSLOT) mbar_init(bars + (B_FULL + lane) * 8, 1);
    } else if (warp == 14) {
      epoch = ld_relaxed(&g_ep[bid]);
      if (lane < NSLOT) mbar_init(bars + (B_EMPTY + lane) * 8, 8);
      const int i = B_XFREE + lane;
      if (i < B_END) mbar_init(bars + i * 8, i >= B_PQFULL ? 1 : ((i == B_XFREE || i >= B_PUBW) ? 4 : 8));
      asm volatile("fence.mbarrier_init.release.cluster;" ::: "memory");
      __syncwarp();
      if (lane == 0) mbar_expect(bars + B_RECV * 8, 64 * 112 * 4);
    } else {
      epoch = ld_relaxed(&g_ep[bid]);
      if (lane == 0) mbar_init(bars + B_PIN * 8, 1);
    }
    fence_async_smem();
    bar_arrive<0, NTHREADS>();
    if (warp == 13) {
      if (elect()) {
        PROFG(4, 0); PROF(4, 1);
#pragma unroll
        for (int w = 0; w < 2; w++) {
          mbar_expect(bars + (B_XFULL + w) * 8, HALF_XR);
          tma3d(sb + OFF_PQ + w * HALF_XR, &tm_x, 0, m * 128 + (w ^ kh ^ 1) * 64, 0, bars + (B_XFULL + w) * 8);
        }
        PROF(4, 2);
      }
    } else if (warp == 12) {
#pragma unroll 1
      for (int i = 0; i < 7; i++) {
        if (elect()) {
          if (i < 5) {
            const uint32_t fb = bars + (B_FULL + i) * 8;
            mbar_expect(fb, SLOT);
            tma2d(sb + i * SLOT, &tm_g, c64, i * 64, fb);
            tma2d(sb + i * SLOT + 8192, &tm_u, c64, i * 64, fb);
          } else {
            prefetch_tma2d(&tm_g, c64, i * 64);
            prefetch_tma2d(&tm_u, c64, i * 64);
          }
        }
      }
      if (lane == 0) PROF(3, 3);
    } else if (warp == 15) {
      if (elect()) {
        mbar_expect(bars + B_PIN * 8, 14400);
        bulk_g2s(sb + 5 * SLOT, reinterpret_cast<const unsigned char*>(w_r) + bid * 7200, 7200, bars + B_PIN * 8);
        bulk_g2s(sb + 5 * SLOT + 7200, reinterpret_cast<const unsigned char*>(w_i) + bid * 7200, 7200, bars + B_PIN * 8);
      }
    }
    bar_sync<1, 128>();
    asm volatile("barrier.cluster.arrive.relaxed.aligned;" ::: "memory");
    if (warp == 12) {
      int slot = 5, ph = 1;
      auto wait_slot = [&]() { mbar_wait(bars + (B_EMPTY + slot) * 8, ph ^ (slot >= 5)); };
      auto adv = [&]() { if (++slot == NSLOT) { slot = 0; ph ^= 1; } };
      const int c32 = 224 * j + ((j & 1) ? 0 : 192);
#pragma unroll 1
      for (int i = 5; i < 25; i++) {
        wait_slot();
        if (elect()) {
          const uint32_t dst = sb + slot * SLOT, fb = bars + (B_FULL + slot) * 8;
          const bool last = i >= 21;
          const int cc = last ? c32 : c64 + 64 * (i / 7), rr = last ? slot * 128 : slot * 64;
          mbar_expect(fb, SLOT);
          tma2d(dst, last ? &tm_g32 : &tm_g, cc, rr, fb);
          tma2d(dst + 8192, last ? &tm_u32 : &tm_u, cc, rr, fb);
        }
        adv();
      }
      if (lane == 0) PROF(3, 0);
      mbar_wait(bars + B_PREP * 8, 0);
      if (lane == 0) PROF(3, 1);
#pragma unroll 1
      for (int i = 4; i < 16; i++) {
        if (lane == 0) PROF(3, 16 + i);
        wait_slot();
        if (elect()) {
          const int bytes = i < 14 ? 14336 : G_IMG / 2;
          const unsigned char* src = i < 14 ? g_Wd + (size_t)j * WD_IMG + i * 14336 : g_G + (size_t)(n * 4 + i - 12) * (G_IMG / 2);
          mbar_expect(bars + (B_FULL + slot) * 8, bytes);
          bulk_g2s(sb + slot * SLOT, src, bytes, bars + (B_FULL + slot) * 8);
        }
        adv();
      }
      if (lane == 0) PROF(3, 2);
    } else if (warp == 13) {
      mbar_wait(bars + B_PUBW * 8, 0);
      if (lane == 0) PROF(4, 7);
      mbar_wait(bars + B_PUBX * 8, 0);
      if (lane == 0) {
        PROF(4, 8);
        red_release(&g_cnt[(j >> 1) * 32]);
        red_relaxed(&g_cnt[6 * 32]);
        PROF(4, 18);
      }
      __syncwarp();
      mbar_wait(bars + B_PUBD * 8, 0);
      if (lane == 0) { PROF(4, 9); red_release(&g_cnt[4 * 32]); PROF(4, 19); }
      __syncwarp();
      mbar_wait(bars + B_LFREE * 8, 0);
      if (elect()) {
        mbar_expect(bars + B_GFULL * 8, G_IMG);
        bulk_g2s(sb + OFF_R + 28672, g_G + (size_t)(n * 2) * G_IMG, G_IMG, bars + B_GFULL * 8);
      }
    } else if (warp == 14) {
      unsigned char* hz = g_H + (size_t)(~epoch & 1) * H_IMG + bid * 57344 + lane * 16;
#pragma unroll 1
      for (int i = 0; i < 14; i++) {
#pragma unroll
        for (int e = 0; e < 8; e++) stg128(hz + i * 4096 + e * 512, 0, 0, 0, 0);
      }
      if (lane == 0) PROF(5, 7);
#pragma unroll 1
      for (int u = 0; u < 2; u++) {
        wait_ge(&g_cnt[(6 - 2 * u) * 32], (epoch + 1) * 128);
        fence_async_global();
        if (lane == 0) { mbar_arrive(bars + (B_PREPW - u) * 8); PROF(5, 9 - u); }
      }
    } else {
      mbar_wait(bars + B_XFREE * 8, 0);
      if (elect()) {
        prefetch_l2(reinterpret_cast<const unsigned char*>(w_gate) + bid * 12544, 12544);
        prefetch_l2(reinterpret_cast<const unsigned char*>(w_up) + bid * 12544, 12544);
      }
      mbar_wait(bars + (B_XFREE + 1) * 8, 0);
      if (elect()) {
        mbar_expect(bars + B_RFULL * 8, 12544);
        bulk_g2s(sb + OFF_R, reinterpret_cast<const unsigned char*>(w_down) + bid * 12544, 12544, bars + B_RFULL * 8);
      }
      if (bid < 113) {
        const int sl = (bid == 112) ? 0 : bid;
        wait_ge(&g_cnt[((sl & 1) + 2 * ((sl >> 1) / 28)) * 32], (epoch + 1) * 32);
        fence_async_global();
        if (elect()) {
          PROF(5, 16);
          mbar_expect(bars + B_XCFULL * 8, 16384);
          bulk_g2s(sb + OFF_EXCH, g_Xc + sl * 2 * S_, 16384, bars + B_XCFULL * 8);
        }
        mbar_wait(bars + B_PREPW * 8, 0);
        if (elect()) {
          mbar_expect(bars + B_WFULL * 8, 16384);
          bulk_g2s(sb + OFF_WS, g_Wt + bid * S_, 16384, bars + B_WFULL * 8);
          PROF(5, 17);
        }
      }
      mbar_wait(bars + B_PREP * 8, 0);
      if (elect()) {
        mbar_expect(bars + B_RFULL * 8, HALF_XR);
        bulk_g2s(sb + OFF_R, g_Wd + (size_t)j * WD_IMG, HALF_XR, bars + B_RFULL * 8);
        PROF(5, 19);
      }
      wait_ge(&g_cnt[5 * 32], (epoch + 1) * 128);
      fence_async_global();
      if (elect()) {
        PROF(5, 18);
        mbar_expect(bars + B_PQFULL * 8, HALF_XR + 256);
        const unsigned char* src = g_PQ + (size_t)(m * 2 + kh) * HALF_XR;
        bulk_g2s(sb + OFF_PQ, src, 28672, bars + B_PQFULL * 8);
        bulk_g2s(sb + OFF_PQ + 28672, src + 28672, 28672, bars + B_PQFULL * 8);
        bulk_g2s(sb + OFF_G, g_gate + m * 128 + kh * 64, 256, bars + B_PQFULL * 8);
      }
    }
    __syncwarp();
    asm volatile("barrier.cluster.wait.aligned;" ::: "memory");
  } else if (warp < 8) {
    asm volatile("setmaxnreg.inc.sync.aligned.u32 208;");
    const int wg = warp >> 2, w4 = warp & 3, g = lane >> 2, t = lane & 3;
    const int rh = wg ^ kh ^ 1;
    const int p = j & 1, r = (j >> 1) & 1, hh = j >> 2;
    const uint32_t epoch = ld_relaxed(&g_ep[bid]);
    if ((tid & 127) == 0) PROF(wg, 30);
#pragma unroll 1
    for (int it = tid; it < 392; it += 256) {
      const int kc = it / 28, sg = it - kc * 28;
      const int k = 2 * (28 * hh + sg) + r;
      const float kf = (float)k * (-6.283185307179586f / 448.0f), a0 = (float)(16 * kc + p) * kf;
      uint32_t c[4], s[4];
#pragma unroll
      for (int q = 0; q < 4; q++) {
        const float a1 = fmaf((float)(2 * q), kf, a0), a2 = fmaf((float)(2 * q + 8), kf, a0);
        c[q] = pack_bf16(__cosf(a1), __cosf(a2)); s[q] = pack_bf16(__sinf(a1), __sinf(a2));
        if (k == 0) s[q] = ((q ^ p) & 1) ? 0xBF80BF80u : 0x3F803F80u;
      }
      const uint32_t a = sb + 6 * SLOT + (kc * 56 + 2 * sg) * 16;
      sts128(a, c[0], c[1], c[2], c[3]);
      sts128(a + 16, s[0], s[1], s[2], s[3]);
    }
    if ((tid & 127) == 0) PROF(wg, 31);
    fence_async_smem();
    bar_sync<0, NTHREADS>();
    asm volatile("barrier.cluster.arrive.relaxed.aligned;" ::: "memory");
    if ((tid & 127) == 0) PROF(wg, 1);

    uint32_t xa[28][4];
    {
      const uint32_t xb = sb + OFF_PQ + wg * HALF_XR + (w4 * 16 + (lane & 15)) * 128;
      mbar_wait(bars + (B_XFULL + wg) * 8, 0);
      if ((tid & 127) == 0) PROF(wg, 2);
#pragma unroll
      for (int kb = 0; kb < 7; kb++) {
#pragma unroll
        for (int kk = 0; kk < 4; kk++) {
          uint32_t a = xb + kb * 8192 + (((2 * kk + (lane >> 4)) ^ (lane & 7)) << 4);
          asm volatile("ldmatrix.sync.aligned.m8n8.x4.shared.b16 {%0,%1,%2,%3}, [%4];"
                       : "=r"(xa[kb * 4 + kk][0]), "=r"(xa[kb * 4 + kk][1]), "=r"(xa[kb * 4 + kk][2]), "=r"(xa[kb * 4 + kk][3]) : "r"(a) : "memory");
        }
      }
    }
    {
      uint32_t ad[7][4];
      const uint32_t sel = p ? 0x7632 : 0x5410;
      const uint32_t sgn = r ? 0xBF80BF80u : 0x3F803F80u;
#pragma unroll
      for (int jj = 0; jj < 7; jj++) {
#pragma unroll
        for (int i = 0; i < 4; i++) {
          int ks = 2 * jj + (i >> 1), rr = i & 1;
          uint32_t lo = __byte_perm(xa[ks][rr], xa[ks][rr + 2], sel);
          uint32_t hi = __byte_perm(xa[ks + 14][rr], xa[ks + 14][rr + 2], sel);
          asm("fma.rn.bf16x2 %0, %1, %2, %3;" : "=r"(ad[jj][i]) : "r"(hi), "r"(sgn), "r"(lo));
        }
      }
      __syncwarp();
      if (lane == 0) mbar_arrive(bars + (B_XFREE + wg) * 8);
      float acc[28];
      wg_fence();
      uint64_t db = mkdesc(sb + 6 * SLOT, 896, 128, 0);
#pragma unroll
      for (int jj = 0; jj < 7; jj++) wgmma_rs_56<0>(acc, ad[jj], db + jj * 112, jj != 0);
      wg_commit();
      wg_wait<0>(); keep(acc);
      if (lane == 0) mbar_arrive(bars + (B_EMPTY + 6) * 8);
      uint32_t* xc = g_Xc + (size_t)((2 * (28 * hh + t) + r) * 2 + p) * S_ + m * 128 + rh * 64 + w4 * 16 + g;
#pragma unroll
      for (int i = 0; i < 7; i++) {
        xc[i * 16 * S_] = pack_bf16(acc[4 * i], acc[4 * i + 1]);
        xc[i * 16 * S_ + 8] = pack_bf16(acc[4 * i + 2], acc[4 * i + 3]);
      }
      __syncwarp();
      if (lane == 0) mbar_arrive(bars + B_PUBX * 8);
    }
    if ((tid & 127) == 0) PROF(wg, 3);
    unsigned char* const hbase = g_H + (size_t)((epoch & 1) * 32 + m * 2 + kh) * (56 * 4096) + rh * 2048 + (tid & 127) * 16;
#pragma unroll 1
    for (int u = 0; u < 3; u++) {
      float acc[64];
      if (wg == 1) { if (u & 1) bar_sync<6, 256>(); else bar_sync<2, 256>(); }
      const uint32_t sbu = opaque(sb);
#pragma unroll
      for (int kb = 0; kb < 7; kb++) {
        mbar_wait(sbu + OFF_BAR + (B_FULL + kb) * 8, u & 1);
        wg_fence();
        uint64_t db = mkdesc(sbu + kb * SLOT, 8192, 1024, 1);
#pragma unroll
        for (int kk = 0; kk < 4; kk++) wgmma_rs_128<1>(acc, xa[kb * 4 + kk], db + kk * 128, (kb | kk) != 0);
        wg_commit();
        if (kb == LEAD1 && wg == 0) { if (u & 1) bar_arrive<6, 256>(); else bar_arrive<2, 256>(); }
        if (kb > 0) { wg_wait<1>(); if (lane == 0) mbar_arrive(sbu + OFF_BAR + (B_EMPTY + kb - 1) * 8); }
      }
      wg_wait<0>(); keep(acc);
      if (lane == 0) mbar_arrive(sbu + OFF_BAR + (B_EMPTY + 6) * 8);
      if ((tid & 127) == 0) PROF(wg, 4 + 2 * u);
      h_epilogue<8>(acc, hbase + (u * 16 + n * 4) * 4096);
      if ((tid & 127) == 0) PROF(wg, 5 + 2 * u);
    }
    {
      float acc[32];
      if (wg == 1) bar_sync<6, 256>();
      const uint32_t sbu = opaque(sb);
#pragma unroll
      for (int it = 0; it < 4; it++) {
        mbar_wait(sbu + OFF_BAR + (B_FULL + it) * 8, 1);
        wg_fence();
        uint64_t db = mkdesc(sbu + it * SLOT, 8192, 512, 2);
#pragma unroll
        for (int kk = 0; kk < 8; kk++) if (it * 8 + kk < 28) wgmma_rs_64<1>(acc, xa[it * 8 + kk], db + kk * 64, (it | kk) != 0);
        wg_commit();
        if (it == 2 && wg == 0) bar_arrive<6, 256>();
        if (it > 0) {
          wg_wait<1>();
          if (lane == 0) mbar_arrive(sbu + OFF_BAR + (B_EMPTY + it - 1) * 8);
#pragma unroll
          for (int i = it * 8 - 8; i < it * 8; i++) if (i < 4 * LA2) ldg128_l2(xa[i], hbase + i * 4096);
        }
      }
      wg_wait<0>(); keep(acc);
      if (lane == 0) mbar_arrive(sbu + OFF_BAR + (B_EMPTY + 3) * 8);
      if ((tid & 127) == 0) PROF(wg, 10);
      h_epilogue<4>(acc, hbase + (48 + n * 2) * 4096);
    }
    asm volatile("barrier.cluster.wait.aligned;" ::: "memory");
    if ((tid & 127) == 0) PROF(wg, 11);

    float acc[56];
    if (wg == 1) bar_sync<2, 256>();
#pragma unroll 1
    for (int it = 0; it < 2; it++) {
#pragma unroll
      for (int e = 0; e < 7; e++) {
        if ((tid & 127) == 0) PROF(wg, 16 + it * 7 + e);
        const bool inr = e < 4 && it == 0;
        if (e >= 4 || it == 1) mbar_wait(bars + (B_FULL + e) * 8, e < 4 ? 0 : it ^ 1);
        else if (e == 0) mbar_wait(bars + B_RFULL * 8, 1);
        frag_ready(xa[e * 4], xa[e * 4 + 1], xa[e * 4 + 2], xa[e * 4 + 3], hbase + (it * 7 + e) * 16384);
        wg_fence();
        const uint64_t db = mkdesc(inr ? sb + OFF_R + e * 14336 : sb + e * SLOT, 1792, 128, 0);
#pragma unroll
        for (int kk = 0; kk < 4; kk++) wgmma_rs_112<1>(acc, xa[e * 4 + kk], db + kk * 224, (e | kk) ? 1 : it);
        wg_commit();
        if (e == 1 && it == 0 && wg == 0) bar_arrive<2, 256>();
        if (it == 0 || e + LA2 < 7) {
          const int nb = it * 7 + e + LA2;
#pragma unroll
          for (int kk = 0; kk < 4; kk++) ldg128_l2(xa[((e + LA2) % 7) * 4 + kk], hbase + (nb * 4 + kk) * 4096);
        }
        wg_wait<1>();
        if (lane == 0) {
          if (it == 0 ? e >= 5 : e <= 2) mbar_arrive(bars + (B_EMPTY + (e + 6) % 7) * 8);
          if (e == 4 && it == 0) {
            mbar_arrive(bars + B_LFREE * 8);
            asm volatile("{\n.reg .b32 ra;\nmapa.shared::cluster.u32 ra, %0, %1;\nmbarrier.arrive.relaxed.cluster.shared::cluster.b64 _, [ra];\n}"
                         :: "r"(bars + B_RFREE * 8), "r"(kh ^ 1) : "memory");
          }
        }
      }
    }
    const int t128 = tid & 127;
    wg_wait<0>(); keep(acc);
    if (wg == 0) {
      if (t128 == 0) PROF(wg, 12);
      mbar_wait_cluster(bars + B_RFREE * 8, 0);
      uint32_t rdst, rbar;
      asm volatile("mapa.shared::cluster.u32 %0, %1, %2;" : "=r"(rdst) : "r"(sb + OFF_R + t128 * 16), "r"(kh ^ 1));
      asm volatile("mapa.shared::cluster.u32 %0, %1, %2;" : "=r"(rbar) : "r"(bars + B_RECV * 8), "r"(kh ^ 1));
#pragma unroll
      for (int i = 0; i < 14; i++)
        asm volatile("st.async.weak.shared::cluster.mbarrier::complete_tx::bytes.v4.f32 [%0], {%1,%2,%3,%4}, [%5];"
                     :: "r"(rdst + i * 2048), "f"(acc[4 * i]), "f"(acc[4 * i + 1]), "f"(acc[4 * i + 2]), "f"(acc[4 * i + 3]), "r"(rbar) : "memory");
    } else {
      float spec[2][28];
      if (t128 == 0) PROF(wg, 12);
      mbar_wait(bars + B_PQFULL * 8, 0);
      if (t128 == 0) { PROF(wg, 13); g_ep[bid] = epoch + 1; }
#pragma unroll
      for (int i = 0; i < 4; i++) {
        if (i == 0) mbar_wait(bars + B_GFULL * 8, 0);
        if (i >= 2) mbar_wait(bars + (B_FULL + i - 2) * 8, 1);
        wg_fence();
        const uint64_t da = mkdesc(sb + OFF_PQ + i * 14336, 1024, 1024, 1);
        const uint64_t db = mkdesc(i < 2 ? sb + OFF_R + 28672 + i * (G_IMG / 2) : sb + (i - 2) * SLOT, 896, 128, 0);
#pragma unroll
        for (int kk = 0; kk < 7; kk++) wgmma_ss_56<1, 0>(spec[i >> 1], da + kk * 128, db + kk * 112, ((i & 1) | kk) != 0);
        wg_commit();
      }
      const float* gs = reinterpret_cast<const float*>(smem + OFF_G) + w4 * 16 + g;
      const float o0 = bf16_round(1.0f - gs[0]), o1 = bf16_round(1.0f - gs[8]);
      const float g0 = gs[0] * (1.0f / (float)(S_ * D_)), g1 = gs[8] * (1.0f / (float)(S_ * D_));
      wg_wait<0>(); keep(spec[0]); keep(spec[1]);
      if (t128 == 0) PROF(wg, 14);
      mbar_wait_cluster(bars + B_RECV * 8, 0);
      if (t128 == 0) PROF(wg, 0);
      float4 o[14];
#pragma unroll
      for (int i = 0; i < 14; i++) o[i] = lds128f(sb + OFF_R + t128 * 16 + i * 2048);
      bar_sync<5, 128>();
      const uint32_t st = sb + OFF_PQ + w4 * 3840;
#pragma unroll
      for (int i = 0; i < 7; i++) {
        uint32_t pk[4];
#pragma unroll
        for (int e = 0; e < 2; e++) {
          const int c = 2 * i + e, si = i * 4 + e;
          pk[2 * e] = pack_bf16(fmaf(acc[4 * c] + o[c].x, o0, g0 * spec[0][si]), fmaf(acc[4 * c + 1] + o[c].y, o0, g0 * spec[1][si]));
          pk[2 * e + 1] = pack_bf16(fmaf(acc[4 * c + 2] + o[c].z, o1, g1 * spec[0][si + 2]), fmaf(acc[4 * c + 3] + o[c].w, o1, g1 * spec[1][si + 2]));
        }
        asm volatile("stmatrix.sync.aligned.m8n8.x4.shared.b16 [%0], {%1,%2,%3,%4};"
                     :: "r"(st + (lane & 15) * 240 + (lane >> 4) * 16 + i * 32), "r"(pk[0]), "r"(pk[1]), "r"(pk[2]), "r"(pk[3]) : "memory");
      }
      __syncwarp();
      if (lane < 28) {
        const int r2 = lane >= 14, cc = lane - r2 * 14;
        unsigned char* ob = reinterpret_cast<unsigned char*>(out) + (size_t)(m * 128 + kh * 64 + w4 * 16 + r2) * (D_ * 2) + n * 224 + cc * 16;
        float4 v[8];
#pragma unroll
        for (int i = 0; i < 8; i++) v[i] = lds128f(st + r2 * 240 + cc * 16 + i * 480);
#pragma unroll
        for (int i = 0; i < 8; i++) stg128(ob + i * (D_ * 4), __float_as_uint(v[i].x), __float_as_uint(v[i].y), __float_as_uint(v[i].z), __float_as_uint(v[i].w));
      }
    }
    if (t128 == 0) { PROF(wg, 15); if (wg) { PROFG(4, 30); PROF(4, 31); } }
  } else {
    asm volatile("setmaxnreg.dec.sync.aligned.u32 72;");
    const int t = tid - 256;
    const int k = bid;
    if (t == 0) PROF(2, 0);
    uint4 gv[7];
#pragma unroll
    for (int i = 0; i < 7; i++) gv[i] = ldg128(reinterpret_cast<const uint4*>(gate_w) + i * 8 + (t & 7));
    if (t < 98) {
      int cid = m * 98 + t, kc = cid / 56, nn = cid - kc * 56;
      int d = 112 * n + 8 * (2 * (nn >> 3) + (nn & 1)) + (nn & 6) + kh;
      int dr = d > 224 ? d - 448 : d;
      const float df = (float)dr * (-6.283185307179586f / 448.0f);
      uint32_t pk[4];
#pragma unroll
      for (int e = 0; e < 4; e++) {
        const float a = (float)(4 * kc + e) * df;
        pk[e] = pack_bf16(2.0f * __cosf(a), 2.0f * __sinf(a));
      }
      if (kc == 0) pk[0] = (((d >> 1) ^ kh) & 1) ? 0xBF803F80u : 0x3F803F80u;
      stg128(g_G + (size_t)(n * 2 + kh) * G_IMG + cid * 16, pk[0], pk[1], pk[2], pk[3]);
    }
    bar_sync<0, NTHREADS>();
    asm volatile("barrier.cluster.arrive.relaxed.aligned;" ::: "memory");
    mbar_wait(bars + B_PIN * 8, 0);
    if (t == 0) PROF(2, 4);
    {
      const uint32_t wa = sb + 5 * SLOT + (((t & 7) - bid) & 7) * 450 + (t >> 3) * 2, wc = wa + 448 - (t >> 3) * 4;
      uint2* dst = g_Wt + (t >> 3) * S_ + 16 * bid + 2 * (t & 7);
#pragma unroll 1
      for (int h = 0; h < 2; h++) {
        uint32_t w[4][8];
#pragma unroll
        for (int i = 0; i < 4; i++) {
#pragma unroll
          for (int e = 0; e < 4; e++) { w[i][2 * e] = lds16(wa + h * 128 + i * 32 + e * 3600); w[i][2 * e + 1] = lds16(wc - h * 128 - i * 32 + e * 3600); }
        }
#pragma unroll
        for (int i = 0; i < 4; i++)
          if (i < 3 || h == 0 || t < 8)
            stg128(dst + (h * 64 + i * 16) * S_, __byte_perm(w[i][0], w[i][1], 0x5410), __byte_perm(w[i][4], w[i][5], 0x5410), __byte_perm(w[i][2], w[i][3], 0x5410), __byte_perm(w[i][6], w[i][7], 0x5410));
      }
    }
    __syncwarp();
    if (lane < 3) mbar_arrive(bars + (lane ? B_EMPTY + 5 : B_PUBW) * 8);
    if (t == 0) PROF(2, 6);
    {
      const int row = n * 16 + (t >> 3), l8 = t & 7;
      mbar_wait(bars + (B_XFULL + 1) * 8, 0);
      float sum = 0.f;
#pragma unroll
      for (int i = 0; i < 7; i++) {
        const uint4 a = lds128(sb + OFF_R + i * 8192 + row * 128 + ((l8 ^ (row & 7)) << 4));
        const uint32_t aa[4] = {a.x, a.y, a.z, a.w}, bb[4] = {gv[i].x, gv[i].y, gv[i].z, gv[i].w};
#pragma unroll
        for (int e = 0; e < 4; e++) {
          const uint32_t pr = as_u(__hmul2(as_b2(aa[e]), as_b2(bb[e])));
          sum += bf_lo(pr) + bf_hi(pr);
        }
      }
      sum += __shfl_xor_sync(0xffffffffu, sum, 1); sum += __shfl_xor_sync(0xffffffffu, sum, 2); sum += __shfl_xor_sync(0xffffffffu, sum, 4);
      if (lane == 0) mbar_arrive(bars + (B_XFREE + 1) * 8);
      if (l8 == 0) g_gate[m * 128 + kh * 64 + row] = bf16_round(__fdividef(1.0f, 1.0f + __expf(-bf16_round(sum))));
    }
    if (t == 0) PROF(2, 11);
    mbar_wait(bars + B_XFREE * 8, 0);
    if (k < 113) {
      const float u = -6.283185307179586f / 2048.0f, t2 = (float)(2 * t) * u, rr = (float)(t >> 4) * u;
#pragma unroll 1
      for (int i = 0; i < 4; i++) {
        const float q = (float)(2 * i), l = (float)((t & 15) + 64 * i);
        sts128(sb + OFF_TW + i * 2048 + t * 16, cis(t2 * q), cis((t2 + u) * q), cis(t2 * (q + 1.0f)), cis((t2 + u) * (q + 1.0f)));
        sts128(sb + OFF_TW + 8192 + i * 2048 + t * 16, cis(rr * l), cis(rr * (l + 16.0f)), cis(rr * (l + 32.0f)), cis(rr * (l + 48.0f)));
      }
      const float l = (float)((t >> 1) & 15) * (8.0f * u), jj = (float)((t >> 5) * 4 + (t & 1) * 2);
      sts64(sb + OFF_TW + 16384 + t * 8, cis(l * jj), cis(l * (jj + 1.0f)));
    }
    if (t == 0) PROF(2, 9);
    mbar_wait(bars + B_RFULL * 8, 0);
    if (t < 112) {
      const int js = bid >> 4, nn = (t >> 1) / 14, cc = (t >> 1) - nn * 14;
      unsigned char* wdst = g_Wd + (size_t)((js >> 2) * 4 + nn) * WD_IMG + cc * 128 + (t & 1) * 16;
      uint4 v[7];
#pragma unroll
      for (int i = 0; i < 7; i++) v[i] = lds128(sb + OFF_R + i * 1792 + (t & 1) * 896 + (t >> 1) * 16);
#pragma unroll
      for (int i = 0; i < 7; i++) {
        int col = 14 * (bid & 15) + 2 * i - (js & 1) * 32;
        if (col < 0) col += 224;
        const int kpos = col < 192 ? (col >> 6) * 256 + (js & 3) * 64 + (col & 63) : 576 + (js & 3) * 32 + col;
        stg128(wdst + (kpos >> 3) * 1792 + (kpos & 7) * 16, v[i].x, v[i].y, v[i].z, v[i].w);
      }
    }
    __syncwarp();
    if (lane == 0) mbar_arrive(bars + B_PUBD * 8);
    bar_sync<3, 128>();
    if (k < 113) {
      if (t == 0) PROF(2, 2);
      mbar_wait(bars + B_XCFULL * 8, 0);
      if (t == 0) PROF(2, 3);
      c2 v[16];
      const uint32_t se = k == 0 ? 0x4410 : (k == 112 ? 0x4432 : 0x3210), so = k == 0 ? 0x4410 : (k == 112 ? 0x3244 : 0x3210);
#pragma unroll
      for (int jj = 0; jj < 8; jj++) {
        const uint2 e2 = lds64(sb + OFF_EXCH + jj * 1024 + t * 8), o2 = lds64(sb + OFF_EXCH + 8192 + jj * 1024 + t * 8);
#pragma unroll
        for (int h = 0; h < 2; h++) {
          const b2 e = as_b2(__byte_perm(h ? e2.y : e2.x, 0, se)), o = as_b2(__byte_perm(h ? o2.y : o2.x, 0, so));
          const uint32_t s = as_u(__hadd2(e, o)), d = as_u(__hsub2(e, o)) ^ 0x80000000u;
          v[2 * jj + h] = mk(as_b2(__byte_perm(s, d, 0x5410)), as_b2(__byte_perm(s, d, 0x7632)));
        }
      }
      if (t == 0) PROF(2, 12);
      columns(v, sb, t);
      if (t == 0) PROF(2, 14);
      const int pre = (k == 112) ? 1 : 2 * k, pim = (k == 112) ? 1 : 2 * k + 1;
      uint32_t* pq = reinterpret_cast<uint32_t*>(g_PQ) + (t >> 5) * 14336;
      uint32_t* pr = pq + pre * 32 + ((((lane >> 2) ^ pre) & 7) << 2) + (lane & 3);
      uint32_t* pi = pq + pim * 32 + ((((lane >> 2) ^ pim) & 7) << 2) + (lane & 3);
#pragma unroll
      for (int jj = 0; jj < 8; jj++) {
        const b2 ar = as_b2(__byte_perm(as_u(v[2 * jj].y), as_u(v[2 * jj + 1].y), 0x5410)), br = as_b2(__byte_perm(as_u(v[2 * jj].y), as_u(v[2 * jj + 1].y), 0x7632));
        const b2 ai = as_b2(__byte_perm(as_u(v[2 * jj].x), as_u(v[2 * jj + 1].x), 0x5410)), bi = as_b2(__byte_perm(as_u(v[2 * jj].x), as_u(v[2 * jj + 1].x), 0x7632));
        pr[jj * 57344] = as_u(__hadd2(ar, br));
        if (k != 112) pr[jj * 57344 + 7168] = as_u(__hsub2(ar, br));
        if (k != 0) pi[jj * 57344 + 7168] = as_u(__hadd2(ai, bi));
        if (k != 0 && k != 112) pi[jj * 57344] = as_u(__hsub2(ai, bi));
      }
      fence_async_smem();
    }
    bar_sync<3, 128>();
    if (t == 0) { PROF(2, 5); red_release(&g_cnt[5 * 32]); PROF(2, 7); }
    __syncwarp();
    asm volatile("barrier.cluster.wait.aligned;" ::: "memory");
  }
}

typedef CUresult (*EncodeFn)(CUtensorMap*, CUtensorMapDataType, cuuint32_t, void*, const cuuint64_t*, const cuuint64_t*, const cuuint32_t*,
                             const cuuint32_t*, CUtensorMapInterleave, CUtensorMapSwizzle, CUtensorMapL2promotion, CUtensorMapFloatOOBfill);

void make_map(EncodeFn enc, CUtensorMap* tm, const void* base, int cols, int rows, int bc, int br, CUtensorMapSwizzle sw) {
  cuuint64_t gd[2] = {(cuuint64_t)cols, (cuuint64_t)rows};
  cuuint64_t gs[1] = {(cuuint64_t)cols * 2};
  cuuint32_t bd[2] = {(cuuint32_t)bc, (cuuint32_t)br};
  cuuint32_t es[2] = {1, 1};
  enc(tm, CU_TENSOR_MAP_DATA_TYPE_BFLOAT16, 2, const_cast<void*>(base), gd, gs, bd, es, CU_TENSOR_MAP_INTERLEAVE_NONE, sw,
      CU_TENSOR_MAP_L2_PROMOTION_L2_128B, CU_TENSOR_MAP_FLOAT_OOB_FILL_NONE);
}

}

extern "C" void kernel_launch(void* const* d_in, const int* in_sizes, int n_in, void* d_out, int out_size) {
  (void)in_sizes; (void)n_in; (void)out_size;
  const __nv_bfloat16* x = (const __nv_bfloat16*)d_in[0];
  const __nv_bfloat16* w_r = (const __nv_bfloat16*)d_in[1];
  const __nv_bfloat16* w_i = (const __nv_bfloat16*)d_in[2];
  const __nv_bfloat16* w_gate = (const __nv_bfloat16*)d_in[4];
  const __nv_bfloat16* w_up = (const __nv_bfloat16*)d_in[5];
  const __nv_bfloat16* w_down = (const __nv_bfloat16*)d_in[6];
  const __nv_bfloat16* gate_w = (const __nv_bfloat16*)d_in[7];
  static EncodeFn enc = nullptr;
  static bool ok = false;
  if (!enc) {
    cudaDriverEntryPointQueryResult qr;
    cudaGetDriverEntryPoint("cuTensorMapEncodeTiled", (void**)&enc, cudaEnableDefault, &qr);
    cudaFuncSetAttribute(fused_kernel, cudaFuncAttributeMaxDynamicSharedMemorySize, SMEM_BYTES);
    cudaFuncAttributes fa;
    cudaFuncGetAttributes(&fa, fused_kernel);
    ok = (fa.numRegs == 128);
  }
  if (!ok) return;
  CUtensorMap tx, tg, tu, tg32, tu32;
  {
    cuuint64_t gd[3] = {64, (cuuint64_t)S_, 7};
    cuuint64_t gs[2] = {(cuuint64_t)D_ * 2, 128};
    cuuint32_t bd[3] = {64, 64, 7};
    cuuint32_t es[3] = {1, 1, 1};
    enc(&tx, CU_TENSOR_MAP_DATA_TYPE_BFLOAT16, 3, const_cast<__nv_bfloat16*>(x), gd, gs, bd, es, CU_TENSOR_MAP_INTERLEAVE_NONE, CU_TENSOR_MAP_SWIZZLE_128B,
        CU_TENSOR_MAP_L2_PROMOTION_L2_128B, CU_TENSOR_MAP_FLOAT_OOB_FILL_NONE);
  }
  make_map(enc, &tg, w_gate, F_, D_, 64, 64, CU_TENSOR_MAP_SWIZZLE_128B);
  make_map(enc, &tu, w_up, F_, D_, 64, 64, CU_TENSOR_MAP_SWIZZLE_128B);
  make_map(enc, &tg32, w_gate, F_, D_, 32, 128, CU_TENSOR_MAP_SWIZZLE_64B);
  make_map(enc, &tu32, w_up, F_, D_, 32, 128, CU_TENSOR_MAP_SWIZZLE_64B);
  fused_kernel<<<128, NTHREADS, SMEM_BYTES>>>(tx, tg, tu, tg32, tu32, w_r, w_i, w_gate, w_up, w_down, gate_w, (__nv_bfloat16*)d_out);
}
```

```cpp
#include <cuda_runtime.h>
#include <cuda_bf16.h>
#include <cuda.h>
#include <stdint.h>

namespace {

constexpr int S_ = 2048, D_ = 448, F_ = 1792;
constexpr int NTHREADS = 512;
constexpr int SLOT = 16384, NSLOT = 7;
constexpr int HALF_XR = 57344;
constexpr int OFF_PQ = NSLOT * SLOT;
constexpr int OFF_R = OFF_PQ + HALF_XR;
constexpr int OFF_EXCH = OFF_PQ;
constexpr int OFF_WS = OFF_EXCH + 18432;
constexpr int OFF_TW = OFF_WS + 16384;
constexpr int OFF_Z = OFF_TW + 17408;
constexpr int OFF_MISC = OFF_R + HALF_XR;
constexpr int OFF_G = OFF_MISC;
constexpr int OFF_BAR = OFF_MISC + 512;
constexpr int SMEM_BYTES = OFF_BAR + 512;
constexpr int B_FULL = 0, B_EMPTY = 7, B_XFULL = 14  ;
constexpr int B_XFREE = 16  , B_PUBX = 18, B_RFREE = 19, B_LFREE = 20;
constexpr int B_PUBW = 21, B_PUBD = 22;
constexpr int B_PQFULL = 23, B_RECV = 24, B_WFULL = 25, B_XCFULL = 26, B_PREP = 27, B_PREPW = 28, B_RFULL = 29, B_GFULL = 30, B_END = 31, B_PIN = 31;

constexpr int WD_IMG = 896 * 112 * 2;
constexpr int G_IMG = 224 * 56 * 2;

__device__ __align__(1024) uint32_t g_Xc[112 * 2 * S_];
constexpr int H_IMG = 32 * 56 * 4096;
__device__ __align__(1024) unsigned char g_H[2 * H_IMG];
__device__ __align__(1024) unsigned char g_PQ[32 * HALF_XR];
__device__ __align__(1024) unsigned char g_Wd[8 * WD_IMG];
__device__ __align__(1024) unsigned char g_G[8 * G_IMG];
__device__ __align__(1024) uint2 g_Wt[113 * S_];
__device__ __align__(1024) float g_gate[S_];
__device__ __align__(128) unsigned int g_ep[128];
__device__ __align__(128) unsigned int g_cnt[8 * 32];

#define PROF(role, idx) do {} while (0)
#define PROFG(role, idx) do {} while (0)

__device__ __forceinline__ uint32_t s2u(const void* p) { return (uint32_t)__cvta_generic_to_shared(p); }
__device__ __forceinline__ void mbar_init(uint32_t b, int c) { asm volatile("mbarrier.init.shared::cta.b64 [%0], %1;" :: "r"(b), "r"(c) : "memory"); }
__device__ __forceinline__ void mbar_expect(uint32_t b, int bytes) { asm volatile("mbarrier.arrive.expect_tx.shared::cta.b64 _, [%0], %1;" :: "r"(b), "r"(bytes) : "memory"); }
__device__ __forceinline__ void mbar_arrive(uint32_t b) { asm volatile("mbarrier.arrive.shared::cta.b64 _, [%0];" :: "r"(b) : "memory"); }
__device__ __forceinline__ void mbar_wait(uint32_t b, int ph) {
  asm volatile("{\n.reg .pred p;\n.reg .u32 c;\nmov.u32 c, 0;\nL_WAIT:\nmbarrier.try_wait.parity.shared::cta.b64 p, [%0], %1;\n@p bra.uni L_DONE;\n"
               "add.u32 c, c, 1;\nsetp.lt.u32 p, c, 4194304;\n@p bra.uni L_WAIT;\ntrap;\nL_DONE:\n}" :: "r"(b), "r"(ph) : "memory");
}
__device__ __forceinline__ void mbar_wait_cluster(uint32_t b, int ph) {
  asm volatile("{\n.reg .pred p;\n.reg .u32 c;\nmov.u32 c, 0;\nL_WAIT:\nmbarrier.try_wait.parity.acquire.cluster.shared::cta.b64 p, [%0], %1;\n@p bra.uni L_DONE;\n"
               "add.u32 c, c, 1;\nsetp.lt.u32 p, c, 4194304;\n@p bra.uni L_WAIT;\ntrap;\nL_DONE:\n}" :: "r"(b), "r"(ph) : "memory");
}
__device__ __forceinline__ uint32_t ld_acquire(const unsigned int* p) { uint32_t v; asm volatile("ld.acquire.gpu.global.u32 %0, [%1];" : "=r"(v) : "l"(p) : "memory"); return v; }
__device__ __forceinline__ uint32_t ld_relaxed(const unsigned int* p) { uint32_t v; asm volatile("ld.relaxed.gpu.global.u32 %0, [%1];" : "=r"(v) : "l"(p) : "memory"); return v; }
__device__ __forceinline__ void wait_ge(const unsigned int* p, uint32_t target) {
#pragma unroll 1
  for (int i = 0; i < (1 << 22); i++) { if ((int)(ld_acquire(p) - target) >= 0) return; }
  __trap();
}
__device__ __forceinline__ void red_release(unsigned int* p) { asm volatile("red.release.gpu.global.add.u32 [%0], 1;" :: "l"(p) : "memory"); }
__device__ __forceinline__ void red_relaxed(unsigned int* p) { asm volatile("red.relaxed.gpu.global.add.u32 [%0], 1;" :: "l"(p) : "memory"); }
__device__ __forceinline__ bool elect() { uint32_t p; asm volatile("{\n.reg .pred p;\nelect.sync _|p, 0xffffffff;\nselp.u32 %0, 1, 0, p;\n}" : "=r"(p)); return p; }
__device__ __forceinline__ void fence_async_smem() { asm volatile("fence.proxy.async.shared::cta;" ::: "memory"); }
__device__ __forceinline__ void fence_async_global() { asm volatile("fence.proxy.async.global;" ::: "memory"); }
template <int ID, int N> __device__ __forceinline__ void bar_sync() { asm volatile("bar.sync %0, %1;" :: "n"(ID), "n"(N) : "memory"); }
template <int ID, int N> __device__ __forceinline__ void bar_arrive() { asm volatile("bar.arrive %0, %1;" :: "n"(ID), "n"(N) : "memory"); }
__device__ __forceinline__ void tma2d(uint32_t dst, const CUtensorMap* tm, int c0, int c1, uint32_t bar) {
  asm volatile("cp.async.bulk.tensor.2d.shared::cluster.global.mbarrier::complete_tx::bytes [%0], [%1, {%3, %4}], [%2];"
               :: "r"(dst), "l"(tm), "r"(bar), "r"(c0), "r"(c1) : "memory");
}
__device__ __forceinline__ void tma3d(uint32_t dst, const CUtensorMap* tm, int c0, int c1, int c2, uint32_t bar) {
  asm volatile("cp.async.bulk.tensor.3d.shared::cluster.global.mbarrier::complete_tx::bytes [%0], [%1, {%3, %4, %5}], [%2];"
               :: "r"(dst), "l"(tm), "r"(bar), "r"(c0), "r"(c1), "r"(c2) : "memory");
}
__device__ __forceinline__ void bulk_g2s(uint32_t dst, const void* src, int bytes, uint32_t bar) {
  asm volatile("cp.async.bulk.shared::cluster.global.mbarrier::complete_tx::bytes [%0], [%1], %2, [%3];"
               :: "r"(dst), "l"(src), "r"(bytes), "r"(bar) : "memory");
}
__device__ __forceinline__ void prefetch_l2(const void* src, int bytes) {
  asm volatile("cp.async.bulk.prefetch.L2.global [%0], %1;" :: "l"(src), "r"(bytes) : "memory");
}
__device__ __forceinline__ void prefetch_tma2d(const CUtensorMap* tm, int c0, int c1) {
  asm volatile("cp.async.bulk.prefetch.tensor.2d.L2.global [%0, {%1, %2}];" :: "l"(tm), "r"(c0), "r"(c1) : "memory");
}
__device__ __forceinline__ uint64_t mkdesc(uint32_t addr, uint32_t lbo, uint32_t sbo, uint32_t mode) {
  return (uint64_t)((addr & 0x3FFFF) >> 4) | ((uint64_t)(lbo >> 4) << 16) | ((uint64_t)(sbo >> 4) << 32) | ((uint64_t)mode << 62);
}
__device__ __forceinline__ void wg_fence() { asm volatile("wgmma.fence.sync.aligned;" ::: "memory"); }
__device__ __forceinline__ void wg_commit() { asm volatile("wgmma.commit_group.sync.aligned;" ::: "memory"); }
template <int N> __device__ __forceinline__ void wg_wait() { asm volatile("wgmma.wait_group.sync.aligned %0;" :: "n"(N) : "memory"); }
template <int N> __device__ __forceinline__ void keep(float (&d)[N]) {
#pragma unroll
  for (int i = 0; i < N; i++) asm volatile("" : "+f"(d[i]) :: "memory");
}
__device__ __forceinline__ uint32_t pack_bf16(float lo, float hi) { uint32_t r; asm("cvt.rn.bf16x2.f32 %0, %1, %2;" : "=r"(r) : "f"(hi), "f"(lo)); return r; }
__device__ __forceinline__ float bf16_round(float v) { return __bfloat162float(__float2bfloat16_rn(v)); }
__device__ __forceinline__ void sts128(uint32_t a, uint32_t x, uint32_t y, uint32_t z, uint32_t w) { asm volatile("st.shared.v4.b32 [%0], {%1,%2,%3,%4};" :: "r"(a), "r"(x), "r"(y), "r"(z), "r"(w) : "memory"); }
__device__ __forceinline__ float4 lds128f(uint32_t a) { float4 v; asm volatile("ld.shared.v4.f32 {%0,%1,%2,%3}, [%4];" : "=f"(v.x), "=f"(v.y), "=f"(v.z), "=f"(v.w) : "r"(a) : "memory"); return v; }

__device__ __forceinline__ uint2 lds64(uint32_t a) { uint2 v; asm volatile("ld.shared.v2.b32 {%0,%1}, [%2];" : "=r"(v.x), "=r"(v.y) : "r"(a) : "memory"); return v; }
__device__ __forceinline__ float bf_lo(uint32_t w) { return __uint_as_float(w << 16); }
__device__ __forceinline__ float bf_hi(uint32_t w) { return __uint_as_float(w & 0xffff0000u); }
__device__ __forceinline__ uint32_t opaque(uint32_t v) { asm volatile("" : "+r"(v)); return v; }
__device__ __forceinline__ uint4 ldg128(const void* p) { uint4 v; asm volatile("ld.global.nc.v4.b32 {%0,%1,%2,%3}, [%4];" : "=r"(v.x), "=r"(v.y), "=r"(v.z), "=r"(v.w) : "l"(p)); return v; }
__device__ __forceinline__ void stg128(void* p, uint32_t x, uint32_t y, uint32_t z, uint32_t w) { asm volatile("st.global.v4.b32 [%0], {%1,%2,%3,%4};" :: "l"(p), "r"(x), "r"(y), "r"(z), "r"(w) : "memory"); }
__device__ __forceinline__ void stg128_l2(void* p, uint32_t x, uint32_t y, uint32_t z, uint32_t w) { asm volatile("st.relaxed.gpu.global.v4.b32 [%0], {%1,%2,%3,%4};" :: "l"(p), "r"(x), "r"(y), "r"(z), "r"(w) : "memory"); }
__device__ __forceinline__ void ldg128_na(uint32_t (&v)[4], const void* p) { asm volatile("ld.global.L1::no_allocate.v4.b32 {%0,%1,%2,%3}, [%4];" : "=r"(v[0]), "=r"(v[1]), "=r"(v[2]), "=r"(v[3]) : "l"(p) : "memory"); }
__device__ __forceinline__ void ldg128_l2(uint32_t (&v)[4], const void* p) { asm volatile("ld.relaxed.gpu.global.v4.b32 {%0,%1,%2,%3}, [%4];" : "=r"(v[0]), "=r"(v[1]), "=r"(v[2]), "=r"(v[3]) : "l"(p) : "memory"); }
__device__ __forceinline__ uint4 lds128(uint32_t a) { uint4 v; asm volatile("ld.shared.v4.b32 {%0,%1,%2,%3}, [%4];" : "=r"(v.x), "=r"(v.y), "=r"(v.z), "=r"(v.w) : "r"(a) : "memory"); return v; }
__device__ __forceinline__ uint32_t lds16(uint32_t a) { uint32_t v; asm volatile("ld.shared.u16 %0, [%1];" : "=r"(v) : "r"(a) : "memory"); return v; }
__device__ __forceinline__ void sts64(uint32_t a, uint32_t x, uint32_t y) { asm volatile("st.shared.v2.b32 [%0], {%1,%2};" :: "r"(a), "r"(x), "r"(y) : "memory"); }
template <int TB> __device__ __forceinline__ void wgmma_rs_128(float (&d)[64], const uint32_t (&a)[4], uint64_t db, int sc) {
  asm volatile("{\n.reg .pred p;\nsetp.ne.b32 p, %69, 0;\n"
    "wgmma.mma_async.sync.aligned.m64n128k16.f32.bf16.bf16 {%0, %1, %2, %3, %4, %5, %6, %7, %8, %9, %10, %11, %12, %13, %14, %15, %16, %17, %18, %19, %20, %21, %22, %23, %24, %25, %26, %27, %28, %29, %30, %31, %32, %33, %34, %35, %36, %37, %38, %39, %40, %41, %42, %43, %44, %45, %46, %47, %48, %49, %50, %51, %52, %53, %54, %55, %56, %57, %58, %59, %60, %61, %62, %63}, {%64, %65, %66, %67}, %68, p, 1, 1, %70;\n}\n"
    : "+f"(d[0]), "+f"(d[1]), "+f"(d[2]), "+f"(d[3]), "+f"(d[4]), "+f"(d[5]), "+f"(d[6]), "+f"(d[7]), "+f"(d[8]), "+f"(d[9]), "+f"(d[10]), "+f"(d[11]), "+f"(d[12]), "+f"(d[13]), "+f"(d[14]), "+f"(d[15]), "+f"(d[16]), "+f"(d[17]), "+f"(d[18]), "+f"(d[19]), "+f"(d[20]), "+f"(d[21]), "+f"(d[22]), "+f"(d[23]), "+f"(d[24]), "+f"(d[25]), "+f"(d[26]), "+f"(d[27]), "+f"(d[28]), "+f"(d[29]), "+f"(d[30]), "+f"(d[31]), "+f"(d[32]), "+f"(d[33]), "+f"(d[34]), "+f"(d[35]), "+f"(d[36]), "+f"(d[37]), "+f"(d[38]), "+f"(d[39]), "+f"(d[40]), "+f"(d[41]), "+f"(d[42]), "+f"(d[43]), "+f"(d[44]), "+f"(d[45]), "+f"(d[46]), "+f"(d[47]), "+f"(d[48]), "+f"(d[49]), "+f"(d[50]), "+f"(d[51]), "+f"(d[52]), "+f"(d[53]), "+f"(d[54]), "+f"(d[55]), "+f"(d[56]), "+f"(d[57]), "+f"(d[58]), "+f"(d[59]), "+f"(d[60]), "+f"(d[61]), "+f"(d[62]), "+f"(d[63])
    : "r"(a[0]), "r"(a[1]), "r"(a[2]), "r"(a[3]), "l"(db), "r"(sc), "n"(TB));
}
template <int TB> __device__ __forceinline__ void wgmma_rs_64(float (&d)[32], const uint32_t (&a)[4], uint64_t db, int sc) {
  asm volatile("{\n.reg .pred p;\nsetp.ne.b32 p, %37, 0;\n"
    "wgmma.mma_async.sync.aligned.m64n64k16.f32.bf16.bf16 {%0, %1, %2, %3, %4, %5, %6, %7, %8, %9, %10, %11, %12, %13, %14, %15, %16, %17, %18, %19, %20, %21, %22, %23, %24, %25, %26, %27, %28, %29, %30, %31}, {%32, %33, %34, %35}, %36, p, 1, 1, %38;\n}\n"
    : "+f"(d[0]), "+f"(d[1]), "+f"(d[2]), "+f"(d[3]), "+f"(d[4]), "+f"(d[5]), "+f"(d[6]), "+f"(d[7]), "+f"(d[8]), "+f"(d[9]), "+f"(d[10]), "+f"(d[11]), "+f"(d[12]), "+f"(d[13]), "+f"(d[14]), "+f"(d[15]), "+f"(d[16]), "+f"(d[17]), "+f"(d[18]), "+f"(d[19]), "+f"(d[20]), "+f"(d[21]), "+f"(d[22]), "+f"(d[23]), "+f"(d[24]), "+f"(d[25]), "+f"(d[26]), "+f"(d[27]), "+f"(d[28]), "+f"(d[29]), "+f"(d[30]), "+f"(d[31])
    : "r"(a[0]), "r"(a[1]), "r"(a[2]), "r"(a[3]), "l"(db), "r"(sc), "n"(TB));
}
template <int TB> __device__ __forceinline__ void wgmma_rs_56(float (&d)[28], const uint32_t (&a)[4], uint64_t db, int sc) {
  asm volatile("{\n.reg .pred p;\nsetp.ne.b32 p, %33, 0;\n"
    "wgmma.mma_async.sync.aligned.m64n56k16.f32.bf16.bf16 {%0, %1, %2, %3, %4, %5, %6, %7, %8, %9, %10, %11, %12, %13, %14, %15, %16, %17, %18, %19, %20, %21, %22, %23, %24, %25, %26, %27}, {%28, %29, %30, %31}, %32, p, 1, 1, %34;\n}\n"
    : "+f"(d[0]), "+f"(d[1]), "+f"(d[2]), "+f"(d[3]), "+f"(d[4]), "+f"(d[5]), "+f"(d[6]), "+f"(d[7]), "+f"(d[8]), "+f"(d[9]), "+f"(d[10]), "+f"(d[11]), "+f"(d[12]), "+f"(d[13]), "+f"(d[14]), "+f"(d[15]), "+f"(d[16]), "+f"(d[17]), "+f"(d[18]), "+f"(d[19]), "+f"(d[20]), "+f"(d[21]), "+f"(d[22]), "+f"(d[23]), "+f"(d[24]), "+f"(d[25]), "+f"(d[26]), "+f"(d[27])
    : "r"(a[0]), "r"(a[1]), "r"(a[2]), "r"(a[3]), "l"(db), "r"(sc), "n"(TB));
}
template <int TB> __device__ __forceinline__ void wgmma_rs_112(float (&d)[56], const uint32_t (&a)[4], uint64_t db, int sc) {
  asm volatile("{\n.reg .pred p;\nsetp.ne.b32 p, %61, 0;\n"
    "wgmma.mma_async.sync.aligned.m64n112k16.f32.bf16.bf16 {%0, %1, %2, %3, %4, %5, %6, %7, %8, %9, %10, %11, %12, %13, %14, %15, %16, %17, %18, %19, %20, %21, %22, %23, %24, %25, %26, %27, %28, %29, %30, %31, %32, %33, %34, %35, %36, %37, %38, %39, %40, %41, %42, %43, %44, %45, %46, %47, %48, %49, %50, %51, %52, %53, %54, %55}, {%56, %57, %58, %59}, %60, p, 1, 1, %62;\n}\n"
    : "+f"(d[0]), "+f"(d[1]), "+f"(d[2]), "+f"(d[3]), "+f"(d[4]), "+f"(d[5]), "+f"(d[6]), "+f"(d[7]), "+f"(d[8]), "+f"(d[9]), "+f"(d[10]), "+f"(d[11]), "+f"(d[12]), "+f"(d[13]), "+f"(d[14]), "+f"(d[15]), "+f"(d[16]), "+f"(d[17]), "+f"(d[18]), "+f"(d[19]), "+f"(d[20]), "+f"(d[21]), "+f"(d[22]), "+f"(d[23]), "+f"(d[24]), "+f"(d[25]), "+f"(d[26]), "+f"(d[27]), "+f"(d[28]), "+f"(d[29]), "+f"(d[30]), "+f"(d[31]), "+f"(d[32]), "+f"(d[33]), "+f"(d[34]), "+f"(d[35]), "+f"(d[36]), "+f"(d[37]), "+f"(d[38]), "+f"(d[39]), "+f"(d[40]), "+f"(d[41]), "+f"(d[42]), "+f"(d[43]), "+f"(d[44]), "+f"(d[45]), "+f"(d[46]), "+f"(d[47]), "+f"(d[48]), "+f"(d[49]), "+f"(d[50]), "+f"(d[51]), "+f"(d[52]), "+f"(d[53]), "+f"(d[54]), "+f"(d[55])
    : "r"(a[0]), "r"(a[1]), "r"(a[2]), "r"(a[3]), "l"(db), "r"(sc), "n"(TB));
}
template <int TA, int TB> __device__ __forceinline__ void wgmma_ss_56(float (&d)[28], uint64_t da, uint64_t db, int sc) {
  asm volatile("{\n.reg .pred p;\nsetp.ne.b32 p, %30, 0;\n"
    "wgmma.mma_async.sync.aligned.m64n56k16.f32.bf16.bf16 {%0, %1, %2, %3, %4, %5, %6, %7, %8, %9, %10, %11, %12, %13, %14, %15, %16, %17, %18, %19, %20, %21, %22, %23, %24, %25, %26, %27}, %28, %29, p, 1, 1, %31, %32;\n}\n"
    : "+f"(d[0]), "+f"(d[1]), "+f"(d[2]), "+f"(d[3]), "+f"(d[4]), "+f"(d[5]), "+f"(d[6]), "+f"(d[7]), "+f"(d[8]), "+f"(d[9]), "+f"(d[10]), "+f"(d[11]), "+f"(d[12]), "+f"(d[13]), "+f"(d[14]), "+f"(d[15]), "+f"(d[16]), "+f"(d[17]), "+f"(d[18]), "+f"(d[19]), "+f"(d[20]), "+f"(d[21]), "+f"(d[22]), "+f"(d[23]), "+f"(d[24]), "+f"(d[25]), "+f"(d[26]), "+f"(d[27])
    : "l"(da), "l"(db), "r"(sc), "n"(TA), "n"(TB));
}

__device__ __forceinline__ uint32_t cis(float a) { return pack_bf16(__cosf(a), __sinf(a)); }

typedef __nv_bfloat162 b2;
struct c2 { b2 x, y; };
__device__ __forceinline__ b2 as_b2(uint32_t u) { return *reinterpret_cast<b2*>(&u); }
__device__ __forceinline__ uint32_t as_u(b2 v) { return *reinterpret_cast<uint32_t*>(&v); }
__device__ __forceinline__ c2 mk(b2 x, b2 y) { c2 r; r.x = x; r.y = y; return r; }
__device__ __forceinline__ c2 cmul(c2 a, b2 wr, b2 wi) { return mk(__hfma2(a.x, wr, __hneg2(__hmul2(a.y, wi))), __hfma2(a.x, wi, __hmul2(a.y, wr))); }
__device__ __forceinline__ void fft4(c2& a0, c2& a1, c2& a2, c2& a3) {
  c2 t0 = mk(__hadd2(a0.x, a2.x), __hadd2(a0.y, a2.y)), t1 = mk(__hsub2(a0.x, a2.x), __hsub2(a0.y, a2.y));
  c2 t2 = mk(__hadd2(a1.x, a3.x), __hadd2(a1.y, a3.y)), t3 = mk(__hsub2(a1.x, a3.x), __hsub2(a1.y, a3.y));
  a0 = mk(__hadd2(t0.x, t2.x), __hadd2(t0.y, t2.y)); a2 = mk(__hsub2(t0.x, t2.x), __hsub2(t0.y, t2.y));
  a1 = mk(__hadd2(t1.x, t3.y), __hsub2(t1.y, t3.x)); a3 = mk(__hsub2(t1.x, t3.y), __hadd2(t1.y, t3.x));
}
__device__ __forceinline__ void fft4_s2(c2& a0, c2& a1, c2& a2, c2& a3, b2 r) {
  const b2 nr = __hneg2(r);
  c2 t0 = mk(__hfma2(a2.x, r, a0.x), __hfma2(a2.y, r, a0.y)), t1 = mk(__hfma2(a2.x, nr, a0.x), __hfma2(a2.y, nr, a0.y));
  c2 t2 = mk(__hadd2(a1.x, a3.x), __hadd2(a1.y, a3.y)), t3 = mk(__hsub2(a1.x, a3.x), __hsub2(a1.y, a3.y));
  a0 = mk(__hadd2(t0.x, t2.x), __hadd2(t0.y, t2.y)); a2 = mk(__hsub2(t0.x, t2.x), __hsub2(t0.y, t2.y));
  a1 = mk(__hadd2(t1.x, t3.y), __hsub2(t1.y, t3.x)); a3 = mk(__hsub2(t1.x, t3.y), __hadd2(t1.y, t3.x));
}
__device__ __forceinline__ void fft4_s13(c2& a0, c2& a1, c2& a2, c2& a3, b2 r) {
  const b2 nr = __hneg2(r);
  c2 t0 = mk(__hadd2(a0.x, a2.x), __hadd2(a0.y, a2.y)), t1 = mk(__hsub2(a0.x, a2.x), __hsub2(a0.y, a2.y));
  c2 t2 = mk(__hadd2(a1.x, a3.x), __hadd2(a1.y, a3.y)), t3 = mk(__hsub2(a1.x, a3.x), __hsub2(a1.y, a3.y));
  a0 = mk(__hfma2(t2.x, r, t0.x), __hfma2(t2.y, r, t0.y)); a2 = mk(__hfma2(t2.x, nr, t0.x), __hfma2(t2.y, nr, t0.y));
  a1 = mk(__hfma2(t3.y, r, t1.x), __hfma2(t3.x, nr, t1.y)); a3 = mk(__hfma2(t3.y, nr, t1.x), __hfma2(t3.x, r, t1.y));
}
__device__ __forceinline__ c2 rot1(c2 a) { return mk(__hadd2(a.x, a.y), __hsub2(a.y, a.x)); }
__device__ __forceinline__ c2 rot3(c2 a) { return mk(__hsub2(a.y, a.x), __hneg2(__hadd2(a.x, a.y))); }
__device__ __forceinline__ c2 mul_mi(c2 a) { return mk(a.y, __hneg2(a.x)); }
template <int O> __device__ __forceinline__ void fft8(c2 (&v)[16]) {
  const b2 r = as_b2(0x3F353F35u), nr = as_b2(0xBF35BF35u);
  fft4(v[O], v[O + 4], v[O + 8], v[O + 12]);
  fft4(v[O + 2], v[O + 6], v[O + 10], v[O + 14]);
  const c2 o0 = v[O + 2], o1 = rot1(v[O + 6]), o2 = v[O + 10], o3 = rot1(v[O + 14]);
  const c2 e0 = v[O], e1 = v[O + 4], e2 = v[O + 8], e3 = v[O + 12];
  v[O] = mk(__hadd2(e0.x, o0.x), __hadd2(e0.y, o0.y));              v[O + 8] = mk(__hsub2(e0.x, o0.x), __hsub2(e0.y, o0.y));
  v[O + 2] = mk(__hfma2(o1.x, r, e1.x), __hfma2(o1.y, r, e1.y));    v[O + 10] = mk(__hfma2(o1.x, nr, e1.x), __hfma2(o1.y, nr, e1.y));
  v[O + 4] = mk(__hadd2(e2.x, o2.y), __hsub2(e2.y, o2.x));          v[O + 12] = mk(__hsub2(e2.x, o2.y), __hadd2(e2.y, o2.x));
  v[O + 6] = mk(__hfma2(o3.y, r, e3.x), __hfma2(o3.x, nr, e3.y));   v[O + 14] = mk(__hfma2(o3.y, nr, e3.x), __hfma2(o3.x, r, e3.y));
}
__device__ __forceinline__ void fft16(c2 (&v)[16]) {
  const b2 r = as_b2(0x3F353F35u), c1 = as_b2(0x3F6D3F6Du), s1 = as_b2(0x3EC43EC4u), nc1 = as_b2(0xBF6DBF6Du), ns1 = as_b2(0xBEC4BEC4u);
#pragma unroll
  for (int a = 0; a < 4; a++) fft4(v[a], v[a + 4], v[a + 8], v[a + 12]);
  v[5] = cmul(v[5], c1, ns1); v[6] = rot1(v[6]); v[7] = cmul(v[7], s1, nc1);
  v[9] = rot1(v[9]); v[10] = mul_mi(v[10]); v[11] = rot3(v[11]);
  v[13] = cmul(v[13], s1, nc1); v[14] = rot3(v[14]); v[15] = cmul(v[15], nc1, s1);
  fft4(v[0], v[1], v[2], v[3]); fft4_s2(v[4], v[5], v[6], v[7], r); fft4_s13(v[8], v[9], v[10], v[11], r); fft4_s2(v[12], v[13], v[14], v[15], r);
  c2 t;
  t = v[1]; v[1] = v[4]; v[4] = t;  t = v[2]; v[2] = v[8]; v[8] = t;  t = v[3]; v[3] = v[12]; v[12] = t;
  t = v[6]; v[6] = v[9]; v[9] = t;  t = v[7]; v[7] = v[13]; v[13] = t; t = v[11]; v[11] = v[14]; v[14] = t;
}

__device__ __forceinline__ void columns(c2 (&v)[16], uint32_t sb, int t) {
  const int l16 = t & 15;
  const uint32_t row = sb + OFF_EXCH + (t >> 4) * 2304;
  const uint32_t pos = sb + OFF_EXCH + (t >> 3) * 144 + (t & 7) * 16;
#pragma unroll 1
  for (int ps = 0; ps < 6; ps++) {
    if (ps == 0 || ps == 5) { fft8<0>(v); fft8<1>(v); } else fft16(v);
    if (ps == 5) break;
    if (ps == 2) {
      const uint32_t ws = sb + OFF_WS + (l16 >> 1) * 128 + ((((t >> 4) + (l16 >> 1)) & 7) * 2 + (l16 & 1)) * 8;
      mbar_wait(sb + OFF_BAR + B_WFULL * 8, 0);
#pragma unroll
      for (int q = 0; q < 16; q++) {
        const uint2 w = lds64(ws + q * 1024);
        const c2 z = cmul(v[q], as_b2(w.x), as_b2(w.y));
        v[q] = mk(z.y, z.x);
      }
      continue;
    }
    {
      const bool full = ps == 0 || ps == 4;
      const uint32_t tw = sb + OFF_TW + (full ? ps * 2048 + t * 16 : 16384 + l16 * 16);
      const uint32_t st = full ? 2048 : 256;
#pragma unroll
      for (int i = 0; i < 4; i++) {
        const uint4 w4 = lds128(tw + i * st);
        const uint32_t w[4] = {w4.x, w4.y, w4.z, w4.w};
#pragma unroll
        for (int e = 0; e < 4; e++) v[4 * i + e] = cmul(v[4 * i + e], __low2bfloat162(as_b2(w[e])), __high2bfloat162(as_b2(w[e])));
      }
    }
    if (ps == 0) {
      bar_sync<3, 128>();
#pragma unroll
      for (int q = 0; q < 8; q++) sts128(pos + q * 2304, as_u(v[2 * q].x), as_u(v[2 * q].y), as_u(v[2 * q + 1].x), as_u(v[2 * q + 1].y));
      bar_sync<3, 128>();
#pragma unroll
      for (int q = 0; q < 16; q++) { const uint2 a = lds64(row + q * 144 + l16 * 8); v[q] = mk(as_b2(a.x), as_b2(a.y)); }
    } else {
      __syncwarp();
#pragma unroll
      for (int q = 0; q < 16; q++) sts64(row + q * 144 + l16 * 8, as_u(v[q].x), as_u(v[q].y));
      if (ps == 4) bar_sync<3, 128>(); else __syncwarp();
      const uint32_t src = ps == 4 ? pos : row + l16 * 144, st = ps == 4 ? 2304 : 16;
#pragma unroll
      for (int q = 0; q < 8; q++) { const uint4 a = lds128(src + q * st); v[2 * q] = mk(as_b2(a.x), as_b2(a.y)); v[2 * q + 1] = mk(as_b2(a.z), as_b2(a.w)); }
    }
  }
}

template <int NH> __device__ __forceinline__ void h_epilogue(float (&acc)[NH * 8], unsigned char* gdst) {
#pragma unroll
  for (int c = 0; c < NH / 2; c++) {
    uint32_t pk[4];
#pragma unroll
    for (int i = 0; i < 4; i++) {
      float hv[2];
#pragma unroll
      for (int e = 0; e < 2; e++) {
        float hg = 0.5f * acc[c * 8 + i * 2 + e], up = acc[NH * 4 + c * 8 + i * 2 + e];
        float th; asm("tanh.approx.f32 %0, %1;" : "=f"(th) : "f"(hg));
        hv[e] = fmaf(hg, th, hg) * up;
      }
      pk[i] = pack_bf16(hv[0], hv[1]);
    }
    stg128_l2(gdst + c * 4096, max(pk[0], 1u), pk[1], pk[2], pk[3]);
  }
}

__device__ __forceinline__ void frag_ready(uint32_t (&a)[4], uint32_t (&b)[4], uint32_t (&c)[4], uint32_t (&d)[4], const unsigned char* p) {
  asm volatile("{\n.reg .pred p;\n.reg .u32 c, m;\nmov.u32 c, 0;\nL_TRY:\n"
               "min.u32 m, %0, %4;\nmin.u32 m, m, %8;\nmin.u32 m, m, %12;\nsetp.eq.u32 p, m, 0;\n"
               "vote.sync.any.pred p, p, 0xffffffff;\n@!p bra.uni L_OK;\n"
               "ld.relaxed.gpu.global.v4.b32 {%0,%1,%2,%3}, [%16];\nld.relaxed.gpu.global.v4.b32 {%4,%5,%6,%7}, [%16+4096];\n"
               "ld.relaxed.gpu.global.v4.b32 {%8,%9,%10,%11}, [%16+8192];\nld.relaxed.gpu.global.v4.b32 {%12,%13,%14,%15}, [%16+12288];\n"
               "add.u32 c, c, 1;\nsetp.lt.u32 p, c, 262144;\n@p bra.uni L_TRY;\ntrap;\nL_OK:\n}"
               : "+r"(a[0]), "+r"(a[1]), "+r"(a[2]), "+r"(a[3]), "+r"(b[0]), "+r"(b[1]), "+r"(b[2]), "+r"(b[3]),
                 "+r"(c[0]), "+r"(c[1]), "+r"(c[2]), "+r"(c[3]), "+r"(d[0]), "+r"(d[1]), "+r"(d[2]), "+r"(d[3])
               : "l"(p) : "memory");
}

#define LDH ldg128_na
#define LA2 5
#define LEAD1 3

__global__ void __cluster_dims__(2, 1, 1) __launch_bounds__(NTHREADS, 1)
fused_kernel(const __grid_constant__ CUtensorMap tm_x, const __grid_constant__ CUtensorMap tm_g, const __grid_constant__ CUtensorMap tm_u,
             const __grid_constant__ CUtensorMap tm_g32, const __grid_constant__ CUtensorMap tm_u32,
             const __nv_bfloat16* __restrict__ w_r, const __nv_bfloat16* __restrict__ w_i,
             const __nv_bfloat16* __restrict__ w_gate, const __nv_bfloat16* __restrict__ w_up,
             const __nv_bfloat16* __restrict__ w_down, const __nv_bfloat16* __restrict__ gate_w, __nv_bfloat16* __restrict__ out) {
  extern __shared__ __align__(1024) unsigned char smem[];
  const uint32_t sb = s2u(smem);
  const uint32_t bars = sb + OFF_BAR;
  const int tid = threadIdx.x, warp = __shfl_sync(0xffffffffu, tid >> 5, 0), lane = tid & 31;
  const int cl = blockIdx.x >> 1, kh = blockIdx.x & 1;
  const int n = cl < 4 ? cl : (cl < 36 ? (cl - 4) >> 3 : (cl - 36) / 7);
  const int m = cl < 4 ? 15 : (cl < 36 ? (cl - 4) & 7 : cl - 28 - 7 * n);
  const int j = kh * 4 + n, bid = m * 8 + n * 2 + kh;

  if (warp >= 12) {
    asm volatile("setmaxnreg.dec.sync.aligned.u32 24;");
    const int c64 = 224 * j + (j & 1) * 32;
    const uint32_t epoch = ld_relaxed(&g_ep[bid]);
    if (warp == 13) {
      if (lane < 2) mbar_init(bars + (B_XFULL + lane) * 8, 1);
    } else if (warp == 12) {
      if (lane < NSLOT) mbar_init(bars + (B_FULL + lane) * 8, 1);
    } else if (warp == 14) {
      if (lane < NSLOT) mbar_init(bars + (B_EMPTY + lane) * 8, 8);
      const int i = B_XFREE + lane;
      if (i < B_END) mbar_init(bars + i * 8, i >= B_PQFULL ? 1 : ((i == B_XFREE || i >= B_PUBW) ? 4 : 8));
      asm volatile("fence.mbarrier_init.release.cluster;" ::: "memory");
      __syncwarp();
      if (lane == 0) mbar_expect(bars + B_RECV * 8, 64 * 112 * 4);
    } else {
      if (lane == 0) mbar_init(bars + B_PIN * 8, 1);
    }
    fence_async_smem();
    bar_arrive<0, NTHREADS>();
    if (warp == 13) {
      if (elect()) {
        PROFG(4, 0); PROF(4, 1);
#pragma unroll
        for (int w = 0; w < 2; w++) {
          mbar_expect(bars + (B_XFULL + w) * 8, HALF_XR);
          tma3d(sb + OFF_PQ + w * HALF_XR, &tm_x, 0, m * 128 + (w ^ kh ^ 1) * 64, 0, bars + (B_XFULL + w) * 8);
        }
        PROF(4, 2);
      }
    } else if (warp == 12) {
#pragma unroll 1
      for (int i = 0; i < 7; i++) {
        if (elect()) {
          if (i < 5) {
            const uint32_t fb = bars + (B_FULL + i) * 8;
            mbar_expect(fb, SLOT);
            tma2d(sb + i * SLOT, &tm_g, c64, i * 64, fb);
            tma2d(sb + i * SLOT + 8192, &tm_u, c64, i * 64, fb);
          } else {
            prefetch_tma2d(&tm_g, c64, i * 64);
            prefetch_tma2d(&tm_u, c64, i * 64);
          }
        }
      }
      if (lane == 0) PROF(3, 3);
    } else if (warp == 15) {
      if (elect()) {
        mbar_expect(bars + B_PIN * 8, 14400);
        bulk_g2s(sb + 5 * SLOT, reinterpret_cast<const unsigned char*>(w_r) + bid * 7200, 7200, bars + B_PIN * 8);
        bulk_g2s(sb + 5 * SLOT + 7200, reinterpret_cast<const unsigned char*>(w_i) + bid * 7200, 7200, bars + B_PIN * 8);
      }
    }
    bar_sync<1, 128>();
    asm volatile("barrier.cluster.arrive.relaxed.aligned;" ::: "memory");
    if (warp == 12) {
      int slot = 5, ph = 1;
      auto wait_slot = [&]() { mbar_wait(bars + (B_EMPTY + slot) * 8, ph ^ (slot >= 5)); };
      auto adv = [&]() { if (++slot == NSLOT) { slot = 0; ph ^= 1; } };
      const int c32 = 224 * j + ((j & 1) ? 0 : 192);
#pragma unroll 1
      for (int i = 5; i < 25; i++) {
        wait_slot();
        if (elect()) {
          const uint32_t dst = sb + slot * SLOT, fb = bars + (B_FULL + slot) * 8;
          const bool last = i >= 21;
          const int cc = last ? c32 : c64 + 64 * (i / 7), rr = last ? slot * 128 : slot * 64;
          mbar_expect(fb, SLOT);
          tma2d(dst, last ? &tm_g32 : &tm_g, cc, rr, fb);
          tma2d(dst + 8192, last ? &tm_u32 : &tm_u, cc, rr, fb);
          if (i >= 11) {
            if (i == 11) mbar_wait(bars + B_PUBD * 8, 0);
            asm volatile("cp.async.bulk.global.shared::cta.bulk_group [%0], [%1], 4096;"
                         :: "l"(g_H + (size_t)(~epoch & 1) * H_IMG + (bid * 14 + i - 11) * 4096), "r"(sb + OFF_Z) : "memory");
          }
        }
        adv();
      }
      if (lane == 0) PROF(3, 0);
      mbar_wait(bars + B_PREP * 8, 0);
      if (lane == 0) PROF(3, 1);
#pragma unroll 1
      for (int i = 4; i < 16; i++) {
        if (lane == 0) PROF(3, 16 + i);
        if (i == 7) {
          asm volatile("cp.async.bulk.commit_group;\ncp.async.bulk.wait_group 0;" ::: "memory");
          bar_arrive<4, 64>();
        }
        wait_slot();
        if (elect()) {
          const int bytes = i < 14 ? 14336 : G_IMG / 2;
          const unsigned char* src = i < 14 ? g_Wd + (size_t)j * WD_IMG + i * 14336 : g_G + (size_t)(n * 4 + i - 12) * (G_IMG / 2);
          mbar_expect(bars + (B_FULL + slot) * 8, bytes);
          bulk_g2s(sb + slot * SLOT, src, bytes, bars + (B_FULL + slot) * 8);
        }
        adv();
      }
      if (lane == 0) PROF(3, 2);
    } else if (warp == 13) {
      mbar_wait(bars + B_PUBW * 8, 0);
      if (lane == 0) PROF(4, 7);
      mbar_wait(bars + B_PUBX * 8, 0);
      if (lane == 0) {
        PROF(4, 8);
        red_release(&g_cnt[(j >> 1) * 32]);
        red_relaxed(&g_cnt[6 * 32]);
        PROF(4, 18);
      }
      __syncwarp();
      mbar_wait(bars + B_PUBD * 8, 0);
      if (lane == 0) { PROF(4, 9); red_release(&g_cnt[4 * 32]); PROF(4, 19); }
      __syncwarp();
      mbar_wait(bars + B_LFREE * 8, 0);
      if (elect()) {
        mbar_expect(bars + B_GFULL * 8, G_IMG);
        bulk_g2s(sb + OFF_R + 28672, g_G + (size_t)(n * 2) * G_IMG, G_IMG, bars + B_GFULL * 8);
      }
    } else if (warp == 14) {
#pragma unroll 1
      for (int u = 0; u < 2; u++) {
        wait_ge(&g_cnt[(6 - 2 * u) * 32], (epoch + 1) * 128);
        fence_async_global();
        if (lane == 0) { mbar_arrive(bars + (B_PREPW - u) * 8); PROF(5, 9 - u); }
      }
    } else {
      mbar_wait(bars + B_XFREE * 8, 0);
      if (elect()) {
        prefetch_l2(reinterpret_cast<const unsigned char*>(w_gate) + bid * 12544, 12544);
        prefetch_l2(reinterpret_cast<const unsigned char*>(w_up) + bid * 12544, 12544);
      }
      mbar_wait(bars + (B_XFREE + 1) * 8, 0);
      if (elect()) {
        mbar_expect(bars + B_RFULL * 8, 12544);
        bulk_g2s(sb + OFF_R, reinterpret_cast<const unsigned char*>(w_down) + bid * 12544, 12544, bars + B_RFULL * 8);
      }
      if (bid < 113) {
        const int sl = (bid == 112) ? 0 : bid;
        wait_ge(&g_cnt[((sl & 1) + 2 * ((sl >> 1) / 28)) * 32], (epoch + 1) * 32);
        fence_async_global();
        if (elect()) {
          PROF(5, 16);
          mbar_expect(bars + B_XCFULL * 8, 16384);
          bulk_g2s(sb + OFF_EXCH, g_Xc + sl * 2 * S_, 16384, bars + B_XCFULL * 8);
        }
        mbar_wait(bars + B_PREPW * 8, 0);
        if (elect()) {
          mbar_expect(bars + B_WFULL * 8, 16384);
          bulk_g2s(sb + OFF_WS, g_Wt + bid * S_, 16384, bars + B_WFULL * 8);
          PROF(5, 17);
        }
      }
      mbar_wait(bars + B_PREP * 8, 0);
      if (elect()) {
        mbar_expect(bars + B_RFULL * 8, HALF_XR);
        bulk_g2s(sb + OFF_R, g_Wd + (size_t)j * WD_IMG, HALF_XR, bars + B_RFULL * 8);
        PROF(5, 19);
      }
      bar_sync<4, 64>();
      wait_ge(&g_cnt[5 * 32], (epoch + 1) * 128);
      fence_async_global();
      if (elect()) {
        PROF(5, 18);
        mbar_expect(bars + B_PQFULL * 8, HALF_XR + 256);
        const unsigned char* src = g_PQ + (size_t)(m * 2 + kh) * HALF_XR;
        bulk_g2s(sb + OFF_PQ, src, 28672, bars + B_PQFULL * 8);
        bulk_g2s(sb + OFF_PQ + 28672, src + 28672, 28672, bars + B_PQFULL * 8);
        bulk_g2s(sb + OFF_G, g_gate + m * 128 + kh * 64, 256, bars + B_PQFULL * 8);
      }
    }
    __syncwarp();
    asm volatile("barrier.cluster.wait.aligned;" ::: "memory");
  } else if (warp < 8) {
    asm volatile("setmaxnreg.inc.sync.aligned.u32 208;");
    const int wg = warp >> 2, w4 = warp & 3, g = lane >> 2, t = lane & 3;
    const int rh = wg ^ kh ^ 1;
    const int p = j & 1, r = (j >> 1) & 1, hh = j >> 2;
    const uint32_t epoch = ld_relaxed(&g_ep[bid]);
    if ((tid & 127) == 0) PROF(wg, 30);
#pragma unroll 1
    for (int it = tid; it < 392; it += 256) {
      const int kc = it / 28, sg = it - kc * 28;
      const int k = 2 * (28 * hh + sg) + r;
      const float kf = (float)k * (-6.283185307179586f / 448.0f), a0 = (float)(16 * kc + p) * kf;
      uint32_t c[4], s[4];
#pragma unroll
      for (int q = 0; q < 4; q++) {
        const float a1 = fmaf((float)(2 * q), kf, a0), a2 = fmaf((float)(2 * q + 8), kf, a0);
        c[q] = pack_bf16(__cosf(a1), __cosf(a2)); s[q] = pack_bf16(__sinf(a1), __sinf(a2));
        if (k == 0) s[q] = ((q ^ p) & 1) ? 0xBF80BF80u : 0x3F803F80u;
      }
      const uint32_t a = sb + 6 * SLOT + (kc * 56 + 2 * sg) * 16;
      sts128(a, c[0], c[1], c[2], c[3]);
      sts128(a + 16, s[0], s[1], s[2], s[3]);
    }
    if ((tid & 127) == 0) PROF(wg, 31);
    fence_async_smem();
    bar_sync<0, NTHREADS>();
    asm volatile("barrier.cluster.arrive.relaxed.aligned;" ::: "memory");
    if ((tid & 127) == 0) PROF(wg, 1);

    uint32_t xa[28][4];
    {
      const uint32_t xb = sb + OFF_PQ + wg * HALF_XR + (w4 * 16 + (lane & 15)) * 128;
      mbar_wait(bars + (B_XFULL + wg) * 8, 0);
      if ((tid & 127) == 0) PROF(wg, 2);
#pragma unroll
      for (int kb = 0; kb < 7; kb++) {
#pragma unroll
        for (int kk = 0; kk < 4; kk++) {
          uint32_t a = xb + kb * 8192 + (((2 * kk + (lane >> 4)) ^ (lane & 7)) << 4);
          asm volatile("ldmatrix.sync.aligned.m8n8.x4.shared.b16 {%0,%1,%2,%3}, [%4];"
                       : "=r"(xa[kb * 4 + kk][0]), "=r"(xa[kb * 4 + kk][1]), "=r"(xa[kb * 4 + kk][2]), "=r"(xa[kb * 4 + kk][3]) : "r"(a) : "memory");
        }
      }
    }
    {
      uint32_t ad[7][4];
      const uint32_t sel = p ? 0x7632 : 0x5410;
      const uint32_t sgn = r ? 0xBF80BF80u : 0x3F803F80u;
#pragma unroll
      for (int jj = 0; jj < 7; jj++) {
#pragma unroll
        for (int i = 0; i < 4; i++) {
          int ks = 2 * jj + (i >> 1), rr = i & 1;
          uint32_t lo = __byte_perm(xa[ks][rr], xa[ks][rr + 2], sel);
          uint32_t hi = __byte_perm(xa[ks + 14][rr], xa[ks + 14][rr + 2], sel);
          asm("fma.rn.bf16x2 %0, %1, %2, %3;" : "=r"(ad[jj][i]) : "r"(hi), "r"(sgn), "r"(lo));
        }
      }
      __syncwarp();
      if (lane == 0) mbar_arrive(bars + (B_XFREE + wg) * 8);
      float acc[28];
      wg_fence();
      uint64_t db = mkdesc(sb + 6 * SLOT, 896, 128, 0);
#pragma unroll
      for (int jj = 0; jj < 7; jj++) wgmma_rs_56<0>(acc, ad[jj], db + jj * 112, jj != 0);
      wg_commit();
      wg_wait<0>(); keep(acc);
      if (lane == 0) mbar_arrive(bars + (B_EMPTY + 6) * 8);
      uint32_t* xc = g_Xc + (size_t)((2 * (28 * hh + t) + r) * 2 + p) * S_ + m * 128 + rh * 64 + w4 * 16 + g;
#pragma unroll
      for (int i = 0; i < 7; i++) {
        xc[i * 16 * S_] = pack_bf16(acc[4 * i], acc[4 * i + 1]);
        xc[i * 16 * S_ + 8] = pack_bf16(acc[4 * i + 2], acc[4 * i + 3]);
      }
      __syncwarp();
      if (lane == 0) mbar_arrive(bars + B_PUBX * 8);
    }
    if ((tid & 127) == 0) PROF(wg, 3);
    unsigned char* const hbase = g_H + (size_t)((epoch & 1) * 32 + m * 2 + kh) * (56 * 4096) + rh * 2048 + (tid & 127) * 16;
#pragma unroll 1
    for (int u = 0; u < 3; u++) {
      float acc[64];
      if (wg == 1) { if (u & 1) bar_sync<6, 256>(); else bar_sync<2, 256>(); }
      const uint32_t sbu = opaque(sb);
#pragma unroll
      for (int kb = 0; kb < 7; kb++) {
        mbar_wait(sbu + OFF_BAR + (B_FULL + kb) * 8, u & 1);
        wg_fence();
        uint64_t db = mkdesc(sbu + kb * SLOT, 8192, 1024, 1);
#pragma unroll
        for (int kk = 0; kk < 4; kk++) wgmma_rs_128<1>(acc, xa[kb * 4 + kk], db + kk * 128, (kb | kk) != 0);
        wg_commit();
        if (kb == LEAD1 && wg == 0) { if (u & 1) bar_arrive<6, 256>(); else bar_arrive<2, 256>(); }
        if (kb > 0) { wg_wait<1>(); if (lane == 0) mbar_arrive(sbu + OFF_BAR + (B_EMPTY + kb - 1) * 8); }
      }
      wg_wait<0>(); keep(acc);
      if (lane == 0) mbar_arrive(sbu + OFF_BAR + (B_EMPTY + 6) * 8);
      if ((tid & 127) == 0) PROF(wg, 4 + 2 * u);
      h_epilogue<8>(acc, hbase + (u * 16 + n * 4) * 4096);
      if ((tid & 127) == 0) PROF(wg, 5 + 2 * u);
    }
    {
      float acc[32];
      if (wg == 1) bar_sync<6, 256>();
      const uint32_t sbu = opaque(sb);
#pragma unroll
      for (int it = 0; it < 4; it++) {
        mbar_wait(sbu + OFF_BAR + (B_FULL + it) * 8, 1);
        wg_fence();
        uint64_t db = mkdesc(sbu + it * SLOT, 8192, 512, 2);
#pragma unroll
        for (int kk = 0; kk < 8; kk++) if (it * 8 + kk < 28) wgmma_rs_64<1>(acc, xa[it * 8 + kk], db + kk * 64, (it | kk) != 0);
        wg_commit();
        if (it == 2 && wg == 0) bar_arrive<6, 256>();
        if (it > 0) {
          wg_wait<1>();
          if (lane == 0) mbar_arrive(sbu + OFF_BAR + (B_EMPTY + it - 1) * 8);
#pragma unroll
          for (int i = it * 8 - 8; i < it * 8; i++) if (i < 4 * LA2) LDH(xa[i], hbase + i * 4096);
        }
      }
      wg_wait<0>(); keep(acc);
      if (lane == 0) mbar_arrive(sbu + OFF_BAR + (B_EMPTY + 3) * 8);
      if ((tid & 127) == 0) PROF(wg, 10);
      h_epilogue<4>(acc, hbase + (48 + n * 2) * 4096);
    }
    asm volatile("barrier.cluster.wait.aligned;" ::: "memory");
    if ((tid & 127) == 0) PROF(wg, 11);

    float acc[56];
    if (wg == 1) bar_sync<2, 256>();
#pragma unroll 1
    for (int it = 0; it < 2; it++) {
#pragma unroll
      for (int e = 0; e < 7; e++) {
        if ((tid & 127) == 0) PROF(wg, 16 + it * 7 + e);
        const bool inr = e < 4 && it == 0;
        if (e >= 4 || it == 1) mbar_wait(bars + (B_FULL + e) * 8, e < 4 ? 0 : it ^ 1);
        else if (e == 0) mbar_wait(bars + B_RFULL * 8, 1);
        frag_ready(xa[e * 4], xa[e * 4 + 1], xa[e * 4 + 2], xa[e * 4 + 3], hbase + (it * 7 + e) * 16384);
        wg_fence();
        const uint64_t db = mkdesc(inr ? sb + OFF_R + e * 14336 : sb + e * SLOT, 1792, 128, 0);
#pragma unroll
        for (int kk = 0; kk < 4; kk++) wgmma_rs_112<1>(acc, xa[e * 4 + kk], db + kk * 224, (e | kk) ? 1 : it);
        wg_commit();
        if (e == 1 && it == 0 && wg == 0) bar_arrive<2, 256>();
        if (it == 0 || e + LA2 < 7) {
          const int nb = it * 7 + e + LA2;
#pragma unroll
          for (int kk = 0; kk < 4; kk++) LDH(xa[((e + LA2) % 7) * 4 + kk], hbase + (nb * 4 + kk) * 4096);
        }
        wg_wait<1>();
        if (lane == 0) {
          if (it == 0 ? e >= 5 : e <= 2) mbar_arrive(bars + (B_EMPTY + (e + 6) % 7) * 8);
          if (e == 4 && it == 0) {
            mbar_arrive(bars + B_LFREE * 8);
            asm volatile("{\n.reg .b32 ra;\nmapa.shared::cluster.u32 ra, %0, %1;\nmbarrier.arrive.relaxed.cluster.shared::cluster.b64 _, [ra];\n}"
                         :: "r"(bars + B_RFREE * 8), "r"(kh ^ 1) : "memory");
          }
        }
      }
    }
    const int t128 = tid & 127;
    wg_wait<0>(); keep(acc);
    if (wg == 0) {
      if (t128 == 0) PROF(wg, 12);
      mbar_wait_cluster(bars + B_RFREE * 8, 0);
      uint32_t rdst, rbar;
      asm volatile("mapa.shared::cluster.u32 %0, %1, %2;" : "=r"(rdst) : "r"(sb + OFF_R + t128 * 16), "r"(kh ^ 1));
      asm volatile("mapa.shared::cluster.u32 %0, %1, %2;" : "=r"(rbar) : "r"(bars + B_RECV * 8), "r"(kh ^ 1));
#pragma unroll
      for (int i = 0; i < 14; i++)
        asm volatile("st.async.weak.shared::cluster.mbarrier::complete_tx::bytes.v4.f32 [%0], {%1,%2,%3,%4}, [%5];"
                     :: "r"(rdst + i * 2048), "f"(acc[4 * i]), "f"(acc[4 * i + 1]), "f"(acc[4 * i + 2]), "f"(acc[4 * i + 3]), "r"(rbar) : "memory");
    } else {
      float spec[2][28];
      if (t128 == 0) PROF(wg, 12);
      mbar_wait(bars + B_PQFULL * 8, 0);
      if (t128 == 0) { PROF(wg, 13); g_ep[bid] = epoch + 1; }
#pragma unroll
      for (int i = 0; i < 4; i++) {
        if (i == 0) mbar_wait(bars + B_GFULL * 8, 0);
        if (i >= 2) mbar_wait(bars + (B_FULL + i - 2) * 8, 1);
        wg_fence();
        const uint64_t da = mkdesc(sb + OFF_PQ + i * 14336, 1024, 1024, 1);
        const uint64_t db = mkdesc(i < 2 ? sb + OFF_R + 28672 + i * (G_IMG / 2) : sb + (i - 2) * SLOT, 896, 128, 0);
#pragma unroll
        for (int kk = 0; kk < 7; kk++) wgmma_ss_56<1, 0>(spec[i >> 1], da + kk * 128, db + kk * 112, ((i & 1) | kk) != 0);
        wg_commit();
      }
      const float* gs = reinterpret_cast<const float*>(smem + OFF_G) + w4 * 16 + g;
      const float o0 = bf16_round(1.0f - gs[0]), o1 = bf16_round(1.0f - gs[8]);
      const float g0 = gs[0] * (1.0f / (float)(S_ * D_)), g1 = gs[8] * (1.0f / (float)(S_ * D_));
      wg_wait<0>(); keep(spec[0]); keep(spec[1]);
      if (t128 == 0) PROF(wg, 14);
      mbar_wait_cluster(bars + B_RECV * 8, 0);
      if (t128 == 0) PROF(wg, 0);
      float4 o[14];
#pragma unroll
      for (int i = 0; i < 14; i++) o[i] = lds128f(sb + OFF_R + t128 * 16 + i * 2048);
      bar_sync<5, 128>();
      const uint32_t st = sb + OFF_PQ + w4 * 3840;
#pragma unroll
      for (int i = 0; i < 7; i++) {
        uint32_t pk[4];
#pragma unroll
        for (int e = 0; e < 2; e++) {
          const int c = 2 * i + e, si = i * 4 + e;
          pk[2 * e] = pack_bf16(fmaf(acc[4 * c] + o[c].x, o0, g0 * spec[0][si]), fmaf(acc[4 * c + 1] + o[c].y, o0, g0 * spec[1][si]));
          pk[2 * e + 1] = pack_bf16(fmaf(acc[4 * c + 2] + o[c].z, o1, g1 * spec[0][si + 2]), fmaf(acc[4 * c + 3] + o[c].w, o1, g1 * spec[1][si + 2]));
        }
        asm volatile("stmatrix.sync.aligned.m8n8.x4.shared.b16 [%0], {%1,%2,%3,%4};"
                     :: "r"(st + (lane & 15) * 240 + (lane >> 4) * 16 + i * 32), "r"(pk[0]), "r"(pk[1]), "r"(pk[2]), "r"(pk[3]) : "memory");
      }
      __syncwarp();
      if (lane < 28) {
        const int r2 = lane >= 14, cc = lane - r2 * 14;
        unsigned char* ob = reinterpret_cast<unsigned char*>(out) + (size_t)(m * 128 + kh * 64 + w4 * 16 + r2) * (D_ * 2) + n * 224 + cc * 16;
        float4 v[8];
#pragma unroll
        for (int i = 0; i < 8; i++) v[i] = lds128f(st + r2 * 240 + cc * 16 + i * 480);
#pragma unroll
        for (int i = 0; i < 8; i++) stg128(ob + i * (D_ * 4), __float_as_uint(v[i].x), __float_as_uint(v[i].y), __float_as_uint(v[i].z), __float_as_uint(v[i].w));
      }
    }
    if (t128 == 0) { PROF(wg, 15); if (wg) { PROFG(4, 30); PROF(4, 31); } }
  } else {
    asm volatile("setmaxnreg.dec.sync.aligned.u32 72;");
    const int t = tid - 256;
    const int k = bid;
    if (t == 0) PROF(2, 0);
    uint4 gv[7];
#pragma unroll
    for (int i = 0; i < 7; i++) gv[i] = ldg128(reinterpret_cast<const uint4*>(gate_w) + i * 8 + (t & 7));
    if (t < 98) {
      int cid = m * 98 + t, kc = cid / 56, nn = cid - kc * 56;
      int d = 112 * n + 8 * (2 * (nn >> 3) + (nn & 1)) + (nn & 6) + kh;
      int dr = d > 224 ? d - 448 : d;
      const float df = (float)dr * (-6.283185307179586f / 448.0f);
      uint32_t pk[4];
#pragma unroll
      for (int e = 0; e < 4; e++) {
        const float a = (float)(4 * kc + e) * df;
        pk[e] = pack_bf16(2.0f * __cosf(a), 2.0f * __sinf(a));
      }
      if (kc == 0) pk[0] = (((d >> 1) ^ kh) & 1) ? 0xBF803F80u : 0x3F803F80u;
      stg128(g_G + (size_t)(n * 2 + kh) * G_IMG + cid * 16, pk[0], pk[1], pk[2], pk[3]);
    }
    bar_sync<0, NTHREADS>();
    asm volatile("barrier.cluster.arrive.relaxed.aligned;" ::: "memory");
    mbar_wait(bars + B_PIN * 8, 0);
    if (t == 0) PROF(2, 4);
    {
      const uint32_t wa = sb + 5 * SLOT + (((t & 7) - bid) & 7) * 450 + (t >> 3) * 2, wc = wa + 448 - (t >> 3) * 4;
      uint2* dst = g_Wt + (t >> 3) * S_ + 16 * bid + 2 * (t & 7);
#pragma unroll 1
      for (int h = 0; h < 2; h++) {
        uint32_t w[4][8];
#pragma unroll
        for (int i = 0; i < 4; i++) {
#pragma unroll
          for (int e = 0; e < 4; e++) { w[i][2 * e] = lds16(wa + h * 128 + i * 32 + e * 3600); w[i][2 * e + 1] = lds16(wc - h * 128 - i * 32 + e * 3600); }
        }
#pragma unroll
        for (int i = 0; i < 4; i++)
          if (i < 3 || h == 0 || t < 8)
            stg128(dst + (h * 64 + i * 16) * S_, __byte_perm(w[i][0], w[i][1], 0x5410), __byte_perm(w[i][4], w[i][5], 0x5410), __byte_perm(w[i][2], w[i][3], 0x5410), __byte_perm(w[i][6], w[i][7], 0x5410));
      }
    }
    __syncwarp();
    if (lane < 3) mbar_arrive(bars + (lane ? B_EMPTY + 5 : B_PUBW) * 8);
    if (t == 0) PROF(2, 6);
    {
      const int row = n * 16 + (t >> 3), l8 = t & 7;
      mbar_wait(bars + (B_XFULL + 1) * 8, 0);
      float sum = 0.f;
#pragma unroll
      for (int i = 0; i < 7; i++) {
        const uint4 a = lds128(sb + OFF_R + i * 8192 + row * 128 + ((l8 ^ (row & 7)) << 4));
        const uint32_t aa[4] = {a.x, a.y, a.z, a.w}, bb[4] = {gv[i].x, gv[i].y, gv[i].z, gv[i].w};
#pragma unroll
        for (int e = 0; e < 4; e++) {
          const uint32_t pr = as_u(__hmul2(as_b2(aa[e]), as_b2(bb[e])));
          sum += bf_lo(pr) + bf_hi(pr);
        }
      }
      sum += __shfl_xor_sync(0xffffffffu, sum, 1); sum += __shfl_xor_sync(0xffffffffu, sum, 2); sum += __shfl_xor_sync(0xffffffffu, sum, 4);
      if (lane == 0) mbar_arrive(bars + (B_XFREE + 1) * 8);
      if (l8 == 0) g_gate[m * 128 + kh * 64 + row] = bf16_round(__fdividef(1.0f, 1.0f + __expf(-bf16_round(sum))));
    }
    if (t == 0) PROF(2, 11);
    mbar_wait(bars + B_XFREE * 8, 0);
    sts128(sb + OFF_Z + t * 16, 0, 0, 0, 0);
    sts128(sb + OFF_Z + 2048 + t * 16, 0, 0, 0, 0);
    fence_async_smem();
    if (k < 113) {
      const float u = -6.283185307179586f / 2048.0f, t2 = (float)(2 * t) * u, rr = (float)(t >> 4) * u;
#pragma unroll 1
      for (int i = 0; i < 4; i++) {
        const float q = (float)(2 * i), l = (float)((t & 15) + 64 * i);
        sts128(sb + OFF_TW + i * 2048 + t * 16, cis(t2 * q), cis((t2 + u) * q), cis(t2 * (q + 1.0f)), cis((t2 + u) * (q + 1.0f)));
        sts128(sb + OFF_TW + 8192 + i * 2048 + t * 16, cis(rr * l), cis(rr * (l + 16.0f)), cis(rr * (l + 32.0f)), cis(rr * (l + 48.0f)));
      }
      const float l = (float)((t >> 1) & 15) * (8.0f * u), jj = (float)((t >> 5) * 4 + (t & 1) * 2);
      sts64(sb + OFF_TW + 16384 + t * 8, cis(l * jj), cis(l * (jj + 1.0f)));
    }
    if (t == 0) PROF(2, 9);
    mbar_wait(bars + B_RFULL * 8, 0);
    if (t < 112) {
      const int js = bid >> 4, nn = (t >> 1) / 14, cc = (t >> 1) - nn * 14;
      unsigned char* wdst = g_Wd + (size_t)((js >> 2) * 4 + nn) * WD_IMG + cc * 128 + (t & 1) * 16;
      uint4 v[7];
#pragma unroll
      for (int i = 0; i < 7; i++) v[i] = lds128(sb + OFF_R + i * 1792 + (t & 1) * 896 + (t >> 1) * 16);
#pragma unroll
      for (int i = 0; i < 7; i++) {
        int col = 14 * (bid & 15) + 2 * i - (js & 1) * 32;
        if (col < 0) col += 224;
        const int kpos = col < 192 ? (col >> 6) * 256 + (js & 3) * 64 + (col & 63) : 576 + (js & 3) * 32 + col;
        stg128(wdst + (kpos >> 3) * 1792 + (kpos & 7) * 16, v[i].x, v[i].y, v[i].z, v[i].w);
      }
    }
    __syncwarp();
    if (lane == 0) mbar_arrive(bars + B_PUBD * 8);
    bar_sync<3, 128>();
    if (k < 113) {
      if (t == 0) PROF(2, 2);
      mbar_wait(bars + B_XCFULL * 8, 0);
      if (t == 0) PROF(2, 3);
      c2 v[16];
      const uint32_t se = k == 0 ? 0x4410 : (k == 112 ? 0x4432 : 0x3210), so = k == 0 ? 0x4410 : (k == 112 ? 0x3244 : 0x3210);
#pragma unroll
      for (int jj = 0; jj < 8; jj++) {
        const uint2 e2 = lds64(sb + OFF_EXCH + jj * 1024 + t * 8), o2 = lds64(sb + OFF_EXCH + 8192 + jj * 1024 + t * 8);
#pragma unroll
        for (int h = 0; h < 2; h++) {
          const b2 e = as_b2(__byte_perm(h ? e2.y : e2.x, 0, se)), o = as_b2(__byte_perm(h ? o2.y : o2.x, 0, so));
          const uint32_t s = as_u(__hadd2(e, o)), d = as_u(__hsub2(e, o)) ^ 0x80000000u;
          v[2 * jj + h] = mk(as_b2(__byte_perm(s, d, 0x5410)), as_b2(__byte_perm(s, d, 0x7632)));
        }
      }
      if (t == 0) PROF(2, 12);
      columns(v, sb, t);
      if (t == 0) PROF(2, 14);
      const int pre = (k == 112) ? 1 : 2 * k, pim = (k == 112) ? 1 : 2 * k + 1;
      uint32_t* pq = reinterpret_cast<uint32_t*>(g_PQ) + (t >> 5) * 14336;
      uint32_t* pr = pq + pre * 32 + ((((lane >> 2) ^ pre) & 7) << 2) + (lane & 3);
      uint32_t* pi = pq + pim * 32 + ((((lane >> 2) ^ pim) & 7) << 2) + (lane & 3);
#pragma unroll
      for (int jj = 0; jj < 8; jj++) {
        const b2 ar = as_b2(__byte_perm(as_u(v[2 * jj].y), as_u(v[2 * jj + 1].y), 0x5410)), br = as_b2(__byte_perm(as_u(v[2 * jj].y), as_u(v[2 * jj + 1].y), 0x7632));
        const b2 ai = as_b2(__byte_perm(as_u(v[2 * jj].x), as_u(v[2 * jj + 1].x), 0x5410)), bi = as_b2(__byte_perm(as_u(v[2 * jj].x), as_u(v[2 * jj + 1].x), 0x7632));
        pr[jj * 57344] = as_u(__hadd2(ar, br));
        if (k != 112) pr[jj * 57344 + 7168] = as_u(__hsub2(ar, br));
        if (k != 0) pi[jj * 57344 + 7168] = as_u(__hadd2(ai, bi));
        if (k != 0 && k != 112) pi[jj * 57344] = as_u(__hsub2(ai, bi));
      }
      fence_async_smem();
    }
    bar_sync<3, 128>();
    if (t == 0) { PROF(2, 5); red_release(&g_cnt[5 * 32]); PROF(2, 7); }
    __syncwarp();
    asm volatile("barrier.cluster.wait.aligned;" ::: "memory");
  }
}

typedef CUresult (*EncodeFn)(CUtensorMap*, CUtensorMapDataType, cuuint32_t, void*, const cuuint64_t*, const cuuint64_t*, const cuuint32_t*,
                             const cuuint32_t*, CUtensorMapInterleave, CUtensorMapSwizzle, CUtensorMapL2promotion, CUtensorMapFloatOOBfill);

void make_map(EncodeFn enc, CUtensorMap* tm, const void* base, int cols, int rows, int bc, int br, CUtensorMapSwizzle sw) {
  cuuint64_t gd[2] = {(cuuint64_t)cols, (cuuint64_t)rows};
  cuuint64_t gs[1] = {(cuuint64_t)cols * 2};
  cuuint32_t bd[2] = {(cuuint32_t)bc, (cuuint32_t)br};
  cuuint32_t es[2] = {1, 1};
  enc(tm, CU_TENSOR_MAP_DATA_TYPE_BFLOAT16, 2, const_cast<void*>(base), gd, gs, bd, es, CU_TENSOR_MAP_INTERLEAVE_NONE, sw,
      CU_TENSOR_MAP_L2_PROMOTION_L2_128B, CU_TENSOR_MAP_FLOAT_OOB_FILL_NONE);
}

}

extern "C" void kernel_launch(void* const* d_in, const int* in_sizes, int n_in, void* d_out, int out_size) {
  (void)in_sizes; (void)n_in; (void)out_size;
  const __nv_bfloat16* x = (const __nv_bfloat16*)d_in[0];
  const __nv_bfloat16* w_r = (const __nv_bfloat16*)d_in[1];
  const __nv_bfloat16* w_i = (const __nv_bfloat16*)d_in[2];
  const __nv_bfloat16* w_gate = (const __nv_bfloat16*)d_in[4];
  const __nv_bfloat16* w_up = (const __nv_bfloat16*)d_in[5];
  const __nv_bfloat16* w_down = (const __nv_bfloat16*)d_in[6];
  const __nv_bfloat16* gate_w = (const __nv_bfloat16*)d_in[7];
  static EncodeFn enc = nullptr;
  static bool ok = false;
  if (!enc) {
    cudaDriverEntryPointQueryResult qr;
    cudaGetDriverEntryPoint("cuTensorMapEncodeTiled", (void**)&enc, cudaEnableDefault, &qr);
    cudaFuncSetAttribute(fused_kernel, cudaFuncAttributeMaxDynamicSharedMemorySize, SMEM_BYTES);
    cudaFuncAttributes fa;
    cudaFuncGetAttributes(&fa, fused_kernel);
    ok = (fa.numRegs == 128);
  }
  if (!ok) return;
  CUtensorMap tx, tg, tu, tg32, tu32;
  {
    cuuint64_t gd[3] = {64, (cuuint64_t)S_, 7};
    cuuint64_t gs[2] = {(cuuint64_t)D_ * 2, 128};
    cuuint32_t bd[3] = {64, 64, 7};
    cuuint32_t es[3] = {1, 1, 1};
    enc(&tx, CU_TENSOR_MAP_DATA_TYPE_BFLOAT16, 3, const_cast<__nv_bfloat16*>(x), gd, gs, bd, es, CU_TENSOR_MAP_INTERLEAVE_NONE, CU_TENSOR_MAP_SWIZZLE_128B,
        CU_TENSOR_MAP_L2_PROMOTION_L2_128B, CU_TENSOR_MAP_FLOAT_OOB_FILL_NONE);
  }
  make_map(enc, &tg, w_gate, F_, D_, 64, 64, CU_TENSOR_MAP_SWIZZLE_128B);
  make_map(enc, &tu, w_up, F_, D_, 64, 64, CU_TENSOR_MAP_SWIZZLE_128B);
  make_map(enc, &tg32, w_gate, F_, D_, 32, 128, CU_TENSOR_MAP_SWIZZLE_64B);
  make_map(enc, &tu32, w_up, F_, D_, 32, 128, CU_TENSOR_MAP_SWIZZLE_64B);
  fused_kernel<<<128, NTHREADS, SMEM_BYTES>>>(tx, tg, tu, tg32, tu32, w_r, w_i, w_gate, w_up, w_down, gate_w, (__nv_bfloat16*)d_out);
}
```

```cpp
#include <cuda_runtime.h>
#include <cuda_bf16.h>
#include <cuda.h>
#include <stdint.h>

namespace {

constexpr int S_ = 2048, D_ = 448, F_ = 1792;
constexpr int NTHREADS = 512;
constexpr int SLOT = 16384, NSLOT = 7;
constexpr int HALF_XR = 57344;
constexpr int OFF_PQ = NSLOT * SLOT;
constexpr int OFF_R = OFF_PQ + HALF_XR;
constexpr int OFF_EXCH = OFF_PQ;
constexpr int OFF_WS = OFF_EXCH + 18432;
constexpr int OFF_TW = OFF_WS + 16384;
constexpr int OFF_MISC = OFF_R + HALF_XR;
constexpr int OFF_G = OFF_MISC;
constexpr int OFF_BAR = OFF_MISC + 512;
constexpr int SMEM_BYTES = OFF_BAR + 512;
constexpr int B_FULL = 0, B_EMPTY = 7, B_XFULL = 14  ;
constexpr int B_XFREE = 16  , B_PUBX = 18, B_RFREE = 19, B_LFREE = 20;
constexpr int B_PUBW = 21, B_PUBD = 22;
constexpr int B_PQFULL = 23, B_RECV = 24, B_WFULL = 25, B_XCFULL = 26, B_PREP = 27, B_PREPW = 28, B_RFULL = 29, B_GFULL = 30, B_END = 31, B_PIN = 31;

constexpr int WD_IMG = 896 * 112 * 2;
constexpr int G_IMG = 224 * 56 * 2;

__device__ __align__(1024) uint32_t g_Xc[112 * 2 * S_];
__device__ __align__(1024) unsigned char g_H[32 * 56 * 4096];
__device__ __align__(1024) unsigned char g_PQ[32 * HALF_XR];
__device__ __align__(1024) unsigned char g_Wd[8 * WD_IMG];
__device__ __align__(1024) unsigned char g_G[8 * G_IMG];
__device__ __align__(1024) uint2 g_Wt[113 * S_];
__device__ __align__(1024) float g_gate[S_];
__device__ __align__(128) unsigned int g_ep[128];
__device__ __align__(128) unsigned int g_cnt[8 * 32];

#define PROF(role, idx) do {} while (0)
#define PROFG(role, idx) do {} while (0)

__device__ __forceinline__ uint32_t s2u(const void* p) { return (uint32_t)__cvta_generic_to_shared(p); }
__device__ __forceinline__ void mbar_init(uint32_t b, int c) { asm volatile("mbarrier.init.shared::cta.b64 [%0], %1;" :: "r"(b), "r"(c) : "memory"); }
__device__ __forceinline__ void mbar_expect(uint32_t b, int bytes) { asm volatile("mbarrier.arrive.expect_tx.shared::cta.b64 _, [%0], %1;" :: "r"(b), "r"(bytes) : "memory"); }
__device__ __forceinline__ void mbar_arrive(uint32_t b) { asm volatile("mbarrier.arrive.shared::cta.b64 _, [%0];" :: "r"(b) : "memory"); }
__device__ __forceinline__ void mbar_wait(uint32_t b, int ph) {
  asm volatile("{\n.reg .pred p;\n.reg .u32 c;\nmov.u32 c, 0;\nL_WAIT:\nmbarrier.try_wait.parity.shared::cta.b64 p, [%0], %1;\n@p bra.uni L_DONE;\n"
               "add.u32 c, c, 1;\nsetp.lt.u32 p, c, 4194304;\n@p bra.uni L_WAIT;\ntrap;\nL_DONE:\n}" :: "r"(b), "r"(ph) : "memory");
}
__device__ __forceinline__ void mbar_wait_cluster(uint32_t b, int ph) {
  asm volatile("{\n.reg .pred p;\n.reg .u32 c;\nmov.u32 c, 0;\nL_WAIT:\nmbarrier.try_wait.parity.acquire.cluster.shared::cta.b64 p, [%0], %1;\n@p bra.uni L_DONE;\n"
               "add.u32 c, c, 1;\nsetp.lt.u32 p, c, 4194304;\n@p bra.uni L_WAIT;\ntrap;\nL_DONE:\n}" :: "r"(b), "r"(ph) : "memory");
}
__device__ __forceinline__ uint32_t ld_acquire(const unsigned int* p) { uint32_t v; asm volatile("ld.acquire.gpu.global.u32 %0, [%1];" : "=r"(v) : "l"(p) : "memory"); return v; }
__device__ __forceinline__ uint32_t ld_relaxed(const unsigned int* p) { uint32_t v; asm volatile("ld.relaxed.gpu.global.u32 %0, [%1];" : "=r"(v) : "l"(p) : "memory"); return v; }
__device__ __forceinline__ void wait_ge(const unsigned int* p, uint32_t target) {
#pragma unroll 1
  for (int i = 0; i < (1 << 22); i++) { if ((int)(ld_acquire(p) - target) >= 0) return; }
  __trap();
}
__device__ __forceinline__ void red_release(unsigned int* p) { asm volatile("red.release.gpu.global.add.u32 [%0], 1;" :: "l"(p) : "memory"); }
__device__ __forceinline__ void red_relaxed(unsigned int* p) { asm volatile("red.relaxed.gpu.global.add.u32 [%0], 1;" :: "l"(p) : "memory"); }
__device__ __forceinline__ bool elect() { uint32_t p; asm volatile("{\n.reg .pred p;\nelect.sync _|p, 0xffffffff;\nselp.u32 %0, 1, 0, p;\n}" : "=r"(p)); return p; }
__device__ __forceinline__ void fence_async_smem() { asm volatile("fence.proxy.async.shared::cta;" ::: "memory"); }
__device__ __forceinline__ void fence_async_global() { asm volatile("fence.proxy.async.global;" ::: "memory"); }
template <int ID, int N> __device__ __forceinline__ void bar_sync() { asm volatile("bar.sync %0, %1;" :: "n"(ID), "n"(N) : "memory"); }
template <int ID, int N> __device__ __forceinline__ void bar_arrive() { asm volatile("bar.arrive %0, %1;" :: "n"(ID), "n"(N) : "memory"); }
__device__ __forceinline__ void tma2d(uint32_t dst, const CUtensorMap* tm, int c0, int c1, uint32_t bar) {
  asm volatile("cp.async.bulk.tensor.2d.shared::cluster.global.mbarrier::complete_tx::bytes [%0], [%1, {%3, %4}], [%2];"
               :: "r"(dst), "l"(tm), "r"(bar), "r"(c0), "r"(c1) : "memory");
}
__device__ __forceinline__ void tma3d(uint32_t dst, const CUtensorMap* tm, int c0, int c1, int c2, uint32_t bar) {
  asm volatile("cp.async.bulk.tensor.3d.shared::cluster.global.mbarrier::complete_tx::bytes [%0], [%1, {%3, %4, %5}], [%2];"
               :: "r"(dst), "l"(tm), "r"(bar), "r"(c0), "r"(c1), "r"(c2) : "memory");
}
__device__ __forceinline__ void bulk_g2s(uint32_t dst, const void* src, int bytes, uint32_t bar) {
  asm volatile("cp.async.bulk.shared::cluster.global.mbarrier::complete_tx::bytes [%0], [%1], %2, [%3];"
               :: "r"(dst), "l"(src), "r"(bytes), "r"(bar) : "memory");
}
__device__ __forceinline__ void prefetch_l2(const void* src, int bytes) {
  asm volatile("cp.async.bulk.prefetch.L2.global [%0], %1;" :: "l"(src), "r"(bytes) : "memory");
}
__device__ __forceinline__ void prefetch_tma2d(const CUtensorMap* tm, int c0, int c1) {
  asm volatile("cp.async.bulk.prefetch.tensor.2d.L2.global [%0, {%1, %2}];" :: "l"(tm), "r"(c0), "r"(c1) : "memory");
}
__device__ __forceinline__ uint64_t mkdesc(uint32_t addr, uint32_t lbo, uint32_t sbo, uint32_t mode) {
  return (uint64_t)((addr & 0x3FFFF) >> 4) | ((uint64_t)(lbo >> 4) << 16) | ((uint64_t)(sbo >> 4) << 32) | ((uint64_t)mode << 62);
}
__device__ __forceinline__ void wg_fence() { asm volatile("wgmma.fence.sync.aligned;" ::: "memory"); }
__device__ __forceinline__ void wg_commit() { asm volatile("wgmma.commit_group.sync.aligned;" ::: "memory"); }
template <int N> __device__ __forceinline__ void wg_wait() { asm volatile("wgmma.wait_group.sync.aligned %0;" :: "n"(N) : "memory"); }
template <int N> __device__ __forceinline__ void keep(float (&d)[N]) {
#pragma unroll
  for (int i = 0; i < N; i++) asm volatile("" : "+f"(d[i]) :: "memory");
}
__device__ __forceinline__ uint32_t pack_bf16(float lo, float hi) { uint32_t r; asm("cvt.rn.bf16x2.f32 %0, %1, %2;" : "=r"(r) : "f"(hi), "f"(lo)); return r; }
__device__ __forceinline__ float bf16_round(float v) { return __bfloat162float(__float2bfloat16_rn(v)); }
__device__ __forceinline__ void sts128(uint32_t a, uint32_t x, uint32_t y, uint32_t z, uint32_t w) { asm volatile("st.shared.v4.b32 [%0], {%1,%2,%3,%4};" :: "r"(a), "r"(x), "r"(y), "r"(z), "r"(w) : "memory"); }
__device__ __forceinline__ float4 lds128f(uint32_t a) { float4 v; asm volatile("ld.shared.v4.f32 {%0,%1,%2,%3}, [%4];" : "=f"(v.x), "=f"(v.y), "=f"(v.z), "=f"(v.w) : "r"(a) : "memory"); return v; }

__device__ __forceinline__ uint2 lds64(uint32_t a) { uint2 v; asm volatile("ld.shared.v2.b32 {%0,%1}, [%2];" : "=r"(v.x), "=r"(v.y) : "r"(a) : "memory"); return v; }
__device__ __forceinline__ float bf_lo(uint32_t w) { return __uint_as_float(w << 16); }
__device__ __forceinline__ float bf_hi(uint32_t w) { return __uint_as_float(w & 0xffff0000u); }
__device__ __forceinline__ uint32_t opaque(uint32_t v) { asm volatile("" : "+r"(v)); return v; }
__device__ __forceinline__ uint4 ldg128(const void* p) { uint4 v; asm volatile("ld.global.nc.v4.b32 {%0,%1,%2,%3}, [%4];" : "=r"(v.x), "=r"(v.y), "=r"(v.z), "=r"(v.w) : "l"(p)); return v; }
__device__ __forceinline__ void stg128(void* p, uint32_t x, uint32_t y, uint32_t z, uint32_t w) { asm volatile("st.global.v4.b32 [%0], {%1,%2,%3,%4};" :: "l"(p), "r"(x), "r"(y), "r"(z), "r"(w) : "memory"); }
__device__ __forceinline__ void stg128_l2(void* p, uint32_t x, uint32_t y, uint32_t z, uint32_t w) { asm volatile("st.relaxed.gpu.global.v4.b32 [%0], {%1,%2,%3,%4};" :: "l"(p), "r"(x), "r"(y), "r"(z), "r"(w) : "memory"); }
__device__ __forceinline__ void ldg128_na(uint32_t (&v)[4], const void* p) { asm volatile("ld.global.L1::no_allocate.v4.b32 {%0,%1,%2,%3}, [%4];" : "=r"(v[0]), "=r"(v[1]), "=r"(v[2]), "=r"(v[3]) : "l"(p) : "memory"); }
__device__ __forceinline__ void ldg128_l2(uint32_t (&v)[4], const void* p) { asm volatile("ld.relaxed.gpu.global.v4.b32 {%0,%1,%2,%3}, [%4];" : "=r"(v[0]), "=r"(v[1]), "=r"(v[2]), "=r"(v[3]) : "l"(p) : "memory"); }
__device__ __forceinline__ uint4 lds128(uint32_t a) { uint4 v; asm volatile("ld.shared.v4.b32 {%0,%1,%2,%3}, [%4];" : "=r"(v.x), "=r"(v.y), "=r"(v.z), "=r"(v.w) : "r"(a) : "memory"); return v; }
__device__ __forceinline__ uint32_t lds16(uint32_t a) { uint32_t v; asm volatile("ld.shared.u16 %0, [%1];" : "=r"(v) : "r"(a) : "memory"); return v; }
__device__ __forceinline__ void sts64(uint32_t a, uint32_t x, uint32_t y) { asm volatile("st.shared.v2.b32 [%0], {%1,%2};" :: "r"(a), "r"(x), "r"(y) : "memory"); }
template <int TB> __device__ __forceinline__ void wgmma_rs_128(float (&d)[64], const uint32_t (&a)[4], uint64_t db, int sc) {
  asm volatile("{\n.reg .pred p;\nsetp.ne.b32 p, %69, 0;\n"
    "wgmma.mma_async.sync.aligned.m64n128k16.f32.bf16.bf16 {%0, %1, %2, %3, %4, %5, %6, %7, %8, %9, %10, %11, %12, %13, %14, %15, %16, %17, %18, %19, %20, %21, %22, %23, %24, %25, %26, %27, %28, %29, %30, %31, %32, %33, %34, %35, %36, %37, %38, %39, %40, %41, %42, %43, %44, %45, %46, %47, %48, %49, %50, %51, %52, %53, %54, %55, %56, %57, %58, %59, %60, %61, %62, %63}, {%64, %65, %66, %67}, %68, p, 1, 1, %70;\n}\n"
    : "+f"(d[0]), "+f"(d[1]), "+f"(d[2]), "+f"(d[3]), "+f"(d[4]), "+f"(d[5]), "+f"(d[6]), "+f"(d[7]), "+f"(d[8]), "+f"(d[9]), "+f"(d[10]), "+f"(d[11]), "+f"(d[12]), "+f"(d[13]), "+f"(d[14]), "+f"(d[15]), "+f"(d[16]), "+f"(d[17]), "+f"(d[18]), "+f"(d[19]), "+f"(d[20]), "+f"(d[21]), "+f"(d[22]), "+f"(d[23]), "+f"(d[24]), "+f"(d[25]), "+f"(d[26]), "+f"(d[27]), "+f"(d[28]), "+f"(d[29]), "+f"(d[30]), "+f"(d[31]), "+f"(d[32]), "+f"(d[33]), "+f"(d[34]), "+f"(d[35]), "+f"(d[36]), "+f"(d[37]), "+f"(d[38]), "+f"(d[39]), "+f"(d[40]), "+f"(d[41]), "+f"(d[42]), "+f"(d[43]), "+f"(d[44]), "+f"(d[45]), "+f"(d[46]), "+f"(d[47]), "+f"(d[48]), "+f"(d[49]), "+f"(d[50]), "+f"(d[51]), "+f"(d[52]), "+f"(d[53]), "+f"(d[54]), "+f"(d[55]), "+f"(d[56]), "+f"(d[57]), "+f"(d[58]), "+f"(d[59]), "+f"(d[60]), "+f"(d[61]), "+f"(d[62]), "+f"(d[63])
    : "r"(a[0]), "r"(a[1]), "r"(a[2]), "r"(a[3]), "l"(db), "r"(sc), "n"(TB));
}
template <int TB> __device__ __forceinline__ void wgmma_rs_64(float (&d)[32], const uint32_t (&a)[4], uint64_t db, int sc) {
  asm volatile("{\n.reg .pred p;\nsetp.ne.b32 p, %37, 0;\n"
    "wgmma.mma_async.sync.aligned.m64n64k16.f32.bf16.bf16 {%0, %1, %2, %3, %4, %5, %6, %7, %8, %9, %10, %11, %12, %13, %14, %15, %16, %17, %18, %19, %20, %21, %22, %23, %24, %25, %26, %27, %28, %29, %30, %31}, {%32, %33, %34, %35}, %36, p, 1, 1, %38;\n}\n"
    : "+f"(d[0]), "+f"(d[1]), "+f"(d[2]), "+f"(d[3]), "+f"(d[4]), "+f"(d[5]), "+f"(d[6]), "+f"(d[7]), "+f"(d[8]), "+f"(d[9]), "+f"(d[10]), "+f"(d[11]), "+f"(d[12]), "+f"(d[13]), "+f"(d[14]), "+f"(d[15]), "+f"(d[16]), "+f"(d[17]), "+f"(d[18]), "+f"(d[19]), "+f"(d[20]), "+f"(d[21]), "+f"(d[22]), "+f"(d[23]), "+f"(d[24]), "+f"(d[25]), "+f"(d[26]), "+f"(d[27]), "+f"(d[28]), "+f"(d[29]), "+f"(d[30]), "+f"(d[31])
    : "r"(a[0]), "r"(a[1]), "r"(a[2]), "r"(a[3]), "l"(db), "r"(sc), "n"(TB));
}
template <int TB> __device__ __forceinline__ void wgmma_rs_56(float (&d)[28], const uint32_t (&a)[4], uint64_t db, int sc) {
  asm volatile("{\n.reg .pred p;\nsetp.ne.b32 p, %33, 0;\n"
    "wgmma.mma_async.sync.aligned.m64n56k16.f32.bf16.bf16 {%0, %1, %2, %3, %4, %5, %6, %7, %8, %9, %10, %11, %12, %13, %14, %15, %16, %17, %18, %19, %20, %21, %22, %23, %24, %25, %26, %27}, {%28, %29, %30, %31}, %32, p, 1, 1, %34;\n}\n"
    : "+f"(d[0]), "+f"(d[1]), "+f"(d[2]), "+f"(d[3]), "+f"(d[4]), "+f"(d[5]), "+f"(d[6]), "+f"(d[7]), "+f"(d[8]), "+f"(d[9]), "+f"(d[10]), "+f"(d[11]), "+f"(d[12]), "+f"(d[13]), "+f"(d[14]), "+f"(d[15]), "+f"(d[16]), "+f"(d[17]), "+f"(d[18]), "+f"(d[19]), "+f"(d[20]), "+f"(d[21]), "+f"(d[22]), "+f"(d[23]), "+f"(d[24]), "+f"(d[25]), "+f"(d[26]), "+f"(d[27])
    : "r"(a[0]), "r"(a[1]), "r"(a[2]), "r"(a[3]), "l"(db), "r"(sc), "n"(TB));
}
template <int TB> __device__ __forceinline__ void wgmma_rs_112(float (&d)[56], const uint32_t (&a)[4], uint64_t db, int sc) {
  asm volatile("{\n.reg .pred p;\nsetp.ne.b32 p, %61, 0;\n"
    "wgmma.mma_async.sync.aligned.m64n112k16.f32.bf16.bf16 {%0, %1, %2, %3, %4, %5, %6, %7, %8, %9, %10, %11, %12, %13, %14, %15, %16, %17, %18, %19, %20, %21, %22, %23, %24, %25, %26, %27, %28, %29, %30, %31, %32, %33, %34, %35, %36, %37, %38, %39, %40, %41, %42, %43, %44, %45, %46, %47, %48, %49, %50, %51, %52, %53, %54, %55}, {%56, %57, %58, %59}, %60, p, 1, 1, %62;\n}\n"
    : "+f"(d[0]), "+f"(d[1]), "+f"(d[2]), "+f"(d[3]), "+f"(d[4]), "+f"(d[5]), "+f"(d[6]), "+f"(d[7]), "+f"(d[8]), "+f"(d[9]), "+f"(d[10]), "+f"(d[11]), "+f"(d[12]), "+f"(d[13]), "+f"(d[14]), "+f"(d[15]), "+f"(d[16]), "+f"(d[17]), "+f"(d[18]), "+f"(d[19]), "+f"(d[20]), "+f"(d[21]), "+f"(d[22]), "+f"(d[23]), "+f"(d[24]), "+f"(d[25]), "+f"(d[26]), "+f"(d[27]), "+f"(d[28]), "+f"(d[29]), "+f"(d[30]), "+f"(d[31]), "+f"(d[32]), "+f"(d[33]), "+f"(d[34]), "+f"(d[35]), "+f"(d[36]), "+f"(d[37]), "+f"(d[38]), "+f"(d[39]), "+f"(d[40]), "+f"(d[41]), "+f"(d[42]), "+f"(d[43]), "+f"(d[44]), "+f"(d[45]), "+f"(d[46]), "+f"(d[47]), "+f"(d[48]), "+f"(d[49]), "+f"(d[50]), "+f"(d[51]), "+f"(d[52]), "+f"(d[53]), "+f"(d[54]), "+f"(d[55])
    : "r"(a[0]), "r"(a[1]), "r"(a[2]), "r"(a[3]), "l"(db), "r"(sc), "n"(TB));
}
template <int TA, int TB> __device__ __forceinline__ void wgmma_ss_56(float (&d)[28], uint64_t da, uint64_t db, int sc) {
  asm volatile("{\n.reg .pred p;\nsetp.ne.b32 p, %30, 0;\n"
    "wgmma.mma_async.sync.aligned.m64n56k16.f32.bf16.bf16 {%0, %1, %2, %3, %4, %5, %6, %7, %8, %9, %10, %11, %12, %13, %14, %15, %16, %17, %18, %19, %20, %21, %22, %23, %24, %25, %26, %27}, %28, %29, p, 1, 1, %31, %32;\n}\n"
    : "+f"(d[0]), "+f"(d[1]), "+f"(d[2]), "+f"(d[3]), "+f"(d[4]), "+f"(d[5]), "+f"(d[6]), "+f"(d[7]), "+f"(d[8]), "+f"(d[9]), "+f"(d[10]), "+f"(d[11]), "+f"(d[12]), "+f"(d[13]), "+f"(d[14]), "+f"(d[15]), "+f"(d[16]), "+f"(d[17]), "+f"(d[18]), "+f"(d[19]), "+f"(d[20]), "+f"(d[21]), "+f"(d[22]), "+f"(d[23]), "+f"(d[24]), "+f"(d[25]), "+f"(d[26]), "+f"(d[27])
    : "l"(da), "l"(db), "r"(sc), "n"(TA), "n"(TB));
}

__device__ __forceinline__ uint32_t cis(float a) { return pack_bf16(__cosf(a), __sinf(a)); }

typedef __nv_bfloat162 b2;
struct c2 { b2 x, y; };
__device__ __forceinline__ b2 as_b2(uint32_t u) { return *reinterpret_cast<b2*>(&u); }
__device__ __forceinline__ uint32_t as_u(b2 v) { return *reinterpret_cast<uint32_t*>(&v); }
__device__ __forceinline__ c2 mk(b2 x, b2 y) { c2 r; r.x = x; r.y = y; return r; }
__device__ __forceinline__ c2 cmul(c2 a, b2 wr, b2 wi) { return mk(__hfma2(a.x, wr, __hneg2(__hmul2(a.y, wi))), __hfma2(a.x, wi, __hmul2(a.y, wr))); }
__device__ __forceinline__ void fft4(c2& a0, c2& a1, c2& a2, c2& a3) {
  c2 t0 = mk(__hadd2(a0.x, a2.x), __hadd2(a0.y, a2.y)), t1 = mk(__hsub2(a0.x, a2.x), __hsub2(a0.y, a2.y));
  c2 t2 = mk(__hadd2(a1.x, a3.x), __hadd2(a1.y, a3.y)), t3 = mk(__hsub2(a1.x, a3.x), __hsub2(a1.y, a3.y));
  a0 = mk(__hadd2(t0.x, t2.x), __hadd2(t0.y, t2.y)); a2 = mk(__hsub2(t0.x, t2.x), __hsub2(t0.y, t2.y));
  a1 = mk(__hadd2(t1.x, t3.y), __hsub2(t1.y, t3.x)); a3 = mk(__hsub2(t1.x, t3.y), __hadd2(t1.y, t3.x));
}
__device__ __forceinline__ void fft4_s2(c2& a0, c2& a1, c2& a2, c2& a3, b2 r) {
  const b2 nr = __hneg2(r);
  c2 t0 = mk(__hfma2(a2.x, r, a0.x), __hfma2(a2.y, r, a0.y)), t1 = mk(__hfma2(a2.x, nr, a0.x), __hfma2(a2.y, nr, a0.y));
  c2 t2 = mk(__hadd2(a1.x, a3.x), __hadd2(a1.y, a3.y)), t3 = mk(__hsub2(a1.x, a3.x), __hsub2(a1.y, a3.y));
  a0 = mk(__hadd2(t0.x, t2.x), __hadd2(t0.y, t2.y)); a2 = mk(__hsub2(t0.x, t2.x), __hsub2(t0.y, t2.y));
  a1 = mk(__hadd2(t1.x, t3.y), __hsub2(t1.y, t3.x)); a3 = mk(__hsub2(t1.x, t3.y), __hadd2(t1.y, t3.x));
}
__device__ __forceinline__ void fft4_s13(c2& a0, c2& a1, c2& a2, c2& a3, b2 r) {
  const b2 nr = __hneg2(r);
  c2 t0 = mk(__hadd2(a0.x, a2.x), __hadd2(a0.y, a2.y)), t1 = mk(__hsub2(a0.x, a2.x), __hsub2(a0.y, a2.y));
  c2 t2 = mk(__hadd2(a1.x, a3.x), __hadd2(a1.y, a3.y)), t3 = mk(__hsub2(a1.x, a3.x), __hsub2(a1.y, a3.y));
  a0 = mk(__hfma2(t2.x, r, t0.x), __hfma2(t2.y, r, t0.y)); a2 = mk(__hfma2(t2.x, nr, t0.x), __hfma2(t2.y, nr, t0.y));
  a1 = mk(__hfma2(t3.y, r, t1.x), __hfma2(t3.x, nr, t1.y)); a3 = mk(__hfma2(t3.y, nr, t1.x), __hfma2(t3.x, r, t1.y));
}
__device__ __forceinline__ c2 rot1(c2 a) { return mk(__hadd2(a.x, a.y), __hsub2(a.y, a.x)); }
__device__ __forceinline__ c2 rot3(c2 a) { return mk(__hsub2(a.y, a.x), __hneg2(__hadd2(a.x, a.y))); }
__device__ __forceinline__ c2 mul_mi(c2 a) { return mk(a.y, __hneg2(a.x)); }
template <int O> __device__ __forceinline__ void fft8(c2 (&v)[16]) {
  const b2 r = as_b2(0x3F353F35u), nr = as_b2(0xBF35BF35u);
  fft4(v[O], v[O + 4], v[O + 8], v[O + 12]);
  fft4(v[O + 2], v[O + 6], v[O + 10], v[O + 14]);
  const c2 o0 = v[O + 2], o1 = rot1(v[O + 6]), o2 = v[O + 10], o3 = rot1(v[O + 14]);
  const c2 e0 = v[O], e1 = v[O + 4], e2 = v[O + 8], e3 = v[O + 12];
  v[O] = mk(__hadd2(e0.x, o0.x), __hadd2(e0.y, o0.y));              v[O + 8] = mk(__hsub2(e0.x, o0.x), __hsub2(e0.y, o0.y));
  v[O + 2] = mk(__hfma2(o1.x, r, e1.x), __hfma2(o1.y, r, e1.y));    v[O + 10] = mk(__hfma2(o1.x, nr, e1.x), __hfma2(o1.y, nr, e1.y));
  v[O + 4] = mk(__hadd2(e2.x, o2.y), __hsub2(e2.y, o2.x));          v[O + 12] = mk(__hsub2(e2.x, o2.y), __hadd2(e2.y, o2.x));
  v[O + 6] = mk(__hfma2(o3.y, r, e3.x), __hfma2(o3.x, nr, e3.y));   v[O + 14] = mk(__hfma2(o3.y, nr, e3.x), __hfma2(o3.x, r, e3.y));
}
__device__ __forceinline__ void fft16(c2 (&v)[16]) {
  const b2 r = as_b2(0x3F353F35u), c1 = as_b2(0x3F6D3F6Du), s1 = as_b2(0x3EC43EC4u), nc1 = as_b2(0xBF6DBF6Du), ns1 = as_b2(0xBEC4BEC4u);
#pragma unroll
  for (int a = 0; a < 4; a++) fft4(v[a], v[a + 4], v[a + 8], v[a + 12]);
  v[5] = cmul(v[5], c1, ns1); v[6] = rot1(v[6]); v[7] = cmul(v[7], s1, nc1);
  v[9] = rot1(v[9]); v[10] = mul_mi(v[10]); v[11] = rot3(v[11]);
  v[13] = cmul(v[13], s1, nc1); v[14] = rot3(v[14]); v[15] = cmul(v[15], nc1, s1);
  fft4(v[0], v[1], v[2], v[3]); fft4_s2(v[4], v[5], v[6], v[7], r); fft4_s13(v[8], v[9], v[10], v[11], r); fft4_s2(v[12], v[13], v[14], v[15], r);
  c2 t;
  t = v[1]; v[1] = v[4]; v[4] = t;  t = v[2]; v[2] = v[8]; v[8] = t;  t = v[3]; v[3] = v[12]; v[12] = t;
  t = v[6]; v[6] = v[9]; v[9] = t;  t = v[7]; v[7] = v[13]; v[13] = t; t = v[11]; v[11] = v[14]; v[14] = t;
}

__device__ __forceinline__ void columns(c2 (&v)[16], uint32_t sb, int t) {
  const int l16 = t & 15;
  const uint32_t row = sb + OFF_EXCH + (t >> 4) * 2304;
  const uint32_t pos = sb + OFF_EXCH + (t >> 3) * 144 + (t & 7) * 16;
#pragma unroll 1
  for (int ps = 0; ps < 6; ps++) {
    if (ps == 0 || ps == 5) { fft8<0>(v); fft8<1>(v); } else fft16(v);
    if (ps == 5) break;
    if (ps == 2) {
      const uint32_t ws = sb + OFF_WS + (l16 >> 1) * 128 + ((((t >> 4) + (l16 >> 1)) & 7) * 2 + (l16 & 1)) * 8;
      mbar_wait(sb + OFF_BAR + B_WFULL * 8, 0);
#pragma unroll
      for (int q = 0; q < 16; q++) {
        const uint2 w = lds64(ws + q * 1024);
        const c2 z = cmul(v[q], as_b2(w.x), as_b2(w.y));
        v[q] = mk(z.y, z.x);
      }
      continue;
    }
    {
      const bool full = ps == 0 || ps == 4;
      const uint32_t tw = sb + OFF_TW + (full ? ps * 2048 + t * 16 : 16384 + l16 * 16);
      const uint32_t st = full ? 2048 : 256;
#pragma unroll
      for (int i = 0; i < 4; i++) {
        const uint4 w4 = lds128(tw + i * st);
        const uint32_t w[4] = {w4.x, w4.y, w4.z, w4.w};
#pragma unroll
        for (int e = 0; e < 4; e++) v[4 * i + e] = cmul(v[4 * i + e], __low2bfloat162(as_b2(w[e])), __high2bfloat162(as_b2(w[e])));
      }
    }
    if (ps == 0) {
      bar_sync<3, 128>();
#pragma unroll
      for (int q = 0; q < 8; q++) sts128(pos + q * 2304, as_u(v[2 * q].x), as_u(v[2 * q].y), as_u(v[2 * q + 1].x), as_u(v[2 * q + 1].y));
      bar_sync<3, 128>();
#pragma unroll
      for (int q = 0; q < 16; q++) { const uint2 a = lds64(row + q * 144 + l16 * 8); v[q] = mk(as_b2(a.x), as_b2(a.y)); }
    } else {
      __syncwarp();
#pragma unroll
      for (int q = 0; q < 16; q++) sts64(row + q * 144 + l16 * 8, as_u(v[q].x), as_u(v[q].y));
      if (ps == 4) bar_sync<3, 128>(); else __syncwarp();
      const uint32_t src = ps == 4 ? pos : row + l16 * 144, st = ps == 4 ? 2304 : 16;
#pragma unroll
      for (int q = 0; q < 8; q++) { const uint4 a = lds128(src + q * st); v[2 * q] = mk(as_b2(a.x), as_b2(a.y)); v[2 * q + 1] = mk(as_b2(a.z), as_b2(a.w)); }
    }
  }
}

template <int NH> __device__ __forceinline__ void h_epilogue(float (&acc)[NH * 8], unsigned char* gdst, uint32_t tag) {
#pragma unroll
  for (int c = 0; c < NH / 2; c++) {
    uint32_t pk[4];
#pragma unroll
    for (int i = 0; i < 4; i++) {
      float hv[2];
#pragma unroll
      for (int e = 0; e < 2; e++) {
        float hg = 0.5f * acc[c * 8 + i * 2 + e], up = acc[NH * 4 + c * 8 + i * 2 + e];
        float th; asm("tanh.approx.f32 %0, %1;" : "=f"(th) : "f"(hg));
        hv[e] = fmaf(hg, th, hg) * up;
      }
      pk[i] = pack_bf16(hv[0], hv[1]);
    }
    stg128_l2(gdst + c * 4096, (pk[0] & ~1u) | tag, pk[1], pk[2], pk[3]);
  }
}

__device__ __forceinline__ void frag_ready(uint32_t (&a)[4], uint32_t (&b)[4], uint32_t (&c)[4], uint32_t (&d)[4], const unsigned char* p, uint32_t tag) {
  asm volatile("{\n.reg .pred p;\n.reg .u32 c, m, q;\nmov.u32 c, 0;\nL_TRY:\n"
               "lop3.b32 m, %0, %4, %17, 0x7E;\nlop3.b32 q, %8, %12, %17, 0x7E;\nlop3.b32 m, m, q, 1, 0xA8;\nsetp.ne.u32 p, m, 0;\n"
               "vote.sync.any.pred p, p, 0xffffffff;\n@!p bra.uni L_OK;\n"
               "ld.relaxed.gpu.global.v4.b32 {%0,%1,%2,%3}, [%16];\nld.relaxed.gpu.global.v4.b32 {%4,%5,%6,%7}, [%16+4096];\n"
               "ld.relaxed.gpu.global.v4.b32 {%8,%9,%10,%11}, [%16+8192];\nld.relaxed.gpu.global.v4.b32 {%12,%13,%14,%15}, [%16+12288];\n"
               "add.u32 c, c, 1;\nsetp.lt.u32 p, c, 262144;\n@p bra.uni L_TRY;\ntrap;\nL_OK:\n}"
               : "+r"(a[0]), "+r"(a[1]), "+r"(a[2]), "+r"(a[3]), "+r"(b[0]), "+r"(b[1]), "+r"(b[2]), "+r"(b[3]),
                 "+r"(c[0]), "+r"(c[1]), "+r"(c[2]), "+r"(c[3]), "+r"(d[0]), "+r"(d[1]), "+r"(d[2]), "+r"(d[3])
               : "l"(p), "r"(tag) : "memory");
}

#define LDH ldg128_na
#define MAP 0
#define WPOS 1
#define LA2 5
#define LEAD1 3

__global__ void __cluster_dims__(2, 1, 1) __launch_bounds__(NTHREADS, 1)
fused_kernel(const __grid_constant__ CUtensorMap tm_x, const __grid_constant__ CUtensorMap tm_g, const __grid_constant__ CUtensorMap tm_u,
             const __grid_constant__ CUtensorMap tm_g32, const __grid_constant__ CUtensorMap tm_u32,
             const __nv_bfloat16* __restrict__ w_r, const __nv_bfloat16* __restrict__ w_i,
             const __nv_bfloat16* __restrict__ w_gate, const __nv_bfloat16* __restrict__ w_up,
             const __nv_bfloat16* __restrict__ w_down, const __nv_bfloat16* __restrict__ gate_w, __nv_bfloat16* __restrict__ out) {
  extern __shared__ __align__(1024) unsigned char smem[];
  const uint32_t sb = s2u(smem);
  const uint32_t bars = sb + OFF_BAR;
  const int tid = threadIdx.x, warp = __shfl_sync(0xffffffffu, tid >> 5, 0), lane = tid & 31;
  const int cl = blockIdx.x >> 1, kh = blockIdx.x & 1;
  const int n0 = cl < 4 ? cl : (cl < 36 ? (cl - 4) >> 3 : (cl - 36) / 7);
  const int m0 = cl < 4 ? 15 : (cl < 36 ? (cl - 4) & 7 : cl - 28 - 7 * n0);
  const int n = MAP == 0 ? n0 : (MAP == 1 ? (m0 & 3) : ((n0 & 1) | ((m0 & 1) << 1)));
  const int m = MAP == 0 ? m0 : (MAP == 1 ? ((m0 & 12) | n0) : ((m0 & 14) | (n0 >> 1)));
  const int j = kh * 4 + n, bid = m * 8 + n * 2 + kh;

  if (warp >= 12) {
    asm volatile("setmaxnreg.dec.sync.aligned.u32 24;");
    const int c64 = 224 * j + (j & 1) * 32;
    const uint32_t epoch = ld_relaxed(&g_ep[bid]);
    if (warp == 12) {
      if (lane < 10) mbar_init(bars + (lane < NSLOT ? B_FULL + lane : (lane < 9 ? B_XFULL - 7 + lane : B_PIN)) * 8, 1);
    } else if (warp == 14) {
      if (lane < NSLOT) mbar_init(bars + (B_EMPTY + lane) * 8, 8);
      const int i = B_XFREE + lane;
      if (i < B_END) mbar_init(bars + i * 8, i >= B_PQFULL ? 1 : ((i == B_XFREE || i >= B_PUBW) ? 4 : 8));
      asm volatile("fence.mbarrier_init.release.cluster;" ::: "memory");
      __syncwarp();
      if (lane == 0) mbar_expect(bars + B_RECV * 8, 64 * 112 * 4);
    } else if (warp == 13) {
      if (lane == 0) { PROFG(4, 0); PROF(4, 1); }
      if (lane < 14) prefetch_tma2d((lane & 1) ? &tm_u : &tm_g, c64, (lane >> 1) * 64);
    } else if (lane < 2) {
      prefetch_l2(reinterpret_cast<const unsigned char*>(lane ? w_i : w_r) + bid * 7200, 7200);
    }
    fence_async_smem();
    bar_arrive<0, NTHREADS>();
    if (warp == 12) {
#pragma unroll 1
      for (int i = 0; i < 5; i++) {
        if (elect()) {
          if (i < 2) {
            mbar_expect(bars + (B_XFULL + i) * 8, HALF_XR);
            tma3d(sb + OFF_PQ + i * HALF_XR, &tm_x, 0, m * 128 + (i ^ kh ^ 1) * 64, 0, bars + (B_XFULL + i) * 8);
          }
          if (i == WPOS) {
            mbar_expect(bars + B_PIN * 8, 14400);
            bulk_g2s(sb + 5 * SLOT, reinterpret_cast<const unsigned char*>(w_r) + bid * 7200, 7200, bars + B_PIN * 8);
            bulk_g2s(sb + 5 * SLOT + 7200, reinterpret_cast<const unsigned char*>(w_i) + bid * 7200, 7200, bars + B_PIN * 8);
          }
          const uint32_t fb = bars + (B_FULL + i) * 8;
          mbar_expect(fb, SLOT);
          tma2d(sb + i * SLOT, &tm_g, c64, i * 64, fb);
          tma2d(sb + i * SLOT + 8192, &tm_u, c64, i * 64, fb);
          PROF(3, 4 + i);
        }
      }
    }
    bar_sync<1, 128>();
    asm volatile("barrier.cluster.arrive.relaxed.aligned;" ::: "memory");
    if (warp == 12) {
      int slot = 5, ph = 1;
      auto wait_slot = [&]() { mbar_wait(bars + (B_EMPTY + slot) * 8, ph ^ (slot >= 5)); };
      auto adv = [&]() { if (++slot == NSLOT) { slot = 0; ph ^= 1; } };
      const int c32 = 224 * j + ((j & 1) ? 0 : 192);
#pragma unroll 1
      for (int i = 5; i < 25; i++) {
        wait_slot();
        if (elect()) {
          const uint32_t dst = sb + slot * SLOT, fb = bars + (B_FULL + slot) * 8;
          const bool last = i >= 21;
          const int cc = last ? c32 : c64 + 64 * (i / 7), rr = last ? slot * 128 : slot * 64;
          mbar_expect(fb, SLOT);
          tma2d(dst, last ? &tm_g32 : &tm_g, cc, rr, fb);
          tma2d(dst + 8192, last ? &tm_u32 : &tm_u, cc, rr, fb);
        }
        adv();
      }
      if (lane == 0) PROF(3, 0);
      mbar_wait(bars + B_PREP * 8, 0);
      if (lane == 0) PROF(3, 1);
#pragma unroll 1
      for (int i = 4; i < 16; i++) {
        if (lane == 0) PROF(3, 16 + i);
        wait_slot();
        if (elect()) {
          const int bytes = i < 14 ? 14336 : G_IMG / 2;
          const unsigned char* src = i < 14 ? g_Wd + (size_t)j * WD_IMG + i * 14336 : g_G + (size_t)(n * 4 + i - 12) * (G_IMG / 2);
          mbar_expect(bars + (B_FULL + slot) * 8, bytes);
          bulk_g2s(sb + slot * SLOT, src, bytes, bars + (B_FULL + slot) * 8);
        }
        adv();
      }
      if (lane == 0) PROF(3, 2);
    } else if (warp == 13) {
      mbar_wait(bars + B_PUBW * 8, 0);
      if (lane == 0) PROF(4, 7);
      mbar_wait(bars + B_PUBX * 8, 0);
      if (lane == 0) {
        PROF(4, 8);
        red_release(&g_cnt[(j >> 1) * 32]);
        red_relaxed(&g_cnt[6 * 32]);
        PROF(4, 18);
      }
      __syncwarp();
      mbar_wait(bars + B_PUBD * 8, 0);
      if (lane == 0) { PROF(4, 9); red_release(&g_cnt[4 * 32]); PROF(4, 19); }
      __syncwarp();
      mbar_wait(bars + B_LFREE * 8, 0);
      if (elect()) {
        mbar_expect(bars + B_GFULL * 8, G_IMG);
        bulk_g2s(sb + OFF_R + 28672, g_G + (size_t)(n * 2) * G_IMG, G_IMG, bars + B_GFULL * 8);
      }
    } else if (warp == 14) {
#pragma unroll 1
      for (int u = 0; u < 2; u++) {
        wait_ge(&g_cnt[(6 - 2 * u) * 32], (epoch + 1) * 128);
        fence_async_global();
        if (lane == 0) { mbar_arrive(bars + (B_PREPW - u) * 8); PROF(5, 9 - u); }
      }
    } else {
      mbar_wait(bars + B_XFREE * 8, 0);
      if (elect()) {
        prefetch_l2(reinterpret_cast<const unsigned char*>(w_gate) + bid * 12544, 12544);
        prefetch_l2(reinterpret_cast<const unsigned char*>(w_up) + bid * 12544, 12544);
      }
      mbar_wait(bars + (B_XFREE + 1) * 8, 0);
      if (elect()) {
        mbar_expect(bars + B_RFULL * 8, 12544);
        bulk_g2s(sb + OFF_R, reinterpret_cast<const unsigned char*>(w_down) + bid * 12544, 12544, bars + B_RFULL * 8);
      }
      if (bid < 113) {
        const int sl = (bid == 112) ? 0 : bid;
        wait_ge(&g_cnt[((sl & 1) + 2 * ((sl >> 1) / 28)) * 32], (epoch + 1) * 32);
        fence_async_global();
        if (elect()) {
          PROF(5, 16);
          mbar_expect(bars + B_XCFULL * 8, 16384);
          bulk_g2s(sb + OFF_EXCH, g_Xc + sl * 2 * S_, 16384, bars + B_XCFULL * 8);
        }
        mbar_wait(bars + B_PREPW * 8, 0);
        if (elect()) {
          mbar_expect(bars + B_WFULL * 8, 16384);
          bulk_g2s(sb + OFF_WS, g_Wt + bid * S_, 16384, bars + B_WFULL * 8);
          PROF(5, 17);
        }
      }
      mbar_wait(bars + B_PREP * 8, 0);
      if (elect()) {
        mbar_expect(bars + B_RFULL * 8, HALF_XR);
        bulk_g2s(sb + OFF_R, g_Wd + (size_t)j * WD_IMG, HALF_XR, bars + B_RFULL * 8);
        PROF(5, 19);
      }
      wait_ge(&g_cnt[5 * 32], (epoch + 1) * 128);
      fence_async_global();
      if (elect()) {
        PROF(5, 18);
        mbar_expect(bars + B_PQFULL * 8, HALF_XR + 256);
        const unsigned char* src = g_PQ + (size_t)(m * 2 + kh) * HALF_XR;
        bulk_g2s(sb + OFF_PQ, src, 28672, bars + B_PQFULL * 8);
        bulk_g2s(sb + OFF_PQ + 28672, src + 28672, 28672, bars + B_PQFULL * 8);
        bulk_g2s(sb + OFF_G, g_gate + m * 128 + kh * 64, 256, bars + B_PQFULL * 8);
      }
    }
    __syncwarp();
    asm volatile("barrier.cluster.wait.aligned;" ::: "memory");
  } else if (warp < 8) {
    asm volatile("setmaxnreg.inc.sync.aligned.u32 208;");
    const int wg = warp >> 2, w4 = warp & 3, g = lane >> 2, t = lane & 3;
    const int rh = wg ^ kh ^ 1;
    const int p = j & 1, r = (j >> 1) & 1, hh = j >> 2;
    const uint32_t epoch = ld_relaxed(&g_ep[bid]);
    if ((tid & 127) == 0) PROF(wg, 30);
#pragma unroll 1
    for (int it = tid; it < 392; it += 256) {
      const int kc = it / 28, sg = it - kc * 28;
      const int k = 2 * (28 * hh + sg) + r;
      const float kf = (float)k * (-6.283185307179586f / 448.0f), a0 = (float)(16 * kc + p) * kf;
      uint32_t c[4], s[4];
#pragma unroll
      for (int q = 0; q < 4; q++) {
        const float a1 = fmaf((float)(2 * q), kf, a0), a2 = fmaf((float)(2 * q + 8), kf, a0);
        c[q] = pack_bf16(__cosf(a1), __cosf(a2)); s[q] = pack_bf16(__sinf(a1), __sinf(a2));
        if (k == 0) s[q] = ((q ^ p) & 1) ? 0xBF80BF80u : 0x3F803F80u;
      }
      const uint32_t a = sb + 6 * SLOT + (kc * 56 + 2 * sg) * 16;
      sts128(a, c[0], c[1], c[2], c[3]);
      sts128(a + 16, s[0], s[1], s[2], s[3]);
    }
    if ((tid & 127) == 0) PROF(wg, 31);
    fence_async_smem();
    bar_sync<0, NTHREADS>();
    asm volatile("barrier.cluster.arrive.relaxed.aligned;" ::: "memory");
    if ((tid & 127) == 0) PROF(wg, 1);

    uint32_t xa[28][4];
    {
      const uint32_t xb = sb + OFF_PQ + wg * HALF_XR + (w4 * 16 + (lane & 15)) * 128;
      mbar_wait(bars + (B_XFULL + wg) * 8, 0);
      if ((tid & 127) == 0) PROF(wg, 2);
#pragma unroll
      for (int kb = 0; kb < 7; kb++) {
#pragma unroll
        for (int kk = 0; kk < 4; kk++) {
          uint32_t a = xb + kb * 8192 + (((2 * kk + (lane >> 4)) ^ (lane & 7)) << 4);
          asm volatile("ldmatrix.sync.aligned.m8n8.x4.shared.b16 {%0,%1,%2,%3}, [%4];"
                       : "=r"(xa[kb * 4 + kk][0]), "=r"(xa[kb * 4 + kk][1]), "=r"(xa[kb * 4 + kk][2]), "=r"(xa[kb * 4 + kk][3]) : "r"(a) : "memory");
        }
      }
    }
    {
      uint32_t ad[7][4];
      const uint32_t sel = p ? 0x7632 : 0x5410;
      const uint32_t sgn = r ? 0xBF80BF80u : 0x3F803F80u;
#pragma unroll
      for (int jj = 0; jj < 7; jj++) {
#pragma unroll
        for (int i = 0; i < 4; i++) {
          int ks = 2 * jj + (i >> 1), rr = i & 1;
          uint32_t lo = __byte_perm(xa[ks][rr], xa[ks][rr + 2], sel);
          uint32_t hi = __byte_perm(xa[ks + 14][rr], xa[ks + 14][rr + 2], sel);
          asm("fma.rn.bf16x2 %0, %1, %2, %3;" : "=r"(ad[jj][i]) : "r"(hi), "r"(sgn), "r"(lo));
        }
      }
      __syncwarp();
      if (lane == 0) mbar_arrive(bars + (B_XFREE + wg) * 8);
      float acc[28];
      wg_fence();
      uint64_t db = mkdesc(sb + 6 * SLOT, 896, 128, 0);
#pragma unroll
      for (int jj = 0; jj < 7; jj++) wgmma_rs_56<0>(acc, ad[jj], db + jj * 112, jj != 0);
      wg_commit();
      wg_wait<0>(); keep(acc);
      if (lane == 0) mbar_arrive(bars + (B_EMPTY + 6) * 8);
      uint32_t* xc = g_Xc + (size_t)((2 * (28 * hh + t) + r) * 2 + p) * S_ + m * 128 + rh * 64 + w4 * 16 + g;
#pragma unroll
      for (int i = 0; i < 7; i++) {
        xc[i * 16 * S_] = pack_bf16(acc[4 * i], acc[4 * i + 1]);
        xc[i * 16 * S_ + 8] = pack_bf16(acc[4 * i + 2], acc[4 * i + 3]);
      }
      __syncwarp();
      if (lane == 0) mbar_arrive(bars + B_PUBX * 8);
    }
    if ((tid & 127) == 0) PROF(wg, 3);
    const uint32_t tag = ~epoch & 1;
    unsigned char* const hbase = g_H + (size_t)(m * 2 + kh) * (56 * 4096) + rh * 2048 + (tid & 127) * 16;
#pragma unroll 1
    for (int u = 0; u < 3; u++) {
      float acc[64];
      if (wg == 1) { if (u & 1) bar_sync<6, 256>(); else bar_sync<2, 256>(); }
      const uint32_t sbu = opaque(sb);
#pragma unroll
      for (int kb = 0; kb < 7; kb++) {
        mbar_wait(sbu + OFF_BAR + (B_FULL + kb) * 8, u & 1);
        wg_fence();
        uint64_t db = mkdesc(sbu + kb * SLOT, 8192, 1024, 1);
#pragma unroll
        for (int kk = 0; kk < 4; kk++) wgmma_rs_128<1>(acc, xa[kb * 4 + kk], db + kk * 128, (kb | kk) != 0);
        wg_commit();
        if (kb == LEAD1 && wg == 0) { if (u & 1) bar_arrive<6, 256>(); else bar_arrive<2, 256>(); }
        if (kb > 0) { wg_wait<1>(); if (lane == 0) mbar_arrive(sbu + OFF_BAR + (B_EMPTY + kb - 1) * 8); }
      }
      wg_wait<0>(); keep(acc);
      if (lane == 0) mbar_arrive(sbu + OFF_BAR + (B_EMPTY + 6) * 8);
      if ((tid & 127) == 0) PROF(wg, 4 + 2 * u);
      h_epilogue<8>(acc, hbase + (u * 16 + n * 4) * 4096, tag);
      if ((tid & 127) == 0) PROF(wg, 5 + 2 * u);
    }
    {
      float acc[32];
      if (wg == 1) bar_sync<6, 256>();
      const uint32_t sbu = opaque(sb);
#pragma unroll
      for (int it = 0; it < 4; it++) {
        mbar_wait(sbu + OFF_BAR + (B_FULL + it) * 8, 1);
        wg_fence();
        uint64_t db = mkdesc(sbu + it * SLOT, 8192, 512, 2);
#pragma unroll
        for (int kk = 0; kk < 8; kk++) if (it * 8 + kk < 28) wgmma_rs_64<1>(acc, xa[it * 8 + kk], db + kk * 64, (it | kk) != 0);
        wg_commit();
        if (it == 2 && wg == 0) bar_arrive<6, 256>();
        if (it > 0) {
          wg_wait<1>();
          if (lane == 0) mbar_arrive(sbu + OFF_BAR + (B_EMPTY + it - 1) * 8);
#pragma unroll
          for (int i = it * 8 - 8; i < it * 8; i++) if (i < 4 * LA2) LDH(xa[i], hbase + i * 4096);
        }
      }
      wg_wait<0>(); keep(acc);
      if (lane == 0) mbar_arrive(sbu + OFF_BAR + (B_EMPTY + 3) * 8);
      if ((tid & 127) == 0) PROF(wg, 10);
      h_epilogue<4>(acc, hbase + (48 + n * 2) * 4096, tag);
    }
    asm volatile("barrier.cluster.wait.aligned;" ::: "memory");
    if ((tid & 127) == 0) PROF(wg, 11);

    float acc[56];
    if (wg == 1) bar_sync<2, 256>();
#pragma unroll 1
    for (int it = 0; it < 2; it++) {
#pragma unroll
      for (int e = 0; e < 7; e++) {
        if ((tid & 127) == 0) PROF(wg, 16 + it * 7 + e);
        const bool inr = e < 4 && it == 0;
        if (e >= 4 || it == 1) mbar_wait(bars + (B_FULL + e) * 8, e < 4 ? 0 : it ^ 1);
        else if (e == 0) mbar_wait(bars + B_RFULL * 8, 1);
        frag_ready(xa[e * 4], xa[e * 4 + 1], xa[e * 4 + 2], xa[e * 4 + 3], hbase + (it * 7 + e) * 16384, tag);
        wg_fence();
        const uint64_t db = mkdesc(inr ? sb + OFF_R + e * 14336 : sb + e * SLOT, 1792, 128, 0);
#pragma unroll
        for (int kk = 0; kk < 4; kk++) wgmma_rs_112<1>(acc, xa[e * 4 + kk], db + kk * 224, (e | kk) ? 1 : it);
        wg_commit();
        if (e == 1 && it == 0 && wg == 0) bar_arrive<2, 256>();
        if (it == 0 || e + LA2 < 7) {
          const int nb = it * 7 + e + LA2;
#pragma unroll
          for (int kk = 0; kk < 4; kk++) LDH(xa[((e + LA2) % 7) * 4 + kk], hbase + (nb * 4 + kk) * 4096);
        }
        wg_wait<1>();
        if (lane == 0) {
          if (it == 0 ? e >= 5 : e <= 2) mbar_arrive(bars + (B_EMPTY + (e + 6) % 7) * 8);
          if (e == 4 && it == 0) {
            mbar_arrive(bars + B_LFREE * 8);
            asm volatile("{\n.reg .b32 ra;\nmapa.shared::cluster.u32 ra, %0, %1;\nmbarrier.arrive.relaxed.cluster.shared::cluster.b64 _, [ra];\n}"
                         :: "r"(bars + B_RFREE * 8), "r"(kh ^ 1) : "memory");
          }
        }
      }
    }
    const int t128 = tid & 127;
    wg_wait<0>(); keep(acc);
    if (wg == 0) {
      if (t128 == 0) PROF(wg, 12);
      mbar_wait_cluster(bars + B_RFREE * 8, 0);
      uint32_t rdst, rbar;
      asm volatile("mapa.shared::cluster.u32 %0, %1, %2;" : "=r"(rdst) : "r"(sb + OFF_R + t128 * 16), "r"(kh ^ 1));
      asm volatile("mapa.shared::cluster.u32 %0, %1, %2;" : "=r"(rbar) : "r"(bars + B_RECV * 8), "r"(kh ^ 1));
#pragma unroll
      for (int i = 0; i < 14; i++)
        asm volatile("st.async.weak.shared::cluster.mbarrier::complete_tx::bytes.v4.f32 [%0], {%1,%2,%3,%4}, [%5];"
                     :: "r"(rdst + i * 2048), "f"(acc[4 * i]), "f"(acc[4 * i + 1]), "f"(acc[4 * i + 2]), "f"(acc[4 * i + 3]), "r"(rbar) : "memory");
    } else {
      float spec[2][28];
      if (t128 == 0) PROF(wg, 12);
      mbar_wait(bars + B_PQFULL * 8, 0);
      if (t128 == 0) { PROF(wg, 13); g_ep[bid] = epoch + 1; }
#pragma unroll
      for (int i = 0; i < 4; i++) {
        if (i == 0) mbar_wait(bars + B_GFULL * 8, 0);
        if (i >= 2) mbar_wait(bars + (B_FULL + i - 2) * 8, 1);
        wg_fence();
        const uint64_t da = mkdesc(sb + OFF_PQ + i * 14336, 1024, 1024, 1);
        const uint64_t db = mkdesc(i < 2 ? sb + OFF_R + 28672 + i * (G_IMG / 2) : sb + (i - 2) * SLOT, 896, 128, 0);
#pragma unroll
        for (int kk = 0; kk < 7; kk++) wgmma_ss_56<1, 0>(spec[i >> 1], da + kk * 128, db + kk * 112, ((i & 1) | kk) != 0);
        wg_commit();
      }
      const float* gs = reinterpret_cast<const float*>(smem + OFF_G) + w4 * 16 + g;
      const float o0 = bf16_round(1.0f - gs[0]), o1 = bf16_round(1.0f - gs[8]);
      const float g0 = gs[0] * (1.0f / (float)(S_ * D_)), g1 = gs[8] * (1.0f / (float)(S_ * D_));
      wg_wait<0>(); keep(spec[0]); keep(spec[1]);
      if (t128 == 0) PROF(wg, 14);
      mbar_wait_cluster(bars + B_RECV * 8, 0);
      if (t128 == 0) PROF(wg, 0);
      float4 o[14];
#pragma unroll
      for (int i = 0; i < 14; i++) o[i] = lds128f(sb + OFF_R + t128 * 16 + i * 2048);
      bar_sync<5, 128>();
      const uint32_t st = sb + OFF_PQ + w4 * 3840;
#pragma unroll
      for (int i = 0; i < 7; i++) {
        uint32_t pk[4];
#pragma unroll
        for (int e = 0; e < 2; e++) {
          const int c = 2 * i + e, si = i * 4 + e;
          pk[2 * e] = pack_bf16(fmaf(acc[4 * c] + o[c].x, o0, g0 * spec[0][si]), fmaf(acc[4 * c + 1] + o[c].y, o0, g0 * spec[1][si]));
          pk[2 * e + 1] = pack_bf16(fmaf(acc[4 * c + 2] + o[c].z, o1, g1 * spec[0][si + 2]), fmaf(acc[4 * c + 3] + o[c].w, o1, g1 * spec[1][si + 2]));
        }
        asm volatile("stmatrix.sync.aligned.m8n8.x4.shared.b16 [%0], {%1,%2,%3,%4};"
                     :: "r"(st + (lane & 15) * 240 + (lane >> 4) * 16 + i * 32), "r"(pk[0]), "r"(pk[1]), "r"(pk[2]), "r"(pk[3]) : "memory");
      }
      __syncwarp();
      if (lane < 28) {
        const int r2 = lane >= 14, cc = lane - r2 * 14;
        unsigned char* ob = reinterpret_cast<unsigned char*>(out) + (size_t)(m * 128 + kh * 64 + w4 * 16 + r2) * (D_ * 2) + n * 224 + cc * 16;
        float4 v[8];
#pragma unroll
        for (int i = 0; i < 8; i++) v[i] = lds128f(st + r2 * 240 + cc * 16 + i * 480);
#pragma unroll
        for (int i = 0; i < 8; i++) stg128(ob + i * (D_ * 4), __float_as_uint(v[i].x), __float_as_uint(v[i].y), __float_as_uint(v[i].z), __float_as_uint(v[i].w));
      }
    }
    if (t128 == 0) { PROF(wg, 15); if (wg) { PROFG(4, 30); PROF(4, 31); } }
  } else {
    asm volatile("setmaxnreg.dec.sync.aligned.u32 72;");
    const int t = tid - 256;
    const int k = bid;
    if (t == 0) PROF(2, 0);
    uint4 gv[7];
#pragma unroll
    for (int i = 0; i < 7; i++) gv[i] = ldg128(reinterpret_cast<const uint4*>(gate_w) + i * 8 + (t & 7));
    if (t < 98) {
      int cid = m * 98 + t, kc = cid / 56, nn = cid - kc * 56;
      int d = 112 * n + 8 * (2 * (nn >> 3) + (nn & 1)) + (nn & 6) + kh;
      int dr = d > 224 ? d - 448 : d;
      const float df = (float)dr * (-6.283185307179586f / 448.0f);
      uint32_t pk[4];
#pragma unroll
      for (int e = 0; e < 4; e++) {
        const float a = (float)(4 * kc + e) * df;
        pk[e] = pack_bf16(2.0f * __cosf(a), 2.0f * __sinf(a));
      }
      if (kc == 0) pk[0] = (((d >> 1) ^ kh) & 1) ? 0xBF803F80u : 0x3F803F80u;
      stg128(g_G + (size_t)(n * 2 + kh) * G_IMG + cid * 16, pk[0], pk[1], pk[2], pk[3]);
    }
    bar_sync<0, NTHREADS>();
    asm volatile("barrier.cluster.arrive.relaxed.aligned;" ::: "memory");
    mbar_wait(bars + B_PIN * 8, 0);
    if (t == 0) PROF(2, 4);
    {
      const uint32_t wa = sb + 5 * SLOT + (((t & 7) - bid) & 7) * 450 + (t >> 3) * 2, wc = wa + 448 - (t >> 3) * 4;
      uint2* dst = g_Wt + (t >> 3) * S_ + 16 * bid + 2 * (t & 7);
#pragma unroll 1
      for (int h = 0; h < 2; h++) {
        uint32_t w[4][8];
#pragma unroll
        for (int i = 0; i < 4; i++) {
#pragma unroll
          for (int e = 0; e < 4; e++) { w[i][2 * e] = lds16(wa + h * 128 + i * 32 + e * 3600); w[i][2 * e + 1] = lds16(wc - h * 128 - i * 32 + e * 3600); }
        }
#pragma unroll
        for (int i = 0; i < 4; i++)
          if (i < 3 || h == 0 || t < 8)
            stg128(dst + (h * 64 + i * 16) * S_, __byte_perm(w[i][0], w[i][1], 0x5410), __byte_perm(w[i][4], w[i][5], 0x5410), __byte_perm(w[i][2], w[i][3], 0x5410), __byte_perm(w[i][6], w[i][7], 0x5410));
      }
    }
    __syncwarp();
    if (lane < 3) mbar_arrive(bars + (lane ? B_EMPTY + 5 : B_PUBW) * 8);
    if (t == 0) PROF(2, 6);
    {
      const int row = n * 16 + (t >> 3), l8 = t & 7;
      mbar_wait(bars + (B_XFULL + 1) * 8, 0);
      float sum = 0.f;
#pragma unroll
      for (int i = 0; i < 7; i++) {
        const uint4 a = lds128(sb + OFF_R + i * 8192 + row * 128 + ((l8 ^ (row & 7)) << 4));
        const uint32_t aa[4] = {a.x, a.y, a.z, a.w}, bb[4] = {gv[i].x, gv[i].y, gv[i].z, gv[i].w};
#pragma unroll
        for (int e = 0; e < 4; e++) {
          const uint32_t pr = as_u(__hmul2(as_b2(aa[e]), as_b2(bb[e])));
          sum += bf_lo(pr) + bf_hi(pr);
        }
      }
      sum += __shfl_xor_sync(0xffffffffu, sum, 1); sum += __shfl_xor_sync(0xffffffffu, sum, 2); sum += __shfl_xor_sync(0xffffffffu, sum, 4);
      if (lane == 0) mbar_arrive(bars + (B_XFREE + 1) * 8);
      if (l8 == 0) g_gate[m * 128 + kh * 64 + row] = bf16_round(__fdividef(1.0f, 1.0f + __expf(-bf16_round(sum))));
    }
    if (t == 0) PROF(2, 11);
    mbar_wait(bars + B_XFREE * 8, 0);
    if (k < 113) {
      const float u = -6.283185307179586f / 2048.0f, t2 = (float)(2 * t) * u, rr = (float)(t >> 4) * u;
#pragma unroll 1
      for (int i = 0; i < 4; i++) {
        const float q = (float)(2 * i), l = (float)((t & 15) + 64 * i);
        sts128(sb + OFF_TW + i * 2048 + t * 16, cis(t2 * q), cis((t2 + u) * q), cis(t2 * (q + 1.0f)), cis((t2 + u) * (q + 1.0f)));
        sts128(sb + OFF_TW + 8192 + i * 2048 + t * 16, cis(rr * l), cis(rr * (l + 16.0f)), cis(rr * (l + 32.0f)), cis(rr * (l + 48.0f)));
      }
      const float l = (float)((t >> 1) & 15) * (8.0f * u), jj = (float)((t >> 5) * 4 + (t & 1) * 2);
      sts64(sb + OFF_TW + 16384 + t * 8, cis(l * jj), cis(l * (jj + 1.0f)));
    }
    if (t == 0) PROF(2, 9);
    mbar_wait(bars + B_RFULL * 8, 0);
    if (t < 112) {
      const int js = bid >> 4, nn = (t >> 1) / 14, cc = (t >> 1) - nn * 14;
      unsigned char* wdst = g_Wd + (size_t)((js >> 2) * 4 + nn) * WD_IMG + cc * 128 + (t & 1) * 16;
      uint4 v[7];
#pragma unroll
      for (int i = 0; i < 7; i++) v[i] = lds128(sb + OFF_R + i * 1792 + (t & 1) * 896 + (t >> 1) * 16);
#pragma unroll
      for (int i = 0; i < 7; i++) {
        int col = 14 * (bid & 15) + 2 * i - (js & 1) * 32;
        if (col < 0) col += 224;
        const int kpos = col < 192 ? (col >> 6) * 256 + (js & 3) * 64 + (col & 63) : 576 + (js & 3) * 32 + col;
        stg128(wdst + (kpos >> 3) * 1792 + (kpos & 7) * 16, v[i].x, v[i].y, v[i].z, v[i].w);
      }
    }
    __syncwarp();
    if (lane == 0) mbar_arrive(bars + B_PUBD * 8);
    bar_sync<3, 128>();
    if (k < 113) {
      if (t == 0) PROF(2, 2);
      mbar_wait(bars + B_XCFULL * 8, 0);
      if (t == 0) PROF(2, 3);
      c2 v[16];
      const uint32_t se = k == 0 ? 0x4410 : (k == 112 ? 0x4432 : 0x3210), so = k == 0 ? 0x4410 : (k == 112 ? 0x3244 : 0x3210);
#pragma unroll
      for (int jj = 0; jj < 8; jj++) {
        const uint2 e2 = lds64(sb + OFF_EXCH + jj * 1024 + t * 8), o2 = lds64(sb + OFF_EXCH + 8192 + jj * 1024 + t * 8);
#pragma unroll
        for (int h = 0; h < 2; h++) {
          const b2 e = as_b2(__byte_perm(h ? e2.y : e2.x, 0, se)), o = as_b2(__byte_perm(h ? o2.y : o2.x, 0, so));
          const uint32_t s = as_u(__hadd2(e, o)), d = as_u(__hsub2(e, o)) ^ 0x80000000u;
          v[2 * jj + h] = mk(as_b2(__byte_perm(s, d, 0x5410)), as_b2(__byte_perm(s, d, 0x7632)));
        }
      }
      if (t == 0) PROF(2, 12);
      columns(v, sb, t);
      if (t == 0) PROF(2, 14);
      const int pre = (k == 112) ? 1 : 2 * k, pim = (k == 112) ? 1 : 2 * k + 1;
      uint32_t* pq = reinterpret_cast<uint32_t*>(g_PQ) + (t >> 5) * 14336;
      uint32_t* pr = pq + pre * 32 + ((((lane >> 2) ^ pre) & 7) << 2) + (lane & 3);
      uint32_t* pi = pq + pim * 32 + ((((lane >> 2) ^ pim) & 7) << 2) + (lane & 3);
#pragma unroll
      for (int jj = 0; jj < 8; jj++) {
        const b2 ar = as_b2(__byte_perm(as_u(v[2 * jj].y), as_u(v[2 * jj + 1].y), 0x5410)), br = as_b2(__byte_perm(as_u(v[2 * jj].y), as_u(v[2 * jj + 1].y), 0x7632));
        const b2 ai = as_b2(__byte_perm(as_u(v[2 * jj].x), as_u(v[2 * jj + 1].x), 0x5410)), bi = as_b2(__byte_perm(as_u(v[2 * jj].x), as_u(v[2 * jj + 1].x), 0x7632));
        pr[jj * 57344] = as_u(__hadd2(ar, br));
        if (k != 112) pr[jj * 57344 + 7168] = as_u(__hsub2(ar, br));
        if (k != 0) pi[jj * 57344 + 7168] = as_u(__hadd2(ai, bi));
        if (k != 0 && k != 112) pi[jj * 57344] = as_u(__hsub2(ai, bi));
      }
      fence_async_smem();
    }
    bar_sync<3, 128>();
    if (t == 0) { PROF(2, 5); red_release(&g_cnt[5 * 32]); PROF(2, 7); }
    __syncwarp();
    asm volatile("barrier.cluster.wait.aligned;" ::: "memory");
  }
}

typedef CUresult (*EncodeFn)(CUtensorMap*, CUtensorMapDataType, cuuint32_t, void*, const cuuint64_t*, const cuuint64_t*, const cuuint32_t*,
                             const cuuint32_t*, CUtensorMapInterleave, CUtensorMapSwizzle, CUtensorMapL2promotion, CUtensorMapFloatOOBfill);

void make_map(EncodeFn enc, CUtensorMap* tm, const void* base, int cols, int rows, int bc, int br, CUtensorMapSwizzle sw) {
  cuuint64_t gd[2] = {(cuuint64_t)cols, (cuuint64_t)rows};
  cuuint64_t gs[1] = {(cuuint64_t)cols * 2};
  cuuint32_t bd[2] = {(cuuint32_t)bc, (cuuint32_t)br};
  cuuint32_t es[2] = {1, 1};
  enc(tm, CU_TENSOR_MAP_DATA_TYPE_BFLOAT16, 2, const_cast<void*>(base), gd, gs, bd, es, CU_TENSOR_MAP_INTERLEAVE_NONE, sw,
      CU_TENSOR_MAP_L2_PROMOTION_L2_128B, CU_TENSOR_MAP_FLOAT_OOB_FILL_NONE);
}

}

extern "C" void kernel_launch(void* const* d_in, const int* in_sizes, int n_in, void* d_out, int out_size) {
  (void)in_sizes; (void)n_in; (void)out_size;
  const __nv_bfloat16* x = (const __nv_bfloat16*)d_in[0];
  const __nv_bfloat16* w_r = (const __nv_bfloat16*)d_in[1];
  const __nv_bfloat16* w_i = (const __nv_bfloat16*)d_in[2];
  const __nv_bfloat16* w_gate = (const __nv_bfloat16*)d_in[4];
  const __nv_bfloat16* w_up = (const __nv_bfloat16*)d_in[5];
  const __nv_bfloat16* w_down = (const __nv_bfloat16*)d_in[6];
  const __nv_bfloat16* gate_w = (const __nv_bfloat16*)d_in[7];
  static EncodeFn enc = nullptr;
  static bool ok = false;
  if (!enc) {
    cudaDriverEntryPointQueryResult qr;
    cudaGetDriverEntryPoint("cuTensorMapEncodeTiled", (void**)&enc, cudaEnableDefault, &qr);
    cudaFuncSetAttribute(fused_kernel, cudaFuncAttributeMaxDynamicSharedMemorySize, SMEM_BYTES);
    cudaFuncAttributes fa;
    cudaFuncGetAttributes(&fa, fused_kernel);
    ok = (fa.numRegs == 128);
  }
  if (!ok) return;
  CUtensorMap tx, tg, tu, tg32, tu32;
  {
    cuuint64_t gd[3] = {64, (cuuint64_t)S_, 7};
    cuuint64_t gs[2] = {(cuuint64_t)D_ * 2, 128};
    cuuint32_t bd[3] = {64, 64, 7};
    cuuint32_t es[3] = {1, 1, 1};
    enc(&tx, CU_TENSOR_MAP_DATA_TYPE_BFLOAT16, 3, const_cast<__nv_bfloat16*>(x), gd, gs, bd, es, CU_TENSOR_MAP_INTERLEAVE_NONE, CU_TENSOR_MAP_SWIZZLE_128B,
        CU_TENSOR_MAP_L2_PROMOTION_L2_128B, CU_TENSOR_MAP_FLOAT_OOB_FILL_NONE);
  }
  make_map(enc, &tg, w_gate, F_, D_, 64, 64, CU_TENSOR_MAP_SWIZZLE_128B);
  make_map(enc, &tu, w_up, F_, D_, 64, 64, CU_TENSOR_MAP_SWIZZLE_128B);
  make_map(enc, &tg32, w_gate, F_, D_, 32, 128, CU_TENSOR_MAP_SWIZZLE_64B);
  make_map(enc, &tu32, w_up, F_, D_, 32, 128, CU_TENSOR_MAP_SWIZZLE_64B);
  fused_kernel<<<128, NTHREADS, SMEM_BYTES>>>(tx, tg, tu, tg32, tu32, w_r, w_i, w_gate, w_up, w_down, gate_w, (__nv_bfloat16*)d_out);
}
```

```cpp
#include <cuda_runtime.h>
#include <cuda_bf16.h>
#include <cuda.h>
#include <stdint.h>

namespace {

constexpr int S_ = 2048, D_ = 448, F_ = 1792;
constexpr int NTHREADS = 512;
constexpr int SLOT = 16384, NSLOT = 7;
constexpr int HALF_XR = 57344;
constexpr int OFF_PQ = NSLOT * SLOT;
constexpr int OFF_R = OFF_PQ + HALF_XR;
constexpr int OFF_EXCH = OFF_PQ;
constexpr int OFF_WS = OFF_EXCH + 18432;
constexpr int OFF_TW = OFF_WS + 16384;
constexpr int OFF_MISC = OFF_R + HALF_XR;
constexpr int OFF_G = OFF_MISC;
constexpr int OFF_BAR = OFF_MISC + 512;
constexpr int SMEM_BYTES = OFF_BAR + 512;
constexpr int B_FULL = 0, B_EMPTY = 7, B_XFULL = 14  ;
constexpr int B_XFREE = 16  , B_PUBX = 18, B_RFREE = 19, B_LFREE = 20;
constexpr int B_PUBW = 21, B_PUBD = 22;
constexpr int B_PQFULL = 23, B_RECV = 24, B_WFULL = 25, B_XCFULL = 26, B_PREP = 27, B_PREPW = 28, B_RFULL = 29, B_GFULL = 30, B_END = 31, B_PIN = 31;

constexpr int WD_IMG = 896 * 112 * 2;
constexpr int G_IMG = 224 * 56 * 2;

__device__ __align__(1024) uint32_t g_Xc[112 * 2 * S_];
__device__ __align__(1024) unsigned char g_H[32 * 56 * 4096];
__device__ __align__(1024) unsigned char g_PQ[32 * HALF_XR];
__device__ __align__(1024) unsigned char g_Wd[8 * WD_IMG];
__device__ __align__(1024) unsigned char g_G[8 * G_IMG];
__device__ __align__(1024) uint2 g_Wt[113 * S_];
__device__ __align__(1024) float g_gate[S_];
__device__ __align__(128) unsigned int g_ep[128];
__device__ __align__(128) unsigned int g_cnt[8 * 32];

#define PROF(role, idx) do {} while (0)
#define PROFG(role, idx) do {} while (0)

__device__ __forceinline__ uint32_t s2u(const void* p) { return (uint32_t)__cvta_generic_to_shared(p); }
__device__ __forceinline__ void mbar_init(uint32_t b, int c) { asm volatile("mbarrier.init.shared::cta.b64 [%0], %1;" :: "r"(b), "r"(c) : "memory"); }
__device__ __forceinline__ void mbar_expect(uint32_t b, int bytes) { asm volatile("mbarrier.arrive.expect_tx.shared::cta.b64 _, [%0], %1;" :: "r"(b), "r"(bytes) : "memory"); }
__device__ __forceinline__ void mbar_arrive(uint32_t b) { asm volatile("mbarrier.arrive.shared::cta.b64 _, [%0];" :: "r"(b) : "memory"); }
__device__ __forceinline__ void mbar_wait(uint32_t b, int ph) {
  asm volatile("{\n.reg .pred p;\n.reg .u32 c;\nmov.u32 c, 0;\nL_WAIT:\nmbarrier.try_wait.parity.shared::cta.b64 p, [%0], %1;\n@p bra.uni L_DONE;\n"
               "add.u32 c, c, 1;\nsetp.lt.u32 p, c, 4194304;\n@p bra.uni L_WAIT;\ntrap;\nL_DONE:\n}" :: "r"(b), "r"(ph) : "memory");
}
__device__ __forceinline__ void mbar_wait_cluster(uint32_t b, int ph) {
  asm volatile("{\n.reg .pred p;\n.reg .u32 c;\nmov.u32 c, 0;\nL_WAIT:\nmbarrier.try_wait.parity.acquire.cluster.shared::cta.b64 p, [%0], %1;\n@p bra.uni L_DONE;\n"
               "add.u32 c, c, 1;\nsetp.lt.u32 p, c, 4194304;\n@p bra.uni L_WAIT;\ntrap;\nL_DONE:\n}" :: "r"(b), "r"(ph) : "memory");
}
__device__ __forceinline__ uint32_t ld_acquire(const unsigned int* p) { uint32_t v; asm volatile("ld.acquire.gpu.global.u32 %0, [%1];" : "=r"(v) : "l"(p) : "memory"); return v; }
__device__ __forceinline__ uint32_t ld_relaxed(const unsigned int* p) { uint32_t v; asm volatile("ld.relaxed.gpu.global.u32 %0, [%1];" : "=r"(v) : "l"(p) : "memory"); return v; }
__device__ __forceinline__ void wait_ge(const unsigned int* p, uint32_t target) {
#pragma unroll 1
  for (int i = 0; i < (1 << 22); i++) { if ((int)(ld_acquire(p) - target) >= 0) return; }
  __trap();
}
__device__ __forceinline__ void red_release(unsigned int* p) { asm volatile("red.release.gpu.global.add.u32 [%0], 1;" :: "l"(p) : "memory"); }
__device__ __forceinline__ void red_relaxed(unsigned int* p) { asm volatile("red.relaxed.gpu.global.add.u32 [%0], 1;" :: "l"(p) : "memory"); }
__device__ __forceinline__ bool elect() { uint32_t p; asm volatile("{\n.reg .pred p;\nelect.sync _|p, 0xffffffff;\nselp.u32 %0, 1, 0, p;\n}" : "=r"(p)); return p; }
__device__ __forceinline__ void fence_async_smem() { asm volatile("fence.proxy.async.shared::cta;" ::: "memory"); }
__device__ __forceinline__ void fence_async_global() { asm volatile("fence.proxy.async.global;" ::: "memory"); }
template <int ID, int N> __device__ __forceinline__ void bar_sync() { asm volatile("bar.sync %0, %1;" :: "n"(ID), "n"(N) : "memory"); }
template <int ID, int N> __device__ __forceinline__ void bar_arrive() { asm volatile("bar.arrive %0, %1;" :: "n"(ID), "n"(N) : "memory"); }
__device__ __forceinline__ void tma2d(uint32_t dst, const CUtensorMap* tm, int c0, int c1, uint32_t bar) {
  asm volatile("cp.async.bulk.tensor.2d.shared::cluster.global.mbarrier::complete_tx::bytes [%0], [%1, {%3, %4}], [%2];"
               :: "r"(dst), "l"(tm), "r"(bar), "r"(c0), "r"(c1) : "memory");
}
__device__ __forceinline__ void tma3d(uint32_t dst, const CUtensorMap* tm, int c0, int c1, int c2, uint32_t bar) {
  asm volatile("cp.async.bulk.tensor.3d.shared::cluster.global.mbarrier::complete_tx::bytes [%0], [%1, {%3, %4, %5}], [%2];"
               :: "r"(dst), "l"(tm), "r"(bar), "r"(c0), "r"(c1), "r"(c2) : "memory");
}
__device__ __forceinline__ void bulk_g2s(uint32_t dst, const void* src, int bytes, uint32_t bar) {
  asm volatile("cp.async.bulk.shared::cluster.global.mbarrier::complete_tx::bytes [%0], [%1], %2, [%3];"
               :: "r"(dst), "l"(src), "r"(bytes), "r"(bar) : "memory");
}
__device__ __forceinline__ void prefetch_l2(const void* src, int bytes) {
  asm volatile("cp.async.bulk.prefetch.L2.global [%0], %1;" :: "l"(src), "r"(bytes) : "memory");
}
__device__ __forceinline__ void prefetch_tma2d(const CUtensorMap* tm, int c0, int c1) {
  asm volatile("cp.async.bulk.prefetch.tensor.2d.L2.global [%0, {%1, %2}];" :: "l"(tm), "r"(c0), "r"(c1) : "memory");
}
__device__ __forceinline__ uint64_t mkdesc(uint32_t addr, uint32_t lbo, uint32_t sbo, uint32_t mode) {
  return (uint64_t)((addr & 0x3FFFF) >> 4) | ((uint64_t)(lbo >> 4) << 16) | ((uint64_t)(sbo >> 4) << 32) | ((uint64_t)mode << 62);
}
__device__ __forceinline__ void wg_fence() { asm volatile("wgmma.fence.sync.aligned;" ::: "memory"); }
__device__ __forceinline__ void wg_commit() { asm volatile("wgmma.commit_group.sync.aligned;" ::: "memory"); }
template <int N> __device__ __forceinline__ void wg_wait() { asm volatile("wgmma.wait_group.sync.aligned %0;" :: "n"(N) : "memory"); }
template <int N> __device__ __forceinline__ void keep(float (&d)[N]) {
#pragma unroll
  for (int i = 0; i < N; i++) asm volatile("" : "+f"(d[i]) :: "memory");
}
__device__ __forceinline__ uint32_t pack_bf16(float lo, float hi) { uint32_t r; asm("cvt.rn.bf16x2.f32 %0, %1, %2;" : "=r"(r) : "f"(hi), "f"(lo)); return r; }
__device__ __forceinline__ float bf16_round(float v) { return __bfloat162float(__float2bfloat16_rn(v)); }
__device__ __forceinline__ void sts128(uint32_t a, uint32_t x, uint32_t y, uint32_t z, uint32_t w) { asm volatile("st.shared.v4.b32 [%0], {%1,%2,%3,%4};" :: "r"(a), "r"(x), "r"(y), "r"(z), "r"(w) : "memory"); }
__device__ __forceinline__ float4 lds128f(uint32_t a) { float4 v; asm volatile("ld.shared.v4.f32 {%0,%1,%2,%3}, [%4];" : "=f"(v.x), "=f"(v.y), "=f"(v.z), "=f"(v.w) : "r"(a) : "memory"); return v; }

__device__ __forceinline__ uint2 lds64(uint32_t a) { uint2 v; asm volatile("ld.shared.v2.b32 {%0,%1}, [%2];" : "=r"(v.x), "=r"(v.y) : "r"(a) : "memory"); return v; }
__device__ __forceinline__ float bf_lo(uint32_t w) { return __uint_as_float(w << 16); }
__device__ __forceinline__ float bf_hi(uint32_t w) { return __uint_as_float(w & 0xffff0000u); }
__device__ __forceinline__ uint32_t opaque(uint32_t v) { asm volatile("" : "+r"(v)); return v; }
__device__ __forceinline__ uint4 ldg128(const void* p) { uint4 v; asm volatile("ld.global.nc.v4.b32 {%0,%1,%2,%3}, [%4];" : "=r"(v.x), "=r"(v.y), "=r"(v.z), "=r"(v.w) : "l"(p)); return v; }
__device__ __forceinline__ void stg128(void* p, uint32_t x, uint32_t y, uint32_t z, uint32_t w) { asm volatile("st.global.v4.b32 [%0], {%1,%2,%3,%4};" :: "l"(p), "r"(x), "r"(y), "r"(z), "r"(w) : "memory"); }
__device__ __forceinline__ void stg128_l2(void* p, uint32_t x, uint32_t y, uint32_t z, uint32_t w) { asm volatile("st.relaxed.gpu.global.v4.b32 [%0], {%1,%2,%3,%4};" :: "l"(p), "r"(x), "r"(y), "r"(z), "r"(w) : "memory"); }
__device__ __forceinline__ void ldg128_na(uint32_t (&v)[4], const void* p) { asm volatile("ld.global.L1::no_allocate.v4.b32 {%0,%1,%2,%3}, [%4];" : "=r"(v[0]), "=r"(v[1]), "=r"(v[2]), "=r"(v[3]) : "l"(p) : "memory"); }
__device__ __forceinline__ void ldg128_l2(uint32_t (&v)[4], const void* p) { asm volatile("ld.relaxed.gpu.global.v4.b32 {%0,%1,%2,%3}, [%4];" : "=r"(v[0]), "=r"(v[1]), "=r"(v[2]), "=r"(v[3]) : "l"(p) : "memory"); }
__device__ __forceinline__ uint4 lds128(uint32_t a) { uint4 v; asm volatile("ld.shared.v4.b32 {%0,%1,%2,%3}, [%4];" : "=r"(v.x), "=r"(v.y), "=r"(v.z), "=r"(v.w) : "r"(a) : "memory"); return v; }
__device__ __forceinline__ uint32_t lds16(uint32_t a) { uint32_t v; asm volatile("ld.shared.u16 %0, [%1];" : "=r"(v) : "r"(a) : "memory"); return v; }
__device__ __forceinline__ void sts64(uint32_t a, uint32_t x, uint32_t y) { asm volatile("st.shared.v2.b32 [%0], {%1,%2};" :: "r"(a), "r"(x), "r"(y) : "memory"); }
template <int TB> __device__ __forceinline__ void wgmma_rs_128(float (&d)[64], const uint32_t (&a)[4], uint64_t db, int sc) {
  asm volatile("{\n.reg .pred p;\nsetp.ne.b32 p, %69, 0;\n"
    "wgmma.mma_async.sync.aligned.m64n128k16.f32.bf16.bf16 {%0, %1, %2, %3, %4, %5, %6, %7, %8, %9, %10, %11, %12, %13, %14, %15, %16, %17, %18, %19, %20, %21, %22, %23, %24, %25, %26, %27, %28, %29, %30, %31, %32, %33, %34, %35, %36, %37, %38, %39, %40, %41, %42, %43, %44, %45, %46, %47, %48, %49, %50, %51, %52, %53, %54, %55, %56, %57, %58, %59, %60, %61, %62, %63}, {%64, %65, %66, %67}, %68, p, 1, 1, %70;\n}\n"
    : "+f"(d[0]), "+f"(d[1]), "+f"(d[2]), "+f"(d[3]), "+f"(d[4]), "+f"(d[5]), "+f"(d[6]), "+f"(d[7]), "+f"(d[8]), "+f"(d[9]), "+f"(d[10]), "+f"(d[11]), "+f"(d[12]), "+f"(d[13]), "+f"(d[14]), "+f"(d[15]), "+f"(d[16]), "+f"(d[17]), "+f"(d[18]), "+f"(d[19]), "+f"(d[20]), "+f"(d[21]), "+f"(d[22]), "+f"(d[23]), "+f"(d[24]), "+f"(d[25]), "+f"(d[26]), "+f"(d[27]), "+f"(d[28]), "+f"(d[29]), "+f"(d[30]), "+f"(d[31]), "+f"(d[32]), "+f"(d[33]), "+f"(d[34]), "+f"(d[35]), "+f"(d[36]), "+f"(d[37]), "+f"(d[38]), "+f"(d[39]), "+f"(d[40]), "+f"(d[41]), "+f"(d[42]), "+f"(d[43]), "+f"(d[44]), "+f"(d[45]), "+f"(d[46]), "+f"(d[47]), "+f"(d[48]), "+f"(d[49]), "+f"(d[50]), "+f"(d[51]), "+f"(d[52]), "+f"(d[53]), "+f"(d[54]), "+f"(d[55]), "+f"(d[56]), "+f"(d[57]), "+f"(d[58]), "+f"(d[59]), "+f"(d[60]), "+f"(d[61]), "+f"(d[62]), "+f"(d[63])
    : "r"(a[0]), "r"(a[1]), "r"(a[2]), "r"(a[3]), "l"(db), "r"(sc), "n"(TB));
}
template <int TB> __device__ __forceinline__ void wgmma_rs_64(float (&d)[32], const uint32_t (&a)[4], uint64_t db, int sc) {
  asm volatile("{\n.reg .pred p;\nsetp.ne.b32 p, %37, 0;\n"
    "wgmma.mma_async.sync.aligned.m64n64k16.f32.bf16.bf16 {%0, %1, %2, %3, %4, %5, %6, %7, %8, %9, %10, %11, %12, %13, %14, %15, %16, %17, %18, %19, %20, %21, %22, %23, %24, %25, %26, %27, %28, %29, %30, %31}, {%32, %33, %34, %35}, %36, p, 1, 1, %38;\n}\n"
    : "+f"(d[0]), "+f"(d[1]), "+f"(d[2]), "+f"(d[3]), "+f"(d[4]), "+f"(d[5]), "+f"(d[6]), "+f"(d[7]), "+f"(d[8]), "+f"(d[9]), "+f"(d[10]), "+f"(d[11]), "+f"(d[12]), "+f"(d[13]), "+f"(d[14]), "+f"(d[15]), "+f"(d[16]), "+f"(d[17]), "+f"(d[18]), "+f"(d[19]), "+f"(d[20]), "+f"(d[21]), "+f"(d[22]), "+f"(d[23]), "+f"(d[24]), "+f"(d[25]), "+f"(d[26]), "+f"(d[27]), "+f"(d[28]), "+f"(d[29]), "+f"(d[30]), "+f"(d[31])
    : "r"(a[0]), "r"(a[1]), "r"(a[2]), "r"(a[3]), "l"(db), "r"(sc), "n"(TB));
}
template <int TB> __device__ __forceinline__ void wgmma_rs_56(float (&d)[28], const uint32_t (&a)[4], uint64_t db, int sc) {
  asm volatile("{\n.reg .pred p;\nsetp.ne.b32 p, %33, 0;\n"
    "wgmma.mma_async.sync.aligned.m64n56k16.f32.bf16.bf16 {%0, %1, %2, %3, %4, %5, %6, %7, %8, %9, %10, %11, %12, %13, %14, %15, %16, %17, %18, %19, %20, %21, %22, %23, %24, %25, %26, %27}, {%28, %29, %30, %31}, %32, p, 1, 1, %34;\n}\n"
    : "+f"(d[0]), "+f"(d[1]), "+f"(d[2]), "+f"(d[3]), "+f"(d[4]), "+f"(d[5]), "+f"(d[6]), "+f"(d[7]), "+f"(d[8]), "+f"(d[9]), "+f"(d[10]), "+f"(d[11]), "+f"(d[12]), "+f"(d[13]), "+f"(d[14]), "+f"(d[15]), "+f"(d[16]), "+f"(d[17]), "+f"(d[18]), "+f"(d[19]), "+f"(d[20]), "+f"(d[21]), "+f"(d[22]), "+f"(d[23]), "+f"(d[24]), "+f"(d[25]), "+f"(d[26]), "+f"(d[27])
    : "r"(a[0]), "r"(a[1]), "r"(a[2]), "r"(a[3]), "l"(db), "r"(sc), "n"(TB));
}
template <int TB> __device__ __forceinline__ void wgmma_rs_112(float (&d)[56], const uint32_t (&a)[4], uint64_t db, int sc) {
  asm volatile("{\n.reg .pred p;\nsetp.ne.b32 p, %61, 0;\n"
    "wgmma.mma_async.sync.aligned.m64n112k16.f32.bf16.bf16 {%0, %1, %2, %3, %4, %5, %6, %7, %8, %9, %10, %11, %12, %13, %14, %15, %16, %17, %18, %19, %20, %21, %22, %23, %24, %25, %26, %27, %28, %29, %30, %31, %32, %33, %34, %35, %36, %37, %38, %39, %40, %41, %42, %43, %44, %45, %46, %47, %48, %49, %50, %51, %52, %53, %54, %55}, {%56, %57, %58, %59}, %60, p, 1, 1, %62;\n}\n"
    : "+f"(d[0]), "+f"(d[1]), "+f"(d[2]), "+f"(d[3]), "+f"(d[4]), "+f"(d[5]), "+f"(d[6]), "+f"(d[7]), "+f"(d[8]), "+f"(d[9]), "+f"(d[10]), "+f"(d[11]), "+f"(d[12]), "+f"(d[13]), "+f"(d[14]), "+f"(d[15]), "+f"(d[16]), "+f"(d[17]), "+f"(d[18]), "+f"(d[19]), "+f"(d[20]), "+f"(d[21]), "+f"(d[22]), "+f"(d[23]), "+f"(d[24]), "+f"(d[25]), "+f"(d[26]), "+f"(d[27]), "+f"(d[28]), "+f"(d[29]), "+f"(d[30]), "+f"(d[31]), "+f"(d[32]), "+f"(d[33]), "+f"(d[34]), "+f"(d[35]), "+f"(d[36]), "+f"(d[37]), "+f"(d[38]), "+f"(d[39]), "+f"(d[40]), "+f"(d[41]), "+f"(d[42]), "+f"(d[43]), "+f"(d[44]), "+f"(d[45]), "+f"(d[46]), "+f"(d[47]), "+f"(d[48]), "+f"(d[49]), "+f"(d[50]), "+f"(d[51]), "+f"(d[52]), "+f"(d[53]), "+f"(d[54]), "+f"(d[55])
    : "r"(a[0]), "r"(a[1]), "r"(a[2]), "r"(a[3]), "l"(db), "r"(sc), "n"(TB));
}
template <int TA, int TB> __device__ __forceinline__ void wgmma_ss_56(float (&d)[28], uint64_t da, uint64_t db, int sc) {
  asm volatile("{\n.reg .pred p;\nsetp.ne.b32 p, %30, 0;\n"
    "wgmma.mma_async.sync.aligned.m64n56k16.f32.bf16.bf16 {%0, %1, %2, %3, %4, %5, %6, %7, %8, %9, %10, %11, %12, %13, %14, %15, %16, %17, %18, %19, %20, %21, %22, %23, %24, %25, %26, %27}, %28, %29, p, 1, 1, %31, %32;\n}\n"
    : "+f"(d[0]), "+f"(d[1]), "+f"(d[2]), "+f"(d[3]), "+f"(d[4]), "+f"(d[5]), "+f"(d[6]), "+f"(d[7]), "+f"(d[8]), "+f"(d[9]), "+f"(d[10]), "+f"(d[11]), "+f"(d[12]), "+f"(d[13]), "+f"(d[14]), "+f"(d[15]), "+f"(d[16]), "+f"(d[17]), "+f"(d[18]), "+f"(d[19]), "+f"(d[20]), "+f"(d[21]), "+f"(d[22]), "+f"(d[23]), "+f"(d[24]), "+f"(d[25]), "+f"(d[26]), "+f"(d[27])
    : "l"(da), "l"(db), "r"(sc), "n"(TA), "n"(TB));
}

__device__ __forceinline__ uint32_t cis(float a) { return pack_bf16(__cosf(a), __sinf(a)); }

typedef __nv_bfloat162 b2;
struct c2 { b2 x, y; };
__device__ __forceinline__ b2 as_b2(uint32_t u) { return *reinterpret_cast<b2*>(&u); }
__device__ __forceinline__ uint32_t as_u(b2 v) { return *reinterpret_cast<uint32_t*>(&v); }
__device__ __forceinline__ c2 mk(b2 x, b2 y) { c2 r; r.x = x; r.y = y; return r; }
__device__ __forceinline__ c2 cmul(c2 a, b2 wr, b2 wi) { return mk(__hfma2(a.x, wr, __hneg2(__hmul2(a.y, wi))), __hfma2(a.x, wi, __hmul2(a.y, wr))); }
__device__ __forceinline__ void fft4(c2& a0, c2& a1, c2& a2, c2& a3) {
  c2 t0 = mk(__hadd2(a0.x, a2.x), __hadd2(a0.y, a2.y)), t1 = mk(__hsub2(a0.x, a2.x), __hsub2(a0.y, a2.y));
  c2 t2 = mk(__hadd2(a1.x, a3.x), __hadd2(a1.y, a3.y)), t3 = mk(__hsub2(a1.x, a3.x), __hsub2(a1.y, a3.y));
  a0 = mk(__hadd2(t0.x, t2.x), __hadd2(t0.y, t2.y)); a2 = mk(__hsub2(t0.x, t2.x), __hsub2(t0.y, t2.y));
  a1 = mk(__hadd2(t1.x, t3.y), __hsub2(t1.y, t3.x)); a3 = mk(__hsub2(t1.x, t3.y), __hadd2(t1.y, t3.x));
}
__device__ __forceinline__ void fft4_s2(c2& a0, c2& a1, c2& a2, c2& a3, b2 r) {
  const b2 nr = __hneg2(r);
  c2 t0 = mk(__hfma2(a2.x, r, a0.x), __hfma2(a2.y, r, a0.y)), t1 = mk(__hfma2(a2.x, nr, a0.x), __hfma2(a2.y, nr, a0.y));
  c2 t2 = mk(__hadd2(a1.x, a3.x), __hadd2(a1.y, a3.y)), t3 = mk(__hsub2(a1.x, a3.x), __hsub2(a1.y, a3.y));
  a0 = mk(__hadd2(t0.x, t2.x), __hadd2(t0.y, t2.y)); a2 = mk(__hsub2(t0.x, t2.x), __hsub2(t0.y, t2.y));
  a1 = mk(__hadd2(t1.x, t3.y), __hsub2(t1.y, t3.x)); a3 = mk(__hsub2(t1.x, t3.y), __hadd2(t1.y, t3.x));
}
__device__ __forceinline__ void fft4_s13(c2& a0, c2& a1, c2& a2, c2& a3, b2 r) {
  const b2 nr = __hneg2(r);
  c2 t0 = mk(__hadd2(a0.x, a2.x), __hadd2(a0.y, a2.y)), t1 = mk(__hsub2(a0.x, a2.x), __hsub2(a0.y, a2.y));
  c2 t2 = mk(__hadd2(a1.x, a3.x), __hadd2(a1.y, a3.y)), t3 = mk(__hsub2(a1.x, a3.x), __hsub2(a1.y, a3.y));
  a0 = mk(__hfma2(t2.x, r, t0.x), __hfma2(t2.y, r, t0.y)); a2 = mk(__hfma2(t2.x, nr, t0.x), __hfma2(t2.y, nr, t0.y));
  a1 = mk(__hfma2(t3.y, r, t1.x), __hfma2(t3.x, nr, t1.y)); a3 = mk(__hfma2(t3.y, nr, t1.x), __hfma2(t3.x, r, t1.y));
}
__device__ __forceinline__ c2 rot1(c2 a) { return mk(__hadd2(a.x, a.y), __hsub2(a.y, a.x)); }
__device__ __forceinline__ c2 rot3(c2 a) { return mk(__hsub2(a.y, a.x), __hneg2(__hadd2(a.x, a.y))); }
__device__ __forceinline__ c2 mul_mi(c2 a) { return mk(a.y, __hneg2(a.x)); }
template <int O> __device__ __forceinline__ void fft8(c2 (&v)[16]) {
  const b2 r = as_b2(0x3F353F35u), nr = as_b2(0xBF35BF35u);
  fft4(v[O], v[O + 4], v[O + 8], v[O + 12]);
  fft4(v[O + 2], v[O + 6], v[O + 10], v[O + 14]);
  const c2 o0 = v[O + 2], o1 = rot1(v[O + 6]), o2 = v[O + 10], o3 = rot1(v[O + 14]);
  const c2 e0 = v[O], e1 = v[O + 4], e2 = v[O + 8], e3 = v[O + 12];
  v[O] = mk(__hadd2(e0.x, o0.x), __hadd2(e0.y, o0.y));              v[O + 8] = mk(__hsub2(e0.x, o0.x), __hsub2(e0.y, o0.y));
  v[O + 2] = mk(__hfma2(o1.x, r, e1.x), __hfma2(o1.y, r, e1.y));    v[O + 10] = mk(__hfma2(o1.x, nr, e1.x), __hfma2(o1.y, nr, e1.y));
  v[O + 4] = mk(__hadd2(e2.x, o2.y), __hsub2(e2.y, o2.x));          v[O + 12] = mk(__hsub2(e2.x, o2.y), __hadd2(e2.y, o2.x));
  v[O + 6] = mk(__hfma2(o3.y, r, e3.x), __hfma2(o3.x, nr, e3.y));   v[O + 14] = mk(__hfma2(o3.y, nr, e3.x), __hfma2(o3.x, r, e3.y));
}
__device__ __forceinline__ void fft16(c2 (&v)[16]) {
  const b2 r = as_b2(0x3F353F35u), c1 = as_b2(0x3F6D3F6Du), s1 = as_b2(0x3EC43EC4u), nc1 = as_b2(0xBF6DBF6Du), ns1 = as_b2(0xBEC4BEC4u);
#pragma unroll
  for (int a = 0; a < 4; a++) fft4(v[a], v[a + 4], v[a + 8], v[a + 12]);
  v[5] = cmul(v[5], c1, ns1); v[6] = rot1(v[6]); v[7] = cmul(v[7], s1, nc1);
  v[9] = rot1(v[9]); v[10] = mul_mi(v[10]); v[11] = rot3(v[11]);
  v[13] = cmul(v[13], s1, nc1); v[14] = rot3(v[14]); v[15] = cmul(v[15], nc1, s1);
  fft4(v[0], v[1], v[2], v[3]); fft4_s2(v[4], v[5], v[6], v[7], r); fft4_s13(v[8], v[9], v[10], v[11], r); fft4_s2(v[12], v[13], v[14], v[15], r);
  c2 t;
  t = v[1]; v[1] = v[4]; v[4] = t;  t = v[2]; v[2] = v[8]; v[8] = t;  t = v[3]; v[3] = v[12]; v[12] = t;
  t = v[6]; v[6] = v[9]; v[9] = t;  t = v[7]; v[7] = v[13]; v[13] = t; t = v[11]; v[11] = v[14]; v[14] = t;
}

__device__ __forceinline__ void columns(c2 (&v)[16], uint32_t sb, int t) {
  const int l16 = t & 15;
  const uint32_t row = sb + OFF_EXCH + (t >> 4) * 2304;
  const uint32_t pos = sb + OFF_EXCH + (t >> 3) * 144 + (t & 7) * 16;
#pragma unroll 1
  for (int ps = 0; ps < 6; ps++) {
    if (ps == 0 || ps == 5) { fft8<0>(v); fft8<1>(v); } else fft16(v);
    if (ps == 5) break;
    if (ps == 2) {
      const uint32_t ws = sb + OFF_WS + (l16 >> 1) * 128 + ((((t >> 4) + (l16 >> 1)) & 7) * 2 + (l16 & 1)) * 8;
      mbar_wait(sb + OFF_BAR + B_WFULL * 8, 0);
#pragma unroll
      for (int q = 0; q < 16; q++) {
        const uint2 w = lds64(ws + q * 1024);
        const c2 z = cmul(v[q], as_b2(w.x), as_b2(w.y));
        v[q] = mk(z.y, z.x);
      }
      continue;
    }
    {
      const bool full = ps == 0 || ps == 4;
      const uint32_t tw = sb + OFF_TW + (full ? ps * 2048 + t * 16 : 16384 + l16 * 16);
      const uint32_t st = full ? 2048 : 256;
#pragma unroll
      for (int i = 0; i < 4; i++) {
        const uint4 w4 = lds128(tw + i * st);
        const uint32_t w[4] = {w4.x, w4.y, w4.z, w4.w};
#pragma unroll
        for (int e = 0; e < 4; e++) v[4 * i + e] = cmul(v[4 * i + e], __low2bfloat162(as_b2(w[e])), __high2bfloat162(as_b2(w[e])));
      }
    }
    if (ps == 0) {
      bar_sync<3, 128>();
#pragma unroll
      for (int q = 0; q < 8; q++) sts128(pos + q * 2304, as_u(v[2 * q].x), as_u(v[2 * q].y), as_u(v[2 * q + 1].x), as_u(v[2 * q + 1].y));
      bar_sync<3, 128>();
#pragma unroll
      for (int q = 0; q < 16; q++) { const uint2 a = lds64(row + q * 144 + l16 * 8); v[q] = mk(as_b2(a.x), as_b2(a.y)); }
    } else {
      __syncwarp();
#pragma unroll
      for (int q = 0; q < 16; q++) sts64(row + q * 144 + l16 * 8, as_u(v[q].x), as_u(v[q].y));
      if (ps == 4) bar_sync<3, 128>(); else __syncwarp();
      const uint32_t src = ps == 4 ? pos : row + l16 * 144, st = ps == 4 ? 2304 : 16;
#pragma unroll
      for (int q = 0; q < 8; q++) { const uint4 a = lds128(src + q * st); v[2 * q] = mk(as_b2(a.x), as_b2(a.y)); v[2 * q + 1] = mk(as_b2(a.z), as_b2(a.w)); }
    }
  }
}

template <int NH> __device__ __forceinline__ void h_epilogue(float (&acc)[NH * 8], unsigned char* gdst, uint32_t tag) {
#pragma unroll
  for (int c = 0; c < NH / 2; c++) {
    uint32_t pk[4];
#pragma unroll
    for (int i = 0; i < 4; i++) {
      float hv[2];
#pragma unroll
      for (int e = 0; e < 2; e++) {
        float hg = 0.5f * acc[c * 8 + i * 2 + e], up = acc[NH * 4 + c * 8 + i * 2 + e];
        float th; asm("tanh.approx.f32 %0, %1;" : "=f"(th) : "f"(hg));
        hv[e] = fmaf(hg, th, hg) * up;
      }
      pk[i] = pack_bf16(hv[0], hv[1]);
    }
    stg128_l2(gdst + c * 4096, (pk[0] & ~1u) | tag, pk[1], pk[2], pk[3]);
  }
}

__device__ __forceinline__ void frag_ready(uint32_t (&a)[4], uint32_t (&b)[4], uint32_t (&c)[4], uint32_t (&d)[4], const unsigned char* p, uint32_t tag) {
  asm volatile("{\n.reg .pred p;\n.reg .u32 c, m, q;\nmov.u32 c, 0;\nL_TRY:\n"
               "lop3.b32 m, %0, %4, %17, 0x7E;\nlop3.b32 q, %8, %12, %17, 0x7E;\nlop3.b32 m, m, q, 1, 0xA8;\nsetp.ne.u32 p, m, 0;\n"
               "vote.sync.any.pred p, p, 0xffffffff;\n@!p bra.uni L_OK;\n"
               "ld.relaxed.gpu.global.v4.b32 {%0,%1,%2,%3}, [%16];\nld.relaxed.gpu.global.v4.b32 {%4,%5,%6,%7}, [%16+4096];\n"
               "ld.relaxed.gpu.global.v4.b32 {%8,%9,%10,%11}, [%16+8192];\nld.relaxed.gpu.global.v4.b32 {%12,%13,%14,%15}, [%16+12288];\n"
               "add.u32 c, c, 1;\nsetp.lt.u32 p, c, 262144;\n@p bra.uni L_TRY;\ntrap;\nL_OK:\n}"
               : "+r"(a[0]), "+r"(a[1]), "+r"(a[2]), "+r"(a[3]), "+r"(b[0]), "+r"(b[1]), "+r"(b[2]), "+r"(b[3]),
                 "+r"(c[0]), "+r"(c[1]), "+r"(c[2]), "+r"(c[3]), "+r"(d[0]), "+r"(d[1]), "+r"(d[2]), "+r"(d[3])
               : "l"(p), "r"(tag) : "memory");
}

#define LDH ldg128_na
#define MAP 0
#define WPOS 1
#define XPOS 1
#define PF 1
#define LA2 5
#define LEAD1 3

__global__ void __cluster_dims__(2, 1, 1) __launch_bounds__(NTHREADS, 1)
fused_kernel(const __grid_constant__ CUtensorMap tm_x, const __grid_constant__ CUtensorMap tm_g, const __grid_constant__ CUtensorMap tm_u,
             const __grid_constant__ CUtensorMap tm_g32, const __grid_constant__ CUtensorMap tm_u32,
             const __nv_bfloat16* __restrict__ x, const __nv_bfloat16* __restrict__ w_r, const __nv_bfloat16* __restrict__ w_i,
             const __nv_bfloat16* __restrict__ w_gate, const __nv_bfloat16* __restrict__ w_up,
             const __nv_bfloat16* __restrict__ w_down, const __nv_bfloat16* __restrict__ gate_w, __nv_bfloat16* __restrict__ out) {
  extern __shared__ __align__(1024) unsigned char smem[];
  const uint32_t sb = s2u(smem);
  const uint32_t bars = sb + OFF_BAR;
  const int tid = threadIdx.x, warp = __shfl_sync(0xffffffffu, tid >> 5, 0), lane = tid & 31;
  const int cl = blockIdx.x >> 1, kh = blockIdx.x & 1;
  const int n0 = cl < 4 ? cl : (cl < 36 ? (cl - 4) >> 3 : (cl - 36) / 7);
  const int m0 = cl < 4 ? 15 : (cl < 36 ? (cl - 4) & 7 : cl - 28 - 7 * n0);
  const int n = MAP == 0 ? n0 : (MAP == 1 ? (m0 & 3) : ((n0 & 1) | ((m0 & 1) << 1)));
  const int m = MAP == 0 ? m0 : (MAP == 1 ? ((m0 & 12) | n0) : ((m0 & 14) | (n0 >> 1)));
  const int j = kh * 4 + n, bid = m * 8 + n * 2 + kh;

  if (PF && tid < 384) {
    const unsigned char* a;
    if (tid < 224) a = reinterpret_cast<const unsigned char*>(x) + bid * 14336 + tid * 64;
    else if (tid < 256) a = reinterpret_cast<const unsigned char*>(gate_w) + (tid & 15) * 56;
    else a = reinterpret_cast<const unsigned char*>(w_r) + bid * 7200 + min(tid - 256, 112) * 64;
    asm volatile("prefetch.global.L2 [%0];" :: "l"(a));
    if (tid < 112) a = reinterpret_cast<const unsigned char*>((tid & 1) ? w_up : w_gate) + (m * 28 + (tid >> 2)) * (F_ * 2) + (224 * j + (j & 1) * 32) * 2 + (tid & 2) * 32;
    else if (tid >= 256) a = reinterpret_cast<const unsigned char*>(w_i) + bid * 7200 + min(tid - 256, 112) * 64;
    asm volatile("prefetch.global.L2 [%0];" :: "l"(a));
  }
  if (warp >= 12) {
    asm volatile("setmaxnreg.dec.sync.aligned.u32 24;");
    const int c64 = 224 * j + (j & 1) * 32;
    const uint32_t epoch = ld_relaxed(&g_ep[bid]);
    if (warp == 12) {
      if (lane < 10) mbar_init(bars + (lane < NSLOT ? B_FULL + lane : (lane < 9 ? B_XFULL - 7 + lane : B_PIN)) * 8, 1);
    } else if (warp == 14) {
      if (lane < NSLOT) mbar_init(bars + (B_EMPTY + lane) * 8, 8);
      const int i = B_XFREE + lane;
      if (i < B_END) mbar_init(bars + i * 8, i >= B_PQFULL ? 1 : ((i == B_XFREE || i >= B_PUBW) ? 4 : 8));
      asm volatile("fence.mbarrier_init.release.cluster;" ::: "memory");
      __syncwarp();
      if (lane == 0) mbar_expect(bars + B_RECV * 8, 64 * 112 * 4);
    } else if (warp == 13) {
      if (lane == 0) { PROFG(4, 0); PROF(4, 1); }
    }
    fence_async_smem();
    bar_arrive<0, NTHREADS>();
    if (warp == 12) {
#pragma unroll 1
      for (int i = 0; i < 5; i++) {
        if (elect()) {
#pragma unroll
          for (int w = 0; w < 2; w++) {
            if (i == w * XPOS) {
              mbar_expect(bars + (B_XFULL + w) * 8, HALF_XR);
              tma3d(sb + OFF_PQ + w * HALF_XR, &tm_x, 0, m * 128 + (w ^ kh ^ 1) * 64, 0, bars + (B_XFULL + w) * 8);
            }
          }
          if (i == WPOS) {
            mbar_expect(bars + B_PIN * 8, 14400);
            bulk_g2s(sb + 5 * SLOT, reinterpret_cast<const unsigned char*>(w_r) + bid * 7200, 7200, bars + B_PIN * 8);
            bulk_g2s(sb + 5 * SLOT + 7200, reinterpret_cast<const unsigned char*>(w_i) + bid * 7200, 7200, bars + B_PIN * 8);
          }
          const uint32_t fb = bars + (B_FULL + i) * 8;
          mbar_expect(fb, SLOT);
          tma2d(sb + i * SLOT, &tm_g, c64, i * 64, fb);
          tma2d(sb + i * SLOT + 8192, &tm_u, c64, i * 64, fb);
          PROF(3, 4 + i);
        }
      }
    }
    bar_sync<1, 128>();
    asm volatile("barrier.cluster.arrive.relaxed.aligned;" ::: "memory");
    if (warp == 12) {
      int slot = 5, ph = 1;
      auto wait_slot = [&]() { mbar_wait(bars + (B_EMPTY + slot) * 8, ph ^ (slot >= 5)); };
      auto adv = [&]() { if (++slot == NSLOT) { slot = 0; ph ^= 1; } };
      const int c32 = 224 * j + ((j & 1) ? 0 : 192);
#pragma unroll 1
      for (int i = 5; i < 25; i++) {
        wait_slot();
        if (elect()) {
          const uint32_t dst = sb + slot * SLOT, fb = bars + (B_FULL + slot) * 8;
          const bool last = i >= 21;
          const int cc = last ? c32 : c64 + 64 * (i / 7), rr = last ? slot * 128 : slot * 64;
          mbar_expect(fb, SLOT);
          tma2d(dst, last ? &tm_g32 : &tm_g, cc, rr, fb);
          tma2d(dst + 8192, last ? &tm_u32 : &tm_u, cc, rr, fb);
        }
        adv();
      }
      if (lane == 0) PROF(3, 0);
      mbar_wait(bars + B_PREP * 8, 0);
      if (lane == 0) PROF(3, 1);
#pragma unroll 1
      for (int i = 4; i < 16; i++) {
        if (lane == 0) PROF(3, 16 + i);
        wait_slot();
        if (elect()) {
          const int bytes = i < 14 ? 14336 : G_IMG / 2;
          const unsigned char* src = i < 14 ? g_Wd + (size_t)j * WD_IMG + i * 14336 : g_G + (size_t)(n * 4 + i - 12) * (G_IMG / 2);
          mbar_expect(bars + (B_FULL + slot) * 8, bytes);
          bulk_g2s(sb + slot * SLOT, src, bytes, bars + (B_FULL + slot) * 8);
        }
        adv();
      }
      if (lane == 0) PROF(3, 2);
    } else if (warp == 13) {
      mbar_wait(bars + B_PUBW * 8, 0);
      if (lane == 0) PROF(4, 7);
      mbar_wait(bars + B_PUBX * 8, 0);
      if (lane == 0) {
        PROF(4, 8);
        red_release(&g_cnt[(j >> 1) * 32]);
        red_relaxed(&g_cnt[6 * 32]);
        PROF(4, 18);
      }
      __syncwarp();
      mbar_wait(bars + B_PUBD * 8, 0);
      if (lane == 0) { PROF(4, 9); red_release(&g_cnt[4 * 32]); PROF(4, 19); }
      __syncwarp();
      mbar_wait(bars + B_LFREE * 8, 0);
      if (elect()) {
        mbar_expect(bars + B_GFULL * 8, G_IMG);
        bulk_g2s(sb + OFF_R + 28672, g_G + (size_t)(n * 2) * G_IMG, G_IMG, bars + B_GFULL * 8);
      }
    } else if (warp == 14) {
#pragma unroll 1
      for (int u = 0; u < 2; u++) {
        wait_ge(&g_cnt[(6 - 2 * u) * 32], (epoch + 1) * 128);
        fence_async_global();
        if (lane == 0) { mbar_arrive(bars + (B_PREPW - u) * 8); PROF(5, 9 - u); }
      }
    } else {
      mbar_wait(bars + B_XFREE * 8, 0);
      if (elect()) {
        prefetch_l2(reinterpret_cast<const unsigned char*>(w_gate) + bid * 12544, 12544);
        prefetch_l2(reinterpret_cast<const unsigned char*>(w_up) + bid * 12544, 12544);
      }
      mbar_wait(bars + (B_XFREE + 1) * 8, 0);
      if (elect()) {
        mbar_expect(bars + B_RFULL * 8, 12544);
        bulk_g2s(sb + OFF_R, reinterpret_cast<const unsigned char*>(w_down) + bid * 12544, 12544, bars + B_RFULL * 8);
      }
      if (bid < 113) {
        const int sl = (bid == 112) ? 0 : bid;
        wait_ge(&g_cnt[((sl & 1) + 2 * ((sl >> 1) / 28)) * 32], (epoch + 1) * 32);
        fence_async_global();
        if (elect()) {
          PROF(5, 16);
          mbar_expect(bars + B_XCFULL * 8, 16384);
          bulk_g2s(sb + OFF_EXCH, g_Xc + sl * 2 * S_, 16384, bars + B_XCFULL * 8);
        }
        mbar_wait(bars + B_PREPW * 8, 0);
        if (elect()) {
          mbar_expect(bars + B_WFULL * 8, 16384);
          bulk_g2s(sb + OFF_WS, g_Wt + bid * S_, 16384, bars + B_WFULL * 8);
          PROF(5, 17);
        }
      }
      mbar_wait(bars + B_PREP * 8, 0);
      if (elect()) {
        mbar_expect(bars + B_RFULL * 8, HALF_XR);
        bulk_g2s(sb + OFF_R, g_Wd + (size_t)j * WD_IMG, HALF_XR, bars + B_RFULL * 8);
        PROF(5, 19);
      }
      wait_ge(&g_cnt[5 * 32], (epoch + 1) * 128);
      fence_async_global();
      if (elect()) {
        PROF(5, 18);
        mbar_expect(bars + B_PQFULL * 8, HALF_XR + 256);
        const unsigned char* src = g_PQ + (size_t)(m * 2 + kh) * HALF_XR;
        bulk_g2s(sb + OFF_PQ, src, 28672, bars + B_PQFULL * 8);
        bulk_g2s(sb + OFF_PQ + 28672, src + 28672, 28672, bars + B_PQFULL * 8);
        bulk_g2s(sb + OFF_G, g_gate + m * 128 + kh * 64, 256, bars + B_PQFULL * 8);
      }
    }
    __syncwarp();
    asm volatile("barrier.cluster.wait.aligned;" ::: "memory");
  } else if (warp < 8) {
    asm volatile("setmaxnreg.inc.sync.aligned.u32 208;");
    const int wg = warp >> 2, w4 = warp & 3, g = lane >> 2, t = lane & 3;
    const int rh = wg ^ kh ^ 1;
    const int p = j & 1, r = (j >> 1) & 1, hh = j >> 2;
    const uint32_t epoch = ld_relaxed(&g_ep[bid]);
    if ((tid & 127) == 0) PROF(wg, 30);
#pragma unroll 1
    for (int it = tid; it < 392; it += 256) {
      const int kc = it / 28, sg = it - kc * 28;
      const int k = 2 * (28 * hh + sg) + r;
      const float kf = (float)k * (-6.283185307179586f / 448.0f), a0 = (float)(16 * kc + p) * kf;
      uint32_t c[4], s[4];
#pragma unroll
      for (int q = 0; q < 4; q++) {
        const float a1 = fmaf((float)(2 * q), kf, a0), a2 = fmaf((float)(2 * q + 8), kf, a0);
        c[q] = pack_bf16(__cosf(a1), __cosf(a2)); s[q] = pack_bf16(__sinf(a1), __sinf(a2));
        if (k == 0) s[q] = ((q ^ p) & 1) ? 0xBF80BF80u : 0x3F803F80u;
      }
      const uint32_t a = sb + 6 * SLOT + (kc * 56 + 2 * sg) * 16;
      sts128(a, c[0], c[1], c[2], c[3]);
      sts128(a + 16, s[0], s[1], s[2], s[3]);
    }
    if ((tid & 127) == 0) PROF(wg, 31);
    fence_async_smem();
    bar_sync<0, NTHREADS>();
    asm volatile("barrier.cluster.arrive.relaxed.aligned;" ::: "memory");
    if ((tid & 127) == 0) PROF(wg, 1);

    uint32_t xa[28][4];
    {
      const uint32_t xb = sb + OFF_PQ + wg * HALF_XR + (w4 * 16 + (lane & 15)) * 128;
      mbar_wait(bars + (B_XFULL + wg) * 8, 0);
      if ((tid & 127) == 0) PROF(wg, 2);
#pragma unroll
      for (int kb = 0; kb < 7; kb++) {
#pragma unroll
        for (int kk = 0; kk < 4; kk++) {
          uint32_t a = xb + kb * 8192 + (((2 * kk + (lane >> 4)) ^ (lane & 7)) << 4);
          asm volatile("ldmatrix.sync.aligned.m8n8.x4.shared.b16 {%0,%1,%2,%3}, [%4];"
                       : "=r"(xa[kb * 4 + kk][0]), "=r"(xa[kb * 4 + kk][1]), "=r"(xa[kb * 4 + kk][2]), "=r"(xa[kb * 4 + kk][3]) : "r"(a) : "memory");
        }
      }
    }
    {
      uint32_t ad[7][4];
      const uint32_t sel = p ? 0x7632 : 0x5410;
      const uint32_t sgn = r ? 0xBF80BF80u : 0x3F803F80u;
#pragma unroll
      for (int jj = 0; jj < 7; jj++) {
#pragma unroll
        for (int i = 0; i < 4; i++) {
          int ks = 2 * jj + (i >> 1), rr = i & 1;
          uint32_t lo = __byte_perm(xa[ks][rr], xa[ks][rr + 2], sel);
          uint32_t hi = __byte_perm(xa[ks + 14][rr], xa[ks + 14][rr + 2], sel);
          asm("fma.rn.bf16x2 %0, %1, %2, %3;" : "=r"(ad[jj][i]) : "r"(hi), "r"(sgn), "r"(lo));
        }
      }
      __syncwarp();
      if (lane == 0) mbar_arrive(bars + (B_XFREE + wg) * 8);
      float acc[28];
      wg_fence();
      uint64_t db = mkdesc(sb + 6 * SLOT, 896, 128, 0);
#pragma unroll
      for (int jj = 0; jj < 7; jj++) wgmma_rs_56<0>(acc, ad[jj], db + jj * 112, jj != 0);
      wg_commit();
      wg_wait<0>(); keep(acc);
      if (lane == 0) mbar_arrive(bars + (B_EMPTY + 6) * 8);
      uint32_t* xc = g_Xc + (size_t)((2 * (28 * hh + t) + r) * 2 + p) * S_ + m * 128 + rh * 64 + w4 * 16 + g;
#pragma unroll
      for (int i = 0; i < 7; i++) {
        xc[i * 16 * S_] = pack_bf16(acc[4 * i], acc[4 * i + 1]);
        xc[i * 16 * S_ + 8] = pack_bf16(acc[4 * i + 2], acc[4 * i + 3]);
      }
      __syncwarp();
      if (lane == 0) mbar_arrive(bars + B_PUBX * 8);
    }
    if ((tid & 127) == 0) PROF(wg, 3);
    const uint32_t tag = ~epoch & 1;
    unsigned char* const hbase = g_H + (size_t)(m * 2 + kh) * (56 * 4096) + rh * 2048 + (tid & 127) * 16;
#pragma unroll 1
    for (int u = 0; u < 3; u++) {
      float acc[64];
      if (wg == 1) { if (u & 1) bar_sync<6, 256>(); else bar_sync<2, 256>(); }
      const uint32_t sbu = opaque(sb);
#pragma unroll
      for (int kb = 0; kb < 7; kb++) {
        mbar_wait(sbu + OFF_BAR + (B_FULL + kb) * 8, u & 1);
        wg_fence();
        uint64_t db = mkdesc(sbu + kb * SLOT, 8192, 1024, 1);
#pragma unroll
        for (int kk = 0; kk < 4; kk++) wgmma_rs_128<1>(acc, xa[kb * 4 + kk], db + kk * 128, (kb | kk) != 0);
        wg_commit();
        if (kb == LEAD1 && wg == 0) { if (u & 1) bar_arrive<6, 256>(); else bar_arrive<2, 256>(); }
        if (kb > 0) { wg_wait<1>(); if (lane == 0) mbar_arrive(sbu + OFF_BAR + (B_EMPTY + kb - 1) * 8); }
      }
      wg_wait<0>(); keep(acc);
      if (lane == 0) mbar_arrive(sbu + OFF_BAR + (B_EMPTY + 6) * 8);
      if ((tid & 127) == 0) PROF(wg, 4 + 2 * u);
      h_epilogue<8>(acc, hbase + (u * 16 + n * 4) * 4096, tag);
      if ((tid & 127) == 0) PROF(wg, 5 + 2 * u);
    }
    {
      float acc[32];
      if (wg == 1) bar_sync<6, 256>();
      const uint32_t sbu = opaque(sb);
#pragma unroll
      for (int it = 0; it < 4; it++) {
        mbar_wait(sbu + OFF_BAR + (B_FULL + it) * 8, 1);
        wg_fence();
        uint64_t db = mkdesc(sbu + it * SLOT, 8192, 512, 2);
#pragma unroll
        for (int kk = 0; kk < 8; kk++) if (it * 8 + kk < 28) wgmma_rs_64<1>(acc, xa[it * 8 + kk], db + kk * 64, (it | kk) != 0);
        wg_commit();
        if (it == 2 && wg == 0) bar_arrive<6, 256>();
        if (it > 0) {
          wg_wait<1>();
          if (lane == 0) mbar_arrive(sbu + OFF_BAR + (B_EMPTY + it - 1) * 8);
#pragma unroll
          for (int i = it * 8 - 8; i < it * 8; i++) if (i < 4 * LA2) LDH(xa[i], hbase + i * 4096);
        }
      }
      wg_wait<0>(); keep(acc);
      if (lane == 0) mbar_arrive(sbu + OFF_BAR + (B_EMPTY + 3) * 8);
      if ((tid & 127) == 0) PROF(wg, 10);
      h_epilogue<4>(acc, hbase + (48 + n * 2) * 4096, tag);
    }
    asm volatile("barrier.cluster.wait.aligned;" ::: "memory");
    if ((tid & 127) == 0) PROF(wg, 11);

    float acc[56];
    if (wg == 1) bar_sync<2, 256>();
#pragma unroll 1
    for (int it = 0; it < 2; it++) {
#pragma unroll
      for (int e = 0; e < 7; e++) {
        if ((tid & 127) == 0) PROF(wg, 16 + it * 7 + e);
        const bool inr = e < 4 && it == 0;
        if (e >= 4 || it == 1) mbar_wait(bars + (B_FULL + e) * 8, e < 4 ? 0 : it ^ 1);
        else if (e == 0) mbar_wait(bars + B_RFULL * 8, 1);
        frag_ready(xa[e * 4], xa[e * 4 + 1], xa[e * 4 + 2], xa[e * 4 + 3], hbase + (it * 7 + e) * 16384, tag);
        wg_fence();
        const uint64_t db = mkdesc(inr ? sb + OFF_R + e * 14336 : sb + e * SLOT, 1792, 128, 0);
#pragma unroll
        for (int kk = 0; kk < 4; kk++) wgmma_rs_112<1>(acc, xa[e * 4 + kk], db + kk * 224, (e | kk) ? 1 : it);
        wg_commit();
        if (e == 1 && it == 0 && wg == 0) bar_arrive<2, 256>();
        if (it == 0 || e + LA2 < 7) {
          const int nb = it * 7 + e + LA2;
#pragma unroll
          for (int kk = 0; kk < 4; kk++) LDH(xa[((e + LA2) % 7) * 4 + kk], hbase + (nb * 4 + kk) * 4096);
        }
        wg_wait<1>();
        if (lane == 0) {
          if (it == 0 ? e >= 5 : e <= 2) mbar_arrive(bars + (B_EMPTY + (e + 6) % 7) * 8);
          if (e == 4 && it == 0) {
            mbar_arrive(bars + B_LFREE * 8);
            asm volatile("{\n.reg .b32 ra;\nmapa.shared::cluster.u32 ra, %0, %1;\nmbarrier.arrive.relaxed.cluster.shared::cluster.b64 _, [ra];\n}"
                         :: "r"(bars + B_RFREE * 8), "r"(kh ^ 1) : "memory");
          }
        }
      }
    }
    const int t128 = tid & 127;
    wg_wait<0>(); keep(acc);
    if (wg == 0) {
      if (t128 == 0) PROF(wg, 12);
      mbar_wait_cluster(bars + B_RFREE * 8, 0);
      uint32_t rdst, rbar;
      asm volatile("mapa.shared::cluster.u32 %0, %1, %2;" : "=r"(rdst) : "r"(sb + OFF_R + t128 * 16), "r"(kh ^ 1));
      asm volatile("mapa.shared::cluster.u32 %0, %1, %2;" : "=r"(rbar) : "r"(bars + B_RECV * 8), "r"(kh ^ 1));
#pragma unroll
      for (int i = 0; i < 14; i++)
        asm volatile("st.async.weak.shared::cluster.mbarrier::complete_tx::bytes.v4.f32 [%0], {%1,%2,%3,%4}, [%5];"
                     :: "r"(rdst + i * 2048), "f"(acc[4 * i]), "f"(acc[4 * i + 1]), "f"(acc[4 * i + 2]), "f"(acc[4 * i + 3]), "r"(rbar) : "memory");
    } else {
      float spec[2][28];
      if (t128 == 0) PROF(wg, 12);
      mbar_wait(bars + B_PQFULL * 8, 0);
      if (t128 == 0) { PROF(wg, 13); g_ep[bid] = epoch + 1; }
#pragma unroll
      for (int i = 0; i < 4; i++) {
        if (i == 0) mbar_wait(bars + B_GFULL * 8, 0);
        if (i >= 2) mbar_wait(bars + (B_FULL + i - 2) * 8, 1);
        wg_fence();
        const uint64_t da = mkdesc(sb + OFF_PQ + i * 14336, 1024, 1024, 1);
        const uint64_t db = mkdesc(i < 2 ? sb + OFF_R + 28672 + i * (G_IMG / 2) : sb + (i - 2) * SLOT, 896, 128, 0);
#pragma unroll
        for (int kk = 0; kk < 7; kk++) wgmma_ss_56<1, 0>(spec[i >> 1], da + kk * 128, db + kk * 112, ((i & 1) | kk) != 0);
        wg_commit();
      }
      const float* gs = reinterpret_cast<const float*>(smem + OFF_G) + w4 * 16 + g;
      const float o0 = bf16_round(1.0f - gs[0]), o1 = bf16_round(1.0f - gs[8]);
      const float g0 = gs[0] * (1.0f / (float)(S_ * D_)), g1 = gs[8] * (1.0f / (float)(S_ * D_));
      wg_wait<0>(); keep(spec[0]); keep(spec[1]);
      if (t128 == 0) PROF(wg, 14);
      mbar_wait_cluster(bars + B_RECV * 8, 0);
      if (t128 == 0) PROF(wg, 0);
      float4 o[14];
#pragma unroll
      for (int i = 0; i < 14; i++) o[i] = lds128f(sb + OFF_R + t128 * 16 + i * 2048);
      bar_sync<5, 128>();
      const uint32_t st = sb + OFF_PQ + w4 * 3840;
#pragma unroll
      for (int i = 0; i < 7; i++) {
        uint32_t pk[4];
#pragma unroll
        for (int e = 0; e < 2; e++) {
          const int c = 2 * i + e, si = i * 4 + e;
          pk[2 * e] = pack_bf16(fmaf(acc[4 * c] + o[c].x, o0, g0 * spec[0][si]), fmaf(acc[4 * c + 1] + o[c].y, o0, g0 * spec[1][si]));
          pk[2 * e + 1] = pack_bf16(fmaf(acc[4 * c + 2] + o[c].z, o1, g1 * spec[0][si + 2]), fmaf(acc[4 * c + 3] + o[c].w, o1, g1 * spec[1][si + 2]));
        }
        asm volatile("stmatrix.sync.aligned.m8n8.x4.shared.b16 [%0], {%1,%2,%3,%4};"
                     :: "r"(st + (lane & 15) * 240 + (lane >> 4) * 16 + i * 32), "r"(pk[0]), "r"(pk[1]), "r"(pk[2]), "r"(pk[3]) : "memory");
      }
      __syncwarp();
      if (lane < 28) {
        const int r2 = lane >= 14, cc = lane - r2 * 14;
        unsigned char* ob = reinterpret_cast<unsigned char*>(out) + (size_t)(m * 128 + kh * 64 + w4 * 16 + r2) * (D_ * 2) + n * 224 + cc * 16;
        float4 v[8];
#pragma unroll
        for (int i = 0; i < 8; i++) v[i] = lds128f(st + r2 * 240 + cc * 16 + i * 480);
#pragma unroll
        for (int i = 0; i < 8; i++) stg128(ob + i * (D_ * 4), __float_as_uint(v[i].x), __float_as_uint(v[i].y), __float_as_uint(v[i].z), __float_as_uint(v[i].w));
      }
    }
    if (t128 == 0) { PROF(wg, 15); if (wg) { PROFG(4, 30); PROF(4, 31); } }
  } else {
    asm volatile("setmaxnreg.dec.sync.aligned.u32 72;");
    const int t = tid - 256;
    const int k = bid;
    if (t == 0) PROF(2, 0);
    uint4 gv[7];
#pragma unroll
    for (int i = 0; i < 7; i++) gv[i] = ldg128(reinterpret_cast<const uint4*>(gate_w) + i * 8 + (t & 7));
    if (t < 98) {
      int cid = m * 98 + t, kc = cid / 56, nn = cid - kc * 56;
      int d = 112 * n + 8 * (2 * (nn >> 3) + (nn & 1)) + (nn & 6) + kh;
      int dr = d > 224 ? d - 448 : d;
      const float df = (float)dr * (-6.283185307179586f / 448.0f);
      uint32_t pk[4];
#pragma unroll
      for (int e = 0; e < 4; e++) {
        const float a = (float)(4 * kc + e) * df;
        pk[e] = pack_bf16(2.0f * __cosf(a), 2.0f * __sinf(a));
      }
      if (kc == 0) pk[0] = (((d >> 1) ^ kh) & 1) ? 0xBF803F80u : 0x3F803F80u;
      stg128(g_G + (size_t)(n * 2 + kh) * G_IMG + cid * 16, pk[0], pk[1], pk[2], pk[3]);
    }
    bar_sync<0, NTHREADS>();
    asm volatile("barrier.cluster.arrive.relaxed.aligned;" ::: "memory");
    mbar_wait(bars + B_PIN * 8, 0);
    if (t == 0) PROF(2, 4);
    {
      const uint32_t wa = sb + 5 * SLOT + (((t & 7) - bid) & 7) * 450 + (t >> 3) * 2, wc = wa + 448 - (t >> 3) * 4;
      uint2* dst = g_Wt + (t >> 3) * S_ + 16 * bid + 2 * (t & 7);
#pragma unroll 1
      for (int h = 0; h < 2; h++) {
        uint32_t w[4][8];
#pragma unroll
        for (int i = 0; i < 4; i++) {
#pragma unroll
          for (int e = 0; e < 4; e++) { w[i][2 * e] = lds16(wa + h * 128 + i * 32 + e * 3600); w[i][2 * e + 1] = lds16(wc - h * 128 - i * 32 + e * 3600); }
        }
#pragma unroll
        for (int i = 0; i < 4; i++)
          if (i < 3 || h == 0 || t < 8)
            stg128(dst + (h * 64 + i * 16) * S_, __byte_perm(w[i][0], w[i][1], 0x5410), __byte_perm(w[i][4], w[i][5], 0x5410), __byte_perm(w[i][2], w[i][3], 0x5410), __byte_perm(w[i][6], w[i][7], 0x5410));
      }
    }
    __syncwarp();
    if (lane < 3) mbar_arrive(bars + (lane ? B_EMPTY + 5 : B_PUBW) * 8);
    if (t == 0) PROF(2, 6);
    {
      const int row = n * 16 + (t >> 3), l8 = t & 7;
      mbar_wait(bars + (B_XFULL + 1) * 8, 0);
      float sum = 0.f;
#pragma unroll
      for (int i = 0; i < 7; i++) {
        const uint4 a = lds128(sb + OFF_R + i * 8192 + row * 128 + ((l8 ^ (row & 7)) << 4));
        const uint32_t aa[4] = {a.x, a.y, a.z, a.w}, bb[4] = {gv[i].x, gv[i].y, gv[i].z, gv[i].w};
#pragma unroll
        for (int e = 0; e < 4; e++) {
          const uint32_t pr = as_u(__hmul2(as_b2(aa[e]), as_b2(bb[e])));
          sum += bf_lo(pr) + bf_hi(pr);
        }
      }
      sum += __shfl_xor_sync(0xffffffffu, sum, 1); sum += __shfl_xor_sync(0xffffffffu, sum, 2); sum += __shfl_xor_sync(0xffffffffu, sum, 4);
      if (lane == 0) mbar_arrive(bars + (B_XFREE + 1) * 8);
      if (l8 == 0) g_gate[m * 128 + kh * 64 + row] = bf16_round(__fdividef(1.0f, 1.0f + __expf(-bf16_round(sum))));
    }
    if (t == 0) PROF(2, 11);
    mbar_wait(bars + B_XFREE * 8, 0);
    if (k < 113) {
      const float u = -6.283185307179586f / 2048.0f, t2 = (float)(2 * t) * u, rr = (float)(t >> 4) * u;
#pragma unroll 1
      for (int i = 0; i < 4; i++) {
        const float q = (float)(2 * i), l = (float)((t & 15) + 64 * i);
        sts128(sb + OFF_TW + i * 2048 + t * 16, cis(t2 * q), cis((t2 + u) * q), cis(t2 * (q + 1.0f)), cis((t2 + u) * (q + 1.0f)));
        sts128(sb + OFF_TW + 8192 + i * 2048 + t * 16, cis(rr * l), cis(rr * (l + 16.0f)), cis(rr * (l + 32.0f)), cis(rr * (l + 48.0f)));
      }
      const float l = (float)((t >> 1) & 15) * (8.0f * u), jj = (float)((t >> 5) * 4 + (t & 1) * 2);
      sts64(sb + OFF_TW + 16384 + t * 8, cis(l * jj), cis(l * (jj + 1.0f)));
    }
    if (t == 0) PROF(2, 9);
    mbar_wait(bars + B_RFULL * 8, 0);
    if (t < 112) {
      const int js = bid >> 4, nn = (t >> 1) / 14, cc = (t >> 1) - nn * 14;
      unsigned char* wdst = g_Wd + (size_t)((js >> 2) * 4 + nn) * WD_IMG + cc * 128 + (t & 1) * 16;
      uint4 v[7];
#pragma unroll
      for (int i = 0; i < 7; i++) v[i] = lds128(sb + OFF_R + i * 1792 + (t & 1) * 896 + (t >> 1) * 16);
#pragma unroll
      for (int i = 0; i < 7; i++) {
        int col = 14 * (bid & 15) + 2 * i - (js & 1) * 32;
        if (col < 0) col += 224;
        const int kpos = col < 192 ? (col >> 6) * 256 + (js & 3) * 64 + (col & 63) : 576 + (js & 3) * 32 + col;
        stg128(wdst + (kpos >> 3) * 1792 + (kpos & 7) * 16, v[i].x, v[i].y, v[i].z, v[i].w);
      }
    }
    __syncwarp();
    if (lane == 0) mbar_arrive(bars + B_PUBD * 8);
    bar_sync<3, 128>();
    if (k < 113) {
      if (t == 0) PROF(2, 2);
      mbar_wait(bars + B_XCFULL * 8, 0);
      if (t == 0) PROF(2, 3);
      c2 v[16];
      const uint32_t se = k == 0 ? 0x4410 : (k == 112 ? 0x4432 : 0x3210), so = k == 0 ? 0x4410 : (k == 112 ? 0x3244 : 0x3210);
#pragma unroll
      for (int jj = 0; jj < 8; jj++) {
        const uint2 e2 = lds64(sb + OFF_EXCH + jj * 1024 + t * 8), o2 = lds64(sb + OFF_EXCH + 8192 + jj * 1024 + t * 8);
#pragma unroll
        for (int h = 0; h < 2; h++) {
          const b2 e = as_b2(__byte_perm(h ? e2.y : e2.x, 0, se)), o = as_b2(__byte_perm(h ? o2.y : o2.x, 0, so));
          const uint32_t s = as_u(__hadd2(e, o)), d = as_u(__hsub2(e, o)) ^ 0x80000000u;
          v[2 * jj + h] = mk(as_b2(__byte_perm(s, d, 0x5410)), as_b2(__byte_perm(s, d, 0x7632)));
        }
      }
      if (t == 0) PROF(2, 12);
      columns(v, sb, t);
      if (t == 0) PROF(2, 14);
      const int pre = (k == 112) ? 1 : 2 * k, pim = (k == 112) ? 1 : 2 * k + 1;
      uint32_t* pq = reinterpret_cast<uint32_t*>(g_PQ) + (t >> 5) * 14336;
      uint32_t* pr = pq + pre * 32 + ((((lane >> 2) ^ pre) & 7) << 2) + (lane & 3);
      uint32_t* pi = pq + pim * 32 + ((((lane >> 2) ^ pim) & 7) << 2) + (lane & 3);
#pragma unroll
      for (int jj = 0; jj < 8; jj++) {
        const b2 ar = as_b2(__byte_perm(as_u(v[2 * jj].y), as_u(v[2 * jj + 1].y), 0x5410)), br = as_b2(__byte_perm(as_u(v[2 * jj].y), as_u(v[2 * jj + 1].y), 0x7632));
        const b2 ai = as_b2(__byte_perm(as_u(v[2 * jj].x), as_u(v[2 * jj + 1].x), 0x5410)), bi = as_b2(__byte_perm(as_u(v[2 * jj].x), as_u(v[2 * jj + 1].x), 0x7632));
        pr[jj * 57344] = as_u(__hadd2(ar, br));
        if (k != 112) pr[jj * 57344 + 7168] = as_u(__hsub2(ar, br));
        if (k != 0) pi[jj * 57344 + 7168] = as_u(__hadd2(ai, bi));
        if (k != 0 && k != 112) pi[jj * 57344] = as_u(__hsub2(ai, bi));
      }
      fence_async_smem();
    }
    bar_sync<3, 128>();
    if (t == 0) { PROF(2, 5); red_release(&g_cnt[5 * 32]); PROF(2, 7); }
    __syncwarp();
    asm volatile("barrier.cluster.wait.aligned;" ::: "memory");
  }
}

typedef CUresult (*EncodeFn)(CUtensorMap*, CUtensorMapDataType, cuuint32_t, void*, const cuuint64_t*, const cuuint64_t*, const cuuint32_t*,
                             const cuuint32_t*, CUtensorMapInterleave, CUtensorMapSwizzle, CUtensorMapL2promotion, CUtensorMapFloatOOBfill);

void make_map(EncodeFn enc, CUtensorMap* tm, const void* base, int cols, int rows, int bc, int br, CUtensorMapSwizzle sw) {
  cuuint64_t gd[2] = {(cuuint64_t)cols, (cuuint64_t)rows};
  cuuint64_t gs[1] = {(cuuint64_t)cols * 2};
  cuuint32_t bd[2] = {(cuuint32_t)bc, (cuuint32_t)br};
  cuuint32_t es[2] = {1, 1};
  enc(tm, CU_TENSOR_MAP_DATA_TYPE_BFLOAT16, 2, const_cast<void*>(base), gd, gs, bd, es, CU_TENSOR_MAP_INTERLEAVE_NONE, sw,
      CU_TENSOR_MAP_L2_PROMOTION_L2_128B, CU_TENSOR_MAP_FLOAT_OOB_FILL_NONE);
}

}

extern "C" void kernel_launch(void* const* d_in, const int* in_sizes, int n_in, void* d_out, int out_size) {
  (void)in_sizes; (void)n_in; (void)out_size;
  const __nv_bfloat16* x = (const __nv_bfloat16*)d_in[0];
  const __nv_bfloat16* w_r = (const __nv_bfloat16*)d_in[1];
  const __nv_bfloat16* w_i = (const __nv_bfloat16*)d_in[2];
  const __nv_bfloat16* w_gate = (const __nv_bfloat16*)d_in[4];
  const __nv_bfloat16* w_up = (const __nv_bfloat16*)d_in[5];
  const __nv_bfloat16* w_down = (const __nv_bfloat16*)d_in[6];
  const __nv_bfloat16* gate_w = (const __nv_bfloat16*)d_in[7];
  static EncodeFn enc = nullptr;
  static bool ok = false;
  if (!enc) {
    cudaDriverEntryPointQueryResult qr;
    cudaGetDriverEntryPoint("cuTensorMapEncodeTiled", (void**)&enc, cudaEnableDefault, &qr);
    cudaFuncSetAttribute(fused_kernel, cudaFuncAttributeMaxDynamicSharedMemorySize, SMEM_BYTES);
    cudaFuncAttributes fa;
    cudaFuncGetAttributes(&fa, fused_kernel);
    ok = (fa.numRegs == 128);
  }
  if (!ok) return;
  CUtensorMap tx, tg, tu, tg32, tu32;
  {
    cuuint64_t gd[3] = {64, (cuuint64_t)S_, 7};
    cuuint64_t gs[2] = {(cuuint64_t)D_ * 2, 128};
    cuuint32_t bd[3] = {64, 64, 7};
    cuuint32_t es[3] = {1, 1, 1};
    enc(&tx, CU_TENSOR_MAP_DATA_TYPE_BFLOAT16, 3, const_cast<__nv_bfloat16*>(x), gd, gs, bd, es, CU_TENSOR_MAP_INTERLEAVE_NONE, CU_TENSOR_MAP_SWIZZLE_128B,
        CU_TENSOR_MAP_L2_PROMOTION_L2_128B, CU_TENSOR_MAP_FLOAT_OOB_FILL_NONE);
  }
  make_map(enc, &tg, w_gate, F_, D_, 64, 64, CU_TENSOR_MAP_SWIZZLE_128B);
  make_map(enc, &tu, w_up, F_, D_, 64, 64, CU_TENSOR_MAP_SWIZZLE_128B);
  make_map(enc, &tg32, w_gate, F_, D_, 32, 128, CU_TENSOR_MAP_SWIZZLE_64B);
  make_map(enc, &tu32, w_up, F_, D_, 32, 128, CU_TENSOR_MAP_SWIZZLE_64B);
  fused_kernel<<<128, NTHREADS, SMEM_BYTES>>>(tx, tg, tu, tg32, tu32, x, w_r, w_i, w_gate, w_up, w_down, gate_w, (__nv_bfloat16*)d_out);
}
```

```cpp
#include <cuda_runtime.h>
#include <cuda_bf16.h>
#include <cuda.h>
#include <stdint.h>

namespace {

constexpr int S_ = 2048, D_ = 448, F_ = 1792;
constexpr int NTHREADS = 512;
constexpr int SLOT = 16384, NSLOT = 7;
constexpr int HALF_XR = 57344;
constexpr int OFF_PQ = NSLOT * SLOT;
constexpr int OFF_R = OFF_PQ + HALF_XR;
constexpr int OFF_EXCH = OFF_PQ;
constexpr int OFF_WS = OFF_EXCH + 18432;
constexpr int OFF_TW = OFF_WS + 16384;
constexpr int OFF_MISC = OFF_R + HALF_XR;
constexpr int OFF_G = OFF_MISC;
constexpr int OFF_BAR = OFF_MISC + 512;
constexpr int SMEM_BYTES = OFF_BAR + 512;
constexpr int B_FULL = 0, B_EMPTY = 7, B_XFULL = 14  ;
constexpr int B_XFREE = 16  , B_PUBX = 18, B_RFREE = 19, B_LFREE = 20;
constexpr int B_PUBW = 21, B_PUBD = 22;
constexpr int B_PQFULL = 23, B_RECV = 24, B_WFULL = 25, B_XCFULL = 26, B_PREP = 27, B_PREPW = 28, B_RFULL = 29, B_GFULL = 30, B_END = 31, B_PIN = 31;

constexpr int WD_IMG = 896 * 112 * 2;
constexpr int G_IMG = 224 * 56 * 2;

__device__ __align__(1024) uint32_t g_Xc[112 * 2 * S_];
__device__ __align__(1024) unsigned char g_H[32 * 56 * 4096];
__device__ __align__(1024) unsigned char g_PQ[32 * HALF_XR];
__device__ __align__(1024) unsigned char g_Wd[8 * WD_IMG];
__device__ __align__(1024) unsigned char g_G[8 * G_IMG];
__device__ __align__(1024) uint2 g_Wt[113 * S_];
__device__ __align__(1024) float g_gate[S_];
__device__ __align__(128) unsigned int g_ep[128];
__device__ __align__(128) unsigned int g_cnt[8 * 32];

#define PROF(role, idx) do {} while (0)
#define PROFG(role, idx) do {} while (0)

__device__ __forceinline__ uint32_t s2u(const void* p) { return (uint32_t)__cvta_generic_to_shared(p); }
__device__ __forceinline__ void mbar_init(uint32_t b, int c) { asm volatile("mbarrier.init.shared::cta.b64 [%0], %1;" :: "r"(b), "r"(c) : "memory"); }
__device__ __forceinline__ void mbar_expect(uint32_t b, int bytes) { asm volatile("mbarrier.arrive.expect_tx.shared::cta.b64 _, [%0], %1;" :: "r"(b), "r"(bytes) : "memory"); }
__device__ __forceinline__ void mbar_arrive(uint32_t b) { asm volatile("mbarrier.arrive.shared::cta.b64 _, [%0];" :: "r"(b) : "memory"); }
__device__ __forceinline__ void mbar_wait(uint32_t b, int ph) {
  asm volatile("{\n.reg .pred p;\n.reg .u32 c;\nmov.u32 c, 0;\nL_WAIT:\nmbarrier.try_wait.parity.shared::cta.b64 p, [%0], %1;\n@p bra.uni L_DONE;\n"
               "add.u32 c, c, 1;\nsetp.lt.u32 p, c, 4194304;\n@p bra.uni L_WAIT;\ntrap;\nL_DONE:\n}" :: "r"(b), "r"(ph) : "memory");
}
__device__ __forceinline__ void mbar_wait_cluster(uint32_t b, int ph) {
  asm volatile("{\n.reg .pred p;\n.reg .u32 c;\nmov.u32 c, 0;\nL_WAIT:\nmbarrier.try_wait.parity.acquire.cluster.shared::cta.b64 p, [%0], %1;\n@p bra.uni L_DONE;\n"
               "add.u32 c, c, 1;\nsetp.lt.u32 p, c, 4194304;\n@p bra.uni L_WAIT;\ntrap;\nL_DONE:\n}" :: "r"(b), "r"(ph) : "memory");
}
__device__ __forceinline__ uint32_t ld_acquire(const unsigned int* p) { uint32_t v; asm volatile("ld.acquire.gpu.global.u32 %0, [%1];" : "=r"(v) : "l"(p) : "memory"); return v; }
__device__ __forceinline__ uint32_t ld_relaxed(const unsigned int* p) { uint32_t v; asm volatile("ld.relaxed.gpu.global.u32 %0, [%1];" : "=r"(v) : "l"(p) : "memory"); return v; }
__device__ __forceinline__ void wait_ge(const unsigned int* p, uint32_t target) {
#pragma unroll 1
  for (int i = 0; i < (1 << 22); i++) { if ((int)(ld_acquire(p) - target) >= 0) return; }
  __trap();
}
__device__ __forceinline__ void red_release(unsigned int* p) { asm volatile("red.release.gpu.global.add.u32 [%0], 1;" :: "l"(p) : "memory"); }
__device__ __forceinline__ void red_relaxed(unsigned int* p) { asm volatile("red.relaxed.gpu.global.add.u32 [%0], 1;" :: "l"(p) : "memory"); }
__device__ __forceinline__ bool elect() { uint32_t p; asm volatile("{\n.reg .pred p;\nelect.sync _|p, 0xffffffff;\nselp.u32 %0, 1, 0, p;\n}" : "=r"(p)); return p; }
__device__ __forceinline__ void fence_async_smem() { asm volatile("fence.proxy.async.shared::cta;" ::: "memory"); }
__device__ __forceinline__ void fence_async_global() { asm volatile("fence.proxy.async.global;" ::: "memory"); }
template <int ID, int N> __device__ __forceinline__ void bar_sync() { asm volatile("bar.sync %0, %1;" :: "n"(ID), "n"(N) : "memory"); }
template <int ID, int N> __device__ __forceinline__ void bar_arrive() { asm volatile("bar.arrive %0, %1;" :: "n"(ID), "n"(N) : "memory"); }
__device__ __forceinline__ void tma2d(uint32_t dst, const CUtensorMap* tm, int c0, int c1, uint32_t bar) {
  asm volatile("cp.async.bulk.tensor.2d.shared::cluster.global.mbarrier::complete_tx::bytes [%0], [%1, {%3, %4}], [%2];"
               :: "r"(dst), "l"(tm), "r"(bar), "r"(c0), "r"(c1) : "memory");
}
__device__ __forceinline__ void tma3d(uint32_t dst, const CUtensorMap* tm, int c0, int c1, int c2, uint32_t bar) {
  asm volatile("cp.async.bulk.tensor.3d.shared::cluster.global.mbarrier::complete_tx::bytes [%0], [%1, {%3, %4, %5}], [%2];"
               :: "r"(dst), "l"(tm), "r"(bar), "r"(c0), "r"(c1), "r"(c2) : "memory");
}
__device__ __forceinline__ void bulk_g2s(uint32_t dst, const void* src, int bytes, uint32_t bar) {
  asm volatile("cp.async.bulk.shared::cluster.global.mbarrier::complete_tx::bytes [%0], [%1], %2, [%3];"
               :: "r"(dst), "l"(src), "r"(bytes), "r"(bar) : "memory");
}
__device__ __forceinline__ void prefetch_l2(const void* src, int bytes) {
  asm volatile("cp.async.bulk.prefetch.L2.global [%0], %1;" :: "l"(src), "r"(bytes) : "memory");
}
__device__ __forceinline__ void prefetch_tma2d(const CUtensorMap* tm, int c0, int c1) {
  asm volatile("cp.async.bulk.prefetch.tensor.2d.L2.global [%0, {%1, %2}];" :: "l"(tm), "r"(c0), "r"(c1) : "memory");
}
__device__ __forceinline__ uint64_t mkdesc(uint32_t addr, uint32_t lbo, uint32_t sbo, uint32_t mode) {
  return (uint64_t)((addr & 0x3FFFF) >> 4) | ((uint64_t)(lbo >> 4) << 16) | ((uint64_t)(sbo >> 4) << 32) | ((uint64_t)mode << 62);
}
__device__ __forceinline__ void wg_fence() { asm volatile("wgmma.fence.sync.aligned;" ::: "memory"); }
__device__ __forceinline__ void wg_commit() { asm volatile("wgmma.commit_group.sync.aligned;" ::: "memory"); }
template <int N> __device__ __forceinline__ void wg_wait() { asm volatile("wgmma.wait_group.sync.aligned %0;" :: "n"(N) : "memory"); }
template <int N> __device__ __forceinline__ void keep(float (&d)[N]) {
#pragma unroll
  for (int i = 0; i < N; i++) asm volatile("" : "+f"(d[i]) :: "memory");
}
__device__ __forceinline__ uint32_t pack_bf16(float lo, float hi) { uint32_t r; asm("cvt.rn.bf16x2.f32 %0, %1, %2;" : "=r"(r) : "f"(hi), "f"(lo)); return r; }
__device__ __forceinline__ float bf16_round(float v) { return __bfloat162float(__float2bfloat16_rn(v)); }
__device__ __forceinline__ void sts128(uint32_t a, uint32_t x, uint32_t y, uint32_t z, uint32_t w) { asm volatile("st.shared.v4.b32 [%0], {%1,%2,%3,%4};" :: "r"(a), "r"(x), "r"(y), "r"(z), "r"(w) : "memory"); }
__device__ __forceinline__ float4 lds128f(uint32_t a) { float4 v; asm volatile("ld.shared.v4.f32 {%0,%1,%2,%3}, [%4];" : "=f"(v.x), "=f"(v.y), "=f"(v.z), "=f"(v.w) : "r"(a) : "memory"); return v; }

__device__ __forceinline__ uint2 lds64(uint32_t a) { uint2 v; asm volatile("ld.shared.v2.b32 {%0,%1}, [%2];" : "=r"(v.x), "=r"(v.y) : "r"(a) : "memory"); return v; }
__device__ __forceinline__ float bf_lo(uint32_t w) { return __uint_as_float(w << 16); }
__device__ __forceinline__ float bf_hi(uint32_t w) { return __uint_as_float(w & 0xffff0000u); }
__device__ __forceinline__ uint32_t opaque(uint32_t v) { asm volatile("" : "+r"(v)); return v; }
__device__ __forceinline__ uint4 ldg128(const void* p) { uint4 v; asm volatile("ld.global.nc.v4.b32 {%0,%1,%2,%3}, [%4];" : "=r"(v.x), "=r"(v.y), "=r"(v.z), "=r"(v.w) : "l"(p)); return v; }
__device__ __forceinline__ void stg128(void* p, uint32_t x, uint32_t y, uint32_t z, uint32_t w) { asm volatile("st.global.v4.b32 [%0], {%1,%2,%3,%4};" :: "l"(p), "r"(x), "r"(y), "r"(z), "r"(w) : "memory"); }
__device__ __forceinline__ void stg128_l2(void* p, uint32_t x, uint32_t y, uint32_t z, uint32_t w) { asm volatile("st.relaxed.gpu.global.v4.b32 [%0], {%1,%2,%3,%4};" :: "l"(p), "r"(x), "r"(y), "r"(z), "r"(w) : "memory"); }
__device__ __forceinline__ void ldg128_na(uint32_t (&v)[4], const void* p) { asm volatile("ld.global.L1::no_allocate.v4.b32 {%0,%1,%2,%3}, [%4];" : "=r"(v[0]), "=r"(v[1]), "=r"(v[2]), "=r"(v[3]) : "l"(p) : "memory"); }
__device__ __forceinline__ void ldg128_l2(uint32_t (&v)[4], const void* p) { asm volatile("ld.relaxed.gpu.global.v4.b32 {%0,%1,%2,%3}, [%4];" : "=r"(v[0]), "=r"(v[1]), "=r"(v[2]), "=r"(v[3]) : "l"(p) : "memory"); }
__device__ __forceinline__ uint4 lds128(uint32_t a) { uint4 v; asm volatile("ld.shared.v4.b32 {%0,%1,%2,%3}, [%4];" : "=r"(v.x), "=r"(v.y), "=r"(v.z), "=r"(v.w) : "r"(a) : "memory"); return v; }
__device__ __forceinline__ uint32_t lds16(uint32_t a) { uint32_t v; asm volatile("ld.shared.u16 %0, [%1];" : "=r"(v) : "r"(a) : "memory"); return v; }
__device__ __forceinline__ void sts64(uint32_t a, uint32_t x, uint32_t y) { asm volatile("st.shared.v2.b32 [%0], {%1,%2};" :: "r"(a), "r"(x), "r"(y) : "memory"); }
template <int TB> __device__ __forceinline__ void wgmma_rs_128(float (&d)[64], const uint32_t (&a)[4], uint64_t db, int sc) {
  asm volatile("{\n.reg .pred p;\nsetp.ne.b32 p, %69, 0;\n"
    "wgmma.mma_async.sync.aligned.m64n128k16.f32.bf16.bf16 {%0, %1, %2, %3, %4, %5, %6, %7, %8, %9, %10, %11, %12, %13, %14, %15, %16, %17, %18, %19, %20, %21, %22, %23, %24, %25, %26, %27, %28, %29, %30, %31, %32, %33, %34, %35, %36, %37, %38, %39, %40, %41, %42, %43, %44, %45, %46, %47, %48, %49, %50, %51, %52, %53, %54, %55, %56, %57, %58, %59, %60, %61, %62, %63}, {%64, %65, %66, %67}, %68, p, 1, 1, %70;\n}\n"
    : "+f"(d[0]), "+f"(d[1]), "+f"(d[2]), "+f"(d[3]), "+f"(d[4]), "+f"(d[5]), "+f"(d[6]), "+f"(d[7]), "+f"(d[8]), "+f"(d[9]), "+f"(d[10]), "+f"(d[11]), "+f"(d[12]), "+f"(d[13]), "+f"(d[14]), "+f"(d[15]), "+f"(d[16]), "+f"(d[17]), "+f"(d[18]), "+f"(d[19]), "+f"(d[20]), "+f"(d[21]), "+f"(d[22]), "+f"(d[23]), "+f"(d[24]), "+f"(d[25]), "+f"(d[26]), "+f"(d[27]), "+f"(d[28]), "+f"(d[29]), "+f"(d[30]), "+f"(d[31]), "+f"(d[32]), "+f"(d[33]), "+f"(d[34]), "+f"(d[35]), "+f"(d[36]), "+f"(d[37]), "+f"(d[38]), "+f"(d[39]), "+f"(d[40]), "+f"(d[41]), "+f"(d[42]), "+f"(d[43]), "+f"(d[44]), "+f"(d[45]), "+f"(d[46]), "+f"(d[47]), "+f"(d[48]), "+f"(d[49]), "+f"(d[50]), "+f"(d[51]), "+f"(d[52]), "+f"(d[53]), "+f"(d[54]), "+f"(d[55]), "+f"(d[56]), "+f"(d[57]), "+f"(d[58]), "+f"(d[59]), "+f"(d[60]), "+f"(d[61]), "+f"(d[62]), "+f"(d[63])
    : "r"(a[0]), "r"(a[1]), "r"(a[2]), "r"(a[3]), "l"(db), "r"(sc), "n"(TB));
}
template <int TB> __device__ __forceinline__ void wgmma_rs_64(float (&d)[32], const uint32_t (&a)[4], uint64_t db, int sc) {
  asm volatile("{\n.reg .pred p;\nsetp.ne.b32 p, %37, 0;\n"
    "wgmma.mma_async.sync.aligned.m64n64k16.f32.bf16.bf16 {%0, %1, %2, %3, %4, %5, %6, %7, %8, %9, %10, %11, %12, %13, %14, %15, %16, %17, %18, %19, %20, %21, %22, %23, %24, %25, %26, %27, %28, %29, %30, %31}, {%32, %33, %34, %35}, %36, p, 1, 1, %38;\n}\n"
    : "+f"(d[0]), "+f"(d[1]), "+f"(d[2]), "+f"(d[3]), "+f"(d[4]), "+f"(d[5]), "+f"(d[6]), "+f"(d[7]), "+f"(d[8]), "+f"(d[9]), "+f"(d[10]), "+f"(d[11]), "+f"(d[12]), "+f"(d[13]), "+f"(d[14]), "+f"(d[15]), "+f"(d[16]), "+f"(d[17]), "+f"(d[18]), "+f"(d[19]), "+f"(d[20]), "+f"(d[21]), "+f"(d[22]), "+f"(d[23]), "+f"(d[24]), "+f"(d[25]), "+f"(d[26]), "+f"(d[27]), "+f"(d[28]), "+f"(d[29]), "+f"(d[30]), "+f"(d[31])
    : "r"(a[0]), "r"(a[1]), "r"(a[2]), "r"(a[3]), "l"(db), "r"(sc), "n"(TB));
}
template <int TB> __device__ __forceinline__ void wgmma_rs_56(float (&d)[28], const uint32_t (&a)[4], uint64_t db, int sc) {
  asm volatile("{\n.reg .pred p;\nsetp.ne.b32 p, %33, 0;\n"
    "wgmma.mma_async.sync.aligned.m64n56k16.f32.bf16.bf16 {%0, %1, %2, %3, %4, %5, %6, %7, %8, %9, %10, %11, %12, %13, %14, %15, %16, %17, %18, %19, %20, %21, %22, %23, %24, %25, %26, %27}, {%28, %29, %30, %31}, %32, p, 1, 1, %34;\n}\n"
    : "+f"(d[0]), "+f"(d[1]), "+f"(d[2]), "+f"(d[3]), "+f"(d[4]), "+f"(d[5]), "+f"(d[6]), "+f"(d[7]), "+f"(d[8]), "+f"(d[9]), "+f"(d[10]), "+f"(d[11]), "+f"(d[12]), "+f"(d[13]), "+f"(d[14]), "+f"(d[15]), "+f"(d[16]), "+f"(d[17]), "+f"(d[18]), "+f"(d[19]), "+f"(d[20]), "+f"(d[21]), "+f"(d[22]), "+f"(d[23]), "+f"(d[24]), "+f"(d[25]), "+f"(d[26]), "+f"(d[27])
    : "r"(a[0]), "r"(a[1]), "r"(a[2]), "r"(a[3]), "l"(db), "r"(sc), "n"(TB));
}
template <int TB> __device__ __forceinline__ void wgmma_rs_112(float (&d)[56], const uint32_t (&a)[4], uint64_t db, int sc) {
  asm volatile("{\n.reg .pred p;\nsetp.ne.b32 p, %61, 0;\n"
    "wgmma.mma_async.sync.aligned.m64n112k16.f32.bf16.bf16 {%0, %1, %2, %3, %4, %5, %6, %7, %8, %9, %10, %11, %12, %13, %14, %15, %16, %17, %18, %19, %20, %21, %22, %23, %24, %25, %26, %27, %28, %29, %30, %31, %32, %33, %34, %35, %36, %37, %38, %39, %40, %41, %42, %43, %44, %45, %46, %47, %48, %49, %50, %51, %52, %53, %54, %55}, {%56, %57, %58, %59}, %60, p, 1, 1, %62;\n}\n"
    : "+f"(d[0]), "+f"(d[1]), "+f"(d[2]), "+f"(d[3]), "+f"(d[4]), "+f"(d[5]), "+f"(d[6]), "+f"(d[7]), "+f"(d[8]), "+f"(d[9]), "+f"(d[10]), "+f"(d[11]), "+f"(d[12]), "+f"(d[13]), "+f"(d[14]), "+f"(d[15]), "+f"(d[16]), "+f"(d[17]), "+f"(d[18]), "+f"(d[19]), "+f"(d[20]), "+f"(d[21]), "+f"(d[22]), "+f"(d[23]), "+f"(d[24]), "+f"(d[25]), "+f"(d[26]), "+f"(d[27]), "+f"(d[28]), "+f"(d[29]), "+f"(d[30]), "+f"(d[31]), "+f"(d[32]), "+f"(d[33]), "+f"(d[34]), "+f"(d[35]), "+f"(d[36]), "+f"(d[37]), "+f"(d[38]), "+f"(d[39]), "+f"(d[40]), "+f"(d[41]), "+f"(d[42]), "+f"(d[43]), "+f"(d[44]), "+f"(d[45]), "+f"(d[46]), "+f"(d[47]), "+f"(d[48]), "+f"(d[49]), "+f"(d[50]), "+f"(d[51]), "+f"(d[52]), "+f"(d[53]), "+f"(d[54]), "+f"(d[55])
    : "r"(a[0]), "r"(a[1]), "r"(a[2]), "r"(a[3]), "l"(db), "r"(sc), "n"(TB));
}
template <int TA, int TB> __device__ __forceinline__ void wgmma_ss_56(float (&d)[28], uint64_t da, uint64_t db, int sc) {
  asm volatile("{\n.reg .pred p;\nsetp.ne.b32 p, %30, 0;\n"
    "wgmma.mma_async.sync.aligned.m64n56k16.f32.bf16.bf16 {%0, %1, %2, %3, %4, %5, %6, %7, %8, %9, %10, %11, %12, %13, %14, %15, %16, %17, %18, %19, %20, %21, %22, %23, %24, %25, %26, %27}, %28, %29, p, 1, 1, %31, %32;\n}\n"
    : "+f"(d[0]), "+f"(d[1]), "+f"(d[2]), "+f"(d[3]), "+f"(d[4]), "+f"(d[5]), "+f"(d[6]), "+f"(d[7]), "+f"(d[8]), "+f"(d[9]), "+f"(d[10]), "+f"(d[11]), "+f"(d[12]), "+f"(d[13]), "+f"(d[14]), "+f"(d[15]), "+f"(d[16]), "+f"(d[17]), "+f"(d[18]), "+f"(d[19]), "+f"(d[20]), "+f"(d[21]), "+f"(d[22]), "+f"(d[23]), "+f"(d[24]), "+f"(d[25]), "+f"(d[26]), "+f"(d[27])
    : "l"(da), "l"(db), "r"(sc), "n"(TA), "n"(TB));
}

__device__ __forceinline__ uint32_t cis(float a) { return pack_bf16(__cosf(a), __sinf(a)); }

typedef __nv_bfloat162 b2;
struct c2 { b2 x, y; };
__device__ __forceinline__ b2 as_b2(uint32_t u) { return *reinterpret_cast<b2*>(&u); }
__device__ __forceinline__ uint32_t as_u(b2 v) { return *reinterpret_cast<uint32_t*>(&v); }
__device__ __forceinline__ c2 mk(b2 x, b2 y) { c2 r; r.x = x; r.y = y; return r; }
__device__ __forceinline__ c2 cmul(c2 a, b2 wr, b2 wi) { return mk(__hfma2(a.x, wr, __hneg2(__hmul2(a.y, wi))), __hfma2(a.x, wi, __hmul2(a.y, wr))); }
__device__ __forceinline__ void fft4(c2& a0, c2& a1, c2& a2, c2& a3) {
  c2 t0 = mk(__hadd2(a0.x, a2.x), __hadd2(a0.y, a2.y)), t1 = mk(__hsub2(a0.x, a2.x), __hsub2(a0.y, a2.y));
  c2 t2 = mk(__hadd2(a1.x, a3.x), __hadd2(a1.y, a3.y)), t3 = mk(__hsub2(a1.x, a3.x), __hsub2(a1.y, a3.y));
  a0 = mk(__hadd2(t0.x, t2.x), __hadd2(t0.y, t2.y)); a2 = mk(__hsub2(t0.x, t2.x), __hsub2(t0.y, t2.y));
  a1 = mk(__hadd2(t1.x, t3.y), __hsub2(t1.y, t3.x)); a3 = mk(__hsub2(t1.x, t3.y), __hadd2(t1.y, t3.x));
}
__device__ __forceinline__ void fft4_s2(c2& a0, c2& a1, c2& a2, c2& a3, b2 r) {
  const b2 nr = __hneg2(r);
  c2 t0 = mk(__hfma2(a2.x, r, a0.x), __hfma2(a2.y, r, a0.y)), t1 = mk(__hfma2(a2.x, nr, a0.x), __hfma2(a2.y, nr, a0.y));
  c2 t2 = mk(__hadd2(a1.x, a3.x), __hadd2(a1.y, a3.y)), t3 = mk(__hsub2(a1.x, a3.x), __hsub2(a1.y, a3.y));
  a0 = mk(__hadd2(t0.x, t2.x), __hadd2(t0.y, t2.y)); a2 = mk(__hsub2(t0.x, t2.x), __hsub2(t0.y, t2.y));
  a1 = mk(__hadd2(t1.x, t3.y), __hsub2(t1.y, t3.x)); a3 = mk(__hsub2(t1.x, t3.y), __hadd2(t1.y, t3.x));
}
__device__ __forceinline__ void fft4_s13(c2& a0, c2& a1, c2& a2, c2& a3, b2 r) {
  const b2 nr = __hneg2(r);
  c2 t0 = mk(__hadd2(a0.x, a2.x), __hadd2(a0.y, a2.y)), t1 = mk(__hsub2(a0.x, a2.x), __hsub2(a0.y, a2.y));
  c2 t2 = mk(__hadd2(a1.x, a3.x), __hadd2(a1.y, a3.y)), t3 = mk(__hsub2(a1.x, a3.x), __hsub2(a1.y, a3.y));
  a0 = mk(__hfma2(t2.x, r, t0.x), __hfma2(t2.y, r, t0.y)); a2 = mk(__hfma2(t2.x, nr, t0.x), __hfma2(t2.y, nr, t0.y));
  a1 = mk(__hfma2(t3.y, r, t1.x), __hfma2(t3.x, nr, t1.y)); a3 = mk(__hfma2(t3.y, nr, t1.x), __hfma2(t3.x, r, t1.y));
}
__device__ __forceinline__ c2 rot1(c2 a) { return mk(__hadd2(a.x, a.y), __hsub2(a.y, a.x)); }
__device__ __forceinline__ c2 rot3(c2 a) { return mk(__hsub2(a.y, a.x), __hneg2(__hadd2(a.x, a.y))); }
__device__ __forceinline__ c2 mul_mi(c2 a) { return mk(a.y, __hneg2(a.x)); }
template <int O> __device__ __forceinline__ void fft8(c2 (&v)[16]) {
  const b2 r = as_b2(0x3F353F35u), nr = as_b2(0xBF35BF35u);
  fft4(v[O], v[O + 4], v[O + 8], v[O + 12]);
  fft4(v[O + 2], v[O + 6], v[O + 10], v[O + 14]);
  const c2 o0 = v[O + 2], o1 = rot1(v[O + 6]), o2 = v[O + 10], o3 = rot1(v[O + 14]);
  const c2 e0 = v[O], e1 = v[O + 4], e2 = v[O + 8], e3 = v[O + 12];
  v[O] = mk(__hadd2(e0.x, o0.x), __hadd2(e0.y, o0.y));              v[O + 8] = mk(__hsub2(e0.x, o0.x), __hsub2(e0.y, o0.y));
  v[O + 2] = mk(__hfma2(o1.x, r, e1.x), __hfma2(o1.y, r, e1.y));    v[O + 10] = mk(__hfma2(o1.x, nr, e1.x), __hfma2(o1.y, nr, e1.y));
  v[O + 4] = mk(__hadd2(e2.x, o2.y), __hsub2(e2.y, o2.x));          v[O + 12] = mk(__hsub2(e2.x, o2.y), __hadd2(e2.y, o2.x));
  v[O + 6] = mk(__hfma2(o3.y, r, e3.x), __hfma2(o3.x, nr, e3.y));   v[O + 14] = mk(__hfma2(o3.y, nr, e3.x), __hfma2(o3.x, r, e3.y));
}
__device__ __forceinline__ void fft16(c2 (&v)[16]) {
  const b2 r = as_b2(0x3F353F35u), c1 = as_b2(0x3F6D3F6Du), s1 = as_b2(0x3EC43EC4u), nc1 = as_b2(0xBF6DBF6Du), ns1 = as_b2(0xBEC4BEC4u);
#pragma unroll
  for (int a = 0; a < 4; a++) fft4(v[a], v[a + 4], v[a + 8], v[a + 12]);
  v[5] = cmul(v[5], c1, ns1); v[6] = rot1(v[6]); v[7] = cmul(v[7], s1, nc1);
  v[9] = rot1(v[9]); v[10] = mul_mi(v[10]); v[11] = rot3(v[11]);
  v[13] = cmul(v[13], s1, nc1); v[14] = rot3(v[14]); v[15] = cmul(v[15], nc1, s1);
  fft4(v[0], v[1], v[2], v[3]); fft4_s2(v[4], v[5], v[6], v[7], r); fft4_s13(v[8], v[9], v[10], v[11], r); fft4_s2(v[12], v[13], v[14], v[15], r);
  c2 t;
  t = v[1]; v[1] = v[4]; v[4] = t;  t = v[2]; v[2] = v[8]; v[8] = t;  t = v[3]; v[3] = v[12]; v[12] = t;
  t = v[6]; v[6] = v[9]; v[9] = t;  t = v[7]; v[7] = v[13]; v[13] = t; t = v[11]; v[11] = v[14]; v[14] = t;
}

__device__ __forceinline__ void columns(c2 (&v)[16], uint32_t sb, int t) {
  const int l16 = t & 15;
  const uint32_t row = sb + OFF_EXCH + (t >> 4) * 2304;
  const uint32_t pos = sb + OFF_EXCH + (t >> 3) * 144 + (t & 7) * 16;
#pragma unroll 1
  for (int ps = 0; ps < 6; ps++) {
    if (ps == 0 || ps == 5) { fft8<0>(v); fft8<1>(v); } else fft16(v);
    if (ps == 5) break;
    if (ps == 2) {
      const uint32_t ws = sb + OFF_WS + (l16 >> 1) * 128 + ((((t >> 4) + (l16 >> 1)) & 7) * 2 + (l16 & 1)) * 8;
      mbar_wait(sb + OFF_BAR + B_WFULL * 8, 0);
#pragma unroll
      for (int q = 0; q < 16; q++) {
        const uint2 w = lds64(ws + q * 1024);
        const c2 z = cmul(v[q], as_b2(w.x), as_b2(w.y));
        v[q] = mk(z.y, z.x);
      }
      continue;
    }
    {
      const bool full = ps == 0 || ps == 4;
      const uint32_t tw = sb + OFF_TW + (full ? ps * 2048 + t * 16 : 16384 + l16 * 16);
      const uint32_t st = full ? 2048 : 256;
#pragma unroll
      for (int i = 0; i < 4; i++) {
        const uint4 w4 = lds128(tw + i * st);
        const uint32_t w[4] = {w4.x, w4.y, w4.z, w4.w};
#pragma unroll
        for (int e = 0; e < 4; e++) v[4 * i + e] = cmul(v[4 * i + e], __low2bfloat162(as_b2(w[e])), __high2bfloat162(as_b2(w[e])));
      }
    }
    if (ps == 0) {
      bar_sync<3, 128>();
#pragma unroll
      for (int q = 0; q < 8; q++) sts128(pos + q * 2304, as_u(v[2 * q].x), as_u(v[2 * q].y), as_u(v[2 * q + 1].x), as_u(v[2 * q + 1].y));
      bar_sync<3, 128>();
#pragma unroll
      for (int q = 0; q < 16; q++) { const uint2 a = lds64(row + q * 144 + l16 * 8); v[q] = mk(as_b2(a.x), as_b2(a.y)); }
    } else {
      __syncwarp();
#pragma unroll
      for (int q = 0; q < 16; q++) sts64(row + q * 144 + l16 * 8, as_u(v[q].x), as_u(v[q].y));
      if (ps == 4) bar_sync<3, 128>(); else __syncwarp();
      const uint32_t src = ps == 4 ? pos : row + l16 * 144, st = ps == 4 ? 2304 : 16;
#pragma unroll
      for (int q = 0; q < 8; q++) { const uint4 a = lds128(src + q * st); v[2 * q] = mk(as_b2(a.x), as_b2(a.y)); v[2 * q + 1] = mk(as_b2(a.z), as_b2(a.w)); }
    }
  }
}

template <int NH> __device__ __forceinline__ void h_epilogue(float (&acc)[NH * 8], unsigned char* gdst, uint32_t tag) {
#pragma unroll
  for (int c = 0; c < NH / 2; c++) {
    uint32_t pk[4];
#pragma unroll
    for (int i = 0; i < 4; i++) {
      float hv[2];
#pragma unroll
      for (int e = 0; e < 2; e++) {
        float hg = 0.5f * acc[c * 8 + i * 2 + e], up = acc[NH * 4 + c * 8 + i * 2 + e];
        float th; asm("tanh.approx.f32 %0, %1;" : "=f"(th) : "f"(hg));
        hv[e] = fmaf(hg, th, hg) * up;
      }
      pk[i] = pack_bf16(hv[0], hv[1]);
    }
    stg128_l2(gdst + c * 4096, (pk[0] & ~1u) | tag, pk[1], pk[2], pk[3]);
  }
}

__device__ __forceinline__ void frag_ready(uint32_t (&a)[4], uint32_t (&b)[4], uint32_t (&c)[4], uint32_t (&d)[4], const unsigned char* p, uint32_t tag) {
  asm volatile("{\n.reg .pred p;\n.reg .u32 c, m, q;\nmov.u32 c, 0;\nL_TRY:\n"
               "lop3.b32 m, %0, %4, %17, 0x7E;\nlop3.b32 q, %8, %12, %17, 0x7E;\nlop3.b32 m, m, q, 1, 0xA8;\nsetp.ne.u32 p, m, 0;\n"
               "vote.sync.any.pred p, p, 0xffffffff;\n@!p bra.uni L_OK;\n"
               "ld.relaxed.gpu.global.v4.b32 {%0,%1,%2,%3}, [%16];\nld.relaxed.gpu.global.v4.b32 {%4,%5,%6,%7}, [%16+4096];\n"
               "ld.relaxed.gpu.global.v4.b32 {%8,%9,%10,%11}, [%16+8192];\nld.relaxed.gpu.global.v4.b32 {%12,%13,%14,%15}, [%16+12288];\n"
               "add.u32 c, c, 1;\nsetp.lt.u32 p, c, 262144;\n@p bra.uni L_TRY;\ntrap;\nL_OK:\n}"
               : "+r"(a[0]), "+r"(a[1]), "+r"(a[2]), "+r"(a[3]), "+r"(b[0]), "+r"(b[1]), "+r"(b[2]), "+r"(b[3]),
                 "+r"(c[0]), "+r"(c[1]), "+r"(c[2]), "+r"(c[3]), "+r"(d[0]), "+r"(d[1]), "+r"(d[2]), "+r"(d[3])
               : "l"(p), "r"(tag) : "memory");
}

#define LDH ldg128_na
#define MAP 0
#define LA2 5
#define LEAD1 3

__global__ void __cluster_dims__(2, 1, 1) __launch_bounds__(NTHREADS, 1)
fused_kernel(const __grid_constant__ CUtensorMap tm_x, const __grid_constant__ CUtensorMap tm_g, const __grid_constant__ CUtensorMap tm_u,
             const __grid_constant__ CUtensorMap tm_g32, const __grid_constant__ CUtensorMap tm_u32,
             const __nv_bfloat16* __restrict__ w_r, const __nv_bfloat16* __restrict__ w_i,
             const __nv_bfloat16* __restrict__ w_gate, const __nv_bfloat16* __restrict__ w_up,
             const __nv_bfloat16* __restrict__ w_down, const __nv_bfloat16* __restrict__ gate_w, __nv_bfloat16* __restrict__ out) {
  extern __shared__ __align__(1024) unsigned char smem[];
  const uint32_t sb = s2u(smem);
  const uint32_t bars = sb + OFF_BAR;
  const int tid = threadIdx.x, warp = __shfl_sync(0xffffffffu, tid >> 5, 0), lane = tid & 31;
  const int cl = blockIdx.x >> 1, kh = blockIdx.x & 1;
  const int n0 = cl < 4 ? cl : (cl < 36 ? (cl - 4) >> 3 : (cl - 36) / 7);
  const int m0 = cl < 4 ? 15 : (cl < 36 ? (cl - 4) & 7 : cl - 28 - 7 * n0);
  const int n = MAP == 0 ? n0 : (MAP == 1 ? (m0 & 3) : ((n0 & 1) | ((m0 & 1) << 1)));
  const int m = MAP == 0 ? m0 : (MAP == 1 ? ((m0 & 12) | n0) : ((m0 & 14) | (n0 >> 1)));
  const int j = kh * 4 + n, bid = m * 8 + n * 2 + kh;

  const int c64 = 224 * j + (j & 1) * 32;
  if (warp == 12) {
    if (lane < 10) mbar_init(bars + (lane < NSLOT ? B_FULL + lane : (lane < 9 ? B_XFULL - 7 + lane : B_PIN)) * 8, 1);
    fence_async_smem();
    bar_arrive<0, NTHREADS - 64>();
    if (elect()) {
      mbar_expect(bars + B_PIN * 8, 14400);
      bulk_g2s(sb + 5 * SLOT, reinterpret_cast<const unsigned char*>(w_r) + bid * 7200, 7200, bars + B_PIN * 8);
      bulk_g2s(sb + 5 * SLOT + 7200, reinterpret_cast<const unsigned char*>(w_i) + bid * 7200, 7200, bars + B_PIN * 8);
#pragma unroll
      for (int w = 0; w < 2; w++) {
        mbar_expect(bars + (B_XFULL + w) * 8, HALF_XR);
        tma3d(sb + OFF_PQ + w * HALF_XR, &tm_x, 0, m * 128 + (w ^ kh ^ 1) * 64, 0, bars + (B_XFULL + w) * 8);
      }
      PROF(3, 3);
    }
#pragma unroll 1
    for (int i = 0; i < 5; i++) {
      if (elect()) {
        const uint32_t fb = bars + (B_FULL + i) * 8;
        mbar_expect(fb, SLOT);
        tma2d(sb + i * SLOT, &tm_g, c64, i * 64, fb);
        tma2d(sb + i * SLOT + 8192, &tm_u, c64, i * 64, fb);
        PROF(3, 4 + i);
      }
    }
    if (lane < 4) prefetch_tma2d((lane & 1) ? &tm_u : &tm_g, c64, 320 + (lane >> 1) * 64);
  } else if (warp == 14) {
    if (lane < NSLOT) mbar_init(bars + (B_EMPTY + lane) * 8, 8);
    const int i = B_XFREE + lane;
    if (i < B_END) mbar_init(bars + i * 8, i >= B_PQFULL ? 1 : ((i == B_XFREE || i >= B_PUBW) ? 4 : 8));
    asm volatile("fence.mbarrier_init.release.cluster;" ::: "memory");
    fence_async_smem();
    __syncwarp();
    if (lane == 0) mbar_expect(bars + B_RECV * 8, 64 * 112 * 4);
    bar_arrive<0, NTHREADS - 64>();
  }
  if (warp >= 12) {
    asm volatile("setmaxnreg.dec.sync.aligned.u32 24;");
    const uint32_t epoch = ld_relaxed(&g_ep[bid]);
    if (warp == 13 && lane == 0) { PROFG(4, 0); PROF(4, 1); }
    bar_sync<1, 128>();
    asm volatile("barrier.cluster.arrive.relaxed.aligned;" ::: "memory");
    if (warp == 12) {
      int slot = 5, ph = 1;
      auto wait_slot = [&]() { mbar_wait(bars + (B_EMPTY + slot) * 8, ph ^ (slot >= 5)); };
      auto adv = [&]() { if (++slot == NSLOT) { slot = 0; ph ^= 1; } };
      const int c32 = 224 * j + ((j & 1) ? 0 : 192);
#pragma unroll 1
      for (int i = 5; i < 25; i++) {
        wait_slot();
        if (elect()) {
          const uint32_t dst = sb + slot * SLOT, fb = bars + (B_FULL + slot) * 8;
          const bool last = i >= 21;
          const int cc = last ? c32 : c64 + 64 * (i / 7), rr = last ? slot * 128 : slot * 64;
          mbar_expect(fb, SLOT);
          tma2d(dst, last ? &tm_g32 : &tm_g, cc, rr, fb);
          tma2d(dst + 8192, last ? &tm_u32 : &tm_u, cc, rr, fb);
        }
        adv();
      }
      if (lane == 0) PROF(3, 0);
      mbar_wait(bars + B_PREP * 8, 0);
      if (lane == 0) PROF(3, 1);
#pragma unroll 1
      for (int i = 4; i < 16; i++) {
        if (lane == 0) PROF(3, 16 + i);
        wait_slot();
        if (elect()) {
          const int bytes = i < 14 ? 14336 : G_IMG / 2;
          const unsigned char* src = i < 14 ? g_Wd + (size_t)j * WD_IMG + i * 14336 : g_G + (size_t)(n * 4 + i - 12) * (G_IMG / 2);
          mbar_expect(bars + (B_FULL + slot) * 8, bytes);
          bulk_g2s(sb + slot * SLOT, src, bytes, bars + (B_FULL + slot) * 8);
        }
        adv();
      }
      if (lane == 0) PROF(3, 2);
    } else if (warp == 13) {
      mbar_wait(bars + B_PUBW * 8, 0);
      if (lane == 0) PROF(4, 7);
      mbar_wait(bars + B_PUBX * 8, 0);
      if (lane == 0) {
        PROF(4, 8);
        red_release(&g_cnt[(j >> 1) * 32]);
        red_relaxed(&g_cnt[6 * 32]);
        PROF(4, 18);
      }
      __syncwarp();
      mbar_wait(bars + B_PUBD * 8, 0);
      if (lane == 0) { PROF(4, 9); red_release(&g_cnt[4 * 32]); PROF(4, 19); }
      __syncwarp();
      mbar_wait(bars + B_LFREE * 8, 0);
      if (elect()) {
        mbar_expect(bars + B_GFULL * 8, G_IMG);
        bulk_g2s(sb + OFF_R + 28672, g_G + (size_t)(n * 2) * G_IMG, G_IMG, bars + B_GFULL * 8);
      }
    } else if (warp == 14) {
#pragma unroll 1
      for (int u = 0; u < 2; u++) {
        wait_ge(&g_cnt[(6 - 2 * u) * 32], (epoch + 1) * 128);
        fence_async_global();
        if (lane == 0) { mbar_arrive(bars + (B_PREPW - u) * 8); PROF(5, 9 - u); }
      }
    } else {
      mbar_wait(bars + B_XFREE * 8, 0);
      if (elect()) {
        prefetch_l2(reinterpret_cast<const unsigned char*>(w_gate) + bid * 12544, 12544);
        prefetch_l2(reinterpret_cast<const unsigned char*>(w_up) + bid * 12544, 12544);
      }
      mbar_wait(bars + (B_XFREE + 1) * 8, 0);
      if (elect()) {
        mbar_expect(bars + B_RFULL * 8, 12544);
        bulk_g2s(sb + OFF_R, reinterpret_cast<const unsigned char*>(w_down) + bid * 12544, 12544, bars + B_RFULL * 8);
      }
      if (bid < 113) {
        const int sl = (bid == 112) ? 0 : bid;
        wait_ge(&g_cnt[((sl & 1) + 2 * ((sl >> 1) / 28)) * 32], (epoch + 1) * 32);
        fence_async_global();
        if (elect()) {
          PROF(5, 16);
          mbar_expect(bars + B_XCFULL * 8, 16384);
          bulk_g2s(sb + OFF_EXCH, g_Xc + sl * 2 * S_, 16384, bars + B_XCFULL * 8);
        }
        mbar_wait(bars + B_PREPW * 8, 0);
        if (elect()) {
          mbar_expect(bars + B_WFULL * 8, 16384);
          bulk_g2s(sb + OFF_WS, g_Wt + bid * S_, 16384, bars + B_WFULL * 8);
          PROF(5, 17);
        }
      }
      mbar_wait(bars + B_PREP * 8, 0);
      if (elect()) {
        mbar_expect(bars + B_RFULL * 8, HALF_XR);
        bulk_g2s(sb + OFF_R, g_Wd + (size_t)j * WD_IMG, HALF_XR, bars + B_RFULL * 8);
        PROF(5, 19);
      }
      wait_ge(&g_cnt[5 * 32], (epoch + 1) * 128);
      fence_async_global();
      if (elect()) {
        PROF(5, 18);
        mbar_expect(bars + B_PQFULL * 8, HALF_XR + 256);
        const unsigned char* src = g_PQ + (size_t)(m * 2 + kh) * HALF_XR;
        bulk_g2s(sb + OFF_PQ, src, 28672, bars + B_PQFULL * 8);
        bulk_g2s(sb + OFF_PQ + 28672, src + 28672, 28672, bars + B_PQFULL * 8);
        bulk_g2s(sb + OFF_G, g_gate + m * 128 + kh * 64, 256, bars + B_PQFULL * 8);
      }
    }
    __syncwarp();
    asm volatile("barrier.cluster.wait.aligned;" ::: "memory");
  } else if (warp < 8) {
    asm volatile("setmaxnreg.inc.sync.aligned.u32 208;");
    const int wg = warp >> 2, w4 = warp & 3, g = lane >> 2, t = lane & 3;
    const int rh = wg ^ kh ^ 1;
    const int p = j & 1, r = (j >> 1) & 1, hh = j >> 2;
    const uint32_t epoch = ld_relaxed(&g_ep[bid]);
    if ((tid & 127) == 0) PROF(wg, 30);
#pragma unroll 1
    for (int it = tid; it < 392; it += 256) {
      const int kc = it / 28, sg = it - kc * 28;
      const int k = 2 * (28 * hh + sg) + r;
      const float kf = (float)k * (-6.283185307179586f / 448.0f), a0 = (float)(16 * kc + p) * kf;
      uint32_t c[4], s[4];
#pragma unroll
      for (int q = 0; q < 4; q++) {
        const float a1 = fmaf((float)(2 * q), kf, a0), a2 = fmaf((float)(2 * q + 8), kf, a0);
        c[q] = pack_bf16(__cosf(a1), __cosf(a2)); s[q] = pack_bf16(__sinf(a1), __sinf(a2));
        if (k == 0) s[q] = ((q ^ p) & 1) ? 0xBF80BF80u : 0x3F803F80u;
      }
      const uint32_t a = sb + 6 * SLOT + (kc * 56 + 2 * sg) * 16;
      sts128(a, c[0], c[1], c[2], c[3]);
      sts128(a + 16, s[0], s[1], s[2], s[3]);
    }
    if ((tid & 127) == 0) PROF(wg, 31);
    fence_async_smem();
    bar_sync<0, NTHREADS - 64>();
    asm volatile("barrier.cluster.arrive.relaxed.aligned;" ::: "memory");
    if ((tid & 127) == 0) PROF(wg, 1);

    uint32_t xa[28][4];
    {
      const uint32_t xb = sb + OFF_PQ + wg * HALF_XR + (w4 * 16 + (lane & 15)) * 128;
      mbar_wait(bars + (B_XFULL + wg) * 8, 0);
      if ((tid & 127) == 0) PROF(wg, 2);
#pragma unroll
      for (int kb = 0; kb < 7; kb++) {
#pragma unroll
        for (int kk = 0; kk < 4; kk++) {
          uint32_t a = xb + kb * 8192 + (((2 * kk + (lane >> 4)) ^ (lane & 7)) << 4);
          asm volatile("ldmatrix.sync.aligned.m8n8.x4.shared.b16 {%0,%1,%2,%3}, [%4];"
                       : "=r"(xa[kb * 4 + kk][0]), "=r"(xa[kb * 4 + kk][1]), "=r"(xa[kb * 4 + kk][2]), "=r"(xa[kb * 4 + kk][3]) : "r"(a) : "memory");
        }
      }
    }
    {
      uint32_t ad[7][4];
      const uint32_t sel = p ? 0x7632 : 0x5410;
      const uint32_t sgn = r ? 0xBF80BF80u : 0x3F803F80u;
#pragma unroll
      for (int jj = 0; jj < 7; jj++) {
#pragma unroll
        for (int i = 0; i < 4; i++) {
          int ks = 2 * jj + (i >> 1), rr = i & 1;
          uint32_t lo = __byte_perm(xa[ks][rr], xa[ks][rr + 2], sel);
          uint32_t hi = __byte_perm(xa[ks + 14][rr], xa[ks + 14][rr + 2], sel);
          asm("fma.rn.bf16x2 %0, %1, %2, %3;" : "=r"(ad[jj][i]) : "r"(hi), "r"(sgn), "r"(lo));
        }
      }
      __syncwarp();
      if (lane == 0) mbar_arrive(bars + (B_XFREE + wg) * 8);
      float acc[28];
      wg_fence();
      uint64_t db = mkdesc(sb + 6 * SLOT, 896, 128, 0);
#pragma unroll
      for (int jj = 0; jj < 7; jj++) wgmma_rs_56<0>(acc, ad[jj], db + jj * 112, jj != 0);
      wg_commit();
      wg_wait<0>(); keep(acc);
      if (lane == 0) mbar_arrive(bars + (B_EMPTY + 6) * 8);
      uint32_t* xc = g_Xc + (size_t)((2 * (28 * hh + t) + r) * 2 + p) * S_ + m * 128 + rh * 64 + w4 * 16 + g;
#pragma unroll
      for (int i = 0; i < 7; i++) {
        xc[i * 16 * S_] = pack_bf16(acc[4 * i], acc[4 * i + 1]);
        xc[i * 16 * S_ + 8] = pack_bf16(acc[4 * i + 2], acc[4 * i + 3]);
      }
      __syncwarp();
      if (lane == 0) mbar_arrive(bars + B_PUBX * 8);
    }
    if ((tid & 127) == 0) PROF(wg, 3);
    const uint32_t tag = ~epoch & 1;
    unsigned char* const hbase = g_H + (size_t)(m * 2 + kh) * (56 * 4096) + rh * 2048 + (tid & 127) * 16;
#pragma unroll 1
    for (int u = 0; u < 3; u++) {
      float acc[64];
      if (wg == 1) { if (u & 1) bar_sync<6, 256>(); else bar_sync<2, 256>(); }
      const uint32_t sbu = opaque(sb);
#pragma unroll
      for (int kb = 0; kb < 7; kb++) {
        mbar_wait(sbu + OFF_BAR + (B_FULL + kb) * 8, u & 1);
        wg_fence();
        uint64_t db = mkdesc(sbu + kb * SLOT, 8192, 1024, 1);
#pragma unroll
        for (int kk = 0; kk < 4; kk++) wgmma_rs_128<1>(acc, xa[kb * 4 + kk], db + kk * 128, (kb | kk) != 0);
        wg_commit();
        if (kb == LEAD1 && wg == 0) { if (u & 1) bar_arrive<6, 256>(); else bar_arrive<2, 256>(); }
        if (kb > 0) { wg_wait<1>(); if (lane == 0) mbar_arrive(sbu + OFF_BAR + (B_EMPTY + kb - 1) * 8); }
      }
      wg_wait<0>(); keep(acc);
      if (lane == 0) mbar_arrive(sbu + OFF_BAR + (B_EMPTY + 6) * 8);
      if ((tid & 127) == 0) PROF(wg, 4 + 2 * u);
      h_epilogue<8>(acc, hbase + (u * 16 + n * 4) * 4096, tag);
      if ((tid & 127) == 0) PROF(wg, 5 + 2 * u);
    }
    {
      float acc[32];
      if (wg == 1) bar_sync<6, 256>();
      const uint32_t sbu = opaque(sb);
#pragma unroll
      for (int it = 0; it < 4; it++) {
        mbar_wait(sbu + OFF_BAR + (B_FULL + it) * 8, 1);
        wg_fence();
        uint64_t db = mkdesc(sbu + it * SLOT, 8192, 512, 2);
#pragma unroll
        for (int kk = 0; kk < 8; kk++) if (it * 8 + kk < 28) wgmma_rs_64<1>(acc, xa[it * 8 + kk], db + kk * 64, (it | kk) != 0);
        wg_commit();
        if (it == 2 && wg == 0) bar_arrive<6, 256>();
        if (it > 0) {
          wg_wait<1>();
          if (lane == 0) mbar_arrive(sbu + OFF_BAR + (B_EMPTY + it - 1) * 8);
#pragma unroll
          for (int i = it * 8 - 8; i < it * 8; i++) if (i < 4 * LA2) LDH(xa[i], hbase + i * 4096);
        }
      }
      wg_wait<0>(); keep(acc);
      if (lane == 0) mbar_arrive(sbu + OFF_BAR + (B_EMPTY + 3) * 8);
      if ((tid & 127) == 0) PROF(wg, 10);
      h_epilogue<4>(acc, hbase + (48 + n * 2) * 4096, tag);
    }
    asm volatile("barrier.cluster.wait.aligned;" ::: "memory");
    if ((tid & 127) == 0) PROF(wg, 11);

    float acc[56];
    if (wg == 1) bar_sync<2, 256>();
#pragma unroll 1
    for (int it = 0; it < 2; it++) {
#pragma unroll
      for (int e = 0; e < 7; e++) {
        if ((tid & 127) == 0) PROF(wg, 16 + it * 7 + e);
        const bool inr = e < 4 && it == 0;
        if (e >= 4 || it == 1) mbar_wait(bars + (B_FULL + e) * 8, e < 4 ? 0 : it ^ 1);
        else if (e == 0) mbar_wait(bars + B_RFULL * 8, 1);
        frag_ready(xa[e * 4], xa[e * 4 + 1], xa[e * 4 + 2], xa[e * 4 + 3], hbase + (it * 7 + e) * 16384, tag);
        wg_fence();
        const uint64_t db = mkdesc(inr ? sb + OFF_R + e * 14336 : sb + e * SLOT, 1792, 128, 0);
#pragma unroll
        for (int kk = 0; kk < 4; kk++) wgmma_rs_112<1>(acc, xa[e * 4 + kk], db + kk * 224, (e | kk) ? 1 : it);
        wg_commit();
        if (e == 1 && it == 0 && wg == 0) bar_arrive<2, 256>();
        if (it == 0 || e + LA2 < 7) {
          const int nb = it * 7 + e + LA2;
#pragma unroll
          for (int kk = 0; kk < 4; kk++) LDH(xa[((e + LA2) % 7) * 4 + kk], hbase + (nb * 4 + kk) * 4096);
        }
        wg_wait<1>();
        if (lane == 0) {
          if (it == 0 ? e >= 5 : e <= 2) mbar_arrive(bars + (B_EMPTY + (e + 6) % 7) * 8);
          if (e == 4 && it == 0) {
            mbar_arrive(bars + B_LFREE * 8);
            asm volatile("{\n.reg .b32 ra;\nmapa.shared::cluster.u32 ra, %0, %1;\nmbarrier.arrive.relaxed.cluster.shared::cluster.b64 _, [ra];\n}"
                         :: "r"(bars + B_RFREE * 8), "r"(kh ^ 1) : "memory");
          }
        }
      }
    }
    const int t128 = tid & 127;
    wg_wait<0>(); keep(acc);
    if (wg == 0) {
      if (t128 == 0) PROF(wg, 12);
      mbar_wait_cluster(bars + B_RFREE * 8, 0);
      uint32_t rdst, rbar;
      asm volatile("mapa.shared::cluster.u32 %0, %1, %2;" : "=r"(rdst) : "r"(sb + OFF_R + t128 * 16), "r"(kh ^ 1));
      asm volatile("mapa.shared::cluster.u32 %0, %1, %2;" : "=r"(rbar) : "r"(bars + B_RECV * 8), "r"(kh ^ 1));
#pragma unroll
      for (int i = 0; i < 14; i++)
        asm volatile("st.async.weak.shared::cluster.mbarrier::complete_tx::bytes.v4.f32 [%0], {%1,%2,%3,%4}, [%5];"
                     :: "r"(rdst + i * 2048), "f"(acc[4 * i]), "f"(acc[4 * i + 1]), "f"(acc[4 * i + 2]), "f"(acc[4 * i + 3]), "r"(rbar) : "memory");
    } else {
      float spec[2][28];
      if (t128 == 0) PROF(wg, 12);
      mbar_wait(bars + B_PQFULL * 8, 0);
      if (t128 == 0) { PROF(wg, 13); g_ep[bid] = epoch + 1; }
#pragma unroll
      for (int i = 0; i < 4; i++) {
        if (i == 0) mbar_wait(bars + B_GFULL * 8, 0);
        if (i >= 2) mbar_wait(bars + (B_FULL + i - 2) * 8, 1);
        wg_fence();
        const uint64_t da = mkdesc(sb + OFF_PQ + i * 14336, 1024, 1024, 1);
        const uint64_t db = mkdesc(i < 2 ? sb + OFF_R + 28672 + i * (G_IMG / 2) : sb + (i - 2) * SLOT, 896, 128, 0);
#pragma unroll
        for (int kk = 0; kk < 7; kk++) wgmma_ss_56<1, 0>(spec[i >> 1], da + kk * 128, db + kk * 112, ((i & 1) | kk) != 0);
        wg_commit();
      }
      const float* gs = reinterpret_cast<const float*>(smem + OFF_G) + w4 * 16 + g;
      const float o0 = bf16_round(1.0f - gs[0]), o1 = bf16_round(1.0f - gs[8]);
      const float g0 = gs[0] * (1.0f / (float)(S_ * D_)), g1 = gs[8] * (1.0f / (float)(S_ * D_));
      wg_wait<0>(); keep(spec[0]); keep(spec[1]);
      if (t128 == 0) PROF(wg, 14);
      mbar_wait_cluster(bars + B_RECV * 8, 0);
      if (t128 == 0) PROF(wg, 0);
      float4 o[14];
#pragma unroll
      for (int i = 0; i < 14; i++) o[i] = lds128f(sb + OFF_R + t128 * 16 + i * 2048);
      bar_sync<5, 128>();
      const uint32_t st = sb + OFF_PQ + w4 * 3840;
#pragma unroll
      for (int i = 0; i < 7; i++) {
        uint32_t pk[4];
#pragma unroll
        for (int e = 0; e < 2; e++) {
          const int c = 2 * i + e, si = i * 4 + e;
          pk[2 * e] = pack_bf16(fmaf(acc[4 * c] + o[c].x, o0, g0 * spec[0][si]), fmaf(acc[4 * c + 1] + o[c].y, o0, g0 * spec[1][si]));
          pk[2 * e + 1] = pack_bf16(fmaf(acc[4 * c + 2] + o[c].z, o1, g1 * spec[0][si + 2]), fmaf(acc[4 * c + 3] + o[c].w, o1, g1 * spec[1][si + 2]));
        }
        asm volatile("stmatrix.sync.aligned.m8n8.x4.shared.b16 [%0], {%1,%2,%3,%4};"
                     :: "r"(st + (lane & 15) * 240 + (lane >> 4) * 16 + i * 32), "r"(pk[0]), "r"(pk[1]), "r"(pk[2]), "r"(pk[3]) : "memory");
      }
      __syncwarp();
      if (lane < 28) {
        const int r2 = lane >= 14, cc = lane - r2 * 14;
        unsigned char* ob = reinterpret_cast<unsigned char*>(out) + (size_t)(m * 128 + kh * 64 + w4 * 16 + r2) * (D_ * 2) + n * 224 + cc * 16;
        float4 v[8];
#pragma unroll
        for (int i = 0; i < 8; i++) v[i] = lds128f(st + r2 * 240 + cc * 16 + i * 480);
#pragma unroll
        for (int i = 0; i < 8; i++) stg128(ob + i * (D_ * 4), __float_as_uint(v[i].x), __float_as_uint(v[i].y), __float_as_uint(v[i].z), __float_as_uint(v[i].w));
      }
    }
    if (t128 == 0) { PROF(wg, 15); if (wg) { PROFG(4, 30); PROF(4, 31); } }
  } else {
    asm volatile("setmaxnreg.dec.sync.aligned.u32 72;");
    const int t = tid - 256;
    const int k = bid;
    if (t == 0) PROF(2, 0);
    uint4 gv[7];
#pragma unroll
    for (int i = 0; i < 7; i++) gv[i] = ldg128(reinterpret_cast<const uint4*>(gate_w) + i * 8 + (t & 7));
    bar_sync<0, NTHREADS - 64>();
    asm volatile("barrier.cluster.arrive.relaxed.aligned;" ::: "memory");
    mbar_wait(bars + B_PIN * 8, 0);
    if (t == 0) PROF(2, 4);
    {
      const uint32_t wa = sb + 5 * SLOT + (((t & 7) - bid) & 7) * 450 + (t >> 3) * 2, wc = wa + 448 - (t >> 3) * 4;
      uint2* dst = g_Wt + (t >> 3) * S_ + 16 * bid + 2 * (t & 7);
#pragma unroll 1
      for (int h = 0; h < 2; h++) {
        uint32_t w[4][8];
#pragma unroll
        for (int i = 0; i < 4; i++) {
#pragma unroll
          for (int e = 0; e < 4; e++) { w[i][2 * e] = lds16(wa + h * 128 + i * 32 + e * 3600); w[i][2 * e + 1] = lds16(wc - h * 128 - i * 32 + e * 3600); }
        }
#pragma unroll
        for (int i = 0; i < 4; i++)
          if (i < 3 || h == 0 || t < 8)
            stg128(dst + (h * 64 + i * 16) * S_, __byte_perm(w[i][0], w[i][1], 0x5410), __byte_perm(w[i][4], w[i][5], 0x5410), __byte_perm(w[i][2], w[i][3], 0x5410), __byte_perm(w[i][6], w[i][7], 0x5410));
      }
    }
    __syncwarp();
    if (lane < 3) mbar_arrive(bars + (lane ? B_EMPTY + 5 : B_PUBW) * 8);
    if (t == 0) PROF(2, 6);
    {
      const int row = n * 16 + (t >> 3), l8 = t & 7;
      mbar_wait(bars + (B_XFULL + 1) * 8, 0);
      float sum = 0.f;
#pragma unroll
      for (int i = 0; i < 7; i++) {
        const uint4 a = lds128(sb + OFF_R + i * 8192 + row * 128 + ((l8 ^ (row & 7)) << 4));
        const uint32_t aa[4] = {a.x, a.y, a.z, a.w}, bb[4] = {gv[i].x, gv[i].y, gv[i].z, gv[i].w};
#pragma unroll
        for (int e = 0; e < 4; e++) {
          const uint32_t pr = as_u(__hmul2(as_b2(aa[e]), as_b2(bb[e])));
          sum += bf_lo(pr) + bf_hi(pr);
        }
      }
      sum += __shfl_xor_sync(0xffffffffu, sum, 1); sum += __shfl_xor_sync(0xffffffffu, sum, 2); sum += __shfl_xor_sync(0xffffffffu, sum, 4);
      if (lane == 0) mbar_arrive(bars + (B_XFREE + 1) * 8);
      if (l8 == 0) g_gate[m * 128 + kh * 64 + row] = bf16_round(__fdividef(1.0f, 1.0f + __expf(-bf16_round(sum))));
    }
    if (t < 98) {
      int cid = m * 98 + t, kc = cid / 56, nn = cid - kc * 56;
      int d = 112 * n + 8 * (2 * (nn >> 3) + (nn & 1)) + (nn & 6) + kh;
      int dr = d > 224 ? d - 448 : d;
      const float df = (float)dr * (-6.283185307179586f / 448.0f);
      uint32_t pk[4];
#pragma unroll
      for (int e = 0; e < 4; e++) {
        const float a = (float)(4 * kc + e) * df;
        pk[e] = pack_bf16(2.0f * __cosf(a), 2.0f * __sinf(a));
      }
      if (kc == 0) pk[0] = (((d >> 1) ^ kh) & 1) ? 0xBF803F80u : 0x3F803F80u;
      stg128(g_G + (size_t)(n * 2 + kh) * G_IMG + cid * 16, pk[0], pk[1], pk[2], pk[3]);
    }
    if (t == 0) PROF(2, 11);
    mbar_wait(bars + B_XFREE * 8, 0);
    if (k < 113) {
      const float u = -6.283185307179586f / 2048.0f, t2 = (float)(2 * t) * u, rr = (float)(t >> 4) * u;
#pragma unroll 1
      for (int i = 0; i < 4; i++) {
        const float q = (float)(2 * i), l = (float)((t & 15) + 64 * i);
        sts128(sb + OFF_TW + i * 2048 + t * 16, cis(t2 * q), cis((t2 + u) * q), cis(t2 * (q + 1.0f)), cis((t2 + u) * (q + 1.0f)));
        sts128(sb + OFF_TW + 8192 + i * 2048 + t * 16, cis(rr * l), cis(rr * (l + 16.0f)), cis(rr * (l + 32.0f)), cis(rr * (l + 48.0f)));
      }
      const float l = (float)((t >> 1) & 15) * (8.0f * u), jj = (float)((t >> 5) * 4 + (t & 1) * 2);
      sts64(sb + OFF_TW + 16384 + t * 8, cis(l * jj), cis(l * (jj + 1.0f)));
    }
    if (t == 0) PROF(2, 9);
    mbar_wait(bars + B_RFULL * 8, 0);
    if (t < 112) {
      const int js = bid >> 4, nn = (t >> 1) / 14, cc = (t >> 1) - nn * 14;
      unsigned char* wdst = g_Wd + (size_t)((js >> 2) * 4 + nn) * WD_IMG + cc * 128 + (t & 1) * 16;
      uint4 v[7];
#pragma unroll
      for (int i = 0; i < 7; i++) v[i] = lds128(sb + OFF_R + i * 1792 + (t & 1) * 896 + (t >> 1) * 16);
#pragma unroll
      for (int i = 0; i < 7; i++) {
        int col = 14 * (bid & 15) + 2 * i - (js & 1) * 32;
        if (col < 0) col += 224;
        const int kpos = col < 192 ? (col >> 6) * 256 + (js & 3) * 64 + (col & 63) : 576 + (js & 3) * 32 + col;
        stg128(wdst + (kpos >> 3) * 1792 + (kpos & 7) * 16, v[i].x, v[i].y, v[i].z, v[i].w);
      }
    }
    __syncwarp();
    if (lane == 0) mbar_arrive(bars + B_PUBD * 8);
    bar_sync<3, 128>();
    if (k < 113) {
      if (t == 0) PROF(2, 2);
      mbar_wait(bars + B_XCFULL * 8, 0);
      if (t == 0) PROF(2, 3);
      c2 v[16];
      const uint32_t se = k == 0 ? 0x4410 : (k == 112 ? 0x4432 : 0x3210), so = k == 0 ? 0x4410 : (k == 112 ? 0x3244 : 0x3210);
#pragma unroll
      for (int jj = 0; jj < 8; jj++) {
        const uint2 e2 = lds64(sb + OFF_EXCH + jj * 1024 + t * 8), o2 = lds64(sb + OFF_EXCH + 8192 + jj * 1024 + t * 8);
#pragma unroll
        for (int h = 0; h < 2; h++) {
          const b2 e = as_b2(__byte_perm(h ? e2.y : e2.x, 0, se)), o = as_b2(__byte_perm(h ? o2.y : o2.x, 0, so));
          const uint32_t s = as_u(__hadd2(e, o)), d = as_u(__hsub2(e, o)) ^ 0x80000000u;
          v[2 * jj + h] = mk(as_b2(__byte_perm(s, d, 0x5410)), as_b2(__byte_perm(s, d, 0x7632)));
        }
      }
      if (t == 0) PROF(2, 12);
      columns(v, sb, t);
      if (t == 0) PROF(2, 14);
      const int pre = (k == 112) ? 1 : 2 * k, pim = (k == 112) ? 1 : 2 * k + 1;
      uint32_t* pq = reinterpret_cast<uint32_t*>(g_PQ) + (t >> 5) * 14336;
      uint32_t* pr = pq + pre * 32 + ((((lane >> 2) ^ pre) & 7) << 2) + (lane & 3);
      uint32_t* pi = pq + pim * 32 + ((((lane >> 2) ^ pim) & 7) << 2) + (lane & 3);
#pragma unroll
      for (int jj = 0; jj < 8; jj++) {
        const b2 ar = as_b2(__byte_perm(as_u(v[2 * jj].y), as_u(v[2 * jj + 1].y), 0x5410)), br = as_b2(__byte_perm(as_u(v[2 * jj].y), as_u(v[2 * jj + 1].y), 0x7632));
        const b2 ai = as_b2(__byte_perm(as_u(v[2 * jj].x), as_u(v[2 * jj + 1].x), 0x5410)), bi = as_b2(__byte_perm(as_u(v[2 * jj].x), as_u(v[2 * jj + 1].x), 0x7632));
        pr[jj * 57344] = as_u(__hadd2(ar, br));
        if (k != 112) pr[jj * 57344 + 7168] = as_u(__hsub2(ar, br));
        if (k != 0) pi[jj * 57344 + 7168] = as_u(__hadd2(ai, bi));
        if (k != 0 && k != 112) pi[jj * 57344] = as_u(__hsub2(ai, bi));
      }
      fence_async_smem();
    }
    bar_sync<3, 128>();
    if (t == 0) { PROF(2, 5); red_release(&g_cnt[5 * 32]); PROF(2, 7); }
    __syncwarp();
    asm volatile("barrier.cluster.wait.aligned;" ::: "memory");
  }
}

typedef CUresult (*EncodeFn)(CUtensorMap*, CUtensorMapDataType, cuuint32_t, void*, const cuuint64_t*, const cuuint64_t*, const cuuint32_t*,
                             const cuuint32_t*, CUtensorMapInterleave, CUtensorMapSwizzle, CUtensorMapL2promotion, CUtensorMapFloatOOBfill);

void make_map(EncodeFn enc, CUtensorMap* tm, const void* base, int cols, int rows, int bc, int br, CUtensorMapSwizzle sw) {
  cuuint64_t gd[2] = {(cuuint64_t)cols, (cuuint64_t)rows};
  cuuint64_t gs[1] = {(cuuint64_t)cols * 2};
  cuuint32_t bd[2] = {(cuuint32_t)bc, (cuuint32_t)br};
  cuuint32_t es[2] = {1, 1};
  enc(tm, CU_TENSOR_MAP_DATA_TYPE_BFLOAT16, 2, const_cast<void*>(base), gd, gs, bd, es, CU_TENSOR_MAP_INTERLEAVE_NONE, sw,
      CU_TENSOR_MAP_L2_PROMOTION_L2_128B, CU_TENSOR_MAP_FLOAT_OOB_FILL_NONE);
}

}

extern "C" void kernel_launch(void* const* d_in, const int* in_sizes, int n_in, void* d_out, int out_size) {
  (void)in_sizes; (void)n_in; (void)out_size;
  const __nv_bfloat16* x = (const __nv_bfloat16*)d_in[0];
  const __nv_bfloat16* w_r = (const __nv_bfloat16*)d_in[1];
  const __nv_bfloat16* w_i = (const __nv_bfloat16*)d_in[2];
  const __nv_bfloat16* w_gate = (const __nv_bfloat16*)d_in[4];
  const __nv_bfloat16* w_up = (const __nv_bfloat16*)d_in[5];
  const __nv_bfloat16* w_down = (const __nv_bfloat16*)d_in[6];
  const __nv_bfloat16* gate_w = (const __nv_bfloat16*)d_in[7];
  static EncodeFn enc = nullptr;
  static bool ok = false;
  if (!enc) {
    cudaDriverEntryPointQueryResult qr;
    cudaGetDriverEntryPoint("cuTensorMapEncodeTiled", (void**)&enc, cudaEnableDefault, &qr);
    cudaFuncSetAttribute(fused_kernel, cudaFuncAttributeMaxDynamicSharedMemorySize, SMEM_BYTES);
    cudaFuncAttributes fa;
    cudaFuncGetAttributes(&fa, fused_kernel);
    ok = (fa.numRegs == 128);
  }
  if (!ok) return;
  CUtensorMap tx, tg, tu, tg32, tu32;
  {
    cuuint64_t gd[3] = {64, (cuuint64_t)S_, 7};
    cuuint64_t gs[2] = {(cuuint64_t)D_ * 2, 128};
    cuuint32_t bd[3] = {64, 64, 7};
    cuuint32_t es[3] = {1, 1, 1};
    enc(&tx, CU_TENSOR_MAP_DATA_TYPE_BFLOAT16, 3, const_cast<__nv_bfloat16*>(x), gd, gs, bd, es, CU_TENSOR_MAP_INTERLEAVE_NONE, CU_TENSOR_MAP_SWIZZLE_128B,
        CU_TENSOR_MAP_L2_PROMOTION_L2_128B, CU_TENSOR_MAP_FLOAT_OOB_FILL_NONE);
  }
  make_map(enc, &tg, w_gate, F_, D_, 64, 64, CU_TENSOR_MAP_SWIZZLE_128B);
  make_map(enc, &tu, w_up, F_, D_, 64, 64, CU_TENSOR_MAP_SWIZZLE_128B);
  make_map(enc, &tg32, w_gate, F_, D_, 32, 128, CU_TENSOR_MAP_SWIZZLE_64B);
  make_map(enc, &tu32, w_up, F_, D_, 32, 128, CU_TENSOR_MAP_SWIZZLE_64B);
  fused_kernel<<<128, NTHREADS, SMEM_BYTES>>>(tx, tg, tu, tg32, tu32, w_r, w_i, w_gate, w_up, w_down, gate_w, (__nv_bfloat16*)d_out);
}
```

```cpp
#include <cuda_runtime.h>
#include <cuda_bf16.h>
#include <cuda.h>
#include <stdint.h>

namespace {

constexpr int S_ = 2048, D_ = 448, F_ = 1792;
constexpr int NTHREADS = 512;
constexpr int SLOT = 16384, NSLOT = 7;
constexpr int HALF_XR = 57344;
constexpr int OFF_PQ = NSLOT * SLOT;
constexpr int OFF_R = OFF_PQ + HALF_XR;
constexpr int OFF_EXCH = OFF_PQ;
constexpr int OFF_WS = OFF_EXCH + 18432;
constexpr int OFF_TW = OFF_WS + 16384;
constexpr int OFF_MISC = OFF_R + HALF_XR;
constexpr int OFF_G = OFF_MISC;
constexpr int OFF_BAR = OFF_MISC + 512;
constexpr int SMEM_BYTES = OFF_BAR + 512;
constexpr int B_FULL = 0, B_EMPTY = 7, B_XFULL = 14  ;
constexpr int B_XFREE = 16  , B_PUBX = 18, B_RFREE = 19, B_LFREE = 20;
constexpr int B_PUBW = 21, B_PUBD = 22;
constexpr int B_PQFULL = 23, B_RECV = 24, B_WFULL = 25, B_XCFULL = 26, B_PREP = 27, B_PREPW = 28, B_RFULL = 29, B_GFULL = 30, B_END = 31, B_PIN = 31;

constexpr int WD_IMG = 896 * 112 * 2;
constexpr int G_IMG = 224 * 56 * 2;

__device__ __align__(1024) uint32_t g_Xc[112 * 2 * S_];
__device__ __align__(1024) unsigned char g_H[32 * 56 * 4096];
__device__ __align__(1024) unsigned char g_PQ[32 * HALF_XR];
__device__ __align__(1024) unsigned char g_Wd[8 * WD_IMG];
__device__ __align__(1024) unsigned char g_G[8 * G_IMG];
__device__ __align__(1024) uint2 g_Wt[113 * S_];
__device__ __align__(1024) float g_gate[S_];
__device__ __align__(128) unsigned int g_ep[128];
__device__ __align__(128) unsigned int g_cnt[8 * 32];

#define PROF(role, idx) do {} while (0)
#define PROFG(role, idx) do {} while (0)

__device__ __forceinline__ uint32_t s2u(const void* p) { return (uint32_t)__cvta_generic_to_shared(p); }
__device__ __forceinline__ void mbar_init(uint32_t b, int c) { asm volatile("mbarrier.init.shared::cta.b64 [%0], %1;" :: "r"(b), "r"(c) : "memory"); }
__device__ __forceinline__ void mbar_expect(uint32_t b, int bytes) { asm volatile("mbarrier.arrive.expect_tx.shared::cta.b64 _, [%0], %1;" :: "r"(b), "r"(bytes) : "memory"); }
__device__ __forceinline__ void mbar_arrive(uint32_t b) { asm volatile("mbarrier.arrive.shared::cta.b64 _, [%0];" :: "r"(b) : "memory"); }
__device__ __forceinline__ void mbar_wait(uint32_t b, int ph) {
  asm volatile("{\n.reg .pred p;\n.reg .u32 c;\nmov.u32 c, 0;\nL_WAIT:\nmbarrier.try_wait.parity.shared::cta.b64 p, [%0], %1;\n@p bra.uni L_DONE;\n"
               "add.u32 c, c, 1;\nsetp.lt.u32 p, c, 4194304;\n@p bra.uni L_WAIT;\ntrap;\nL_DONE:\n}" :: "r"(b), "r"(ph) : "memory");
}
__device__ __forceinline__ void mbar_wait_cluster(uint32_t b, int ph) {
  asm volatile("{\n.reg .pred p;\n.reg .u32 c;\nmov.u32 c, 0;\nL_WAIT:\nmbarrier.try_wait.parity.acquire.cluster.shared::cta.b64 p, [%0], %1;\n@p bra.uni L_DONE;\n"
               "add.u32 c, c, 1;\nsetp.lt.u32 p, c, 4194304;\n@p bra.uni L_WAIT;\ntrap;\nL_DONE:\n}" :: "r"(b), "r"(ph) : "memory");
}
__device__ __forceinline__ uint32_t ld_acquire(const unsigned int* p) { uint32_t v; asm volatile("ld.acquire.gpu.global.u32 %0, [%1];" : "=r"(v) : "l"(p) : "memory"); return v; }
__device__ __forceinline__ uint32_t ld_relaxed(const unsigned int* p) { uint32_t v; asm volatile("ld.relaxed.gpu.global.u32 %0, [%1];" : "=r"(v) : "l"(p) : "memory"); return v; }
__device__ __forceinline__ void wait_ge(const unsigned int* p, uint32_t target) {
#pragma unroll 1
  for (int i = 0; i < (1 << 22); i++) { if ((int)(ld_acquire(p) - target) >= 0) return; }
  __trap();
}
__device__ __forceinline__ void red_release(unsigned int* p) { asm volatile("red.release.gpu.global.add.u32 [%0], 1;" :: "l"(p) : "memory"); }
__device__ __forceinline__ void red_relaxed(unsigned int* p) { asm volatile("red.relaxed.gpu.global.add.u32 [%0], 1;" :: "l"(p) : "memory"); }
__device__ __forceinline__ bool elect() { uint32_t p; asm volatile("{\n.reg .pred p;\nelect.sync _|p, 0xffffffff;\nselp.u32 %0, 1, 0, p;\n}" : "=r"(p)); return p; }
__device__ __forceinline__ void fence_async_smem() { asm volatile("fence.proxy.async.shared::cta;" ::: "memory"); }
__device__ __forceinline__ void fence_async_global() { asm volatile("fence.proxy.async.global;" ::: "memory"); }
template <int ID, int N> __device__ __forceinline__ void bar_sync() { asm volatile("bar.sync %0, %1;" :: "n"(ID), "n"(N) : "memory"); }
template <int ID, int N> __device__ __forceinline__ void bar_arrive() { asm volatile("bar.arrive %0, %1;" :: "n"(ID), "n"(N) : "memory"); }
__device__ __forceinline__ void tma2d(uint32_t dst, const CUtensorMap* tm, int c0, int c1, uint32_t bar) {
  asm volatile("cp.async.bulk.tensor.2d.shared::cluster.global.mbarrier::complete_tx::bytes [%0], [%1, {%3, %4}], [%2];"
               :: "r"(dst), "l"(tm), "r"(bar), "r"(c0), "r"(c1) : "memory");
}
__device__ __forceinline__ void tma3d(uint32_t dst, const CUtensorMap* tm, int c0, int c1, int c2, uint32_t bar) {
  asm volatile("cp.async.bulk.tensor.3d.shared::cluster.global.mbarrier::complete_tx::bytes [%0], [%1, {%3, %4, %5}], [%2];"
               :: "r"(dst), "l"(tm), "r"(bar), "r"(c0), "r"(c1), "r"(c2) : "memory");
}
__device__ __forceinline__ void bulk_g2s(uint32_t dst, const void* src, int bytes, uint32_t bar) {
  asm volatile("cp.async.bulk.shared::cluster.global.mbarrier::complete_tx::bytes [%0], [%1], %2, [%3];"
               :: "r"(dst), "l"(src), "r"(bytes), "r"(bar) : "memory");
}
__device__ __forceinline__ void prefetch_l2(const void* src, int bytes) {
  asm volatile("cp.async.bulk.prefetch.L2.global [%0], %1;" :: "l"(src), "r"(bytes) : "memory");
}
__device__ __forceinline__ void prefetch_tma2d(const CUtensorMap* tm, int c0, int c1) {
  asm volatile("cp.async.bulk.prefetch.tensor.2d.L2.global [%0, {%1, %2}];" :: "l"(tm), "r"(c0), "r"(c1) : "memory");
}
__device__ __forceinline__ uint64_t mkdesc(uint32_t addr, uint32_t lbo, uint32_t sbo, uint32_t mode) {
  return (uint64_t)((addr & 0x3FFFF) >> 4) | ((uint64_t)(lbo >> 4) << 16) | ((uint64_t)(sbo >> 4) << 32) | ((uint64_t)mode << 62);
}
__device__ __forceinline__ void wg_fence() { asm volatile("wgmma.fence.sync.aligned;" ::: "memory"); }
__device__ __forceinline__ void wg_commit() { asm volatile("wgmma.commit_group.sync.aligned;" ::: "memory"); }
template <int N> __device__ __forceinline__ void wg_wait() { asm volatile("wgmma.wait_group.sync.aligned %0;" :: "n"(N) : "memory"); }
template <int N> __device__ __forceinline__ void keep(float (&d)[N]) {
#pragma unroll
  for (int i = 0; i < N; i++) asm volatile("" : "+f"(d[i]) :: "memory");
}
__device__ __forceinline__ uint32_t pack_bf16(float lo, float hi) { uint32_t r; asm("cvt.rn.bf16x2.f32 %0, %1, %2;" : "=r"(r) : "f"(hi), "f"(lo)); return r; }
__device__ __forceinline__ float bf16_round(float v) { return __bfloat162float(__float2bfloat16_rn(v)); }
__device__ __forceinline__ void sts128(uint32_t a, uint32_t x, uint32_t y, uint32_t z, uint32_t w) { asm volatile("st.shared.v4.b32 [%0], {%1,%2,%3,%4};" :: "r"(a), "r"(x), "r"(y), "r"(z), "r"(w) : "memory"); }
__device__ __forceinline__ float4 lds128f(uint32_t a) { float4 v; asm volatile("ld.shared.v4.f32 {%0,%1,%2,%3}, [%4];" : "=f"(v.x), "=f"(v.y), "=f"(v.z), "=f"(v.w) : "r"(a) : "memory"); return v; }

__device__ __forceinline__ uint2 lds64(uint32_t a) { uint2 v; asm volatile("ld.shared.v2.b32 {%0,%1}, [%2];" : "=r"(v.x), "=r"(v.y) : "r"(a) : "memory"); return v; }
__device__ __forceinline__ float bf_lo(uint32_t w) { return __uint_as_float(w << 16); }
__device__ __forceinline__ float bf_hi(uint32_t w) { return __uint_as_float(w & 0xffff0000u); }
__device__ __forceinline__ uint32_t opaque(uint32_t v) { asm volatile("" : "+r"(v)); return v; }
__device__ __forceinline__ uint4 ldg128(const void* p) { uint4 v; asm volatile("ld.global.nc.v4.b32 {%0,%1,%2,%3}, [%4];" : "=r"(v.x), "=r"(v.y), "=r"(v.z), "=r"(v.w) : "l"(p)); return v; }
__device__ __forceinline__ void stg128(void* p, uint32_t x, uint32_t y, uint32_t z, uint32_t w) { asm volatile("st.global.v4.b32 [%0], {%1,%2,%3,%4};" :: "l"(p), "r"(x), "r"(y), "r"(z), "r"(w) : "memory"); }
__device__ __forceinline__ void stg128_l2(void* p, uint32_t x, uint32_t y, uint32_t z, uint32_t w) { asm volatile("st.relaxed.gpu.global.v4.b32 [%0], {%1,%2,%3,%4};" :: "l"(p), "r"(x), "r"(y), "r"(z), "r"(w) : "memory"); }
__device__ __forceinline__ void ldg128_na(uint32_t (&v)[4], const void* p) { asm volatile("ld.global.L1::no_allocate.v4.b32 {%0,%1,%2,%3}, [%4];" : "=r"(v[0]), "=r"(v[1]), "=r"(v[2]), "=r"(v[3]) : "l"(p) : "memory"); }
__device__ __forceinline__ void ldg128_l2(uint32_t (&v)[4], const void* p) { asm volatile("ld.relaxed.gpu.global.v4.b32 {%0,%1,%2,%3}, [%4];" : "=r"(v[0]), "=r"(v[1]), "=r"(v[2]), "=r"(v[3]) : "l"(p) : "memory"); }
__device__ __forceinline__ uint4 lds128(uint32_t a) { uint4 v; asm volatile("ld.shared.v4.b32 {%0,%1,%2,%3}, [%4];" : "=r"(v.x), "=r"(v.y), "=r"(v.z), "=r"(v.w) : "r"(a) : "memory"); return v; }
__device__ __forceinline__ uint32_t lds16(uint32_t a) { uint32_t v; asm volatile("ld.shared.u16 %0, [%1];" : "=r"(v) : "r"(a) : "memory"); return v; }
__device__ __forceinline__ void sts64(uint32_t a, uint32_t x, uint32_t y) { asm volatile("st.shared.v2.b32 [%0], {%1,%2};" :: "r"(a), "r"(x), "r"(y) : "memory"); }
template <int TB> __device__ __forceinline__ void wgmma_rs_128(float (&d)[64], const uint32_t (&a)[4], uint64_t db, int sc) {
  asm volatile("{\n.reg .pred p;\nsetp.ne.b32 p, %69, 0;\n"
    "wgmma.mma_async.sync.aligned.m64n128k16.f32.bf16.bf16 {%0, %1, %2, %3, %4, %5, %6, %7, %8, %9, %10, %11, %12, %13, %14, %15, %16, %17, %18, %19, %20, %21, %22, %23, %24, %25, %26, %27, %28, %29, %30, %31, %32, %33, %34, %35, %36, %37, %38, %39, %40, %41, %42, %43, %44, %45, %46, %47, %48, %49, %50, %51, %52, %53, %54, %55, %56, %57, %58, %59, %60, %61, %62, %63}, {%64, %65, %66, %67}, %68, p, 1, 1, %70;\n}\n"
    : "+f"(d[0]), "+f"(d[1]), "+f"(d[2]), "+f"(d[3]), "+f"(d[4]), "+f"(d[5]), "+f"(d[6]), "+f"(d[7]), "+f"(d[8]), "+f"(d[9]), "+f"(d[10]), "+f"(d[11]), "+f"(d[12]), "+f"(d[13]), "+f"(d[14]), "+f"(d[15]), "+f"(d[16]), "+f"(d[17]), "+f"(d[18]), "+f"(d[19]), "+f"(d[20]), "+f"(d[21]), "+f"(d[22]), "+f"(d[23]), "+f"(d[24]), "+f"(d[25]), "+f"(d[26]), "+f"(d[27]), "+f"(d[28]), "+f"(d[29]), "+f"(d[30]), "+f"(d[31]), "+f"(d[32]), "+f"(d[33]), "+f"(d[34]), "+f"(d[35]), "+f"(d[36]), "+f"(d[37]), "+f"(d[38]), "+f"(d[39]), "+f"(d[40]), "+f"(d[41]), "+f"(d[42]), "+f"(d[43]), "+f"(d[44]), "+f"(d[45]), "+f"(d[46]), "+f"(d[47]), "+f"(d[48]), "+f"(d[49]), "+f"(d[50]), "+f"(d[51]), "+f"(d[52]), "+f"(d[53]), "+f"(d[54]), "+f"(d[55]), "+f"(d[56]), "+f"(d[57]), "+f"(d[58]), "+f"(d[59]), "+f"(d[60]), "+f"(d[61]), "+f"(d[62]), "+f"(d[63])
    : "r"(a[0]), "r"(a[1]), "r"(a[2]), "r"(a[3]), "l"(db), "r"(sc), "n"(TB));
}
template <int TB> __device__ __forceinline__ void wgmma_rs_64(float (&d)[32], const uint32_t (&a)[4], uint64_t db, int sc) {
  asm volatile("{\n.reg .pred p;\nsetp.ne.b32 p, %37, 0;\n"
    "wgmma.mma_async.sync.aligned.m64n64k16.f32.bf16.bf16 {%0, %1, %2, %3, %4, %5, %6, %7, %8, %9, %10, %11, %12, %13, %14, %15, %16, %17, %18, %19, %20, %21, %22, %23, %24, %25, %26, %27, %28, %29, %30, %31}, {%32, %33, %34, %35}, %36, p, 1, 1, %38;\n}\n"
    : "+f"(d[0]), "+f"(d[1]), "+f"(d[2]), "+f"(d[3]), "+f"(d[4]), "+f"(d[5]), "+f"(d[6]), "+f"(d[7]), "+f"(d[8]), "+f"(d[9]), "+f"(d[10]), "+f"(d[11]), "+f"(d[12]), "+f"(d[13]), "+f"(d[14]), "+f"(d[15]), "+f"(d[16]), "+f"(d[17]), "+f"(d[18]), "+f"(d[19]), "+f"(d[20]), "+f"(d[21]), "+f"(d[22]), "+f"(d[23]), "+f"(d[24]), "+f"(d[25]), "+f"(d[26]), "+f"(d[27]), "+f"(d[28]), "+f"(d[29]), "+f"(d[30]), "+f"(d[31])
    : "r"(a[0]), "r"(a[1]), "r"(a[2]), "r"(a[3]), "l"(db), "r"(sc), "n"(TB));
}
template <int TB> __device__ __forceinline__ void wgmma_rs_56(float (&d)[28], const uint32_t (&a)[4], uint64_t db, int sc) {
  asm volatile("{\n.reg .pred p;\nsetp.ne.b32 p, %33, 0;\n"
    "wgmma.mma_async.sync.aligned.m64n56k16.f32.bf16.bf16 {%0, %1, %2, %3, %4, %5, %6, %7, %8, %9, %10, %11, %12, %13, %14, %15, %16, %17, %18, %19, %20, %21, %22, %23, %24, %25, %26, %27}, {%28, %29, %30, %31}, %32, p, 1, 1, %34;\n}\n"
    : "+f"(d[0]), "+f"(d[1]), "+f"(d[2]), "+f"(d[3]), "+f"(d[4]), "+f"(d[5]), "+f"(d[6]), "+f"(d[7]), "+f"(d[8]), "+f"(d[9]), "+f"(d[10]), "+f"(d[11]), "+f"(d[12]), "+f"(d[13]), "+f"(d[14]), "+f"(d[15]), "+f"(d[16]), "+f"(d[17]), "+f"(d[18]), "+f"(d[19]), "+f"(d[20]), "+f"(d[21]), "+f"(d[22]), "+f"(d[23]), "+f"(d[24]), "+f"(d[25]), "+f"(d[26]), "+f"(d[27])
    : "r"(a[0]), "r"(a[1]), "r"(a[2]), "r"(a[3]), "l"(db), "r"(sc), "n"(TB));
}
template <int TB> __device__ __forceinline__ void wgmma_rs_112(float (&d)[56], const uint32_t (&a)[4], uint64_t db, int sc) {
  asm volatile("{\n.reg .pred p;\nsetp.ne.b32 p, %61, 0;\n"
    "wgmma.mma_async.sync.aligned.m64n112k16.f32.bf16.bf16 {%0, %1, %2, %3, %4, %5, %6, %7, %8, %9, %10, %11, %12, %13, %14, %15, %16, %17, %18, %19, %20, %21, %22, %23, %24, %25, %26, %27, %28, %29, %30, %31, %32, %33, %34, %35, %36, %37, %38, %39, %40, %41, %42, %43, %44, %45, %46, %47, %48, %49, %50, %51, %52, %53, %54, %55}, {%56, %57, %58, %59}, %60, p, 1, 1, %62;\n}\n"
    : "+f"(d[0]), "+f"(d[1]), "+f"(d[2]), "+f"(d[3]), "+f"(d[4]), "+f"(d[5]), "+f"(d[6]), "+f"(d[7]), "+f"(d[8]), "+f"(d[9]), "+f"(d[10]), "+f"(d[11]), "+f"(d[12]), "+f"(d[13]), "+f"(d[14]), "+f"(d[15]), "+f"(d[16]), "+f"(d[17]), "+f"(d[18]), "+f"(d[19]), "+f"(d[20]), "+f"(d[21]), "+f"(d[22]), "+f"(d[23]), "+f"(d[24]), "+f"(d[25]), "+f"(d[26]), "+f"(d[27]), "+f"(d[28]), "+f"(d[29]), "+f"(d[30]), "+f"(d[31]), "+f"(d[32]), "+f"(d[33]), "+f"(d[34]), "+f"(d[35]), "+f"(d[36]), "+f"(d[37]), "+f"(d[38]), "+f"(d[39]), "+f"(d[40]), "+f"(d[41]), "+f"(d[42]), "+f"(d[43]), "+f"(d[44]), "+f"(d[45]), "+f"(d[46]), "+f"(d[47]), "+f"(d[48]), "+f"(d[49]), "+f"(d[50]), "+f"(d[51]), "+f"(d[52]), "+f"(d[53]), "+f"(d[54]), "+f"(d[55])
    : "r"(a[0]), "r"(a[1]), "r"(a[2]), "r"(a[3]), "l"(db), "r"(sc), "n"(TB));
}
template <int TA, int TB> __device__ __forceinline__ void wgmma_ss_56(float (&d)[28], uint64_t da, uint64_t db, int sc) {
  asm volatile("{\n.reg .pred p;\nsetp.ne.b32 p, %30, 0;\n"
    "wgmma.mma_async.sync.aligned.m64n56k16.f32.bf16.bf16 {%0, %1, %2, %3, %4, %5, %6, %7, %8, %9, %10, %11, %12, %13, %14, %15, %16, %17, %18, %19, %20, %21, %22, %23, %24, %25, %26, %27}, %28, %29, p, 1, 1, %31, %32;\n}\n"
    : "+f"(d[0]), "+f"(d[1]), "+f"(d[2]), "+f"(d[3]), "+f"(d[4]), "+f"(d[5]), "+f"(d[6]), "+f"(d[7]), "+f"(d[8]), "+f"(d[9]), "+f"(d[10]), "+f"(d[11]), "+f"(d[12]), "+f"(d[13]), "+f"(d[14]), "+f"(d[15]), "+f"(d[16]), "+f"(d[17]), "+f"(d[18]), "+f"(d[19]), "+f"(d[20]), "+f"(d[21]), "+f"(d[22]), "+f"(d[23]), "+f"(d[24]), "+f"(d[25]), "+f"(d[26]), "+f"(d[27])
    : "l"(da), "l"(db), "r"(sc), "n"(TA), "n"(TB));
}

__device__ __forceinline__ uint32_t cis(float a) { return pack_bf16(__cosf(a), __sinf(a)); }

typedef __nv_bfloat162 b2;
struct c2 { b2 x, y; };
__device__ __forceinline__ b2 as_b2(uint32_t u) { return *reinterpret_cast<b2*>(&u); }
__device__ __forceinline__ uint32_t as_u(b2 v) { return *reinterpret_cast<uint32_t*>(&v); }
__device__ __forceinline__ c2 mk(b2 x, b2 y) { c2 r; r.x = x; r.y = y; return r; }
__device__ __forceinline__ c2 cmul(c2 a, b2 wr, b2 wi) { return mk(__hfma2(a.x, wr, __hneg2(__hmul2(a.y, wi))), __hfma2(a.x, wi, __hmul2(a.y, wr))); }
__device__ __forceinline__ void fft4(c2& a0, c2& a1, c2& a2, c2& a3) {
  c2 t0 = mk(__hadd2(a0.x, a2.x), __hadd2(a0.y, a2.y)), t1 = mk(__hsub2(a0.x, a2.x), __hsub2(a0.y, a2.y));
  c2 t2 = mk(__hadd2(a1.x, a3.x), __hadd2(a1.y, a3.y)), t3 = mk(__hsub2(a1.x, a3.x), __hsub2(a1.y, a3.y));
  a0 = mk(__hadd2(t0.x, t2.x), __hadd2(t0.y, t2.y)); a2 = mk(__hsub2(t0.x, t2.x), __hsub2(t0.y, t2.y));
  a1 = mk(__hadd2(t1.x, t3.y), __hsub2(t1.y, t3.x)); a3 = mk(__hsub2(t1.x, t3.y), __hadd2(t1.y, t3.x));
}
__device__ __forceinline__ void fft4_s2(c2& a0, c2& a1, c2& a2, c2& a3, b2 r) {
  const b2 nr = __hneg2(r);
  c2 t0 = mk(__hfma2(a2.x, r, a0.x), __hfma2(a2.y, r, a0.y)), t1 = mk(__hfma2(a2.x, nr, a0.x), __hfma2(a2.y, nr, a0.y));
  c2 t2 = mk(__hadd2(a1.x, a3.x), __hadd2(a1.y, a3.y)), t3 = mk(__hsub2(a1.x, a3.x), __hsub2(a1.y, a3.y));
  a0 = mk(__hadd2(t0.x, t2.x), __hadd2(t0.y, t2.y)); a2 = mk(__hsub2(t0.x, t2.x), __hsub2(t0.y, t2.y));
  a1 = mk(__hadd2(t1.x, t3.y), __hsub2(t1.y, t3.x)); a3 = mk(__hsub2(t1.x, t3.y), __hadd2(t1.y, t3.x));
}
__device__ __forceinline__ void fft4_s13(c2& a0, c2& a1, c2& a2, c2& a3, b2 r) {
  const b2 nr = __hneg2(r);
  c2 t0 = mk(__hadd2(a0.x, a2.x), __hadd2(a0.y, a2.y)), t1 = mk(__hsub2(a0.x, a2.x), __hsub2(a0.y, a2.y));
  c2 t2 = mk(__hadd2(a1.x, a3.x), __hadd2(a1.y, a3.y)), t3 = mk(__hsub2(a1.x, a3.x), __hsub2(a1.y, a3.y));
  a0 = mk(__hfma2(t2.x, r, t0.x), __hfma2(t2.y, r, t0.y)); a2 = mk(__hfma2(t2.x, nr, t0.x), __hfma2(t2.y, nr, t0.y));
  a1 = mk(__hfma2(t3.y, r, t1.x), __hfma2(t3.x, nr, t1.y)); a3 = mk(__hfma2(t3.y, nr, t1.x), __hfma2(t3.x, r, t1.y));
}
__device__ __forceinline__ c2 rot1(c2 a) { return mk(__hadd2(a.x, a.y), __hsub2(a.y, a.x)); }
__device__ __forceinline__ c2 rot3(c2 a) { return mk(__hsub2(a.y, a.x), __hneg2(__hadd2(a.x, a.y))); }
__device__ __forceinline__ c2 mul_mi(c2 a) { return mk(a.y, __hneg2(a.x)); }
template <int O> __device__ __forceinline__ void fft8(c2 (&v)[16]) {
  const b2 r = as_b2(0x3F353F35u), nr = as_b2(0xBF35BF35u);
  fft4(v[O], v[O + 4], v[O + 8], v[O + 12]);
  fft4(v[O + 2], v[O + 6], v[O + 10], v[O + 14]);
  const c2 o0 = v[O + 2], o1 = rot1(v[O + 6]), o2 = v[O + 10], o3 = rot1(v[O + 14]);
  const c2 e0 = v[O], e1 = v[O + 4], e2 = v[O + 8], e3 = v[O + 12];
  v[O] = mk(__hadd2(e0.x, o0.x), __hadd2(e0.y, o0.y));              v[O + 8] = mk(__hsub2(e0.x, o0.x), __hsub2(e0.y, o0.y));
  v[O + 2] = mk(__hfma2(o1.x, r, e1.x), __hfma2(o1.y, r, e1.y));    v[O + 10] = mk(__hfma2(o1.x, nr, e1.x), __hfma2(o1.y, nr, e1.y));
  v[O + 4] = mk(__hadd2(e2.x, o2.y), __hsub2(e2.y, o2.x));          v[O + 12] = mk(__hsub2(e2.x, o2.y), __hadd2(e2.y, o2.x));
  v[O + 6] = mk(__hfma2(o3.y, r, e3.x), __hfma2(o3.x, nr, e3.y));   v[O + 14] = mk(__hfma2(o3.y, nr, e3.x), __hfma2(o3.x, r, e3.y));
}
__device__ __forceinline__ void fft16(c2 (&v)[16]) {
  const b2 r = as_b2(0x3F353F35u), c1 = as_b2(0x3F6D3F6Du), s1 = as_b2(0x3EC43EC4u), nc1 = as_b2(0xBF6DBF6Du), ns1 = as_b2(0xBEC4BEC4u);
#pragma unroll
  for (int a = 0; a < 4; a++) fft4(v[a], v[a + 4], v[a + 8], v[a + 12]);
  v[5] = cmul(v[5], c1, ns1); v[6] = rot1(v[6]); v[7] = cmul(v[7], s1, nc1);
  v[9] = rot1(v[9]); v[10] = mul_mi(v[10]); v[11] = rot3(v[11]);
  v[13] = cmul(v[13], s1, nc1); v[14] = rot3(v[14]); v[15] = cmul(v[15], nc1, s1);
  fft4(v[0], v[1], v[2], v[3]); fft4_s2(v[4], v[5], v[6], v[7], r); fft4_s13(v[8], v[9], v[10], v[11], r); fft4_s2(v[12], v[13], v[14], v[15], r);
  c2 t;
  t = v[1]; v[1] = v[4]; v[4] = t;  t = v[2]; v[2] = v[8]; v[8] = t;  t = v[3]; v[3] = v[12]; v[12] = t;
  t = v[6]; v[6] = v[9]; v[9] = t;  t = v[7]; v[7] = v[13]; v[13] = t; t = v[11]; v[11] = v[14]; v[14] = t;
}

__device__ __forceinline__ void columns(c2 (&v)[16], uint32_t sb, int t) {
  const int l16 = t & 15;
  const uint32_t row = sb + OFF_EXCH + (t >> 4) * 2304;
  const uint32_t pos = sb + OFF_EXCH + (t >> 3) * 144 + (t & 7) * 16;
#pragma unroll 1
  for (int ps = 0; ps < 6; ps++) {
    if (ps == 0 || ps == 5) { fft8<0>(v); fft8<1>(v); } else fft16(v);
    if (ps == 5) break;
    if (ps == 2) {
      const uint32_t ws = sb + OFF_WS + (l16 >> 1) * 128 + ((((t >> 4) + (l16 >> 1)) & 7) * 2 + (l16 & 1)) * 8;
      mbar_wait(sb + OFF_BAR + B_WFULL * 8, 0);
#pragma unroll
      for (int q = 0; q < 16; q++) {
        const uint2 w = lds64(ws + q * 1024);
        const c2 z = cmul(v[q], as_b2(w.x), as_b2(w.y));
        v[q] = mk(z.y, z.x);
      }
      continue;
    }
    {
      const bool full = ps == 0 || ps == 4;
      const uint32_t tw = sb + OFF_TW + (full ? ps * 2048 + t * 16 : 16384 + l16 * 16);
      const uint32_t st = full ? 2048 : 256;
#pragma unroll
      for (int i = 0; i < 4; i++) {
        const uint4 w4 = lds128(tw + i * st);
        const uint32_t w[4] = {w4.x, w4.y, w4.z, w4.w};
#pragma unroll
        for (int e = 0; e < 4; e++) v[4 * i + e] = cmul(v[4 * i + e], __low2bfloat162(as_b2(w[e])), __high2bfloat162(as_b2(w[e])));
      }
    }
    if (ps == 0) {
      bar_sync<3, 128>();
#pragma unroll
      for (int q = 0; q < 8; q++) sts128(pos + q * 2304, as_u(v[2 * q].x), as_u(v[2 * q].y), as_u(v[2 * q + 1].x), as_u(v[2 * q + 1].y));
      bar_sync<3, 128>();
#pragma unroll
      for (int q = 0; q < 16; q++) { const uint2 a = lds64(row + q * 144 + l16 * 8); v[q] = mk(as_b2(a.x), as_b2(a.y)); }
    } else {
      __syncwarp();
#pragma unroll
      for (int q = 0; q < 16; q++) sts64(row + q * 144 + l16 * 8, as_u(v[q].x), as_u(v[q].y));
      if (ps == 4) bar_sync<3, 128>(); else __syncwarp();
      const uint32_t src = ps == 4 ? pos : row + l16 * 144, st = ps == 4 ? 2304 : 16;
#pragma unroll
      for (int q = 0; q < 8; q++) { const uint4 a = lds128(src + q * st); v[2 * q] = mk(as_b2(a.x), as_b2(a.y)); v[2 * q + 1] = mk(as_b2(a.z), as_b2(a.w)); }
    }
  }
}

template <int NH> __device__ __forceinline__ void h_epilogue(float (&acc)[NH * 8], unsigned char* gdst, uint32_t tag) {
#pragma unroll
  for (int c = 0; c < NH / 2; c++) {
    uint32_t pk[4];
#pragma unroll
    for (int i = 0; i < 4; i++) {
      float hv[2];
#pragma unroll
      for (int e = 0; e < 2; e++) {
        float hg = 0.5f * acc[c * 8 + i * 2 + e], up = acc[NH * 4 + c * 8 + i * 2 + e];
        float th; asm("tanh.approx.f32 %0, %1;" : "=f"(th) : "f"(hg));
        hv[e] = fmaf(hg, th, hg) * up;
      }
      pk[i] = pack_bf16(hv[0], hv[1]);
    }
    stg128_l2(gdst + c * 4096, (pk[0] & ~1u) | tag, pk[1], pk[2], pk[3]);
  }
}

__device__ __forceinline__ void frag_ready(uint32_t (&a)[4], uint32_t (&b)[4], uint32_t (&c)[4], uint32_t (&d)[4], const unsigned char* p, uint32_t tag) {
  asm volatile("{\n.reg .pred p;\n.reg .u32 c, m, q;\nmov.u32 c, 0;\nL_TRY:\n"
               "lop3.b32 m, %0, %4, %17, 0x7E;\nlop3.b32 q, %8, %12, %17, 0x7E;\nlop3.b32 m, m, q, 1, 0xA8;\nsetp.ne.u32 p, m, 0;\n"
               "vote.sync.any.pred p, p, 0xffffffff;\n@!p bra.uni L_OK;\n"
               "ld.relaxed.gpu.global.v4.b32 {%0,%1,%2,%3}, [%16];\nld.relaxed.gpu.global.v4.b32 {%4,%5,%6,%7}, [%16+4096];\n"
               "ld.relaxed.gpu.global.v4.b32 {%8,%9,%10,%11}, [%16+8192];\nld.relaxed.gpu.global.v4.b32 {%12,%13,%14,%15}, [%16+12288];\n"
               "add.u32 c, c, 1;\nsetp.lt.u32 p, c, 262144;\n@p bra.uni L_TRY;\ntrap;\nL_OK:\n}"
               : "+r"(a[0]), "+r"(a[1]), "+r"(a[2]), "+r"(a[3]), "+r"(b[0]), "+r"(b[1]), "+r"(b[2]), "+r"(b[3]),
                 "+r"(c[0]), "+r"(c[1]), "+r"(c[2]), "+r"(c[3]), "+r"(d[0]), "+r"(d[1]), "+r"(d[2]), "+r"(d[3])
               : "l"(p), "r"(tag) : "memory");
}

#define LDH ldg128_na
#define MAP 0
#define LA2 5
#define LEAD1 3

__global__ void __cluster_dims__(2, 1, 1) __launch_bounds__(NTHREADS, 1)
fused_kernel(const __grid_constant__ CUtensorMap tm_x, const __grid_constant__ CUtensorMap tm_g, const __grid_constant__ CUtensorMap tm_u,
             const __grid_constant__ CUtensorMap tm_g32, const __grid_constant__ CUtensorMap tm_u32,
             const __nv_bfloat16* __restrict__ w_r, const __nv_bfloat16* __restrict__ w_i,
             const __nv_bfloat16* __restrict__ w_gate, const __nv_bfloat16* __restrict__ w_up,
             const __nv_bfloat16* __restrict__ w_down, const __nv_bfloat16* __restrict__ gate_w, __nv_bfloat16* __restrict__ out) {
  extern __shared__ __align__(1024) unsigned char smem[];
  const uint32_t sb = s2u(smem);
  const uint32_t bars = sb + OFF_BAR;
  const int tid = threadIdx.x, warp = __shfl_sync(0xffffffffu, tid >> 5, 0), lane = tid & 31;
  const int cl = blockIdx.x >> 1, kh = blockIdx.x & 1;
  const int n0 = cl < 4 ? cl : (cl < 36 ? (cl - 4) >> 3 : (cl - 36) / 7);
  const int m0 = cl < 4 ? 15 : (cl < 36 ? (cl - 4) & 7 : cl - 28 - 7 * n0);
  const int n = MAP == 0 ? n0 : (MAP == 1 ? (m0 & 3) : ((n0 & 1) | ((m0 & 1) << 1)));
  const int m = MAP == 0 ? m0 : (MAP == 1 ? ((m0 & 12) | n0) : ((m0 & 14) | (n0 >> 1)));
  const int j = kh * 4 + n, bid = m * 8 + n * 2 + kh;

  const int c64 = 224 * j + (j & 1) * 32;
  if (warp < 8) {
    asm volatile("setmaxnreg.inc.sync.aligned.u32 208;");
    const int wg = warp >> 2, w4 = warp & 3, g = lane >> 2, t = lane & 3;
    const int rh = wg ^ kh ^ 1;
    const int p = j & 1, r = (j >> 1) & 1, hh = j >> 2;
    const uint32_t epoch = ld_relaxed(&g_ep[bid]);
    if ((tid & 127) == 0) PROF(wg, 30);
#pragma unroll 1
    for (int it = tid; it < 392; it += 256) {
      const int kc = it / 28, sg = it - kc * 28;
      const int k = 2 * (28 * hh + sg) + r;
      const float kf = (float)k * (-6.283185307179586f / 448.0f), a0 = (float)(16 * kc + p) * kf;
      uint32_t c[4], s[4];
#pragma unroll
      for (int q = 0; q < 4; q++) {
        const float a1 = fmaf((float)(2 * q), kf, a0), a2 = fmaf((float)(2 * q + 8), kf, a0);
        c[q] = pack_bf16(__cosf(a1), __cosf(a2)); s[q] = pack_bf16(__sinf(a1), __sinf(a2));
        if (k == 0) s[q] = ((q ^ p) & 1) ? 0xBF80BF80u : 0x3F803F80u;
      }
      const uint32_t a = sb + 6 * SLOT + (kc * 56 + 2 * sg) * 16;
      sts128(a, c[0], c[1], c[2], c[3]);
      sts128(a + 16, s[0], s[1], s[2], s[3]);
    }
    if ((tid & 127) == 0) PROF(wg, 31);
    fence_async_smem();
    bar_sync<0, NTHREADS - 64>();
    asm volatile("barrier.cluster.arrive.relaxed.aligned;" ::: "memory");
    if ((tid & 127) == 0) PROF(wg, 1);

    uint32_t xa[28][4];
    {
      const uint32_t xb = sb + OFF_PQ + wg * HALF_XR + (w4 * 16 + (lane & 15)) * 128;
      mbar_wait(bars + (B_XFULL + wg) * 8, 0);
      if ((tid & 127) == 0) PROF(wg, 2);
#pragma unroll
      for (int kb = 0; kb < 7; kb++) {
#pragma unroll
        for (int kk = 0; kk < 4; kk++) {
          uint32_t a = xb + kb * 8192 + (((2 * kk + (lane >> 4)) ^ (lane & 7)) << 4);
          asm volatile("ldmatrix.sync.aligned.m8n8.x4.shared.b16 {%0,%1,%2,%3}, [%4];"
                       : "=r"(xa[kb * 4 + kk][0]), "=r"(xa[kb * 4 + kk][1]), "=r"(xa[kb * 4 + kk][2]), "=r"(xa[kb * 4 + kk][3]) : "r"(a) : "memory");
        }
      }
    }
    {
      uint32_t ad[7][4];
      const uint32_t sel = p ? 0x7632 : 0x5410;
      const uint32_t sgn = r ? 0xBF80BF80u : 0x3F803F80u;
#pragma unroll
      for (int jj = 0; jj < 7; jj++) {
#pragma unroll
        for (int i = 0; i < 4; i++) {
          int ks = 2 * jj + (i >> 1), rr = i & 1;
          uint32_t lo = __byte_perm(xa[ks][rr], xa[ks][rr + 2], sel);
          uint32_t hi = __byte_perm(xa[ks + 14][rr], xa[ks + 14][rr + 2], sel);
          asm("fma.rn.bf16x2 %0, %1, %2, %3;" : "=r"(ad[jj][i]) : "r"(hi), "r"(sgn), "r"(lo));
        }
      }
      __syncwarp();
      if (lane == 0) mbar_arrive(bars + (B_XFREE + wg) * 8);
      float acc[28];
      wg_fence();
      uint64_t db = mkdesc(sb + 6 * SLOT, 896, 128, 0);
#pragma unroll
      for (int jj = 0; jj < 7; jj++) wgmma_rs_56<0>(acc, ad[jj], db + jj * 112, jj != 0);
      wg_commit();
      wg_wait<0>(); keep(acc);
      if (lane == 0) mbar_arrive(bars + (B_EMPTY + 6) * 8);
      uint32_t* xc = g_Xc + (size_t)((2 * (28 * hh + t) + r) * 2 + p) * S_ + m * 128 + rh * 64 + w4 * 16 + g;
#pragma unroll
      for (int i = 0; i < 7; i++) {
        xc[i * 16 * S_] = pack_bf16(acc[4 * i], acc[4 * i + 1]);
        xc[i * 16 * S_ + 8] = pack_bf16(acc[4 * i + 2], acc[4 * i + 3]);
      }
      __syncwarp();
      if (lane == 0) mbar_arrive(bars + B_PUBX * 8);
    }
    if ((tid & 127) == 0) PROF(wg, 3);
    const uint32_t tag = ~epoch & 1;
    unsigned char* const hbase = g_H + (size_t)(m * 2 + kh) * (56 * 4096) + rh * 2048 + (tid & 127) * 16;
#pragma unroll 1
    for (int u = 0; u < 3; u++) {
      float acc[64];
      if (wg == 1) { if (u & 1) bar_sync<6, 256>(); else bar_sync<2, 256>(); }
      const uint32_t sbu = opaque(sb);
#pragma unroll
      for (int kb = 0; kb < 7; kb++) {
        mbar_wait(sbu + OFF_BAR + (B_FULL + kb) * 8, u & 1);
        wg_fence();
        uint64_t db = mkdesc(sbu + kb * SLOT, 8192, 1024, 1);
#pragma unroll
        for (int kk = 0; kk < 4; kk++) wgmma_rs_128<1>(acc, xa[kb * 4 + kk], db + kk * 128, (kb | kk) != 0);
        wg_commit();
        if (kb == LEAD1 && wg == 0) { if (u & 1) bar_arrive<6, 256>(); else bar_arrive<2, 256>(); }
        if (kb > 0) { wg_wait<1>(); if (lane == 0) mbar_arrive(sbu + OFF_BAR + (B_EMPTY + kb - 1) * 8); }
      }
      wg_wait<0>(); keep(acc);
      if (lane == 0) mbar_arrive(sbu + OFF_BAR + (B_EMPTY + 6) * 8);
      if ((tid & 127) == 0) PROF(wg, 4 + 2 * u);
      h_epilogue<8>(acc, hbase + (u * 16 + n * 4) * 4096, tag);
      if ((tid & 127) == 0) PROF(wg, 5 + 2 * u);
    }
    {
      float acc[32];
      if (wg == 1) bar_sync<6, 256>();
      const uint32_t sbu = opaque(sb);
#pragma unroll
      for (int it = 0; it < 4; it++) {
        mbar_wait(sbu + OFF_BAR + (B_FULL + it) * 8, 1);
        wg_fence();
        uint64_t db = mkdesc(sbu + it * SLOT, 8192, 512, 2);
#pragma unroll
        for (int kk = 0; kk < 8; kk++) if (it * 8 + kk < 28) wgmma_rs_64<1>(acc, xa[it * 8 + kk], db + kk * 64, (it | kk) != 0);
        wg_commit();
        if (it == 2 && wg == 0) bar_arrive<6, 256>();
        if (it > 0) {
          wg_wait<1>();
          if (lane == 0) mbar_arrive(sbu + OFF_BAR + (B_EMPTY + it - 1) * 8);
#pragma unroll
          for (int i = it * 8 - 8; i < it * 8; i++) if (i < 4 * LA2) LDH(xa[i], hbase + i * 4096);
        }
      }
      wg_wait<0>(); keep(acc);
      if (lane == 0) mbar_arrive(sbu + OFF_BAR + (B_EMPTY + 3) * 8);
      if ((tid & 127) == 0) PROF(wg, 10);
      h_epilogue<4>(acc, hbase + (48 + n * 2) * 4096, tag);
    }
    asm volatile("barrier.cluster.wait.aligned;" ::: "memory");
    if ((tid & 127) == 0) PROF(wg, 11);

    float acc[56];
    if (wg == 1) bar_sync<2, 256>();
#pragma unroll 1
    for (int it = 0; it < 2; it++) {
#pragma unroll
      for (int e = 0; e < 7; e++) {
        if ((tid & 127) == 0) PROF(wg, 16 + it * 7 + e);
        const bool inr = e < 4 && it == 0;
        if (e >= 4 || it == 1) mbar_wait(bars + (B_FULL + e) * 8, e < 4 ? 0 : it ^ 1);
        else if (e == 0) mbar_wait(bars + B_RFULL * 8, 1);
        frag_ready(xa[e * 4], xa[e * 4 + 1], xa[e * 4 + 2], xa[e * 4 + 3], hbase + (it * 7 + e) * 16384, tag);
        wg_fence();
        const uint64_t db = mkdesc(inr ? sb + OFF_R + e * 14336 : sb + e * SLOT, 1792, 128, 0);
#pragma unroll
        for (int kk = 0; kk < 4; kk++) wgmma_rs_112<1>(acc, xa[e * 4 + kk], db + kk * 224, (e | kk) ? 1 : it);
        wg_commit();
        if (e == 1 && it == 0 && wg == 0) bar_arrive<2, 256>();
        if (it == 0 || e + LA2 < 7) {
          const int nb = it * 7 + e + LA2;
#pragma unroll
          for (int kk = 0; kk < 4; kk++) LDH(xa[((e + LA2) % 7) * 4 + kk], hbase + (nb * 4 + kk) * 4096);
        }
        wg_wait<1>();
        if (lane == 0) {
          if (it == 0 ? e >= 5 : e <= 2) mbar_arrive(bars + (B_EMPTY + (e + 6) % 7) * 8);
          if (e == 4 && it == 0) {
            mbar_arrive(bars + B_LFREE * 8);
            asm volatile("{\n.reg .b32 ra;\nmapa.shared::cluster.u32 ra, %0, %1;\nmbarrier.arrive.relaxed.cluster.shared::cluster.b64 _, [ra];\n}"
                         :: "r"(bars + B_RFREE * 8), "r"(kh ^ 1) : "memory");
          }
        }
      }
    }
    const int t128 = tid & 127;
    wg_wait<0>(); keep(acc);
    if (wg == 0) {
      if (t128 == 0) PROF(wg, 12);
      mbar_wait_cluster(bars + B_RFREE * 8, 0);
      uint32_t rdst, rbar;
      asm volatile("mapa.shared::cluster.u32 %0, %1, %2;" : "=r"(rdst) : "r"(sb + OFF_R + t128 * 16), "r"(kh ^ 1));
      asm volatile("mapa.shared::cluster.u32 %0, %1, %2;" : "=r"(rbar) : "r"(bars + B_RECV * 8), "r"(kh ^ 1));
#pragma unroll
      for (int i = 0; i < 14; i++)
        asm volatile("st.async.weak.shared::cluster.mbarrier::complete_tx::bytes.v4.f32 [%0], {%1,%2,%3,%4}, [%5];"
                     :: "r"(rdst + i * 2048), "f"(acc[4 * i]), "f"(acc[4 * i + 1]), "f"(acc[4 * i + 2]), "f"(acc[4 * i + 3]), "r"(rbar) : "memory");
    } else {
      float spec[2][28];
      if (t128 == 0) PROF(wg, 12);
      mbar_wait(bars + B_PQFULL * 8, 0);
      if (t128 == 0) { PROF(wg, 13); g_ep[bid] = epoch + 1; }
#pragma unroll
      for (int i = 0; i < 4; i++) {
        if (i == 0) mbar_wait(bars + B_GFULL * 8, 0);
        if (i >= 2) mbar_wait(bars + (B_FULL + i - 2) * 8, 1);
        wg_fence();
        const uint64_t da = mkdesc(sb + OFF_PQ + i * 14336, 1024, 1024, 1);
        const uint64_t db = mkdesc(i < 2 ? sb + OFF_R + 28672 + i * (G_IMG / 2) : sb + (i - 2) * SLOT, 896, 128, 0);
#pragma unroll
        for (int kk = 0; kk < 7; kk++) wgmma_ss_56<1, 0>(spec[i >> 1], da + kk * 128, db + kk * 112, ((i & 1) | kk) != 0);
        wg_commit();
      }
      const float* gs = reinterpret_cast<const float*>(smem + OFF_G) + w4 * 16 + g;
      const float o0 = bf16_round(1.0f - gs[0]), o1 = bf16_round(1.0f - gs[8]);
      const float g0 = gs[0] * (1.0f / (float)(S_ * D_)), g1 = gs[8] * (1.0f / (float)(S_ * D_));
      wg_wait<0>(); keep(spec[0]); keep(spec[1]);
      if (t128 == 0) PROF(wg, 14);
      mbar_wait_cluster(bars + B_RECV * 8, 0);
      if (t128 == 0) PROF(wg, 0);
      float4 o[14];
#pragma unroll
      for (int i = 0; i < 14; i++) o[i] = lds128f(sb + OFF_R + t128 * 16 + i * 2048);
      bar_sync<5, 128>();
      const uint32_t st = sb + OFF_PQ + w4 * 3840;
#pragma unroll
      for (int i = 0; i < 7; i++) {
        uint32_t pk[4];
#pragma unroll
        for (int e = 0; e < 2; e++) {
          const int c = 2 * i + e, si = i * 4 + e;
          pk[2 * e] = pack_bf16(fmaf(acc[4 * c] + o[c].x, o0, g0 * spec[0][si]), fmaf(acc[4 * c + 1] + o[c].y, o0, g0 * spec[1][si]));
          pk[2 * e + 1] = pack_bf16(fmaf(acc[4 * c + 2] + o[c].z, o1, g1 * spec[0][si + 2]), fmaf(acc[4 * c + 3] + o[c].w, o1, g1 * spec[1][si + 2]));
        }
        asm volatile("stmatrix.sync.aligned.m8n8.x4.shared.b16 [%0], {%1,%2,%3,%4};"
                     :: "r"(st + (lane & 15) * 240 + (lane >> 4) * 16 + i * 32), "r"(pk[0]), "r"(pk[1]), "r"(pk[2]), "r"(pk[3]) : "memory");
      }
      __syncwarp();
      if (lane < 28) {
        const int r2 = lane >= 14, cc = lane - r2 * 14;
        unsigned char* ob = reinterpret_cast<unsigned char*>(out) + (size_t)(m * 128 + kh * 64 + w4 * 16 + r2) * (D_ * 2) + n * 224 + cc * 16;
        float4 v[8];
#pragma unroll
        for (int i = 0; i < 8; i++) v[i] = lds128f(st + r2 * 240 + cc * 16 + i * 480);
#pragma unroll
        for (int i = 0; i < 8; i++) stg128(ob + i * (D_ * 4), __float_as_uint(v[i].x), __float_as_uint(v[i].y), __float_as_uint(v[i].z), __float_as_uint(v[i].w));
      }
    }
    if (t128 == 0) { PROF(wg, 15); if (wg) { PROFG(4, 30); PROF(4, 31); } }
  } else if (warp < 12) {
    asm volatile("setmaxnreg.dec.sync.aligned.u32 72;");
    const int t = tid - 256;
    const int k = bid;
    if (t == 0) PROF(2, 0);
    uint4 gv[7];
#pragma unroll
    for (int i = 0; i < 7; i++) gv[i] = ldg128(reinterpret_cast<const uint4*>(gate_w) + i * 8 + (t & 7));
    bar_sync<0, NTHREADS - 64>();
    asm volatile("barrier.cluster.arrive.relaxed.aligned;" ::: "memory");
    mbar_wait(bars + B_PIN * 8, 0);
    if (t == 0) PROF(2, 4);
    {
      const uint32_t wa = sb + 5 * SLOT + (((t & 7) - bid) & 7) * 450 + (t >> 3) * 2, wc = wa + 448 - (t >> 3) * 4;
      uint2* dst = g_Wt + (t >> 3) * S_ + 16 * bid + 2 * (t & 7);
#pragma unroll 1
      for (int h = 0; h < 2; h++) {
        uint32_t w[4][8];
#pragma unroll
        for (int i = 0; i < 4; i++) {
#pragma unroll
          for (int e = 0; e < 4; e++) { w[i][2 * e] = lds16(wa + h * 128 + i * 32 + e * 3600); w[i][2 * e + 1] = lds16(wc - h * 128 - i * 32 + e * 3600); }
        }
#pragma unroll
        for (int i = 0; i < 4; i++)
          if (i < 3 || h == 0 || t < 8)
            stg128(dst + (h * 64 + i * 16) * S_, __byte_perm(w[i][0], w[i][1], 0x5410), __byte_perm(w[i][4], w[i][5], 0x5410), __byte_perm(w[i][2], w[i][3], 0x5410), __byte_perm(w[i][6], w[i][7], 0x5410));
      }
    }
    __syncwarp();
    if (lane < 3) mbar_arrive(bars + (lane ? B_EMPTY + 5 : B_PUBW) * 8);
    if (t == 0) PROF(2, 6);
    {
      const int row = n * 16 + (t >> 3), l8 = t & 7;
      mbar_wait(bars + (B_XFULL + 1) * 8, 0);
      float sum = 0.f;
#pragma unroll
      for (int i = 0; i < 7; i++) {
        const uint4 a = lds128(sb + OFF_R + i * 8192 + row * 128 + ((l8 ^ (row & 7)) << 4));
        const uint32_t aa[4] = {a.x, a.y, a.z, a.w}, bb[4] = {gv[i].x, gv[i].y, gv[i].z, gv[i].w};
#pragma unroll
        for (int e = 0; e < 4; e++) {
          const uint32_t pr = as_u(__hmul2(as_b2(aa[e]), as_b2(bb[e])));
          sum += bf_lo(pr) + bf_hi(pr);
        }
      }
      sum += __shfl_xor_sync(0xffffffffu, sum, 1); sum += __shfl_xor_sync(0xffffffffu, sum, 2); sum += __shfl_xor_sync(0xffffffffu, sum, 4);
      if (lane == 0) mbar_arrive(bars + (B_XFREE + 1) * 8);
      if (l8 == 0) g_gate[m * 128 + kh * 64 + row] = bf16_round(__fdividef(1.0f, 1.0f + __expf(-bf16_round(sum))));
    }
    if (t < 98) {
      int cid = m * 98 + t, kc = cid / 56, nn = cid - kc * 56;
      int d = 112 * n + 8 * (2 * (nn >> 3) + (nn & 1)) + (nn & 6) + kh;
      int dr = d > 224 ? d - 448 : d;
      const float df = (float)dr * (-6.283185307179586f / 448.0f);
      uint32_t pk[4];
#pragma unroll
      for (int e = 0; e < 4; e++) {
        const float a = (float)(4 * kc + e) * df;
        pk[e] = pack_bf16(2.0f * __cosf(a), 2.0f * __sinf(a));
      }
      if (kc == 0) pk[0] = (((d >> 1) ^ kh) & 1) ? 0xBF803F80u : 0x3F803F80u;
      stg128(g_G + (size_t)(n * 2 + kh) * G_IMG + cid * 16, pk[0], pk[1], pk[2], pk[3]);
    }
    if (t == 0) PROF(2, 11);
    mbar_wait(bars + B_XFREE * 8, 0);
    if (k < 113) {
      const float u = -6.283185307179586f / 2048.0f, t2 = (float)(2 * t) * u, rr = (float)(t >> 4) * u;
#pragma unroll 1
      for (int i = 0; i < 4; i++) {
        const float q = (float)(2 * i), l = (float)((t & 15) + 64 * i);
        sts128(sb + OFF_TW + i * 2048 + t * 16, cis(t2 * q), cis((t2 + u) * q), cis(t2 * (q + 1.0f)), cis((t2 + u) * (q + 1.0f)));
        sts128(sb + OFF_TW + 8192 + i * 2048 + t * 16, cis(rr * l), cis(rr * (l + 16.0f)), cis(rr * (l + 32.0f)), cis(rr * (l + 48.0f)));
      }
      const float l = (float)((t >> 1) & 15) * (8.0f * u), jj = (float)((t >> 5) * 4 + (t & 1) * 2);
      sts64(sb + OFF_TW + 16384 + t * 8, cis(l * jj), cis(l * (jj + 1.0f)));
    }
    if (t == 0) PROF(2, 9);
    mbar_wait(bars + B_RFULL * 8, 0);
    if (t < 112) {
      const int js = bid >> 4, nn = (t >> 1) / 14, cc = (t >> 1) - nn * 14;
      unsigned char* wdst = g_Wd + (size_t)((js >> 2) * 4 + nn) * WD_IMG + cc * 128 + (t & 1) * 16;
      uint4 v[7];
#pragma unroll
      for (int i = 0; i < 7; i++) v[i] = lds128(sb + OFF_R + i * 1792 + (t & 1) * 896 + (t >> 1) * 16);
#pragma unroll
      for (int i = 0; i < 7; i++) {
        int col = 14 * (bid & 15) + 2 * i - (js & 1) * 32;
        if (col < 0) col += 224;
        const int kpos = col < 192 ? (col >> 6) * 256 + (js & 3) * 64 + (col & 63) : 576 + (js & 3) * 32 + col;
        stg128(wdst + (kpos >> 3) * 1792 + (kpos & 7) * 16, v[i].x, v[i].y, v[i].z, v[i].w);
      }
    }
    __syncwarp();
    if (lane == 0) mbar_arrive(bars + B_PUBD * 8);
    bar_sync<3, 128>();
    if (k < 113) {
      if (t == 0) PROF(2, 2);
      mbar_wait(bars + B_XCFULL * 8, 0);
      if (t == 0) PROF(2, 3);
      c2 v[16];
      const uint32_t se = k == 0 ? 0x4410 : (k == 112 ? 0x4432 : 0x3210), so = k == 0 ? 0x4410 : (k == 112 ? 0x3244 : 0x3210);
#pragma unroll
      for (int jj = 0; jj < 8; jj++) {
        const uint2 e2 = lds64(sb + OFF_EXCH + jj * 1024 + t * 8), o2 = lds64(sb + OFF_EXCH + 8192 + jj * 1024 + t * 8);
#pragma unroll
        for (int h = 0; h < 2; h++) {
          const b2 e = as_b2(__byte_perm(h ? e2.y : e2.x, 0, se)), o = as_b2(__byte_perm(h ? o2.y : o2.x, 0, so));
          const uint32_t s = as_u(__hadd2(e, o)), d = as_u(__hsub2(e, o)) ^ 0x80000000u;
          v[2 * jj + h] = mk(as_b2(__byte_perm(s, d, 0x5410)), as_b2(__byte_perm(s, d, 0x7632)));
        }
      }
      if (t == 0) PROF(2, 12);
      columns(v, sb, t);
      if (t == 0) PROF(2, 14);
      const int pre = (k == 112) ? 1 : 2 * k, pim = (k == 112) ? 1 : 2 * k + 1;
      uint32_t* pq = reinterpret_cast<uint32_t*>(g_PQ) + (t >> 5) * 14336;
      uint32_t* pr = pq + pre * 32 + ((((lane >> 2) ^ pre) & 7) << 2) + (lane & 3);
      uint32_t* pi = pq + pim * 32 + ((((lane >> 2) ^ pim) & 7) << 2) + (lane & 3);
#pragma unroll
      for (int jj = 0; jj < 8; jj++) {
        const b2 ar = as_b2(__byte_perm(as_u(v[2 * jj].y), as_u(v[2 * jj + 1].y), 0x5410)), br = as_b2(__byte_perm(as_u(v[2 * jj].y), as_u(v[2 * jj + 1].y), 0x7632));
        const b2 ai = as_b2(__byte_perm(as_u(v[2 * jj].x), as_u(v[2 * jj + 1].x), 0x5410)), bi = as_b2(__byte_perm(as_u(v[2 * jj].x), as_u(v[2 * jj + 1].x), 0x7632));
        pr[jj * 57344] = as_u(__hadd2(ar, br));
        if (k != 112) pr[jj * 57344 + 7168] = as_u(__hsub2(ar, br));
        if (k != 0) pi[jj * 57344 + 7168] = as_u(__hadd2(ai, bi));
        if (k != 0 && k != 112) pi[jj * 57344] = as_u(__hsub2(ai, bi));
      }
      fence_async_smem();
    }
    bar_sync<3, 128>();
    if (t == 0) { PROF(2, 5); red_release(&g_cnt[5 * 32]); PROF(2, 7); }
    __syncwarp();
    asm volatile("barrier.cluster.wait.aligned;" ::: "memory");
  } else {
    asm volatile("setmaxnreg.dec.sync.aligned.u32 24;");
    if (warp == 12) {
      if (lane < 10) mbar_init(bars + (lane < NSLOT ? B_FULL + lane : (lane < 9 ? B_XFULL - 7 + lane : B_PIN)) * 8, 1);
      fence_async_smem();
      bar_arrive<0, NTHREADS - 64>();
      if (elect()) {
        mbar_expect(bars + B_PIN * 8, 14400);
        bulk_g2s(sb + 5 * SLOT, reinterpret_cast<const unsigned char*>(w_r) + bid * 7200, 7200, bars + B_PIN * 8);
        bulk_g2s(sb + 5 * SLOT + 7200, reinterpret_cast<const unsigned char*>(w_i) + bid * 7200, 7200, bars + B_PIN * 8);
#pragma unroll
        for (int w = 0; w < 2; w++) {
          mbar_expect(bars + (B_XFULL + w) * 8, HALF_XR);
          tma3d(sb + OFF_PQ + w * HALF_XR, &tm_x, 0, m * 128 + (w ^ kh ^ 1) * 64, 0, bars + (B_XFULL + w) * 8);
        }
        PROF(3, 3);
      }
#pragma unroll 1
      for (int i = 0; i < 5; i++) {
        if (elect()) {
          const uint32_t fb = bars + (B_FULL + i) * 8;
          mbar_expect(fb, SLOT);
          tma2d(sb + i * SLOT, &tm_g, c64, i * 64, fb);
          tma2d(sb + i * SLOT + 8192, &tm_u, c64, i * 64, fb);
          PROF(3, 4 + i);
        }
      }
      if (lane < 4) prefetch_tma2d((lane & 1) ? &tm_u : &tm_g, c64, 320 + (lane >> 1) * 64);
    } else if (warp == 14) {
      if (lane < NSLOT) mbar_init(bars + (B_EMPTY + lane) * 8, 8);
      const int i = B_XFREE + lane;
      if (i < B_END) mbar_init(bars + i * 8, i >= B_PQFULL ? 1 : ((i == B_XFREE || i >= B_PUBW) ? 4 : 8));
      asm volatile("fence.mbarrier_init.release.cluster;" ::: "memory");
      fence_async_smem();
      __syncwarp();
      if (lane == 0) mbar_expect(bars + B_RECV * 8, 64 * 112 * 4);
      bar_arrive<0, NTHREADS - 64>();
    }
    const uint32_t epoch = ld_relaxed(&g_ep[bid]);
    if (warp == 13 && lane == 0) { PROFG(4, 0); PROF(4, 1); }
    bar_sync<1, 128>();
    asm volatile("barrier.cluster.arrive.relaxed.aligned;" ::: "memory");
    if (warp == 12) {
      int slot = 5, ph = 1;
      auto wait_slot = [&]() { mbar_wait(bars + (B_EMPTY + slot) * 8, ph ^ (slot >= 5)); };
      auto adv = [&]() { if (++slot == NSLOT) { slot = 0; ph ^= 1; } };
      const int c32 = 224 * j + ((j & 1) ? 0 : 192);
#pragma unroll 1
      for (int i = 5; i < 25; i++) {
        wait_slot();
        if (elect()) {
          const uint32_t dst = sb + slot * SLOT, fb = bars + (B_FULL + slot) * 8;
          const bool last = i >= 21;
          const int cc = last ? c32 : c64 + 64 * (i / 7), rr = last ? slot * 128 : slot * 64;
          mbar_expect(fb, SLOT);
          tma2d(dst, last ? &tm_g32 : &tm_g, cc, rr, fb);
          tma2d(dst + 8192, last ? &tm_u32 : &tm_u, cc, rr, fb);
        }
        adv();
      }
      if (lane == 0) PROF(3, 0);
      mbar_wait(bars + B_PREP * 8, 0);
      if (lane == 0) PROF(3, 1);
#pragma unroll 1
      for (int i = 4; i < 16; i++) {
        if (lane == 0) PROF(3, 16 + i);
        wait_slot();
        if (elect()) {
          const int bytes = i < 14 ? 14336 : G_IMG / 2;
          const unsigned char* src = i < 14 ? g_Wd + (size_t)j * WD_IMG + i * 14336 : g_G + (size_t)(n * 4 + i - 12) * (G_IMG / 2);
          mbar_expect(bars + (B_FULL + slot) * 8, bytes);
          bulk_g2s(sb + slot * SLOT, src, bytes, bars + (B_FULL + slot) * 8);
        }
        adv();
      }
      if (lane == 0) PROF(3, 2);
    } else if (warp == 13) {
      mbar_wait(bars + B_PUBW * 8, 0);
      if (lane == 0) PROF(4, 7);
      mbar_wait(bars + B_PUBX * 8, 0);
      if (lane == 0) {
        PROF(4, 8);
        red_release(&g_cnt[(j >> 1) * 32]);
        red_relaxed(&g_cnt[6 * 32]);
        PROF(4, 18);
      }
      __syncwarp();
      mbar_wait(bars + B_PUBD * 8, 0);
      if (lane == 0) { PROF(4, 9); red_release(&g_cnt[4 * 32]); PROF(4, 19); }
      __syncwarp();
      mbar_wait(bars + B_LFREE * 8, 0);
      if (elect()) {
        mbar_expect(bars + B_GFULL * 8, G_IMG);
        bulk_g2s(sb + OFF_R + 28672, g_G + (size_t)(n * 2) * G_IMG, G_IMG, bars + B_GFULL * 8);
      }
    } else if (warp == 14) {
#pragma unroll 1
      for (int u = 0; u < 2; u++) {
        wait_ge(&g_cnt[(6 - 2 * u) * 32], (epoch + 1) * 128);
        fence_async_global();
        if (lane == 0) { mbar_arrive(bars + (B_PREPW - u) * 8); PROF(5, 9 - u); }
      }
    } else {
      mbar_wait(bars + B_XFREE * 8, 0);
      if (elect()) {
        prefetch_l2(reinterpret_cast<const unsigned char*>(w_gate) + bid * 12544, 12544);
        prefetch_l2(reinterpret_cast<const unsigned char*>(w_up) + bid * 12544, 12544);
      }
      mbar_wait(bars + (B_XFREE + 1) * 8, 0);
      if (elect()) {
        mbar_expect(bars + B_RFULL * 8, 12544);
        bulk_g2s(sb + OFF_R, reinterpret_cast<const unsigned char*>(w_down) + bid * 12544, 12544, bars + B_RFULL * 8);
      }
      if (bid < 113) {
        const int sl = (bid == 112) ? 0 : bid;
        wait_ge(&g_cnt[((sl & 1) + 2 * ((sl >> 1) / 28)) * 32], (epoch + 1) * 32);
        fence_async_global();
        if (elect()) {
          PROF(5, 16);
          mbar_expect(bars + B_XCFULL * 8, 16384);
          bulk_g2s(sb + OFF_EXCH, g_Xc + sl * 2 * S_, 16384, bars + B_XCFULL * 8);
        }
        mbar_wait(bars + B_PREPW * 8, 0);
        if (elect()) {
          mbar_expect(bars + B_WFULL * 8, 16384);
          bulk_g2s(sb + OFF_WS, g_Wt + bid * S_, 16384, bars + B_WFULL * 8);
          PROF(5, 17);
        }
      }
      mbar_wait(bars + B_PREP * 8, 0);
      if (elect()) {
        mbar_expect(bars + B_RFULL * 8, HALF_XR);
        bulk_g2s(sb + OFF_R, g_Wd + (size_t)j * WD_IMG, HALF_XR, bars + B_RFULL * 8);
        PROF(5, 19);
      }
      wait_ge(&g_cnt[5 * 32], (epoch + 1) * 128);
      fence_async_global();
      if (elect()) {
        PROF(5, 18);
        mbar_expect(bars + B_PQFULL * 8, HALF_XR + 256);
        const unsigned char* src = g_PQ + (size_t)(m * 2 + kh) * HALF_XR;
        bulk_g2s(sb + OFF_PQ, src, 28672, bars + B_PQFULL * 8);
        bulk_g2s(sb + OFF_PQ + 28672, src + 28672, 28672, bars + B_PQFULL * 8);
        bulk_g2s(sb + OFF_G, g_gate + m * 128 + kh * 64, 256, bars + B_PQFULL * 8);
      }
    }
    __syncwarp();
    asm volatile("barrier.cluster.wait.aligned;" ::: "memory");
  }
}

typedef CUresult (*EncodeFn)(CUtensorMap*, CUtensorMapDataType, cuuint32_t, void*, const cuuint64_t*, const cuuint64_t*, const cuuint32_t*,
                             const cuuint32_t*, CUtensorMapInterleave, CUtensorMapSwizzle, CUtensorMapL2promotion, CUtensorMapFloatOOBfill);

void make_map(EncodeFn enc, CUtensorMap* tm, const void* base, int cols, int rows, int bc, int br, CUtensorMapSwizzle sw) {
  cuuint64_t gd[2] = {(cuuint64_t)cols, (cuuint64_t)rows};
  cuuint64_t gs[1] = {(cuuint64_t)cols * 2};
  cuuint32_t bd[2] = {(cuuint32_t)bc, (cuuint32_t)br};
  cuuint32_t es[2] = {1, 1};
  enc(tm, CU_TENSOR_MAP_DATA_TYPE_BFLOAT16, 2, const_cast<void*>(base), gd, gs, bd, es, CU_TENSOR_MAP_INTERLEAVE_NONE, sw,
      CU_TENSOR_MAP_L2_PROMOTION_L2_128B, CU_TENSOR_MAP_FLOAT_OOB_FILL_NONE);
}

}

extern "C" void kernel_launch(void* const* d_in, const int* in_sizes, int n_in, void* d_out, int out_size) {
  (void)in_sizes; (void)n_in; (void)out_size;
  const __nv_bfloat16* x = (const __nv_bfloat16*)d_in[0];
  const __nv_bfloat16* w_r = (const __nv_bfloat16*)d_in[1];
  const __nv_bfloat16* w_i = (const __nv_bfloat16*)d_in[2];
  const __nv_bfloat16* w_gate = (const __nv_bfloat16*)d_in[4];
  const __nv_bfloat16* w_up = (const __nv_bfloat16*)d_in[5];
  const __nv_bfloat16* w_down = (const __nv_bfloat16*)d_in[6];
  const __nv_bfloat16* gate_w = (const __nv_bfloat16*)d_in[7];
  static EncodeFn enc = nullptr;
  static bool ok = false;
  if (!enc) {
    cudaDriverEntryPointQueryResult qr;
    cudaGetDriverEntryPoint("cuTensorMapEncodeTiled", (void**)&enc, cudaEnableDefault, &qr);
    cudaFuncSetAttribute(fused_kernel, cudaFuncAttributeMaxDynamicSharedMemorySize, SMEM_BYTES);
    cudaFuncAttributes fa;
    cudaFuncGetAttributes(&fa, fused_kernel);
    ok = (fa.numRegs == 128);
  }
  if (!ok) return;
  CUtensorMap tx, tg, tu, tg32, tu32;
  {
    cuuint64_t gd[3] = {64, (cuuint64_t)S_, 7};
    cuuint64_t gs[2] = {(cuuint64_t)D_ * 2, 128};
    cuuint32_t bd[3] = {64, 64, 7};
    cuuint32_t es[3] = {1, 1, 1};
    enc(&tx, CU_TENSOR_MAP_DATA_TYPE_BFLOAT16, 3, const_cast<__nv_bfloat16*>(x), gd, gs, bd, es, CU_TENSOR_MAP_INTERLEAVE_NONE, CU_TENSOR_MAP_SWIZZLE_128B,
        CU_TENSOR_MAP_L2_PROMOTION_L2_128B, CU_TENSOR_MAP_FLOAT_OOB_FILL_NONE);
  }
  make_map(enc, &tg, w_gate, F_, D_, 64, 64, CU_TENSOR_MAP_SWIZZLE_128B);
  make_map(enc, &tu, w_up, F_, D_, 64, 64, CU_TENSOR_MAP_SWIZZLE_128B);
  make_map(enc, &tg32, w_gate, F_, D_, 32, 128, CU_TENSOR_MAP_SWIZZLE_64B);
  make_map(enc, &tu32, w_up, F_, D_, 32, 128, CU_TENSOR_MAP_SWIZZLE_64B);
  fused_kernel<<<128, NTHREADS, SMEM_BYTES>>>(tx, tg, tu, tg32, tu32, w_r, w_i, w_gate, w_up, w_down, gate_w, (__nv_bfloat16*)d_out);
}
```

```cpp
#include <cuda_runtime.h>
#include <cuda_bf16.h>
#include <cuda.h>
#include <stdint.h>

namespace {

constexpr int S_ = 2048, D_ = 448, F_ = 1792;
constexpr int NTHREADS = 512;
constexpr int SLOT = 16384, NSLOT = 7;
constexpr int HALF_XR = 57344;
constexpr int OFF_PQ = NSLOT * SLOT;
constexpr int OFF_R = OFF_PQ + HALF_XR;
constexpr int OFF_EXCH = OFF_PQ;
constexpr int OFF_WS = OFF_EXCH + 18432;
constexpr int OFF_TW = OFF_WS + 16384;
constexpr int OFF_MISC = OFF_R + HALF_XR;
constexpr int OFF_G = OFF_MISC;
constexpr int OFF_BAR = OFF_MISC + 512;
constexpr int SMEM_BYTES = OFF_BAR + 512;
constexpr int B_FULL = 0, B_EMPTY = 7, B_XFULL = 14  ;
constexpr int B_XFREE = 16  , B_PUBX = 18, B_RFREE = 19, B_LFREE = 20;
constexpr int B_PUBW = 21, B_PUBD = 22;
constexpr int B_PQFULL = 23, B_RECV = 24, B_WFULL = 25, B_XCFULL = 26, B_PREP = 27, B_PREPW = 28, B_RFULL = 29, B_GFULL = 30, B_END = 31, B_PIN = 31;

constexpr int WD_IMG = 896 * 112 * 2;
constexpr int G_IMG = 224 * 56 * 2;

__device__ __align__(1024) uint32_t g_Xc[112 * 2 * S_];
__device__ __align__(1024) unsigned char g_H[32 * 56 * 4096];
__device__ __align__(1024) unsigned char g_PQ[32 * HALF_XR];
__device__ __align__(1024) unsigned char g_Wd[8 * WD_IMG];
__device__ __align__(1024) unsigned char g_G[8 * G_IMG];
__device__ __align__(1024) uint2 g_Wt[113 * S_];
__device__ __align__(1024) float g_gate[S_];
__device__ __align__(128) unsigned int g_ep[128];
__device__ __align__(128) unsigned int g_cnt[8 * 32];

#define PROF(role, idx) do {} while (0)
#define PROFG(role, idx) do {} while (0)

__device__ __forceinline__ uint32_t s2u(const void* p) { return (uint32_t)__cvta_generic_to_shared(p); }
__device__ __forceinline__ void mbar_init(uint32_t b, int c) { asm volatile("mbarrier.init.shared::cta.b64 [%0], %1;" :: "r"(b), "r"(c) : "memory"); }
__device__ __forceinline__ void mbar_expect(uint32_t b, int bytes) { asm volatile("mbarrier.arrive.expect_tx.shared::cta.b64 _, [%0], %1;" :: "r"(b), "r"(bytes) : "memory"); }
__device__ __forceinline__ void mbar_arrive(uint32_t b) { asm volatile("mbarrier.arrive.shared::cta.b64 _, [%0];" :: "r"(b) : "memory"); }
__device__ __forceinline__ void mbar_wait(uint32_t b, int ph) {
  asm volatile("{\n.reg .pred p;\n.reg .u32 c;\nmov.u32 c, 0;\nL_WAIT:\nmbarrier.try_wait.parity.shared::cta.b64 p, [%0], %1;\n@p bra.uni L_DONE;\n"
               "add.u32 c, c, 1;\nsetp.lt.u32 p, c, 4194304;\n@p bra.uni L_WAIT;\ntrap;\nL_DONE:\n}" :: "r"(b), "r"(ph) : "memory");
}
__device__ __forceinline__ void mbar_wait_cluster(uint32_t b, int ph) {
  asm volatile("{\n.reg .pred p;\n.reg .u32 c;\nmov.u32 c, 0;\nL_WAIT:\nmbarrier.try_wait.parity.acquire.cluster.shared::cta.b64 p, [%0], %1;\n@p bra.uni L_DONE;\n"
               "add.u32 c, c, 1;\nsetp.lt.u32 p, c, 4194304;\n@p bra.uni L_WAIT;\ntrap;\nL_DONE:\n}" :: "r"(b), "r"(ph) : "memory");
}
__device__ __forceinline__ uint32_t ld_acquire(const unsigned int* p) { uint32_t v; asm volatile("ld.acquire.gpu.global.u32 %0, [%1];" : "=r"(v) : "l"(p) : "memory"); return v; }
__device__ __forceinline__ uint32_t ld_relaxed(const unsigned int* p) { uint32_t v; asm volatile("ld.relaxed.gpu.global.u32 %0, [%1];" : "=r"(v) : "l"(p) : "memory"); return v; }
__device__ __forceinline__ void wait_ge(const unsigned int* p, uint32_t target) {
#pragma unroll 1
  for (int i = 0; i < (1 << 22); i++) { if ((int)(ld_acquire(p) - target) >= 0) return; }
  __trap();
}
__device__ __forceinline__ void red_release(unsigned int* p) { asm volatile("red.release.gpu.global.add.u32 [%0], 1;" :: "l"(p) : "memory"); }
__device__ __forceinline__ void red_relaxed(unsigned int* p) { asm volatile("red.relaxed.gpu.global.add.u32 [%0], 1;" :: "l"(p) : "memory"); }
__device__ __forceinline__ bool elect() { uint32_t p; asm volatile("{\n.reg .pred p;\nelect.sync _|p, 0xffffffff;\nselp.u32 %0, 1, 0, p;\n}" : "=r"(p)); return p; }
__device__ __forceinline__ void fence_async_smem() { asm volatile("fence.proxy.async.shared::cta;" ::: "memory"); }
__device__ __forceinline__ void fence_async_global() { asm volatile("fence.proxy.async.global;" ::: "memory"); }
template <int ID, int N> __device__ __forceinline__ void bar_sync() { asm volatile("bar.sync %0, %1;" :: "n"(ID), "n"(N) : "memory"); }
template <int ID, int N> __device__ __forceinline__ void bar_arrive() { asm volatile("bar.arrive %0, %1;" :: "n"(ID), "n"(N) : "memory"); }
__device__ __forceinline__ void tma2d(uint32_t dst, const CUtensorMap* tm, int c0, int c1, uint32_t bar) {
  asm volatile("cp.async.bulk.tensor.2d.shared::cluster.global.mbarrier::complete_tx::bytes [%0], [%1, {%3, %4}], [%2];"
               :: "r"(dst), "l"(tm), "r"(bar), "r"(c0), "r"(c1) : "memory");
}
__device__ __forceinline__ void tma3d(uint32_t dst, const CUtensorMap* tm, int c0, int c1, int c2, uint32_t bar) {
  asm volatile("cp.async.bulk.tensor.3d.shared::cluster.global.mbarrier::complete_tx::bytes [%0], [%1, {%3, %4, %5}], [%2];"
               :: "r"(dst), "l"(tm), "r"(bar), "r"(c0), "r"(c1), "r"(c2) : "memory");
}
__device__ __forceinline__ void bulk_g2s(uint32_t dst, const void* src, int bytes, uint32_t bar) {
  asm volatile("cp.async.bulk.shared::cluster.global.mbarrier::complete_tx::bytes [%0], [%1], %2, [%3];"
               :: "r"(dst), "l"(src), "r"(bytes), "r"(bar) : "memory");
}
__device__ __forceinline__ void prefetch_l2(const void* src, int bytes) {
  asm volatile("cp.async.bulk.prefetch.L2.global [%0], %1;" :: "l"(src), "r"(bytes) : "memory");
}
__device__ __forceinline__ void prefetch_tma2d(const CUtensorMap* tm, int c0, int c1) {
  asm volatile("cp.async.bulk.prefetch.tensor.2d.L2.global [%0, {%1, %2}];" :: "l"(tm), "r"(c0), "r"(c1) : "memory");
}
__device__ __forceinline__ uint64_t mkdesc(uint32_t addr, uint32_t lbo, uint32_t sbo, uint32_t mode) {
  return (uint64_t)((addr & 0x3FFFF) >> 4) | ((uint64_t)(lbo >> 4) << 16) | ((uint64_t)(sbo >> 4) << 32) | ((uint64_t)mode << 62);
}
__device__ __forceinline__ void wg_fence() { asm volatile("wgmma.fence.sync.aligned;" ::: "memory"); }
__device__ __forceinline__ void wg_commit() { asm volatile("wgmma.commit_group.sync.aligned;" ::: "memory"); }
template <int N> __device__ __forceinline__ void wg_wait() { asm volatile("wgmma.wait_group.sync.aligned %0;" :: "n"(N) : "memory"); }
template <int N> __device__ __forceinline__ void keep(float (&d)[N]) {
#pragma unroll
  for (int i = 0; i < N; i++) asm volatile("" : "+f"(d[i]) :: "memory");
}
__device__ __forceinline__ uint32_t pack_bf16(float lo, float hi) { uint32_t r; asm("cvt.rn.bf16x2.f32 %0, %1, %2;" : "=r"(r) : "f"(hi), "f"(lo)); return r; }
__device__ __forceinline__ float bf16_round(float v) { return __bfloat162float(__float2bfloat16_rn(v)); }
__device__ __forceinline__ void sts128(uint32_t a, uint32_t x, uint32_t y, uint32_t z, uint32_t w) { asm volatile("st.shared.v4.b32 [%0], {%1,%2,%3,%4};" :: "r"(a), "r"(x), "r"(y), "r"(z), "r"(w) : "memory"); }
__device__ __forceinline__ float4 lds128f(uint32_t a) { float4 v; asm volatile("ld.shared.v4.f32 {%0,%1,%2,%3}, [%4];" : "=f"(v.x), "=f"(v.y), "=f"(v.z), "=f"(v.w) : "r"(a) : "memory"); return v; }

__device__ __forceinline__ uint2 lds64(uint32_t a) { uint2 v; asm volatile("ld.shared.v2.b32 {%0,%1}, [%2];" : "=r"(v.x), "=r"(v.y) : "r"(a) : "memory"); return v; }
__device__ __forceinline__ float bf_lo(uint32_t w) { return __uint_as_float(w << 16); }
__device__ __forceinline__ float bf_hi(uint32_t w) { return __uint_as_float(w & 0xffff0000u); }
__device__ __forceinline__ uint32_t opaque(uint32_t v) { asm volatile("" : "+r"(v)); return v; }
__device__ __forceinline__ uint4 ldg128(const void* p) { uint4 v; asm volatile("ld.global.nc.v4.b32 {%0,%1,%2,%3}, [%4];" : "=r"(v.x), "=r"(v.y), "=r"(v.z), "=r"(v.w) : "l"(p)); return v; }
__device__ __forceinline__ void stg128(void* p, uint32_t x, uint32_t y, uint32_t z, uint32_t w) { asm volatile("st.global.v4.b32 [%0], {%1,%2,%3,%4};" :: "l"(p), "r"(x), "r"(y), "r"(z), "r"(w) : "memory"); }
__device__ __forceinline__ void stg128_l2(void* p, uint32_t x, uint32_t y, uint32_t z, uint32_t w) { asm volatile("st.relaxed.gpu.global.v4.b32 [%0], {%1,%2,%3,%4};" :: "l"(p), "r"(x), "r"(y), "r"(z), "r"(w) : "memory"); }
__device__ __forceinline__ void ldg128_na(uint32_t (&v)[4], const void* p) { asm volatile("ld.global.L1::no_allocate.v4.b32 {%0,%1,%2,%3}, [%4];" : "=r"(v[0]), "=r"(v[1]), "=r"(v[2]), "=r"(v[3]) : "l"(p) : "memory"); }
__device__ __forceinline__ void ldg128_l2(uint32_t (&v)[4], const void* p) { asm volatile("ld.relaxed.gpu.global.v4.b32 {%0,%1,%2,%3}, [%4];" : "=r"(v[0]), "=r"(v[1]), "=r"(v[2]), "=r"(v[3]) : "l"(p) : "memory"); }
__device__ __forceinline__ uint4 lds128(uint32_t a) { uint4 v; asm volatile("ld.shared.v4.b32 {%0,%1,%2,%3}, [%4];" : "=r"(v.x), "=r"(v.y), "=r"(v.z), "=r"(v.w) : "r"(a) : "memory"); return v; }
__device__ __forceinline__ uint32_t lds16(uint32_t a) { uint32_t v; asm volatile("ld.shared.u16 %0, [%1];" : "=r"(v) : "r"(a) : "memory"); return v; }
__device__ __forceinline__ void sts64(uint32_t a, uint32_t x, uint32_t y) { asm volatile("st.shared.v2.b32 [%0], {%1,%2};" :: "r"(a), "r"(x), "r"(y) : "memory"); }
template <int TB> __device__ __forceinline__ void wgmma_rs_128(float (&d)[64], const uint32_t (&a)[4], uint64_t db, int sc) {
  asm volatile("{\n.reg .pred p;\nsetp.ne.b32 p, %69, 0;\n"
    "wgmma.mma_async.sync.aligned.m64n128k16.f32.bf16.bf16 {%0, %1, %2, %3, %4, %5, %6, %7, %8, %9, %10, %11, %12, %13, %14, %15, %16, %17, %18, %19, %20, %21, %22, %23, %24, %25, %26, %27, %28, %29, %30, %31, %32, %33, %34, %35, %36, %37, %38, %39, %40, %41, %42, %43, %44, %45, %46, %47, %48, %49, %50, %51, %52, %53, %54, %55, %56, %57, %58, %59, %60, %61, %62, %63}, {%64, %65, %66, %67}, %68, p, 1, 1, %70;\n}\n"
    : "+f"(d[0]), "+f"(d[1]), "+f"(d[2]), "+f"(d[3]), "+f"(d[4]), "+f"(d[5]), "+f"(d[6]), "+f"(d[7]), "+f"(d[8]), "+f"(d[9]), "+f"(d[10]), "+f"(d[11]), "+f"(d[12]), "+f"(d[13]), "+f"(d[14]), "+f"(d[15]), "+f"(d[16]), "+f"(d[17]), "+f"(d[18]), "+f"(d[19]), "+f"(d[20]), "+f"(d[21]), "+f"(d[22]), "+f"(d[23]), "+f"(d[24]), "+f"(d[25]), "+f"(d[26]), "+f"(d[27]), "+f"(d[28]), "+f"(d[29]), "+f"(d[30]), "+f"(d[31]), "+f"(d[32]), "+f"(d[33]), "+f"(d[34]), "+f"(d[35]), "+f"(d[36]), "+f"(d[37]), "+f"(d[38]), "+f"(d[39]), "+f"(d[40]), "+f"(d[41]), "+f"(d[42]), "+f"(d[43]), "+f"(d[44]), "+f"(d[45]), "+f"(d[46]), "+f"(d[47]), "+f"(d[48]), "+f"(d[49]), "+f"(d[50]), "+f"(d[51]), "+f"(d[52]), "+f"(d[53]), "+f"(d[54]), "+f"(d[55]), "+f"(d[56]), "+f"(d[57]), "+f"(d[58]), "+f"(d[59]), "+f"(d[60]), "+f"(d[61]), "+f"(d[62]), "+f"(d[63])
    : "r"(a[0]), "r"(a[1]), "r"(a[2]), "r"(a[3]), "l"(db), "r"(sc), "n"(TB));
}
template <int TB> __device__ __forceinline__ void wgmma_rs_64(float (&d)[32], const uint32_t (&a)[4], uint64_t db, int sc) {
  asm volatile("{\n.reg .pred p;\nsetp.ne.b32 p, %37, 0;\n"
    "wgmma.mma_async.sync.aligned.m64n64k16.f32.bf16.bf16 {%0, %1, %2, %3, %4, %5, %6, %7, %8, %9, %10, %11, %12, %13, %14, %15, %16, %17, %18, %19, %20, %21, %22, %23, %24, %25, %26, %27, %28, %29, %30, %31}, {%32, %33, %34, %35}, %36, p, 1, 1, %38;\n}\n"
    : "+f"(d[0]), "+f"(d[1]), "+f"(d[2]), "+f"(d[3]), "+f"(d[4]), "+f"(d[5]), "+f"(d[6]), "+f"(d[7]), "+f"(d[8]), "+f"(d[9]), "+f"(d[10]), "+f"(d[11]), "+f"(d[12]), "+f"(d[13]), "+f"(d[14]), "+f"(d[15]), "+f"(d[16]), "+f"(d[17]), "+f"(d[18]), "+f"(d[19]), "+f"(d[20]), "+f"(d[21]), "+f"(d[22]), "+f"(d[23]), "+f"(d[24]), "+f"(d[25]), "+f"(d[26]), "+f"(d[27]), "+f"(d[28]), "+f"(d[29]), "+f"(d[30]), "+f"(d[31])
    : "r"(a[0]), "r"(a[1]), "r"(a[2]), "r"(a[3]), "l"(db), "r"(sc), "n"(TB));
}
template <int TB> __device__ __forceinline__ void wgmma_rs_56(float (&d)[28], const uint32_t (&a)[4], uint64_t db, int sc) {
  asm volatile("{\n.reg .pred p;\nsetp.ne.b32 p, %33, 0;\n"
    "wgmma.mma_async.sync.aligned.m64n56k16.f32.bf16.bf16 {%0, %1, %2, %3, %4, %5, %6, %7, %8, %9, %10, %11, %12, %13, %14, %15, %16, %17, %18, %19, %20, %21, %22, %23, %24, %25, %26, %27}, {%28, %29, %30, %31}, %32, p, 1, 1, %34;\n}\n"
    : "+f"(d[0]), "+f"(d[1]), "+f"(d[2]), "+f"(d[3]), "+f"(d[4]), "+f"(d[5]), "+f"(d[6]), "+f"(d[7]), "+f"(d[8]), "+f"(d[9]), "+f"(d[10]), "+f"(d[11]), "+f"(d[12]), "+f"(d[13]), "+f"(d[14]), "+f"(d[15]), "+f"(d[16]), "+f"(d[17]), "+f"(d[18]), "+f"(d[19]), "+f"(d[20]), "+f"(d[21]), "+f"(d[22]), "+f"(d[23]), "+f"(d[24]), "+f"(d[25]), "+f"(d[26]), "+f"(d[27])
    : "r"(a[0]), "r"(a[1]), "r"(a[2]), "r"(a[3]), "l"(db), "r"(sc), "n"(TB));
}
template <int TB> __device__ __forceinline__ void wgmma_rs_112(float (&d)[56], const uint32_t (&a)[4], uint64_t db, int sc) {
  asm volatile("{\n.reg .pred p;\nsetp.ne.b32 p, %61, 0;\n"
    "wgmma.mma_async.sync.aligned.m64n112k16.f32.bf16.bf16 {%0, %1, %2, %3, %4, %5, %6, %7, %8, %9, %10, %11, %12, %13, %14, %15, %16, %17, %18, %19, %20, %21, %22, %23, %24, %25, %26, %27, %28, %29, %30, %31, %32, %33, %34, %35, %36, %37, %38, %39, %40, %41, %42, %43, %44, %45, %46, %47, %48, %49, %50, %51, %52, %53, %54, %55}, {%56, %57, %58, %59}, %60, p, 1, 1, %62;\n}\n"
    : "+f"(d[0]), "+f"(d[1]), "+f"(d[2]), "+f"(d[3]), "+f"(d[4]), "+f"(d[5]), "+f"(d[6]), "+f"(d[7]), "+f"(d[8]), "+f"(d[9]), "+f"(d[10]), "+f"(d[11]), "+f"(d[12]), "+f"(d[13]), "+f"(d[14]), "+f"(d[15]), "+f"(d[16]), "+f"(d[17]), "+f"(d[18]), "+f"(d[19]), "+f"(d[20]), "+f"(d[21]), "+f"(d[22]), "+f"(d[23]), "+f"(d[24]), "+f"(d[25]), "+f"(d[26]), "+f"(d[27]), "+f"(d[28]), "+f"(d[29]), "+f"(d[30]), "+f"(d[31]), "+f"(d[32]), "+f"(d[33]), "+f"(d[34]), "+f"(d[35]), "+f"(d[36]), "+f"(d[37]), "+f"(d[38]), "+f"(d[39]), "+f"(d[40]), "+f"(d[41]), "+f"(d[42]), "+f"(d[43]), "+f"(d[44]), "+f"(d[45]), "+f"(d[46]), "+f"(d[47]), "+f"(d[48]), "+f"(d[49]), "+f"(d[50]), "+f"(d[51]), "+f"(d[52]), "+f"(d[53]), "+f"(d[54]), "+f"(d[55])
    : "r"(a[0]), "r"(a[1]), "r"(a[2]), "r"(a[3]), "l"(db), "r"(sc), "n"(TB));
}
template <int TA, int TB> __device__ __forceinline__ void wgmma_ss_56(float (&d)[28], uint64_t da, uint64_t db, int sc) {
  asm volatile("{\n.reg .pred p;\nsetp.ne.b32 p, %30, 0;\n"
    "wgmma.mma_async.sync.aligned.m64n56k16.f32.bf16.bf16 {%0, %1, %2, %3, %4, %5, %6, %7, %8, %9, %10, %11, %12, %13, %14, %15, %16, %17, %18, %19, %20, %21, %22, %23, %24, %25, %26, %27}, %28, %29, p, 1, 1, %31, %32;\n}\n"
    : "+f"(d[0]), "+f"(d[1]), "+f"(d[2]), "+f"(d[3]), "+f"(d[4]), "+f"(d[5]), "+f"(d[6]), "+f"(d[7]), "+f"(d[8]), "+f"(d[9]), "+f"(d[10]), "+f"(d[11]), "+f"(d[12]), "+f"(d[13]), "+f"(d[14]), "+f"(d[15]), "+f"(d[16]), "+f"(d[17]), "+f"(d[18]), "+f"(d[19]), "+f"(d[20]), "+f"(d[21]), "+f"(d[22]), "+f"(d[23]), "+f"(d[24]), "+f"(d[25]), "+f"(d[26]), "+f"(d[27])
    : "l"(da), "l"(db), "r"(sc), "n"(TA), "n"(TB));
}

__device__ __forceinline__ uint32_t cis(float a) { return pack_bf16(__cosf(a), __sinf(a)); }

typedef __nv_bfloat162 b2;
struct c2 { b2 x, y; };
__device__ __forceinline__ b2 as_b2(uint32_t u) { return *reinterpret_cast<b2*>(&u); }
__device__ __forceinline__ uint32_t as_u(b2 v) { return *reinterpret_cast<uint32_t*>(&v); }
__device__ __forceinline__ c2 mk(b2 x, b2 y) { c2 r; r.x = x; r.y = y; return r; }
__device__ __forceinline__ c2 cmul(c2 a, b2 wr, b2 wi) { return mk(__hfma2(a.x, wr, __hneg2(__hmul2(a.y, wi))), __hfma2(a.x, wi, __hmul2(a.y, wr))); }
__device__ __forceinline__ void fft4(c2& a0, c2& a1, c2& a2, c2& a3) {
  c2 t0 = mk(__hadd2(a0.x, a2.x), __hadd2(a0.y, a2.y)), t1 = mk(__hsub2(a0.x, a2.x), __hsub2(a0.y, a2.y));
  c2 t2 = mk(__hadd2(a1.x, a3.x), __hadd2(a1.y, a3.y)), t3 = mk(__hsub2(a1.x, a3.x), __hsub2(a1.y, a3.y));
  a0 = mk(__hadd2(t0.x, t2.x), __hadd2(t0.y, t2.y)); a2 = mk(__hsub2(t0.x, t2.x), __hsub2(t0.y, t2.y));
  a1 = mk(__hadd2(t1.x, t3.y), __hsub2(t1.y, t3.x)); a3 = mk(__hsub2(t1.x, t3.y), __hadd2(t1.y, t3.x));
}
__device__ __forceinline__ void fft4_s2(c2& a0, c2& a1, c2& a2, c2& a3, b2 r) {
  const b2 nr = __hneg2(r);
  c2 t0 = mk(__hfma2(a2.x, r, a0.x), __hfma2(a2.y, r, a0.y)), t1 = mk(__hfma2(a2.x, nr, a0.x), __hfma2(a2.y, nr, a0.y));
  c2 t2 = mk(__hadd2(a1.x, a3.x), __hadd2(a1.y, a3.y)), t3 = mk(__hsub2(a1.x, a3.x), __hsub2(a1.y, a3.y));
  a0 = mk(__hadd2(t0.x, t2.x), __hadd2(t0.y, t2.y)); a2 = mk(__hsub2(t0.x, t2.x), __hsub2(t0.y, t2.y));
  a1 = mk(__hadd2(t1.x, t3.y), __hsub2(t1.y, t3.x)); a3 = mk(__hsub2(t1.x, t3.y), __hadd2(t1.y, t3.x));
}
__device__ __forceinline__ void fft4_s13(c2& a0, c2& a1, c2& a2, c2& a3, b2 r) {
  const b2 nr = __hneg2(r);
  c2 t0 = mk(__hadd2(a0.x, a2.x), __hadd2(a0.y, a2.y)), t1 = mk(__hsub2(a0.x, a2.x), __hsub2(a0.y, a2.y));
  c2 t2 = mk(__hadd2(a1.x, a3.x), __hadd2(a1.y, a3.y)), t3 = mk(__hsub2(a1.x, a3.x), __hsub2(a1.y, a3.y));
  a0 = mk(__hfma2(t2.x, r, t0.x), __hfma2(t2.y, r, t0.y)); a2 = mk(__hfma2(t2.x, nr, t0.x), __hfma2(t2.y, nr, t0.y));
  a1 = mk(__hfma2(t3.y, r, t1.x), __hfma2(t3.x, nr, t1.y)); a3 = mk(__hfma2(t3.y, nr, t1.x), __hfma2(t3.x, r, t1.y));
}
__device__ __forceinline__ c2 rot1(c2 a) { return mk(__hadd2(a.x, a.y), __hsub2(a.y, a.x)); }
__device__ __forceinline__ c2 rot3(c2 a) { return mk(__hsub2(a.y, a.x), __hneg2(__hadd2(a.x, a.y))); }
__device__ __forceinline__ c2 mul_mi(c2 a) { return mk(a.y, __hneg2(a.x)); }
template <int O> __device__ __forceinline__ void fft8(c2 (&v)[16]) {
  const b2 r = as_b2(0x3F353F35u), nr = as_b2(0xBF35BF35u);
  fft4(v[O], v[O + 4], v[O + 8], v[O + 12]);
  fft4(v[O + 2], v[O + 6], v[O + 10], v[O + 14]);
  const c2 o0 = v[O + 2], o1 = rot1(v[O + 6]), o2 = v[O + 10], o3 = rot1(v[O + 14]);
  const c2 e0 = v[O], e1 = v[O + 4], e2 = v[O + 8], e3 = v[O + 12];
  v[O] = mk(__hadd2(e0.x, o0.x), __hadd2(e0.y, o0.y));              v[O + 8] = mk(__hsub2(e0.x, o0.x), __hsub2(e0.y, o0.y));
  v[O + 2] = mk(__hfma2(o1.x, r, e1.x), __hfma2(o1.y, r, e1.y));    v[O + 10] = mk(__hfma2(o1.x, nr, e1.x), __hfma2(o1.y, nr, e1.y));
  v[O + 4] = mk(__hadd2(e2.x, o2.y), __hsub2(e2.y, o2.x));          v[O + 12] = mk(__hsub2(e2.x, o2.y), __hadd2(e2.y, o2.x));
  v[O + 6] = mk(__hfma2(o3.y, r, e3.x), __hfma2(o3.x, nr, e3.y));   v[O + 14] = mk(__hfma2(o3.y, nr, e3.x), __hfma2(o3.x, r, e3.y));
}
__device__ __forceinline__ void fft16(c2 (&v)[16]) {
  const b2 r = as_b2(0x3F353F35u), c1 = as_b2(0x3F6D3F6Du), s1 = as_b2(0x3EC43EC4u), nc1 = as_b2(0xBF6DBF6Du), ns1 = as_b2(0xBEC4BEC4u);
#pragma unroll
  for (int a = 0; a < 4; a++) fft4(v[a], v[a + 4], v[a + 8], v[a + 12]);
  v[5] = cmul(v[5], c1, ns1); v[6] = rot1(v[6]); v[7] = cmul(v[7], s1, nc1);
  v[9] = rot1(v[9]); v[10] = mul_mi(v[10]); v[11] = rot3(v[11]);
  v[13] = cmul(v[13], s1, nc1); v[14] = rot3(v[14]); v[15] = cmul(v[15], nc1, s1);
  fft4(v[0], v[1], v[2], v[3]); fft4_s2(v[4], v[5], v[6], v[7], r); fft4_s13(v[8], v[9], v[10], v[11], r); fft4_s2(v[12], v[13], v[14], v[15], r);
  c2 t;
  t = v[1]; v[1] = v[4]; v[4] = t;  t = v[2]; v[2] = v[8]; v[8] = t;  t = v[3]; v[3] = v[12]; v[12] = t;
  t = v[6]; v[6] = v[9]; v[9] = t;  t = v[7]; v[7] = v[13]; v[13] = t; t = v[11]; v[11] = v[14]; v[14] = t;
}

__device__ __forceinline__ void columns(c2 (&v)[16], uint32_t sb, int t) {
  const int l16 = t & 15;
  const uint32_t row = sb + OFF_EXCH + (t >> 4) * 2304;
  const uint32_t pos = sb + OFF_EXCH + (t >> 3) * 144 + (t & 7) * 16;
#pragma unroll 1
  for (int ps = 0; ps < 6; ps++) {
    if (ps == 0 || ps == 5) { fft8<0>(v); fft8<1>(v); } else fft16(v);
    if (ps == 5) break;
    if (ps == 2) {
      const uint32_t ws = sb + OFF_WS + (l16 >> 1) * 128 + ((((t >> 4) + (l16 >> 1)) & 7) * 2 + (l16 & 1)) * 8;
      mbar_wait(sb + OFF_BAR + B_WFULL * 8, 0);
#pragma unroll
      for (int q = 0; q < 16; q++) {
        const uint2 w = lds64(ws + q * 1024);
        const c2 z = cmul(v[q], as_b2(w.x), as_b2(w.y));
        v[q] = mk(z.y, z.x);
      }
      continue;
    }
    {
      const bool full = ps == 0 || ps == 4;
      const uint32_t tw = sb + OFF_TW + (full ? ps * 2048 + t * 16 : 16384 + l16 * 16);
      const uint32_t st = full ? 2048 : 256;
#pragma unroll
      for (int i = 0; i < 4; i++) {
        const uint4 w4 = lds128(tw + i * st);
        const uint32_t w[4] = {w4.x, w4.y, w4.z, w4.w};
#pragma unroll
        for (int e = 0; e < 4; e++) v[4 * i + e] = cmul(v[4 * i + e], __low2bfloat162(as_b2(w[e])), __high2bfloat162(as_b2(w[e])));
      }
    }
    if (ps == 0) {
      bar_sync<3, 128>();
#pragma unroll
      for (int q = 0; q < 8; q++) sts128(pos + q * 2304, as_u(v[2 * q].x), as_u(v[2 * q].y), as_u(v[2 * q + 1].x), as_u(v[2 * q + 1].y));
      bar_sync<3, 128>();
#pragma unroll
      for (int q = 0; q < 16; q++) { const uint2 a = lds64(row + q * 144 + l16 * 8); v[q] = mk(as_b2(a.x), as_b2(a.y)); }
    } else {
      __syncwarp();
#pragma unroll
      for (int q = 0; q < 16; q++) sts64(row + q * 144 + l16 * 8, as_u(v[q].x), as_u(v[q].y));
      if (ps == 4) bar_sync<3, 128>(); else __syncwarp();
      const uint32_t src = ps == 4 ? pos : row + l16 * 144, st = ps == 4 ? 2304 : 16;
#pragma unroll
      for (int q = 0; q < 8; q++) { const uint4 a = lds128(src + q * st); v[2 * q] = mk(as_b2(a.x), as_b2(a.y)); v[2 * q + 1] = mk(as_b2(a.z), as_b2(a.w)); }
    }
  }
}

template <int NH> __device__ __forceinline__ void h_epilogue(float (&acc)[NH * 8], unsigned char* gdst, uint32_t tag) {
#pragma unroll
  for (int c = 0; c < NH / 2; c++) {
    uint32_t pk[4];
#pragma unroll
    for (int i = 0; i < 4; i++) {
      float hv[2];
#pragma unroll
      for (int e = 0; e < 2; e++) {
        float hg = 0.5f * acc[c * 8 + i * 2 + e], up = acc[NH * 4 + c * 8 + i * 2 + e];
        float th; asm("tanh.approx.f32 %0, %1;" : "=f"(th) : "f"(hg));
        hv[e] = fmaf(hg, th, hg) * up;
      }
      pk[i] = pack_bf16(hv[0], hv[1]);
    }
    stg128_l2(gdst + c * 4096, (pk[0] & ~1u) | tag, pk[1], pk[2], pk[3]);
  }
}

__device__ __forceinline__ void frag_ready(uint32_t (&a)[4], uint32_t (&b)[4], uint32_t (&c)[4], uint32_t (&d)[4], const unsigned char* p, uint32_t tag) {
  asm volatile("{\n.reg .pred p;\n.reg .u32 c, m, q;\nmov.u32 c, 0;\nL_TRY:\n"
               "lop3.b32 m, %0, %4, %17, 0x7E;\nlop3.b32 q, %8, %12, %17, 0x7E;\nlop3.b32 m, m, q, 1, 0xA8;\nsetp.ne.u32 p, m, 0;\n"
               "vote.sync.any.pred p, p, 0xffffffff;\n@!p bra.uni L_OK;\n"
               "ld.relaxed.gpu.global.v4.b32 {%0,%1,%2,%3}, [%16];\nld.relaxed.gpu.global.v4.b32 {%4,%5,%6,%7}, [%16+4096];\n"
               "ld.relaxed.gpu.global.v4.b32 {%8,%9,%10,%11}, [%16+8192];\nld.relaxed.gpu.global.v4.b32 {%12,%13,%14,%15}, [%16+12288];\n"
               "add.u32 c, c, 1;\nsetp.lt.u32 p, c, 262144;\n@p bra.uni L_TRY;\ntrap;\nL_OK:\n}"
               : "+r"(a[0]), "+r"(a[1]), "+r"(a[2]), "+r"(a[3]), "+r"(b[0]), "+r"(b[1]), "+r"(b[2]), "+r"(b[3]),
                 "+r"(c[0]), "+r"(c[1]), "+r"(c[2]), "+r"(c[3]), "+r"(d[0]), "+r"(d[1]), "+r"(d[2]), "+r"(d[3])
               : "l"(p), "r"(tag) : "memory");
}

#define LDH ldg128_na
#define MAP 0
#define WPOS 1
#define LA2 5
#define LEAD1 3

__global__ void __cluster_dims__(2, 1, 1) __launch_bounds__(NTHREADS, 1)
fused_kernel(const __grid_constant__ CUtensorMap tm_x, const __grid_constant__ CUtensorMap tm_g, const __grid_constant__ CUtensorMap tm_u,
             const __grid_constant__ CUtensorMap tm_g32, const __grid_constant__ CUtensorMap tm_u32,
             const __nv_bfloat16* __restrict__ w_r, const __nv_bfloat16* __restrict__ w_i,
             const __nv_bfloat16* __restrict__ w_gate, const __nv_bfloat16* __restrict__ w_up,
             const __nv_bfloat16* __restrict__ w_down, const __nv_bfloat16* __restrict__ gate_w, __nv_bfloat16* __restrict__ out) {
  extern __shared__ __align__(1024) unsigned char smem[];
  const uint32_t sb = s2u(smem);
  const uint32_t bars = sb + OFF_BAR;
  const int tid = threadIdx.x, warp = __shfl_sync(0xffffffffu, tid >> 5, 0), lane = tid & 31;
  const int cl = blockIdx.x >> 1, kh = blockIdx.x & 1;
  const int n0 = cl < 4 ? cl : (cl < 36 ? (cl - 4) >> 3 : (cl - 36) / 7);
  const int m0 = cl < 4 ? 15 : (cl < 36 ? (cl - 4) & 7 : cl - 28 - 7 * n0);
  const int n = MAP == 0 ? n0 : (MAP == 1 ? (m0 & 3) : ((n0 & 1) | ((m0 & 1) << 1)));
  const int m = MAP == 0 ? m0 : (MAP == 1 ? ((m0 & 12) | n0) : ((m0 & 14) | (n0 >> 1)));
  const int j = kh * 4 + n, bid = m * 8 + n * 2 + kh;

  const int c64 = 224 * j + (j & 1) * 32;
  if (warp < 8) {
    asm volatile("setmaxnreg.inc.sync.aligned.u32 208;");
    const int wg = warp >> 2, w4 = warp & 3, g = lane >> 2, t = lane & 3;
    const int rh = wg ^ kh ^ 1;
    const int p = j & 1, r = (j >> 1) & 1, hh = j >> 2;
    const uint32_t epoch = ld_relaxed(&g_ep[bid]);
    if ((tid & 127) == 0) PROF(wg, 30);
#pragma unroll 1
    for (int it = tid; it < 392; it += 256) {
      const int kc = it / 28, sg = it - kc * 28;
      const int k = 2 * (28 * hh + sg) + r;
      const float kf = (float)k * (-6.283185307179586f / 448.0f), a0 = (float)(16 * kc + p) * kf;
      uint32_t c[4], s[4];
#pragma unroll
      for (int q = 0; q < 4; q++) {
        const float a1 = fmaf((float)(2 * q), kf, a0), a2 = fmaf((float)(2 * q + 8), kf, a0);
        c[q] = pack_bf16(__cosf(a1), __cosf(a2)); s[q] = pack_bf16(__sinf(a1), __sinf(a2));
        if (k == 0) s[q] = ((q ^ p) & 1) ? 0xBF80BF80u : 0x3F803F80u;
      }
      const uint32_t a = sb + 5 * SLOT + (kc * 56 + 2 * sg) * 16;
      sts128(a, c[0], c[1], c[2], c[3]);
      sts128(a + 16, s[0], s[1], s[2], s[3]);
    }
    if ((tid & 127) == 0) PROF(wg, 31);
    fence_async_smem();
    bar_sync<0, NTHREADS - 64>();
    asm volatile("barrier.cluster.arrive.relaxed.aligned;" ::: "memory");
    if ((tid & 127) == 0) PROF(wg, 1);

    uint32_t xa[28][4];
    {
      const uint32_t xb = sb + OFF_PQ + wg * HALF_XR + (w4 * 16 + (lane & 15)) * 128;
      mbar_wait(bars + (B_XFULL + wg) * 8, 0);
      if ((tid & 127) == 0) PROF(wg, 2);
#pragma unroll
      for (int kb = 0; kb < 7; kb++) {
#pragma unroll
        for (int kk = 0; kk < 4; kk++) {
          uint32_t a = xb + kb * 8192 + (((2 * kk + (lane >> 4)) ^ (lane & 7)) << 4);
          asm volatile("ldmatrix.sync.aligned.m8n8.x4.shared.b16 {%0,%1,%2,%3}, [%4];"
                       : "=r"(xa[kb * 4 + kk][0]), "=r"(xa[kb * 4 + kk][1]), "=r"(xa[kb * 4 + kk][2]), "=r"(xa[kb * 4 + kk][3]) : "r"(a) : "memory");
        }
      }
    }
    {
      uint32_t ad[7][4];
      const uint32_t sel = p ? 0x7632 : 0x5410;
      const uint32_t sgn = r ? 0xBF80BF80u : 0x3F803F80u;
#pragma unroll
      for (int jj = 0; jj < 7; jj++) {
#pragma unroll
        for (int i = 0; i < 4; i++) {
          int ks = 2 * jj + (i >> 1), rr = i & 1;
          uint32_t lo = __byte_perm(xa[ks][rr], xa[ks][rr + 2], sel);
          uint32_t hi = __byte_perm(xa[ks + 14][rr], xa[ks + 14][rr + 2], sel);
          asm("fma.rn.bf16x2 %0, %1, %2, %3;" : "=r"(ad[jj][i]) : "r"(hi), "r"(sgn), "r"(lo));
        }
      }
      __syncwarp();
      if (lane == 0) mbar_arrive(bars + (B_XFREE + wg) * 8);
      float acc[28];
      wg_fence();
      uint64_t db = mkdesc(sb + 5 * SLOT, 896, 128, 0);
#pragma unroll
      for (int jj = 0; jj < 7; jj++) wgmma_rs_56<0>(acc, ad[jj], db + jj * 112, jj != 0);
      wg_commit();
      wg_wait<0>(); keep(acc);
      if (lane == 0) mbar_arrive(bars + (B_EMPTY + 5) * 8);
      uint32_t* xc = g_Xc + (size_t)((2 * (28 * hh + t) + r) * 2 + p) * S_ + m * 128 + rh * 64 + w4 * 16 + g;
#pragma unroll
      for (int i = 0; i < 7; i++) {
        xc[i * 16 * S_] = pack_bf16(acc[4 * i], acc[4 * i + 1]);
        xc[i * 16 * S_ + 8] = pack_bf16(acc[4 * i + 2], acc[4 * i + 3]);
      }
      __syncwarp();
      if (lane == 0) mbar_arrive(bars + B_PUBX * 8);
    }
    if ((tid & 127) == 0) PROF(wg, 3);
    const uint32_t tag = ~epoch & 1;
    unsigned char* const hbase = g_H + (size_t)(m * 2 + kh) * (56 * 4096) + rh * 2048 + (tid & 127) * 16;
#pragma unroll 1
    for (int u = 0; u < 3; u++) {
      float acc[64];
      if (wg == 1) { if (u & 1) bar_sync<6, 256>(); else bar_sync<2, 256>(); }
      const uint32_t sbu = opaque(sb);
#pragma unroll
      for (int kb = 0; kb < 7; kb++) {
        mbar_wait(sbu + OFF_BAR + (B_FULL + kb) * 8, u & 1);
        wg_fence();
        uint64_t db = mkdesc(sbu + kb * SLOT, 8192, 1024, 1);
#pragma unroll
        for (int kk = 0; kk < 4; kk++) wgmma_rs_128<1>(acc, xa[kb * 4 + kk], db + kk * 128, (kb | kk) != 0);
        wg_commit();
        if (kb == LEAD1 && wg == 0) { if (u & 1) bar_arrive<6, 256>(); else bar_arrive<2, 256>(); }
        if (kb > 0) { wg_wait<1>(); if (lane == 0) mbar_arrive(sbu + OFF_BAR + (B_EMPTY + kb - 1) * 8); }
      }
      wg_wait<0>(); keep(acc);
      if (lane == 0) mbar_arrive(sbu + OFF_BAR + (B_EMPTY + 6) * 8);
      if ((tid & 127) == 0) PROF(wg, 4 + 2 * u);
      h_epilogue<8>(acc, hbase + (u * 16 + n * 4) * 4096, tag);
      if ((tid & 127) == 0) PROF(wg, 5 + 2 * u);
    }
    {
      float acc[32];
      if (wg == 1) bar_sync<6, 256>();
      const uint32_t sbu = opaque(sb);
#pragma unroll
      for (int it = 0; it < 4; it++) {
        mbar_wait(sbu + OFF_BAR + (B_FULL + it) * 8, 1);
        wg_fence();
        uint64_t db = mkdesc(sbu + it * SLOT, 8192, 512, 2);
#pragma unroll
        for (int kk = 0; kk < 8; kk++) if (it * 8 + kk < 28) wgmma_rs_64<1>(acc, xa[it * 8 + kk], db + kk * 64, (it | kk) != 0);
        wg_commit();
        if (it == 2 && wg == 0) bar_arrive<6, 256>();
        if (it > 0) {
          wg_wait<1>();
          if (lane == 0) mbar_arrive(sbu + OFF_BAR + (B_EMPTY + it - 1) * 8);
#pragma unroll
          for (int i = it * 8 - 8; i < it * 8; i++) if (i < 4 * LA2) LDH(xa[i], hbase + i * 4096);
        }
      }
      wg_wait<0>(); keep(acc);
      if (lane == 0) mbar_arrive(sbu + OFF_BAR + (B_EMPTY + 3) * 8);
      if ((tid & 127) == 0) PROF(wg, 10);
      h_epilogue<4>(acc, hbase + (48 + n * 2) * 4096, tag);
    }
    asm volatile("barrier.cluster.wait.aligned;" ::: "memory");
    if ((tid & 127) == 0) PROF(wg, 11);

    float acc[56];
    if (wg == 1) bar_sync<2, 256>();
#pragma unroll 1
    for (int it = 0; it < 2; it++) {
#pragma unroll
      for (int e = 0; e < 7; e++) {
        if ((tid & 127) == 0) PROF(wg, 16 + it * 7 + e);
        const bool inr = e < 4 && it == 0;
        if (e >= 4 || it == 1) mbar_wait(bars + (B_FULL + e) * 8, e < 4 ? 0 : it ^ 1);
        else if (e == 0) mbar_wait(bars + B_RFULL * 8, 1);
        frag_ready(xa[e * 4], xa[e * 4 + 1], xa[e * 4 + 2], xa[e * 4 + 3], hbase + (it * 7 + e) * 16384, tag);
        wg_fence();
        const uint64_t db = mkdesc(inr ? sb + OFF_R + e * 14336 : sb + e * SLOT, 1792, 128, 0);
#pragma unroll
        for (int kk = 0; kk < 4; kk++) wgmma_rs_112<1>(acc, xa[e * 4 + kk], db + kk * 224, (e | kk) ? 1 : it);
        wg_commit();
        if (e == 1 && it == 0 && wg == 0) bar_arrive<2, 256>();
        if (it == 0 || e + LA2 < 7) {
          const int nb = it * 7 + e + LA2;
#pragma unroll
          for (int kk = 0; kk < 4; kk++) LDH(xa[((e + LA2) % 7) * 4 + kk], hbase + (nb * 4 + kk) * 4096);
        }
        wg_wait<1>();
        if (lane == 0) {
          if (it == 0 ? e >= 5 : e <= 2) mbar_arrive(bars + (B_EMPTY + (e + 6) % 7) * 8);
          if (e == 4 && it == 0) {
            mbar_arrive(bars + B_LFREE * 8);
            asm volatile("{\n.reg .b32 ra;\nmapa.shared::cluster.u32 ra, %0, %1;\nmbarrier.arrive.relaxed.cluster.shared::cluster.b64 _, [ra];\n}"
                         :: "r"(bars + B_RFREE * 8), "r"(kh ^ 1) : "memory");
          }
        }
      }
    }
    const int t128 = tid & 127;
    wg_wait<0>(); keep(acc);
    if (wg == 0) {
      if (t128 == 0) PROF(wg, 12);
      mbar_wait_cluster(bars + B_RFREE * 8, 0);
      uint32_t rdst, rbar;
      asm volatile("mapa.shared::cluster.u32 %0, %1, %2;" : "=r"(rdst) : "r"(sb + OFF_R + t128 * 16), "r"(kh ^ 1));
      asm volatile("mapa.shared::cluster.u32 %0, %1, %2;" : "=r"(rbar) : "r"(bars + B_RECV * 8), "r"(kh ^ 1));
#pragma unroll
      for (int i = 0; i < 14; i++)
        asm volatile("st.async.weak.shared::cluster.mbarrier::complete_tx::bytes.v4.f32 [%0], {%1,%2,%3,%4}, [%5];"
                     :: "r"(rdst + i * 2048), "f"(acc[4 * i]), "f"(acc[4 * i + 1]), "f"(acc[4 * i + 2]), "f"(acc[4 * i + 3]), "r"(rbar) : "memory");
    } else {
      float spec[2][28];
      if (t128 == 0) PROF(wg, 12);
      mbar_wait(bars + B_PQFULL * 8, 0);
      if (t128 == 0) { PROF(wg, 13); g_ep[bid] = epoch + 1; }
#pragma unroll
      for (int i = 0; i < 4; i++) {
        if (i == 0) mbar_wait(bars + B_GFULL * 8, 0);
        if (i >= 2) mbar_wait(bars + (B_FULL + i - 2) * 8, 1);
        wg_fence();
        const uint64_t da = mkdesc(sb + OFF_PQ + i * 14336, 1024, 1024, 1);
        const uint64_t db = mkdesc(i < 2 ? sb + OFF_R + 28672 + i * (G_IMG / 2) : sb + (i - 2) * SLOT, 896, 128, 0);
#pragma unroll
        for (int kk = 0; kk < 7; kk++) wgmma_ss_56<1, 0>(spec[i >> 1], da + kk * 128, db + kk * 112, ((i & 1) | kk) != 0);
        wg_commit();
      }
      const float* gs = reinterpret_cast<const float*>(smem + OFF_G) + w4 * 16 + g;
      const float o0 = bf16_round(1.0f - gs[0]), o1 = bf16_round(1.0f - gs[8]);
      const float g0 = gs[0] * (1.0f / (float)(S_ * D_)), g1 = gs[8] * (1.0f / (float)(S_ * D_));
      wg_wait<0>(); keep(spec[0]); keep(spec[1]);
      if (t128 == 0) PROF(wg, 14);
      mbar_wait_cluster(bars + B_RECV * 8, 0);
      if (t128 == 0) PROF(wg, 0);
      float4 o[14];
#pragma unroll
      for (int i = 0; i < 14; i++) o[i] = lds128f(sb + OFF_R + t128 * 16 + i * 2048);
      bar_sync<5, 128>();
      const uint32_t st = sb + OFF_PQ + w4 * 3840;
#pragma unroll
      for (int i = 0; i < 7; i++) {
        uint32_t pk[4];
#pragma unroll
        for (int e = 0; e < 2; e++) {
          const int c = 2 * i + e, si = i * 4 + e;
          pk[2 * e] = pack_bf16(fmaf(acc[4 * c] + o[c].x, o0, g0 * spec[0][si]), fmaf(acc[4 * c + 1] + o[c].y, o0, g0 * spec[1][si]));
          pk[2 * e + 1] = pack_bf16(fmaf(acc[4 * c + 2] + o[c].z, o1, g1 * spec[0][si + 2]), fmaf(acc[4 * c + 3] + o[c].w, o1, g1 * spec[1][si + 2]));
        }
        asm volatile("stmatrix.sync.aligned.m8n8.x4.shared.b16 [%0], {%1,%2,%3,%4};"
                     :: "r"(st + (lane & 15) * 240 + (lane >> 4) * 16 + i * 32), "r"(pk[0]), "r"(pk[1]), "r"(pk[2]), "r"(pk[3]) : "memory");
      }
      __syncwarp();
      if (lane < 28) {
        const int r2 = lane >= 14, cc = lane - r2 * 14;
        unsigned char* ob = reinterpret_cast<unsigned char*>(out) + (size_t)(m * 128 + kh * 64 + w4 * 16 + r2) * (D_ * 2) + n * 224 + cc * 16;
        float4 v[8];
#pragma unroll
        for (int i = 0; i < 8; i++) v[i] = lds128f(st + r2 * 240 + cc * 16 + i * 480);
#pragma unroll
        for (int i = 0; i < 8; i++) stg128(ob + i * (D_ * 4), __float_as_uint(v[i].x), __float_as_uint(v[i].y), __float_as_uint(v[i].z), __float_as_uint(v[i].w));
      }
    }
    if (t128 == 0) { PROF(wg, 15); if (wg) { PROFG(4, 30); PROF(4, 31); } }
  } else if (warp < 12) {
    asm volatile("setmaxnreg.dec.sync.aligned.u32 72;");
    const int t = tid - 256;
    const int k = bid;
    if (t == 0) PROF(2, 0);
    uint4 gv[7];
#pragma unroll
    for (int i = 0; i < 7; i++) gv[i] = ldg128(reinterpret_cast<const uint4*>(gate_w) + i * 8 + (t & 7));
    bar_sync<0, NTHREADS - 64>();
    asm volatile("barrier.cluster.arrive.relaxed.aligned;" ::: "memory");
    mbar_wait(bars + B_PIN * 8, 0);
    if (t == 0) PROF(2, 4);
    {
      const uint32_t wa = sb + 6 * SLOT + (((t & 7) - bid) & 7) * 450 + (t >> 3) * 2, wc = wa + 448 - (t >> 3) * 4;
      uint2* dst = g_Wt + (t >> 3) * S_ + 16 * bid + 2 * (t & 7);
#pragma unroll 1
      for (int h = 0; h < 2; h++) {
        uint32_t w[4][8];
#pragma unroll
        for (int i = 0; i < 4; i++) {
#pragma unroll
          for (int e = 0; e < 4; e++) { w[i][2 * e] = lds16(wa + h * 128 + i * 32 + e * 3600); w[i][2 * e + 1] = lds16(wc - h * 128 - i * 32 + e * 3600); }
        }
        if (h == 1) {
          const uint32_t z = __reduce_or_sync(0xffffffffu, w[3][7] | w[3][6]) >> 16;
          if (lane < 2) mbar_arrive(bars + (B_EMPTY + 6) * 8 + z);
        }
#pragma unroll
        for (int i = 0; i < 4; i++)
          if (i < 3 || h == 0 || t < 8)
            stg128(dst + (h * 64 + i * 16) * S_, __byte_perm(w[i][0], w[i][1], 0x5410), __byte_perm(w[i][4], w[i][5], 0x5410), __byte_perm(w[i][2], w[i][3], 0x5410), __byte_perm(w[i][6], w[i][7], 0x5410));
      }
    }
    __syncwarp();
    if (lane == 0) mbar_arrive(bars + B_PUBW * 8);
    if (t == 0) PROF(2, 6);
    {
      const int row = n * 16 + (t >> 3), l8 = t & 7;
      mbar_wait(bars + (B_XFULL + 1) * 8, 0);
      float sum = 0.f;
#pragma unroll
      for (int i = 0; i < 7; i++) {
        const uint4 a = lds128(sb + OFF_R + i * 8192 + row * 128 + ((l8 ^ (row & 7)) << 4));
        const uint32_t aa[4] = {a.x, a.y, a.z, a.w}, bb[4] = {gv[i].x, gv[i].y, gv[i].z, gv[i].w};
#pragma unroll
        for (int e = 0; e < 4; e++) {
          const uint32_t pr = as_u(__hmul2(as_b2(aa[e]), as_b2(bb[e])));
          sum += bf_lo(pr) + bf_hi(pr);
        }
      }
      sum += __shfl_xor_sync(0xffffffffu, sum, 1); sum += __shfl_xor_sync(0xffffffffu, sum, 2); sum += __shfl_xor_sync(0xffffffffu, sum, 4);
      if (lane == 0) mbar_arrive(bars + (B_XFREE + 1) * 8);
      if (l8 == 0) g_gate[m * 128 + kh * 64 + row] = bf16_round(__fdividef(1.0f, 1.0f + __expf(-bf16_round(sum))));
    }
    if (t < 98) {
      int cid = m * 98 + t, kc = cid / 56, nn = cid - kc * 56;
      int d = 112 * n + 8 * (2 * (nn >> 3) + (nn & 1)) + (nn & 6) + kh;
      int dr = d > 224 ? d - 448 : d;
      const float df = (float)dr * (-6.283185307179586f / 448.0f);
      uint32_t pk[4];
#pragma unroll
      for (int e = 0; e < 4; e++) {
        const float a = (float)(4 * kc + e) * df;
        pk[e] = pack_bf16(2.0f * __cosf(a), 2.0f * __sinf(a));
      }
      if (kc == 0) pk[0] = (((d >> 1) ^ kh) & 1) ? 0xBF803F80u : 0x3F803F80u;
      stg128(g_G + (size_t)(n * 2 + kh) * G_IMG + cid * 16, pk[0], pk[1], pk[2], pk[3]);
    }
    if (t == 0) PROF(2, 11);
    mbar_wait(bars + B_XFREE * 8, 0);
    if (k < 113) {
      const float u = -6.283185307179586f / 2048.0f, t2 = (float)(2 * t) * u, rr = (float)(t >> 4) * u;
#pragma unroll 1
      for (int i = 0; i < 4; i++) {
        const float q = (float)(2 * i), l = (float)((t & 15) + 64 * i);
        sts128(sb + OFF_TW + i * 2048 + t * 16, cis(t2 * q), cis((t2 + u) * q), cis(t2 * (q + 1.0f)), cis((t2 + u) * (q + 1.0f)));
        sts128(sb + OFF_TW + 8192 + i * 2048 + t * 16, cis(rr * l), cis(rr * (l + 16.0f)), cis(rr * (l + 32.0f)), cis(rr * (l + 48.0f)));
      }
      const float l = (float)((t >> 1) & 15) * (8.0f * u), jj = (float)((t >> 5) * 4 + (t & 1) * 2);
      sts64(sb + OFF_TW + 16384 + t * 8, cis(l * jj), cis(l * (jj + 1.0f)));
    }
    if (t == 0) PROF(2, 9);
    mbar_wait(bars + B_RFULL * 8, 0);
    if (t < 112) {
      const int js = bid >> 4, nn = (t >> 1) / 14, cc = (t >> 1) - nn * 14;
      unsigned char* wdst = g_Wd + (size_t)((js >> 2) * 4 + nn) * WD_IMG + cc * 128 + (t & 1) * 16;
      uint4 v[7];
#pragma unroll
      for (int i = 0; i < 7; i++) v[i] = lds128(sb + OFF_R + i * 1792 + (t & 1) * 896 + (t >> 1) * 16);
#pragma unroll
      for (int i = 0; i < 7; i++) {
        int col = 14 * (bid & 15) + 2 * i - (js & 1) * 32;
        if (col < 0) col += 224;
        const int kpos = col < 192 ? (col >> 6) * 256 + (js & 3) * 64 + (col & 63) : 576 + (js & 3) * 32 + col;
        stg128(wdst + (kpos >> 3) * 1792 + (kpos & 7) * 16, v[i].x, v[i].y, v[i].z, v[i].w);
      }
    }
    __syncwarp();
    if (lane == 0) mbar_arrive(bars + B_PUBD * 8);
    bar_sync<3, 128>();
    if (k < 113) {
      if (t == 0) PROF(2, 2);
      mbar_wait(bars + B_XCFULL * 8, 0);
      if (t == 0) PROF(2, 3);
      c2 v[16];
      const uint32_t se = k == 0 ? 0x4410 : (k == 112 ? 0x4432 : 0x3210), so = k == 0 ? 0x4410 : (k == 112 ? 0x3244 : 0x3210);
#pragma unroll
      for (int jj = 0; jj < 8; jj++) {
        const uint2 e2 = lds64(sb + OFF_EXCH + jj * 1024 + t * 8), o2 = lds64(sb + OFF_EXCH + 8192 + jj * 1024 + t * 8);
#pragma unroll
        for (int h = 0; h < 2; h++) {
          const b2 e = as_b2(__byte_perm(h ? e2.y : e2.x, 0, se)), o = as_b2(__byte_perm(h ? o2.y : o2.x, 0, so));
          const uint32_t s = as_u(__hadd2(e, o)), d = as_u(__hsub2(e, o)) ^ 0x80000000u;
          v[2 * jj + h] = mk(as_b2(__byte_perm(s, d, 0x5410)), as_b2(__byte_perm(s, d, 0x7632)));
        }
      }
      if (t == 0) PROF(2, 12);
      columns(v, sb, t);
      if (t == 0) PROF(2, 14);
      const int pre = (k == 112) ? 1 : 2 * k, pim = (k == 112) ? 1 : 2 * k + 1;
      uint32_t* pq = reinterpret_cast<uint32_t*>(g_PQ) + (t >> 5) * 14336;
      uint32_t* pr = pq + pre * 32 + ((((lane >> 2) ^ pre) & 7) << 2) + (lane & 3);
      uint32_t* pi = pq + pim * 32 + ((((lane >> 2) ^ pim) & 7) << 2) + (lane & 3);
#pragma unroll
      for (int jj = 0; jj < 8; jj++) {
        const b2 ar = as_b2(__byte_perm(as_u(v[2 * jj].y), as_u(v[2 * jj + 1].y), 0x5410)), br = as_b2(__byte_perm(as_u(v[2 * jj].y), as_u(v[2 * jj + 1].y), 0x7632));
        const b2 ai = as_b2(__byte_perm(as_u(v[2 * jj].x), as_u(v[2 * jj + 1].x), 0x5410)), bi = as_b2(__byte_perm(as_u(v[2 * jj].x), as_u(v[2 * jj + 1].x), 0x7632));
        pr[jj * 57344] = as_u(__hadd2(ar, br));
        if (k != 112) pr[jj * 57344 + 7168] = as_u(__hsub2(ar, br));
        if (k != 0) pi[jj * 57344 + 7168] = as_u(__hadd2(ai, bi));
        if (k != 0 && k != 112) pi[jj * 57344] = as_u(__hsub2(ai, bi));
      }
      fence_async_smem();
    }
    bar_sync<3, 128>();
    if (t == 0) { PROF(2, 5); red_release(&g_cnt[5 * 32]); PROF(2, 7); }
    __syncwarp();
    asm volatile("barrier.cluster.wait.aligned;" ::: "memory");
  } else {
    asm volatile("setmaxnreg.dec.sync.aligned.u32 24;");
    if (warp == 12) {
      if (elect()) {
        mbar_init(bars + B_XFULL * 8, 1); mbar_init(bars + (B_XFULL + 1) * 8, 1);
        fence_async_smem();
#pragma unroll
        for (int w = 0; w < 2; w++) {
          mbar_expect(bars + (B_XFULL + w) * 8, HALF_XR);
          tma3d(sb + OFF_PQ + w * HALF_XR, &tm_x, 0, m * 128 + (w ^ kh ^ 1) * 64, 0, bars + (B_XFULL + w) * 8);
        }
        PROF(3, 3);
#pragma unroll
        for (int i = 0; i < NSLOT; i++) mbar_init(bars + (B_FULL + i) * 8, 1);
        mbar_init(bars + B_PIN * 8, 1);
        fence_async_smem();
      }
      bar_arrive<0, NTHREADS - 64>();
#pragma unroll 1
      for (int i = 0; i < 5; i++) {
        if (elect()) {
          if (i == WPOS) {
            mbar_expect(bars + B_PIN * 8, 14400);
            bulk_g2s(sb + 6 * SLOT, reinterpret_cast<const unsigned char*>(w_r) + bid * 7200, 7200, bars + B_PIN * 8);
            bulk_g2s(sb + 6 * SLOT + 7200, reinterpret_cast<const unsigned char*>(w_i) + bid * 7200, 7200, bars + B_PIN * 8);
          }
          const uint32_t fb = bars + (B_FULL + i) * 8;
          mbar_expect(fb, SLOT);
          tma2d(sb + i * SLOT, &tm_g, c64, i * 64, fb);
          tma2d(sb + i * SLOT + 8192, &tm_u, c64, i * 64, fb);
          PROF(3, 4 + i);
        }
      }
      if (elect()) {
        prefetch_tma2d(&tm_g, c64, 320); prefetch_tma2d(&tm_u, c64, 320);
        prefetch_tma2d(&tm_g, c64, 384); prefetch_tma2d(&tm_u, c64, 384);
      }
    } else if (warp == 14) {
      if (elect()) {
#pragma unroll
        for (int i = B_EMPTY; i < B_END; i++)
          if (i < B_XFULL || i >= B_XFREE) mbar_init(bars + i * 8, i >= B_PQFULL ? 1 : ((i == B_XFREE || i >= B_PUBW) ? 4 : 8));
        asm volatile("fence.mbarrier_init.release.cluster;" ::: "memory");
        fence_async_smem();
        mbar_expect(bars + B_RECV * 8, 64 * 112 * 4);
      }
      bar_arrive<0, NTHREADS - 64>();
    }
    const uint32_t epoch = ld_relaxed(&g_ep[bid]);
    if (warp == 13 && lane == 0) { PROFG(4, 0); PROF(4, 1); }
    bar_sync<1, 128>();
    asm volatile("barrier.cluster.arrive.relaxed.aligned;" ::: "memory");
    if (warp == 12) {
      int slot = 5, ph = 1;
      auto wait_slot = [&]() { mbar_wait(bars + (B_EMPTY + slot) * 8, ph ^ (slot >= 5)); };
      auto adv = [&]() { if (++slot == NSLOT) { slot = 0; ph ^= 1; } };
      const int c32 = 224 * j + ((j & 1) ? 0 : 192);
#pragma unroll 1
      for (int i = 5; i < 25; i++) {
        wait_slot();
        if (elect()) {
          const uint32_t dst = sb + slot * SLOT, fb = bars + (B_FULL + slot) * 8;
          const bool last = i >= 21;
          const int cc = last ? c32 : c64 + 64 * (i / 7), rr = last ? slot * 128 : slot * 64;
          mbar_expect(fb, SLOT);
          tma2d(dst, last ? &tm_g32 : &tm_g, cc, rr, fb);
          tma2d(dst + 8192, last ? &tm_u32 : &tm_u, cc, rr, fb);
        }
        adv();
      }
      if (lane == 0) PROF(3, 0);
      mbar_wait(bars + B_PREP * 8, 0);
      if (lane == 0) PROF(3, 1);
#pragma unroll 1
      for (int i = 4; i < 16; i++) {
        if (lane == 0) PROF(3, 16 + i);
        wait_slot();
        if (elect()) {
          const int bytes = i < 14 ? 14336 : G_IMG / 2;
          const unsigned char* src = i < 14 ? g_Wd + (size_t)j * WD_IMG + i * 14336 : g_G + (size_t)(n * 4 + i - 12) * (G_IMG / 2);
          mbar_expect(bars + (B_FULL + slot) * 8, bytes);
          bulk_g2s(sb + slot * SLOT, src, bytes, bars + (B_FULL + slot) * 8);
        }
        adv();
      }
      if (lane == 0) PROF(3, 2);
    } else if (warp == 13) {
      mbar_wait(bars + B_PUBW * 8, 0);
      if (lane == 0) PROF(4, 7);
      mbar_wait(bars + B_PUBX * 8, 0);
      if (lane == 0) {
        PROF(4, 8);
        red_release(&g_cnt[(j >> 1) * 32]);
        red_relaxed(&g_cnt[6 * 32]);
        PROF(4, 18);
      }
      __syncwarp();
      mbar_wait(bars + B_PUBD * 8, 0);
      if (lane == 0) { PROF(4, 9); red_release(&g_cnt[4 * 32]); PROF(4, 19); }
      __syncwarp();
      mbar_wait(bars + B_LFREE * 8, 0);
      if (elect()) {
        mbar_expect(bars + B_GFULL * 8, G_IMG);
        bulk_g2s(sb + OFF_R + 28672, g_G + (size_t)(n * 2) * G_IMG, G_IMG, bars + B_GFULL * 8);
      }
    } else if (warp == 14) {
#pragma unroll 1
      for (int u = 0; u < 2; u++) {
        wait_ge(&g_cnt[(6 - 2 * u) * 32], (epoch + 1) * 128);
        fence_async_global();
        if (lane == 0) { mbar_arrive(bars + (B_PREPW - u) * 8); PROF(5, 9 - u); }
      }
    } else {
      mbar_wait(bars + B_XFREE * 8, 0);
      if (elect()) {
        prefetch_l2(reinterpret_cast<const unsigned char*>(w_gate) + bid * 12544, 12544);
        prefetch_l2(reinterpret_cast<const unsigned char*>(w_up) + bid * 12544, 12544);
      }
      mbar_wait(bars + (B_XFREE + 1) * 8, 0);
      if (elect()) {
        mbar_expect(bars + B_RFULL * 8, 12544);
        bulk_g2s(sb + OFF_R, reinterpret_cast<const unsigned char*>(w_down) + bid * 12544, 12544, bars + B_RFULL * 8);
      }
      if (bid < 113) {
        const int sl = (bid == 112) ? 0 : bid;
        wait_ge(&g_cnt[((sl & 1) + 2 * ((sl >> 1) / 28)) * 32], (epoch + 1) * 32);
        fence_async_global();
        if (elect()) {
          PROF(5, 16);
          mbar_expect(bars + B_XCFULL * 8, 16384);
          bulk_g2s(sb + OFF_EXCH, g_Xc + sl * 2 * S_, 16384, bars + B_XCFULL * 8);
        }
        mbar_wait(bars + B_PREPW * 8, 0);
        if (elect()) {
          mbar_expect(bars + B_WFULL * 8, 16384);
          bulk_g2s(sb + OFF_WS, g_Wt + bid * S_, 16384, bars + B_WFULL * 8);
          PROF(5, 17);
        }
      }
      mbar_wait(bars + B_PREP * 8, 0);
      if (elect()) {
        mbar_expect(bars + B_RFULL * 8, HALF_XR);
        bulk_g2s(sb + OFF_R, g_Wd + (size_t)j * WD_IMG, HALF_XR, bars + B_RFULL * 8);
        PROF(5, 19);
      }
      wait_ge(&g_cnt[5 * 32], (epoch + 1) * 128);
      fence_async_global();
      if (elect()) {
        PROF(5, 18);
        mbar_expect(bars + B_PQFULL * 8, HALF_XR + 256);
        const unsigned char* src = g_PQ + (size_t)(m * 2 + kh) * HALF_XR;
        bulk_g2s(sb + OFF_PQ, src, 28672, bars + B_PQFULL * 8);
        bulk_g2s(sb + OFF_PQ + 28672, src + 28672, 28672, bars + B_PQFULL * 8);
        bulk_g2s(sb + OFF_G, g_gate + m * 128 + kh * 64, 256, bars + B_PQFULL * 8);
      }
    }
    __syncwarp();
    asm volatile("barrier.cluster.wait.aligned;" ::: "memory");
  }
}

typedef CUresult (*EncodeFn)(CUtensorMap*, CUtensorMapDataType, cuuint32_t, void*, const cuuint64_t*, const cuuint64_t*, const cuuint32_t*,
                             const cuuint32_t*, CUtensorMapInterleave, CUtensorMapSwizzle, CUtensorMapL2promotion, CUtensorMapFloatOOBfill);

void make_map(EncodeFn enc, CUtensorMap* tm, const void* base, int cols, int rows, int bc, int br, CUtensorMapSwizzle sw) {
  cuuint64_t gd[2] = {(cuuint64_t)cols, (cuuint64_t)rows};
  cuuint64_t gs[1] = {(cuuint64_t)cols * 2};
  cuuint32_t bd[2] = {(cuuint32_t)bc, (cuuint32_t)br};
  cuuint32_t es[2] = {1, 1};
  enc(tm, CU_TENSOR_MAP_DATA_TYPE_BFLOAT16, 2, const_cast<void*>(base), gd, gs, bd, es, CU_TENSOR_MAP_INTERLEAVE_NONE, sw,
      CU_TENSOR_MAP_L2_PROMOTION_L2_128B, CU_TENSOR_MAP_FLOAT_OOB_FILL_NONE);
}

}

extern "C" void kernel_launch(void* const* d_in, const int* in_sizes, int n_in, void* d_out, int out_size) {
  (void)in_sizes; (void)n_in; (void)out_size;
  const __nv_bfloat16* x = (const __nv_bfloat16*)d_in[0];
  const __nv_bfloat16* w_r = (const __nv_bfloat16*)d_in[1];
  const __nv_bfloat16* w_i = (const __nv_bfloat16*)d_in[2];
  const __nv_bfloat16* w_gate = (const __nv_bfloat16*)d_in[4];
  const __nv_bfloat16* w_up = (const __nv_bfloat16*)d_in[5];
  const __nv_bfloat16* w_down = (const __nv_bfloat16*)d_in[6];
  const __nv_bfloat16* gate_w = (const __nv_bfloat16*)d_in[7];
  static EncodeFn enc = nullptr;
  static bool ok = false;
  if (!enc) {
    cudaDriverEntryPointQueryResult qr;
    cudaGetDriverEntryPoint("cuTensorMapEncodeTiled", (void**)&enc, cudaEnableDefault, &qr);
    cudaFuncSetAttribute(fused_kernel, cudaFuncAttributeMaxDynamicSharedMemorySize, SMEM_BYTES);
    cudaFuncAttributes fa;
    cudaFuncGetAttributes(&fa, fused_kernel);
    ok = (fa.numRegs == 128);
  }
  if (!ok) return;
  CUtensorMap tx, tg, tu, tg32, tu32;
  {
    cuuint64_t gd[3] = {64, (cuuint64_t)S_, 7};
    cuuint64_t gs[2] = {(cuuint64_t)D_ * 2, 128};
    cuuint32_t bd[3] = {64, 64, 7};
    cuuint32_t es[3] = {1, 1, 1};
    enc(&tx, CU_TENSOR_MAP_DATA_TYPE_BFLOAT16, 3, const_cast<__nv_bfloat16*>(x), gd, gs, bd, es, CU_TENSOR_MAP_INTERLEAVE_NONE, CU_TENSOR_MAP_SWIZZLE_128B,
        CU_TENSOR_MAP_L2_PROMOTION_L2_128B, CU_TENSOR_MAP_FLOAT_OOB_FILL_NONE);
  }
  make_map(enc, &tg, w_gate, F_, D_, 64, 64, CU_TENSOR_MAP_SWIZZLE_128B);
  make_map(enc, &tu, w_up, F_, D_, 64, 64, CU_TENSOR_MAP_SWIZZLE_128B);
  make_map(enc, &tg32, w_gate, F_, D_, 32, 128, CU_TENSOR_MAP_SWIZZLE_64B);
  make_map(enc, &tu32, w_up, F_, D_, 32, 128, CU_TENSOR_MAP_SWIZZLE_64B);
  fused_kernel<<<128, NTHREADS, SMEM_BYTES>>>(tx, tg, tu, tg32, tu32, w_r, w_i, w_gate, w_up, w_down, gate_w, (__nv_bfloat16*)d_out);
}
```

```cpp
#include <cuda_runtime.h>
#include <cuda_bf16.h>
#include <cuda.h>
#include <stdint.h>

namespace {

constexpr int S_ = 2048, D_ = 448, F_ = 1792;
constexpr int NTHREADS = 512;
constexpr int SLOT = 16384, NSLOT = 7;
constexpr int HALF_XR = 57344;
constexpr int OFF_PQ = NSLOT * SLOT;
constexpr int OFF_R = OFF_PQ + HALF_XR;
constexpr int OFF_EXCH = OFF_PQ;
constexpr int OFF_WS = OFF_EXCH + 18432;
constexpr int OFF_TW = OFF_WS + 16384;
constexpr int OFF_MISC = OFF_R + HALF_XR;
constexpr int OFF_G = OFF_MISC;
constexpr int OFF_BAR = OFF_MISC + 512;
constexpr int SMEM_BYTES = OFF_BAR + 512;
constexpr int B_FULL = 0, B_EMPTY = 7, B_XFULL = 14  ;
constexpr int B_XFREE = 16  , B_PUBX = 18, B_RFREE = 19, B_LFREE = 20;
constexpr int B_PUBW = 21, B_PUBD = 22;
constexpr int B_PQFULL = 23, B_RECV = 24, B_WFULL = 25, B_XCFULL = 26, B_PREP = 27, B_PREPW = 28, B_RFULL = 29, B_GFULL = 30, B_END = 31, B_PIN = 31;

constexpr int WD_IMG = 896 * 112 * 2;
constexpr int G_IMG = 224 * 56 * 2;

__device__ __align__(1024) uint32_t g_Xc[112 * 2 * S_];
__device__ __align__(1024) unsigned char g_H[32 * 56 * 4096];
__device__ __align__(1024) unsigned char g_PQ[32 * HALF_XR];
__device__ __align__(1024) unsigned char g_Wd[8 * WD_IMG];
__device__ __align__(1024) unsigned char g_G[8 * G_IMG];
__device__ __align__(1024) uint2 g_Wt[113 * S_];
__device__ __align__(1024) float g_gate[S_];
__device__ __align__(128) unsigned int g_ep[128];
__device__ __align__(128) unsigned int g_cnt[8 * 32];

#define PROF(role, idx) do {} while (0)
#define PROFG(role, idx) do {} while (0)

__device__ __forceinline__ uint32_t s2u(const void* p) { return (uint32_t)__cvta_generic_to_shared(p); }
__device__ __forceinline__ void mbar_init(uint32_t b, int c) { asm volatile("mbarrier.init.shared::cta.b64 [%0], %1;" :: "r"(b), "r"(c) : "memory"); }
__device__ __forceinline__ void mbar_expect(uint32_t b, int bytes) { asm volatile("mbarrier.arrive.expect_tx.shared::cta.b64 _, [%0], %1;" :: "r"(b), "r"(bytes) : "memory"); }
__device__ __forceinline__ void mbar_arrive(uint32_t b) { asm volatile("mbarrier.arrive.shared::cta.b64 _, [%0];" :: "r"(b) : "memory"); }
__device__ __forceinline__ void mbar_wait(uint32_t b, int ph) {
  asm volatile("{\n.reg .pred p;\n.reg .u32 c;\nmov.u32 c, 0;\nL_WAIT:\nmbarrier.try_wait.parity.shared::cta.b64 p, [%0], %1;\n@p bra.uni L_DONE;\n"
               "add.u32 c, c, 1;\nsetp.lt.u32 p, c, 4194304;\n@p bra.uni L_WAIT;\ntrap;\nL_DONE:\n}" :: "r"(b), "r"(ph) : "memory");
}
__device__ __forceinline__ void mbar_wait_cluster(uint32_t b, int ph) {
  asm volatile("{\n.reg .pred p;\n.reg .u32 c;\nmov.u32 c, 0;\nL_WAIT:\nmbarrier.try_wait.parity.acquire.cluster.shared::cta.b64 p, [%0], %1;\n@p bra.uni L_DONE;\n"
               "add.u32 c, c, 1;\nsetp.lt.u32 p, c, 4194304;\n@p bra.uni L_WAIT;\ntrap;\nL_DONE:\n}" :: "r"(b), "r"(ph) : "memory");
}
__device__ __forceinline__ uint32_t ld_acquire(const unsigned int* p) { uint32_t v; asm volatile("ld.acquire.gpu.global.u32 %0, [%1];" : "=r"(v) : "l"(p) : "memory"); return v; }
__device__ __forceinline__ uint32_t ld_relaxed(const unsigned int* p) { uint32_t v; asm volatile("ld.relaxed.gpu.global.u32 %0, [%1];" : "=r"(v) : "l"(p) : "memory"); return v; }
__device__ __forceinline__ void wait_ge(const unsigned int* p, uint32_t target) {
#pragma unroll 1
  for (int i = 0; i < (1 << 22); i++) { if ((int)(ld_acquire(p) - target) >= 0) return; }
  __trap();
}
__device__ __forceinline__ void red_release(unsigned int* p) { asm volatile("red.release.gpu.global.add.u32 [%0], 1;" :: "l"(p) : "memory"); }
__device__ __forceinline__ void red_relaxed(unsigned int* p) { asm volatile("red.relaxed.gpu.global.add.u32 [%0], 1;" :: "l"(p) : "memory"); }
__device__ __forceinline__ bool elect() { uint32_t p; asm volatile("{\n.reg .pred p;\nelect.sync _|p, 0xffffffff;\nselp.u32 %0, 1, 0, p;\n}" : "=r"(p)); return p; }
__device__ __forceinline__ void fence_async_smem() { asm volatile("fence.proxy.async.shared::cta;" ::: "memory"); }
__device__ __forceinline__ void fence_async_global() { asm volatile("fence.proxy.async.global;" ::: "memory"); }
template <int ID, int N> __device__ __forceinline__ void bar_sync() { asm volatile("bar.sync %0, %1;" :: "n"(ID), "n"(N) : "memory"); }
template <int ID, int N> __device__ __forceinline__ void bar_arrive() { asm volatile("bar.arrive %0, %1;" :: "n"(ID), "n"(N) : "memory"); }
__device__ __forceinline__ void tma2d(uint32_t dst, const CUtensorMap* tm, int c0, int c1, uint32_t bar) {
  asm volatile("cp.async.bulk.tensor.2d.shared::cluster.global.mbarrier::complete_tx::bytes [%0], [%1, {%3, %4}], [%2];"
               :: "r"(dst), "l"(tm), "r"(bar), "r"(c0), "r"(c1) : "memory");
}
__device__ __forceinline__ void tma3d(uint32_t dst, const CUtensorMap* tm, int c0, int c1, int c2, uint32_t bar) {
  asm volatile("cp.async.bulk.tensor.3d.shared::cluster.global.mbarrier::complete_tx::bytes [%0], [%1, {%3, %4, %5}], [%2];"
               :: "r"(dst), "l"(tm), "r"(bar), "r"(c0), "r"(c1), "r"(c2) : "memory");
}
__device__ __forceinline__ void bulk_g2s(uint32_t dst, const void* src, int bytes, uint32_t bar) {
  asm volatile("cp.async.bulk.shared::cluster.global.mbarrier::complete_tx::bytes [%0], [%1], %2, [%3];"
               :: "r"(dst), "l"(src), "r"(bytes), "r"(bar) : "memory");
}
__device__ __forceinline__ void prefetch_l2(const void* src, int bytes) {
  asm volatile("cp.async.bulk.prefetch.L2.global [%0], %1;" :: "l"(src), "r"(bytes) : "memory");
}
__device__ __forceinline__ void prefetch_tma2d(const CUtensorMap* tm, int c0, int c1) {
  asm volatile("cp.async.bulk.prefetch.tensor.2d.L2.global [%0, {%1, %2}];" :: "l"(tm), "r"(c0), "r"(c1) : "memory");
}
__device__ __forceinline__ uint64_t mkdesc(uint32_t addr, uint32_t lbo, uint32_t sbo, uint32_t mode) {
  return (uint64_t)((addr & 0x3FFFF) >> 4) | ((uint64_t)(lbo >> 4) << 16) | ((uint64_t)(sbo >> 4) << 32) | ((uint64_t)mode << 62);
}
__device__ __forceinline__ void wg_fence() { asm volatile("wgmma.fence.sync.aligned;" ::: "memory"); }
__device__ __forceinline__ void wg_commit() { asm volatile("wgmma.commit_group.sync.aligned;" ::: "memory"); }
template <int N> __device__ __forceinline__ void wg_wait() { asm volatile("wgmma.wait_group.sync.aligned %0;" :: "n"(N) : "memory"); }
template <int N> __device__ __forceinline__ void keep(float (&d)[N]) {
#pragma unroll
  for (int i = 0; i < N; i++) asm volatile("" : "+f"(d[i]) :: "memory");
}
__device__ __forceinline__ uint32_t pack_bf16(float lo, float hi) { uint32_t r; asm("cvt.rn.bf16x2.f32 %0, %1, %2;" : "=r"(r) : "f"(hi), "f"(lo)); return r; }
__device__ __forceinline__ float bf16_round(float v) { return __bfloat162float(__float2bfloat16_rn(v)); }
__device__ __forceinline__ void sts128(uint32_t a, uint32_t x, uint32_t y, uint32_t z, uint32_t w) { asm volatile("st.shared.v4.b32 [%0], {%1,%2,%3,%4};" :: "r"(a), "r"(x), "r"(y), "r"(z), "r"(w) : "memory"); }
__device__ __forceinline__ float4 lds128f(uint32_t a) { float4 v; asm volatile("ld.shared.v4.f32 {%0,%1,%2,%3}, [%4];" : "=f"(v.x), "=f"(v.y), "=f"(v.z), "=f"(v.w) : "r"(a) : "memory"); return v; }

__device__ __forceinline__ uint2 lds64(uint32_t a) { uint2 v; asm volatile("ld.shared.v2.b32 {%0,%1}, [%2];" : "=r"(v.x), "=r"(v.y) : "r"(a) : "memory"); return v; }
__device__ __forceinline__ float bf_lo(uint32_t w) { return __uint_as_float(w << 16); }
__device__ __forceinline__ float bf_hi(uint32_t w) { return __uint_as_float(w & 0xffff0000u); }
__device__ __forceinline__ uint32_t opaque(uint32_t v) { asm volatile("" : "+r"(v)); return v; }
__device__ __forceinline__ uint4 ldg128(const void* p) { uint4 v; asm volatile("ld.global.nc.v4.b32 {%0,%1,%2,%3}, [%4];" : "=r"(v.x), "=r"(v.y), "=r"(v.z), "=r"(v.w) : "l"(p)); return v; }
__device__ __forceinline__ void stg128(void* p, uint32_t x, uint32_t y, uint32_t z, uint32_t w) { asm volatile("st.global.v4.b32 [%0], {%1,%2,%3,%4};" :: "l"(p), "r"(x), "r"(y), "r"(z), "r"(w) : "memory"); }
__device__ __forceinline__ void stg128_l2(void* p, uint32_t x, uint32_t y, uint32_t z, uint32_t w) { asm volatile("st.relaxed.gpu.global.v4.b32 [%0], {%1,%2,%3,%4};" :: "l"(p), "r"(x), "r"(y), "r"(z), "r"(w) : "memory"); }
__device__ __forceinline__ void ldg128_na(uint32_t (&v)[4], const void* p) { asm volatile("ld.global.L1::no_allocate.v4.b32 {%0,%1,%2,%3}, [%4];" : "=r"(v[0]), "=r"(v[1]), "=r"(v[2]), "=r"(v[3]) : "l"(p) : "memory"); }
__device__ __forceinline__ void ldg128_l2(uint32_t (&v)[4], const void* p) { asm volatile("ld.relaxed.gpu.global.v4.b32 {%0,%1,%2,%3}, [%4];" : "=r"(v[0]), "=r"(v[1]), "=r"(v[2]), "=r"(v[3]) : "l"(p) : "memory"); }
__device__ __forceinline__ uint4 lds128(uint32_t a) { uint4 v; asm volatile("ld.shared.v4.b32 {%0,%1,%2,%3}, [%4];" : "=r"(v.x), "=r"(v.y), "=r"(v.z), "=r"(v.w) : "r"(a) : "memory"); return v; }
__device__ __forceinline__ uint32_t lds16(uint32_t a) { uint32_t v; asm volatile("ld.shared.u16 %0, [%1];" : "=r"(v) : "r"(a) : "memory"); return v; }
__device__ __forceinline__ void sts64(uint32_t a, uint32_t x, uint32_t y) { asm volatile("st.shared.v2.b32 [%0], {%1,%2};" :: "r"(a), "r"(x), "r"(y) : "memory"); }
template <int TB> __device__ __forceinline__ void wgmma_rs_128(float (&d)[64], const uint32_t (&a)[4], uint64_t db, int sc) {
  asm volatile("{\n.reg .pred p;\nsetp.ne.b32 p, %69, 0;\n"
    "wgmma.mma_async.sync.aligned.m64n128k16.f32.bf16.bf16 {%0, %1, %2, %3, %4, %5, %6, %7, %8, %9, %10, %11, %12, %13, %14, %15, %16, %17, %18, %19, %20, %21, %22, %23, %24, %25, %26, %27, %28, %29, %30, %31, %32, %33, %34, %35, %36, %37, %38, %39, %40, %41, %42, %43, %44, %45, %46, %47, %48, %49, %50, %51, %52, %53, %54, %55, %56, %57, %58, %59, %60, %61, %62, %63}, {%64, %65, %66, %67}, %68, p, 1, 1, %70;\n}\n"
    : "+f"(d[0]), "+f"(d[1]), "+f"(d[2]), "+f"(d[3]), "+f"(d[4]), "+f"(d[5]), "+f"(d[6]), "+f"(d[7]), "+f"(d[8]), "+f"(d[9]), "+f"(d[10]), "+f"(d[11]), "+f"(d[12]), "+f"(d[13]), "+f"(d[14]), "+f"(d[15]), "+f"(d[16]), "+f"(d[17]), "+f"(d[18]), "+f"(d[19]), "+f"(d[20]), "+f"(d[21]), "+f"(d[22]), "+f"(d[23]), "+f"(d[24]), "+f"(d[25]), "+f"(d[26]), "+f"(d[27]), "+f"(d[28]), "+f"(d[29]), "+f"(d[30]), "+f"(d[31]), "+f"(d[32]), "+f"(d[33]), "+f"(d[34]), "+f"(d[35]), "+f"(d[36]), "+f"(d[37]), "+f"(d[38]), "+f"(d[39]), "+f"(d[40]), "+f"(d[41]), "+f"(d[42]), "+f"(d[43]), "+f"(d[44]), "+f"(d[45]), "+f"(d[46]), "+f"(d[47]), "+f"(d[48]), "+f"(d[49]), "+f"(d[50]), "+f"(d[51]), "+f"(d[52]), "+f"(d[53]), "+f"(d[54]), "+f"(d[55]), "+f"(d[56]), "+f"(d[57]), "+f"(d[58]), "+f"(d[59]), "+f"(d[60]), "+f"(d[61]), "+f"(d[62]), "+f"(d[63])
    : "r"(a[0]), "r"(a[1]), "r"(a[2]), "r"(a[3]), "l"(db), "r"(sc), "n"(TB));
}
template <int TB> __device__ __forceinline__ void wgmma_rs_64(float (&d)[32], const uint32_t (&a)[4], uint64_t db, int sc) {
  asm volatile("{\n.reg .pred p;\nsetp.ne.b32 p, %37, 0;\n"
    "wgmma.mma_async.sync.aligned.m64n64k16.f32.bf16.bf16 {%0, %1, %2, %3, %4, %5, %6, %7, %8, %9, %10, %11, %12, %13, %14, %15, %16, %17, %18, %19, %20, %21, %22, %23, %24, %25, %26, %27, %28, %29, %30, %31}, {%32, %33, %34, %35}, %36, p, 1, 1, %38;\n}\n"
    : "+f"(d[0]), "+f"(d[1]), "+f"(d[2]), "+f"(d[3]), "+f"(d[4]), "+f"(d[5]), "+f"(d[6]), "+f"(d[7]), "+f"(d[8]), "+f"(d[9]), "+f"(d[10]), "+f"(d[11]), "+f"(d[12]), "+f"(d[13]), "+f"(d[14]), "+f"(d[15]), "+f"(d[16]), "+f"(d[17]), "+f"(d[18]), "+f"(d[19]), "+f"(d[20]), "+f"(d[21]), "+f"(d[22]), "+f"(d[23]), "+f"(d[24]), "+f"(d[25]), "+f"(d[26]), "+f"(d[27]), "+f"(d[28]), "+f"(d[29]), "+f"(d[30]), "+f"(d[31])
    : "r"(a[0]), "r"(a[1]), "r"(a[2]), "r"(a[3]), "l"(db), "r"(sc), "n"(TB));
}
template <int TB> __device__ __forceinline__ void wgmma_rs_56(float (&d)[28], const uint32_t (&a)[4], uint64_t db, int sc) {
  asm volatile("{\n.reg .pred p;\nsetp.ne.b32 p, %33, 0;\n"
    "wgmma.mma_async.sync.aligned.m64n56k16.f32.bf16.bf16 {%0, %1, %2, %3, %4, %5, %6, %7, %8, %9, %10, %11, %12, %13, %14, %15, %16, %17, %18, %19, %20, %21, %22, %23, %24, %25, %26, %27}, {%28, %29, %30, %31}, %32, p, 1, 1, %34;\n}\n"
    : "+f"(d[0]), "+f"(d[1]), "+f"(d[2]), "+f"(d[3]), "+f"(d[4]), "+f"(d[5]), "+f"(d[6]), "+f"(d[7]), "+f"(d[8]), "+f"(d[9]), "+f"(d[10]), "+f"(d[11]), "+f"(d[12]), "+f"(d[13]), "+f"(d[14]), "+f"(d[15]), "+f"(d[16]), "+f"(d[17]), "+f"(d[18]), "+f"(d[19]), "+f"(d[20]), "+f"(d[21]), "+f"(d[22]), "+f"(d[23]), "+f"(d[24]), "+f"(d[25]), "+f"(d[26]), "+f"(d[27])
    : "r"(a[0]), "r"(a[1]), "r"(a[2]), "r"(a[3]), "l"(db), "r"(sc), "n"(TB));
}
template <int TB> __device__ __forceinline__ void wgmma_rs_112(float (&d)[56], const uint32_t (&a)[4], uint64_t db, int sc) {
  asm volatile("{\n.reg .pred p;\nsetp.ne.b32 p, %61, 0;\n"
    "wgmma.mma_async.sync.aligned.m64n112k16.f32.bf16.bf16 {%0, %1, %2, %3, %4, %5, %6, %7, %8, %9, %10, %11, %12, %13, %14, %15, %16, %17, %18, %19, %20, %21, %22, %23, %24, %25, %26, %27, %28, %29, %30, %31, %32, %33, %34, %35, %36, %37, %38, %39, %40, %41, %42, %43, %44, %45, %46, %47, %48, %49, %50, %51, %52, %53, %54, %55}, {%56, %57, %58, %59}, %60, p, 1, 1, %62;\n}\n"
    : "+f"(d[0]), "+f"(d[1]), "+f"(d[2]), "+f"(d[3]), "+f"(d[4]), "+f"(d[5]), "+f"(d[6]), "+f"(d[7]), "+f"(d[8]), "+f"(d[9]), "+f"(d[10]), "+f"(d[11]), "+f"(d[12]), "+f"(d[13]), "+f"(d[14]), "+f"(d[15]), "+f"(d[16]), "+f"(d[17]), "+f"(d[18]), "+f"(d[19]), "+f"(d[20]), "+f"(d[21]), "+f"(d[22]), "+f"(d[23]), "+f"(d[24]), "+f"(d[25]), "+f"(d[26]), "+f"(d[27]), "+f"(d[28]), "+f"(d[29]), "+f"(d[30]), "+f"(d[31]), "+f"(d[32]), "+f"(d[33]), "+f"(d[34]), "+f"(d[35]), "+f"(d[36]), "+f"(d[37]), "+f"(d[38]), "+f"(d[39]), "+f"(d[40]), "+f"(d[41]), "+f"(d[42]), "+f"(d[43]), "+f"(d[44]), "+f"(d[45]), "+f"(d[46]), "+f"(d[47]), "+f"(d[48]), "+f"(d[49]), "+f"(d[50]), "+f"(d[51]), "+f"(d[52]), "+f"(d[53]), "+f"(d[54]), "+f"(d[55])
    : "r"(a[0]), "r"(a[1]), "r"(a[2]), "r"(a[3]), "l"(db), "r"(sc), "n"(TB));
}
template <int TA, int TB> __device__ __forceinline__ void wgmma_ss_56(float (&d)[28], uint64_t da, uint64_t db, int sc) {
  asm volatile("{\n.reg .pred p;\nsetp.ne.b32 p, %30, 0;\n"
    "wgmma.mma_async.sync.aligned.m64n56k16.f32.bf16.bf16 {%0, %1, %2, %3, %4, %5, %6, %7, %8, %9, %10, %11, %12, %13, %14, %15, %16, %17, %18, %19, %20, %21, %22, %23, %24, %25, %26, %27}, %28, %29, p, 1, 1, %31, %32;\n}\n"
    : "+f"(d[0]), "+f"(d[1]), "+f"(d[2]), "+f"(d[3]), "+f"(d[4]), "+f"(d[5]), "+f"(d[6]), "+f"(d[7]), "+f"(d[8]), "+f"(d[9]), "+f"(d[10]), "+f"(d[11]), "+f"(d[12]), "+f"(d[13]), "+f"(d[14]), "+f"(d[15]), "+f"(d[16]), "+f"(d[17]), "+f"(d[18]), "+f"(d[19]), "+f"(d[20]), "+f"(d[21]), "+f"(d[22]), "+f"(d[23]), "+f"(d[24]), "+f"(d[25]), "+f"(d[26]), "+f"(d[27])
    : "l"(da), "l"(db), "r"(sc), "n"(TA), "n"(TB));
}

__device__ __forceinline__ uint32_t cis(float a) { return pack_bf16(__cosf(a), __sinf(a)); }

typedef __nv_bfloat162 b2;
struct c2 { b2 x, y; };
__device__ __forceinline__ b2 as_b2(uint32_t u) { return *reinterpret_cast<b2*>(&u); }
__device__ __forceinline__ uint32_t as_u(b2 v) { return *reinterpret_cast<uint32_t*>(&v); }
__device__ __forceinline__ c2 mk(b2 x, b2 y) { c2 r; r.x = x; r.y = y; return r; }
__device__ __forceinline__ c2 cmul(c2 a, b2 wr, b2 wi) { return mk(__hfma2(a.x, wr, __hneg2(__hmul2(a.y, wi))), __hfma2(a.x, wi, __hmul2(a.y, wr))); }
__device__ __forceinline__ void fft4(c2& a0, c2& a1, c2& a2, c2& a3) {
  c2 t0 = mk(__hadd2(a0.x, a2.x), __hadd2(a0.y, a2.y)), t1 = mk(__hsub2(a0.x, a2.x), __hsub2(a0.y, a2.y));
  c2 t2 = mk(__hadd2(a1.x, a3.x), __hadd2(a1.y, a3.y)), t3 = mk(__hsub2(a1.x, a3.x), __hsub2(a1.y, a3.y));
  a0 = mk(__hadd2(t0.x, t2.x), __hadd2(t0.y, t2.y)); a2 = mk(__hsub2(t0.x, t2.x), __hsub2(t0.y, t2.y));
  a1 = mk(__hadd2(t1.x, t3.y), __hsub2(t1.y, t3.x)); a3 = mk(__hsub2(t1.x, t3.y), __hadd2(t1.y, t3.x));
}
__device__ __forceinline__ void fft4_s2(c2& a0, c2& a1, c2& a2, c2& a3, b2 r) {
  const b2 nr = __hneg2(r);
  c2 t0 = mk(__hfma2(a2.x, r, a0.x), __hfma2(a2.y, r, a0.y)), t1 = mk(__hfma2(a2.x, nr, a0.x), __hfma2(a2.y, nr, a0.y));
  c2 t2 = mk(__hadd2(a1.x, a3.x), __hadd2(a1.y, a3.y)), t3 = mk(__hsub2(a1.x, a3.x), __hsub2(a1.y, a3.y));
  a0 = mk(__hadd2(t0.x, t2.x), __hadd2(t0.y, t2.y)); a2 = mk(__hsub2(t0.x, t2.x), __hsub2(t0.y, t2.y));
  a1 = mk(__hadd2(t1.x, t3.y), __hsub2(t1.y, t3.x)); a3 = mk(__hsub2(t1.x, t3.y), __hadd2(t1.y, t3.x));
}
__device__ __forceinline__ void fft4_s13(c2& a0, c2& a1, c2& a2, c2& a3, b2 r) {
  const b2 nr = __hneg2(r);
  c2 t0 = mk(__hadd2(a0.x, a2.x), __hadd2(a0.y, a2.y)), t1 = mk(__hsub2(a0.x, a2.x), __hsub2(a0.y, a2.y));
  c2 t2 = mk(__hadd2(a1.x, a3.x), __hadd2(a1.y, a3.y)), t3 = mk(__hsub2(a1.x, a3.x), __hsub2(a1.y, a3.y));
  a0 = mk(__hfma2(t2.x, r, t0.x), __hfma2(t2.y, r, t0.y)); a2 = mk(__hfma2(t2.x, nr, t0.x), __hfma2(t2.y, nr, t0.y));
  a1 = mk(__hfma2(t3.y, r, t1.x), __hfma2(t3.x, nr, t1.y)); a3 = mk(__hfma2(t3.y, nr, t1.x), __hfma2(t3.x, r, t1.y));
}
__device__ __forceinline__ c2 rot1(c2 a) { return mk(__hadd2(a.x, a.y), __hsub2(a.y, a.x)); }
__device__ __forceinline__ c2 rot3(c2 a) { return mk(__hsub2(a.y, a.x), __hneg2(__hadd2(a.x, a.y))); }
__device__ __forceinline__ c2 mul_mi(c2 a) { return mk(a.y, __hneg2(a.x)); }
template <int O> __device__ __forceinline__ void fft8(c2 (&v)[16]) {
  const b2 r = as_b2(0x3F353F35u), nr = as_b2(0xBF35BF35u);
  fft4(v[O], v[O + 4], v[O + 8], v[O + 12]);
  fft4(v[O + 2], v[O + 6], v[O + 10], v[O + 14]);
  const c2 o0 = v[O + 2], o1 = rot1(v[O + 6]), o2 = v[O + 10], o3 = rot1(v[O + 14]);
  const c2 e0 = v[O], e1 = v[O + 4], e2 = v[O + 8], e3 = v[O + 12];
  v[O] = mk(__hadd2(e0.x, o0.x), __hadd2(e0.y, o0.y));              v[O + 8] = mk(__hsub2(e0.x, o0.x), __hsub2(e0.y, o0.y));
  v[O + 2] = mk(__hfma2(o1.x, r, e1.x), __hfma2(o1.y, r, e1.y));    v[O + 10] = mk(__hfma2(o1.x, nr, e1.x), __hfma2(o1.y, nr, e1.y));
  v[O + 4] = mk(__hadd2(e2.x, o2.y), __hsub2(e2.y, o2.x));          v[O + 12] = mk(__hsub2(e2.x, o2.y), __hadd2(e2.y, o2.x));
  v[O + 6] = mk(__hfma2(o3.y, r, e3.x), __hfma2(o3.x, nr, e3.y));   v[O + 14] = mk(__hfma2(o3.y, nr, e3.x), __hfma2(o3.x, r, e3.y));
}
__device__ __forceinline__ void fft16(c2 (&v)[16]) {
  const b2 r = as_b2(0x3F353F35u), c1 = as_b2(0x3F6D3F6Du), s1 = as_b2(0x3EC43EC4u), nc1 = as_b2(0xBF6DBF6Du), ns1 = as_b2(0xBEC4BEC4u);
#pragma unroll
  for (int a = 0; a < 4; a++) fft4(v[a], v[a + 4], v[a + 8], v[a + 12]);
  v[5] = cmul(v[5], c1, ns1); v[6] = rot1(v[6]); v[7] = cmul(v[7], s1, nc1);
  v[9] = rot1(v[9]); v[10] = mul_mi(v[10]); v[11] = rot3(v[11]);
  v[13] = cmul(v[13], s1, nc1); v[14] = rot3(v[14]); v[15] = cmul(v[15], nc1, s1);
  fft4(v[0], v[1], v[2], v[3]); fft4_s2(v[4], v[5], v[6], v[7], r); fft4_s13(v[8], v[9], v[10], v[11], r); fft4_s2(v[12], v[13], v[14], v[15], r);
  c2 t;
  t = v[1]; v[1] = v[4]; v[4] = t;  t = v[2]; v[2] = v[8]; v[8] = t;  t = v[3]; v[3] = v[12]; v[12] = t;
  t = v[6]; v[6] = v[9]; v[9] = t;  t = v[7]; v[7] = v[13]; v[13] = t; t = v[11]; v[11] = v[14]; v[14] = t;
}

__device__ __forceinline__ void columns(c2 (&v)[16], uint32_t sb, int t) {
  const int l16 = t & 15;
  const uint32_t row = sb + OFF_EXCH + (t >> 4) * 2304;
  const uint32_t pos = sb + OFF_EXCH + (t >> 3) * 144 + (t & 7) * 16;
#pragma unroll 1
  for (int ps = 0; ps < 6; ps++) {
    if (ps == 0 || ps == 5) { fft8<0>(v); fft8<1>(v); } else fft16(v);
    if (ps == 5) break;
    if (ps == 2) {
      const uint32_t ws = sb + OFF_WS + (l16 >> 1) * 128 + ((((t >> 4) + (l16 >> 1)) & 7) * 2 + (l16 & 1)) * 8;
      mbar_wait(sb + OFF_BAR + B_WFULL * 8, 0);
#pragma unroll
      for (int q = 0; q < 16; q++) {
        const uint2 w = lds64(ws + q * 1024);
        const c2 z = cmul(v[q], as_b2(w.x), as_b2(w.y));
        v[q] = mk(z.y, z.x);
      }
      continue;
    }
    {
      const bool full = ps == 0 || ps == 4;
      const uint32_t tw = sb + OFF_TW + (full ? ps * 2048 + t * 16 : 16384 + l16 * 16);
      const uint32_t st = full ? 2048 : 256;
#pragma unroll
      for (int i = 0; i < 4; i++) {
        const uint4 w4 = lds128(tw + i * st);
        const uint32_t w[4] = {w4.x, w4.y, w4.z, w4.w};
#pragma unroll
        for (int e = 0; e < 4; e++) v[4 * i + e] = cmul(v[4 * i + e], __low2bfloat162(as_b2(w[e])), __high2bfloat162(as_b2(w[e])));
      }
    }
    if (ps == 0) {
      bar_sync<3, 128>();
#pragma unroll
      for (int q = 0; q < 8; q++) sts128(pos + q * 2304, as_u(v[2 * q].x), as_u(v[2 * q].y), as_u(v[2 * q + 1].x), as_u(v[2 * q + 1].y));
      bar_sync<3, 128>();
#pragma unroll
      for (int q = 0; q < 16; q++) { const uint2 a = lds64(row + q * 144 + l16 * 8); v[q] = mk(as_b2(a.x), as_b2(a.y)); }
    } else {
      __syncwarp();
#pragma unroll
      for (int q = 0; q < 16; q++) sts64(row + q * 144 + l16 * 8, as_u(v[q].x), as_u(v[q].y));
      if (ps == 4) bar_sync<3, 128>(); else __syncwarp();
      const uint32_t src = ps == 4 ? pos : row + l16 * 144, st = ps == 4 ? 2304 : 16;
#pragma unroll
      for (int q = 0; q < 8; q++) { const uint4 a = lds128(src + q * st); v[2 * q] = mk(as_b2(a.x), as_b2(a.y)); v[2 * q + 1] = mk(as_b2(a.z), as_b2(a.w)); }
    }
  }
}

template <int NH> __device__ __forceinline__ void h_epilogue(float (&acc)[NH * 8], unsigned char* gdst, uint32_t tag) {
#pragma unroll
  for (int c = 0; c < NH / 2; c++) {
    uint32_t pk[4];
#pragma unroll
    for (int i = 0; i < 4; i++) {
      float hv[2];
#pragma unroll
      for (int e = 0; e < 2; e++) {
        float hg = 0.5f * acc[c * 8 + i * 2 + e], up = acc[NH * 4 + c * 8 + i * 2 + e];
        float th; asm("tanh.approx.f32 %0, %1;" : "=f"(th) : "f"(hg));
        hv[e] = fmaf(hg, th, hg) * up;
      }
      pk[i] = pack_bf16(hv[0], hv[1]);
    }
    stg128_l2(gdst + c * 4096, (pk[0] & ~1u) | tag, pk[1], pk[2], pk[3]);
  }
}

__device__ __forceinline__ void frag_ready(uint32_t (&a)[4], uint32_t (&b)[4], uint32_t (&c)[4], uint32_t (&d)[4], const unsigned char* p, uint32_t tag) {
  asm volatile("{\n.reg .pred p;\n.reg .u32 c, m, q;\nmov.u32 c, 0;\nL_TRY:\n"
               "lop3.b32 m, %0, %4, %17, 0x7E;\nlop3.b32 q, %8, %12, %17, 0x7E;\nlop3.b32 m, m, q, 1, 0xA8;\nsetp.ne.u32 p, m, 0;\n"
               "vote.sync.any.pred p, p, 0xffffffff;\n@!p bra.uni L_OK;\n"
               "ld.relaxed.gpu.global.v4.b32 {%0,%1,%2,%3}, [%16];\nld.relaxed.gpu.global.v4.b32 {%4,%5,%6,%7}, [%16+4096];\n"
               "ld.relaxed.gpu.global.v4.b32 {%8,%9,%10,%11}, [%16+8192];\nld.relaxed.gpu.global.v4.b32 {%12,%13,%14,%15}, [%16+12288];\n"
               "add.u32 c, c, 1;\nsetp.lt.u32 p, c, 262144;\n@p bra.uni L_TRY;\ntrap;\nL_OK:\n}"
               : "+r"(a[0]), "+r"(a[1]), "+r"(a[2]), "+r"(a[3]), "+r"(b[0]), "+r"(b[1]), "+r"(b[2]), "+r"(b[3]),
                 "+r"(c[0]), "+r"(c[1]), "+r"(c[2]), "+r"(c[3]), "+r"(d[0]), "+r"(d[1]), "+r"(d[2]), "+r"(d[3])
               : "l"(p), "r"(tag) : "memory");
}

#define LDH ldg128_na
#define MAP 0
#define WPOS 0
#define XPRI 1
#define LA2 5
#define LEAD1 3

__global__ void __cluster_dims__(2, 1, 1) __launch_bounds__(NTHREADS, 1)
fused_kernel(const __grid_constant__ CUtensorMap tm_x, const __grid_constant__ CUtensorMap tm_g, const __grid_constant__ CUtensorMap tm_u,
             const __grid_constant__ CUtensorMap tm_g32, const __grid_constant__ CUtensorMap tm_u32,
             const __nv_bfloat16* __restrict__ w_r, const __nv_bfloat16* __restrict__ w_i,
             const __nv_bfloat16* __restrict__ w_gate, const __nv_bfloat16* __restrict__ w_up,
             const __nv_bfloat16* __restrict__ w_down, const __nv_bfloat16* __restrict__ gate_w, __nv_bfloat16* __restrict__ out) {
  extern __shared__ __align__(1024) unsigned char smem[];
  const uint32_t sb = s2u(smem);
  const uint32_t bars = sb + OFF_BAR;
  const int tid = threadIdx.x, warp = __shfl_sync(0xffffffffu, tid >> 5, 0), lane = tid & 31;
  const int cl = blockIdx.x >> 1, kh = blockIdx.x & 1;
  const int n0 = cl < 4 ? cl : (cl < 36 ? (cl - 4) >> 3 : (cl - 36) / 7);
  const int m0 = cl < 4 ? 15 : (cl < 36 ? (cl - 4) & 7 : cl - 28 - 7 * n0);
  const int n = MAP == 0 ? n0 : (MAP == 1 ? (m0 & 3) : ((n0 & 1) | ((m0 & 1) << 1)));
  const int m = MAP == 0 ? m0 : (MAP == 1 ? ((m0 & 12) | n0) : ((m0 & 14) | (n0 >> 1)));
  const int j = kh * 4 + n, bid = m * 8 + n * 2 + kh;

  const int c64 = 224 * j + (j & 1) * 32;
  if (warp < 8) {
    asm volatile("setmaxnreg.inc.sync.aligned.u32 208;");
    const int wg = warp >> 2, w4 = warp & 3, g = lane >> 2, t = lane & 3;
    const int rh = wg ^ kh ^ 1;
    const int p = j & 1, r = (j >> 1) & 1, hh = j >> 2;
    const uint32_t epoch = ld_relaxed(&g_ep[bid]);
    if ((tid & 127) == 0) PROF(wg, 30);
#pragma unroll 1
    for (int it = tid; it < 392; it += 256) {
      const int kc = it / 28, sg = it - kc * 28;
      const int k = 2 * (28 * hh + sg) + r;
      const float kf = (float)k * (-6.283185307179586f / 448.0f), a0 = (float)(16 * kc + p) * kf;
      uint32_t c[4], s[4];
#pragma unroll
      for (int q = 0; q < 4; q++) {
        const float a1 = fmaf((float)(2 * q), kf, a0), a2 = fmaf((float)(2 * q + 8), kf, a0);
        c[q] = pack_bf16(__cosf(a1), __cosf(a2)); s[q] = pack_bf16(__sinf(a1), __sinf(a2));
        if (k == 0) s[q] = ((q ^ p) & 1) ? 0xBF80BF80u : 0x3F803F80u;
      }
      const uint32_t a = sb + 5 * SLOT + (kc * 56 + 2 * sg) * 16;
      sts128(a, c[0], c[1], c[2], c[3]);
      sts128(a + 16, s[0], s[1], s[2], s[3]);
    }
    if ((tid & 127) == 0) PROF(wg, 31);
    fence_async_smem();
    bar_sync<0, NTHREADS - 64>();
    asm volatile("barrier.cluster.arrive.relaxed.aligned;" ::: "memory");
    if ((tid & 127) == 0) PROF(wg, 1);

    uint32_t xa[28][4];
    {
      const uint32_t xb = sb + OFF_PQ + wg * HALF_XR + (w4 * 16 + (lane & 15)) * 128;
      mbar_wait(bars + (B_XFULL + wg) * 8, 0);
      if (XPRI && wg) mbar_wait(bars + B_XFREE * 8, 0);
      if ((tid & 127) == 0) PROF(wg, 2);
#pragma unroll
      for (int kb = 0; kb < 7; kb++) {
#pragma unroll
        for (int kk = 0; kk < 4; kk++) {
          uint32_t a = xb + kb * 8192 + (((2 * kk + (lane >> 4)) ^ (lane & 7)) << 4);
          asm volatile("ldmatrix.sync.aligned.m8n8.x4.shared.b16 {%0,%1,%2,%3}, [%4];"
                       : "=r"(xa[kb * 4 + kk][0]), "=r"(xa[kb * 4 + kk][1]), "=r"(xa[kb * 4 + kk][2]), "=r"(xa[kb * 4 + kk][3]) : "r"(a) : "memory");
        }
      }
    }
    {
      uint32_t ad[7][4];
      const uint32_t sel = p ? 0x7632 : 0x5410;
      const uint32_t sgn = r ? 0xBF80BF80u : 0x3F803F80u;
#pragma unroll
      for (int jj = 0; jj < 7; jj++) {
#pragma unroll
        for (int i = 0; i < 4; i++) {
          int ks = 2 * jj + (i >> 1), rr = i & 1;
          uint32_t lo = __byte_perm(xa[ks][rr], xa[ks][rr + 2], sel);
          uint32_t hi = __byte_perm(xa[ks + 14][rr], xa[ks + 14][rr + 2], sel);
          asm("fma.rn.bf16x2 %0, %1, %2, %3;" : "=r"(ad[jj][i]) : "r"(hi), "r"(sgn), "r"(lo));
        }
      }
      __syncwarp();
      if (lane == 0) mbar_arrive(bars + (B_XFREE + wg) * 8);
      float acc[28];
      wg_fence();
      uint64_t db = mkdesc(sb + 5 * SLOT, 896, 128, 0);
#pragma unroll
      for (int jj = 0; jj < 7; jj++) wgmma_rs_56<0>(acc, ad[jj], db + jj * 112, jj != 0);
      wg_commit();
      wg_wait<0>(); keep(acc);
      if (lane == 0) mbar_arrive(bars + (B_EMPTY + 5) * 8);
      uint32_t* xc = g_Xc + (size_t)((2 * (28 * hh + t) + r) * 2 + p) * S_ + m * 128 + rh * 64 + w4 * 16 + g;
#pragma unroll
      for (int i = 0; i < 7; i++) {
        xc[i * 16 * S_] = pack_bf16(acc[4 * i], acc[4 * i + 1]);
        xc[i * 16 * S_ + 8] = pack_bf16(acc[4 * i + 2], acc[4 * i + 3]);
      }
      __syncwarp();
      if (lane == 0) mbar_arrive(bars + B_PUBX * 8);
    }
    if ((tid & 127) == 0) PROF(wg, 3);
    const uint32_t tag = ~epoch & 1;
    unsigned char* const hbase = g_H + (size_t)(m * 2 + kh) * (56 * 4096) + rh * 2048 + (tid & 127) * 16;
#pragma unroll 1
    for (int u = 0; u < 3; u++) {
      float acc[64];
      if (wg == 1) { if (u & 1) bar_sync<6, 256>(); else bar_sync<2, 256>(); }
      const uint32_t sbu = opaque(sb);
#pragma unroll
      for (int kb = 0; kb < 7; kb++) {
        mbar_wait(sbu + OFF_BAR + (B_FULL + kb) * 8, u & 1);
        wg_fence();
        uint64_t db = mkdesc(sbu + kb * SLOT, 8192, 1024, 1);
#pragma unroll
        for (int kk = 0; kk < 4; kk++) wgmma_rs_128<1>(acc, xa[kb * 4 + kk], db + kk * 128, (kb | kk) != 0);
        wg_commit();
        if (kb == LEAD1 && wg == 0) { if (u & 1) bar_arrive<6, 256>(); else bar_arrive<2, 256>(); }
        if (kb > 0) { wg_wait<1>(); if (lane == 0) mbar_arrive(sbu + OFF_BAR + (B_EMPTY + kb - 1) * 8); }
      }
      wg_wait<0>(); keep(acc);
      if (lane == 0) mbar_arrive(sbu + OFF_BAR + (B_EMPTY + 6) * 8);
      if ((tid & 127) == 0) PROF(wg, 4 + 2 * u);
      h_epilogue<8>(acc, hbase + (u * 16 + n * 4) * 4096, tag);
      if ((tid & 127) == 0) PROF(wg, 5 + 2 * u);
    }
    {
      float acc[32];
      if (wg == 1) bar_sync<6, 256>();
      const uint32_t sbu = opaque(sb);
#pragma unroll
      for (int it = 0; it < 4; it++) {
        mbar_wait(sbu + OFF_BAR + (B_FULL + it) * 8, 1);
        wg_fence();
        uint64_t db = mkdesc(sbu + it * SLOT, 8192, 512, 2);
#pragma unroll
        for (int kk = 0; kk < 8; kk++) if (it * 8 + kk < 28) wgmma_rs_64<1>(acc, xa[it * 8 + kk], db + kk * 64, (it | kk) != 0);
        wg_commit();
        if (it == 2 && wg == 0) bar_arrive<6, 256>();
        if (it > 0) {
          wg_wait<1>();
          if (lane == 0) mbar_arrive(sbu + OFF_BAR + (B_EMPTY + it - 1) * 8);
#pragma unroll
          for (int i = it * 8 - 8; i < it * 8; i++) if (i < 4 * LA2) LDH(xa[i], hbase + i * 4096);
        }
      }
      wg_wait<0>(); keep(acc);
      if (lane == 0) mbar_arrive(sbu + OFF_BAR + (B_EMPTY + 3) * 8);
      if ((tid & 127) == 0) PROF(wg, 10);
      h_epilogue<4>(acc, hbase + (48 + n * 2) * 4096, tag);
    }
    asm volatile("barrier.cluster.wait.aligned;" ::: "memory");
    if ((tid & 127) == 0) PROF(wg, 11);

    float acc[56];
    if (wg == 1) bar_sync<2, 256>();
#pragma unroll 1
    for (int it = 0; it < 2; it++) {
#pragma unroll
      for (int e = 0; e < 7; e++) {
        if ((tid & 127) == 0) PROF(wg, 16 + it * 7 + e);
        const bool inr = e < 4 && it == 0;
        if (e >= 4 || it == 1) mbar_wait(bars + (B_FULL + e) * 8, e < 4 ? 0 : it ^ 1);
        else if (e == 0) mbar_wait(bars + B_RFULL * 8, 1);
        frag_ready(xa[e * 4], xa[e * 4 + 1], xa[e * 4 + 2], xa[e * 4 + 3], hbase + (it * 7 + e) * 16384, tag);
        wg_fence();
        const uint64_t db = mkdesc(inr ? sb + OFF_R + e * 14336 : sb + e * SLOT, 1792, 128, 0);
#pragma unroll
        for (int kk = 0; kk < 4; kk++) wgmma_rs_112<1>(acc, xa[e * 4 + kk], db + kk * 224, (e | kk) ? 1 : it);
        wg_commit();
        if (e == 1 && it == 0 && wg == 0) bar_arrive<2, 256>();
        if (it == 0 || e + LA2 < 7) {
          const int nb = it * 7 + e + LA2;
#pragma unroll
          for (int kk = 0; kk < 4; kk++) LDH(xa[((e + LA2) % 7) * 4 + kk], hbase + (nb * 4 + kk) * 4096);
        }
        wg_wait<1>();
        if (lane == 0) {
          if (it == 0 ? e >= 5 : e <= 2) mbar_arrive(bars + (B_EMPTY + (e + 6) % 7) * 8);
          if (e == 4 && it == 0) {
            mbar_arrive(bars + B_LFREE * 8);
            asm volatile("{\n.reg .b32 ra;\nmapa.shared::cluster.u32 ra, %0, %1;\nmbarrier.arrive.relaxed.cluster.shared::cluster.b64 _, [ra];\n}"
                         :: "r"(bars + B_RFREE * 8), "r"(kh ^ 1) : "memory");
          }
        }
      }
    }
    const int t128 = tid & 127;
    wg_wait<0>(); keep(acc);
    if (wg == 0) {
      if (t128 == 0) PROF(wg, 12);
      mbar_wait_cluster(bars + B_RFREE * 8, 0);
      uint32_t rdst, rbar;
      asm volatile("mapa.shared::cluster.u32 %0, %1, %2;" : "=r"(rdst) : "r"(sb + OFF_R + t128 * 16), "r"(kh ^ 1));
      asm volatile("mapa.shared::cluster.u32 %0, %1, %2;" : "=r"(rbar) : "r"(bars + B_RECV * 8), "r"(kh ^ 1));
#pragma unroll
      for (int i = 0; i < 14; i++)
        asm volatile("st.async.weak.shared::cluster.mbarrier::complete_tx::bytes.v4.f32 [%0], {%1,%2,%3,%4}, [%5];"
                     :: "r"(rdst + i * 2048), "f"(acc[4 * i]), "f"(acc[4 * i + 1]), "f"(acc[4 * i + 2]), "f"(acc[4 * i + 3]), "r"(rbar) : "memory");
    } else {
      float spec[2][28];
      if (t128 == 0) PROF(wg, 12);
      mbar_wait(bars + B_PQFULL * 8, 0);
      if (t128 == 0) { PROF(wg, 13); g_ep[bid] = epoch + 1; }
#pragma unroll
      for (int i = 0; i < 4; i++) {
        if (i == 0) mbar_wait(bars + B_GFULL * 8, 0);
        if (i >= 2) mbar_wait(bars + (B_FULL + i - 2) * 8, 1);
        wg_fence();
        const uint64_t da = mkdesc(sb + OFF_PQ + i * 14336, 1024, 1024, 1);
        const uint64_t db = mkdesc(i < 2 ? sb + OFF_R + 28672 + i * (G_IMG / 2) : sb + (i - 2) * SLOT, 896, 128, 0);
#pragma unroll
        for (int kk = 0; kk < 7; kk++) wgmma_ss_56<1, 0>(spec[i >> 1], da + kk * 128, db + kk * 112, ((i & 1) | kk) != 0);
        wg_commit();
      }
      const float* gs = reinterpret_cast<const float*>(smem + OFF_G) + w4 * 16 + g;
      const float o0 = bf16_round(1.0f - gs[0]), o1 = bf16_round(1.0f - gs[8]);
      const float g0 = gs[0] * (1.0f / (float)(S_ * D_)), g1 = gs[8] * (1.0f / (float)(S_ * D_));
      wg_wait<0>(); keep(spec[0]); keep(spec[1]);
      if (t128 == 0) PROF(wg, 14);
      mbar_wait_cluster(bars + B_RECV * 8, 0);
      if (t128 == 0) PROF(wg, 0);
      float4 o[14];
#pragma unroll
      for (int i = 0; i < 14; i++) o[i] = lds128f(sb + OFF_R + t128 * 16 + i * 2048);
      bar_sync<5, 128>();
      const uint32_t st = sb + OFF_PQ + w4 * 3840;
#pragma unroll
      for (int i = 0; i < 7; i++) {
        uint32_t pk[4];
#pragma unroll
        for (int e = 0; e < 2; e++) {
          const int c = 2 * i + e, si = i * 4 + e;
          pk[2 * e] = pack_bf16(fmaf(acc[4 * c] + o[c].x, o0, g0 * spec[0][si]), fmaf(acc[4 * c + 1] + o[c].y, o0, g0 * spec[1][si]));
          pk[2 * e + 1] = pack_bf16(fmaf(acc[4 * c + 2] + o[c].z, o1, g1 * spec[0][si + 2]), fmaf(acc[4 * c + 3] + o[c].w, o1, g1 * spec[1][si + 2]));
        }
        asm volatile("stmatrix.sync.aligned.m8n8.x4.shared.b16 [%0], {%1,%2,%3,%4};"
                     :: "r"(st + (lane & 15) * 240 + (lane >> 4) * 16 + i * 32), "r"(pk[0]), "r"(pk[1]), "r"(pk[2]), "r"(pk[3]) : "memory");
      }
      __syncwarp();
      if (lane < 28) {
        const int r2 = lane >= 14, cc = lane - r2 * 14;
        unsigned char* ob = reinterpret_cast<unsigned char*>(out) + (size_t)(m * 128 + kh * 64 + w4 * 16 + r2) * (D_ * 2) + n * 224 + cc * 16;
        float4 v[8];
#pragma unroll
        for (int i = 0; i < 8; i++) v[i] = lds128f(st + r2 * 240 + cc * 16 + i * 480);
#pragma unroll
        for (int i = 0; i < 8; i++) stg128(ob + i * (D_ * 4), __float_as_uint(v[i].x), __float_as_uint(v[i].y), __float_as_uint(v[i].z), __float_as_uint(v[i].w));
      }
    }
    if (t128 == 0) { PROF(wg, 15); if (wg) { PROFG(4, 30); PROF(4, 31); } }
  } else if (warp < 12) {
    asm volatile("setmaxnreg.dec.sync.aligned.u32 72;");
    const int t = tid - 256;
    const int k = bid;
    if (t == 0) PROF(2, 0);
    uint4 gv[7];
#pragma unroll
    for (int i = 0; i < 7; i++) gv[i] = ldg128(reinterpret_cast<const uint4*>(gate_w) + i * 8 + (t & 7));
    if (t < 98) {
      int cid = m * 98 + t, kc = cid / 56, nn = cid - kc * 56;
      int d = 112 * n + 8 * (2 * (nn >> 3) + (nn & 1)) + (nn & 6) + kh;
      int dr = d > 224 ? d - 448 : d;
      const float df = (float)dr * (-6.283185307179586f / 448.0f);
      uint32_t pk[4];
#pragma unroll
      for (int e = 0; e < 4; e++) {
        const float a = (float)(4 * kc + e) * df;
        pk[e] = pack_bf16(2.0f * __cosf(a), 2.0f * __sinf(a));
      }
      if (kc == 0) pk[0] = (((d >> 1) ^ kh) & 1) ? 0xBF803F80u : 0x3F803F80u;
      stg128(g_G + (size_t)(n * 2 + kh) * G_IMG + cid * 16, pk[0], pk[1], pk[2], pk[3]);
    }
    bar_sync<0, NTHREADS - 64>();
    asm volatile("barrier.cluster.arrive.relaxed.aligned;" ::: "memory");
    {
      const int row = n * 16 + (t >> 3), l8 = t & 7;
      mbar_wait(bars + (B_XFULL + 1) * 8, 0);
      float sum = 0.f;
#pragma unroll
      for (int i = 0; i < 7; i++) {
        const uint4 a = lds128(sb + OFF_R + i * 8192 + row * 128 + ((l8 ^ (row & 7)) << 4));
        const uint32_t aa[4] = {a.x, a.y, a.z, a.w}, bb[4] = {gv[i].x, gv[i].y, gv[i].z, gv[i].w};
#pragma unroll
        for (int e = 0; e < 4; e++) {
          const uint32_t pr = as_u(__hmul2(as_b2(aa[e]), as_b2(bb[e])));
          sum += bf_lo(pr) + bf_hi(pr);
        }
      }
      sum += __shfl_xor_sync(0xffffffffu, sum, 1); sum += __shfl_xor_sync(0xffffffffu, sum, 2); sum += __shfl_xor_sync(0xffffffffu, sum, 4);
      if (lane == 0) mbar_arrive(bars + (B_XFREE + 1) * 8);
      if (l8 == 0) g_gate[m * 128 + kh * 64 + row] = bf16_round(__fdividef(1.0f, 1.0f + __expf(-bf16_round(sum))));
    }
    if (t == 0) PROF(2, 11);
    mbar_wait(bars + B_PIN * 8, 0);
    if (t == 0) PROF(2, 4);
    {
      const uint32_t wa = sb + 6 * SLOT + (((t & 7) - bid) & 7) * 450 + (t >> 3) * 2, wc = wa + 448 - (t >> 3) * 4;
      uint2* dst = g_Wt + (t >> 3) * S_ + 16 * bid + 2 * (t & 7);
#pragma unroll 1
      for (int h = 0; h < 2; h++) {
        uint32_t w[4][8];
#pragma unroll
        for (int i = 0; i < 4; i++) {
#pragma unroll
          for (int e = 0; e < 4; e++) { w[i][2 * e] = lds16(wa + h * 128 + i * 32 + e * 3600); w[i][2 * e + 1] = lds16(wc - h * 128 - i * 32 + e * 3600); }
        }
        if (h == 1) {
          const uint32_t z = __reduce_or_sync(0xffffffffu, w[3][7] | w[3][6]) >> 16;
          if (lane < 2) mbar_arrive(bars + (B_EMPTY + 6) * 8 + z);
        }
#pragma unroll
        for (int i = 0; i < 4; i++)
          if (i < 3 || h == 0 || t < 8)
            stg128(dst + (h * 64 + i * 16) * S_, __byte_perm(w[i][0], w[i][1], 0x5410), __byte_perm(w[i][4], w[i][5], 0x5410), __byte_perm(w[i][2], w[i][3], 0x5410), __byte_perm(w[i][6], w[i][7], 0x5410));
      }
    }
    __syncwarp();
    if (lane == 0) mbar_arrive(bars + B_PUBW * 8);
    if (t == 0) PROF(2, 6);
    mbar_wait(bars + B_XFREE * 8, 0);
    if (k < 113) {
      const float u = -6.283185307179586f / 2048.0f, t2 = (float)(2 * t) * u, rr = (float)(t >> 4) * u;
#pragma unroll 1
      for (int i = 0; i < 4; i++) {
        const float q = (float)(2 * i), l = (float)((t & 15) + 64 * i);
        sts128(sb + OFF_TW + i * 2048 + t * 16, cis(t2 * q), cis((t2 + u) * q), cis(t2 * (q + 1.0f)), cis((t2 + u) * (q + 1.0f)));
        sts128(sb + OFF_TW + 8192 + i * 2048 + t * 16, cis(rr * l), cis(rr * (l + 16.0f)), cis(rr * (l + 32.0f)), cis(rr * (l + 48.0f)));
      }
      const float l = (float)((t >> 1) & 15) * (8.0f * u), jj = (float)((t >> 5) * 4 + (t & 1) * 2);
      sts64(sb + OFF_TW + 16384 + t * 8, cis(l * jj), cis(l * (jj + 1.0f)));
    }
    if (t == 0) PROF(2, 9);
    mbar_wait(bars + B_RFULL * 8, 0);
    if (t < 112) {
      const int js = bid >> 4, nn = (t >> 1) / 14, cc = (t >> 1) - nn * 14;
      unsigned char* wdst = g_Wd + (size_t)((js >> 2) * 4 + nn) * WD_IMG + cc * 128 + (t & 1) * 16;
      uint4 v[7];
#pragma unroll
      for (int i = 0; i < 7; i++) v[i] = lds128(sb + OFF_R + i * 1792 + (t & 1) * 896 + (t >> 1) * 16);
#pragma unroll
      for (int i = 0; i < 7; i++) {
        int col = 14 * (bid & 15) + 2 * i - (js & 1) * 32;
        if (col < 0) col += 224;
        const int kpos = col < 192 ? (col >> 6) * 256 + (js & 3) * 64 + (col & 63) : 576 + (js & 3) * 32 + col;
        stg128(wdst + (kpos >> 3) * 1792 + (kpos & 7) * 16, v[i].x, v[i].y, v[i].z, v[i].w);
      }
    }
    __syncwarp();
    if (lane == 0) mbar_arrive(bars + B_PUBD * 8);
    bar_sync<3, 128>();
    if (k < 113) {
      if (t == 0) PROF(2, 2);
      mbar_wait(bars + B_XCFULL * 8, 0);
      if (t == 0) PROF(2, 3);
      c2 v[16];
      const uint32_t se = k == 0 ? 0x4410 : (k == 112 ? 0x4432 : 0x3210), so = k == 0 ? 0x4410 : (k == 112 ? 0x3244 : 0x3210);
#pragma unroll
      for (int jj = 0; jj < 8; jj++) {
        const uint2 e2 = lds64(sb + OFF_EXCH + jj * 1024 + t * 8), o2 = lds64(sb + OFF_EXCH + 8192 + jj * 1024 + t * 8);
#pragma unroll
        for (int h = 0; h < 2; h++) {
          const b2 e = as_b2(__byte_perm(h ? e2.y : e2.x, 0, se)), o = as_b2(__byte_perm(h ? o2.y : o2.x, 0, so));
          const uint32_t s = as_u(__hadd2(e, o)), d = as_u(__hsub2(e, o)) ^ 0x80000000u;
          v[2 * jj + h] = mk(as_b2(__byte_perm(s, d, 0x5410)), as_b2(__byte_perm(s, d, 0x7632)));
        }
      }
      if (t == 0) PROF(2, 12);
      columns(v, sb, t);
      if (t == 0) PROF(2, 14);
      const int pre = (k == 112) ? 1 : 2 * k, pim = (k == 112) ? 1 : 2 * k + 1;
      uint32_t* pq = reinterpret_cast<uint32_t*>(g_PQ) + (t >> 5) * 14336;
      uint32_t* pr = pq + pre * 32 + ((((lane >> 2) ^ pre) & 7) << 2) + (lane & 3);
      uint32_t* pi = pq + pim * 32 + ((((lane >> 2) ^ pim) & 7) << 2) + (lane & 3);
#pragma unroll
      for (int jj = 0; jj < 8; jj++) {
        const b2 ar = as_b2(__byte_perm(as_u(v[2 * jj].y), as_u(v[2 * jj + 1].y), 0x5410)), br = as_b2(__byte_perm(as_u(v[2 * jj].y), as_u(v[2 * jj + 1].y), 0x7632));
        const b2 ai = as_b2(__byte_perm(as_u(v[2 * jj].x), as_u(v[2 * jj + 1].x), 0x5410)), bi = as_b2(__byte_perm(as_u(v[2 * jj].x), as_u(v[2 * jj + 1].x), 0x7632));
        pr[jj * 57344] = as_u(__hadd2(ar, br));
        if (k != 112) pr[jj * 57344 + 7168] = as_u(__hsub2(ar, br));
        if (k != 0) pi[jj * 57344 + 7168] = as_u(__hadd2(ai, bi));
        if (k != 0 && k != 112) pi[jj * 57344] = as_u(__hsub2(ai, bi));
      }
      fence_async_smem();
    }
    bar_sync<3, 128>();
    if (t == 0) { PROF(2, 5); red_release(&g_cnt[5 * 32]); PROF(2, 7); }
    __syncwarp();
    asm volatile("barrier.cluster.wait.aligned;" ::: "memory");
  } else {
    asm volatile("setmaxnreg.dec.sync.aligned.u32 24;");
    if (warp == 12) {
      if (elect()) {
        mbar_init(bars + B_XFULL * 8, 1); mbar_init(bars + (B_XFULL + 1) * 8, 1);
        fence_async_smem();
#pragma unroll
        for (int w = 0; w < 2; w++) {
          mbar_expect(bars + (B_XFULL + w) * 8, HALF_XR);
          tma3d(sb + OFF_PQ + w * HALF_XR, &tm_x, 0, m * 128 + (w ^ kh ^ 1) * 64, 0, bars + (B_XFULL + w) * 8);
        }
        PROF(3, 3);
#pragma unroll
        for (int i = 0; i < NSLOT; i++) mbar_init(bars + (B_FULL + i) * 8, 1);
        mbar_init(bars + B_PIN * 8, 1);
        fence_async_smem();
      }
      bar_arrive<0, NTHREADS - 64>();
#pragma unroll 1
      for (int i = 0; i < 5; i++) {
        if (elect()) {
          if (i == WPOS) {
            mbar_expect(bars + B_PIN * 8, 14400);
            bulk_g2s(sb + 6 * SLOT, reinterpret_cast<const unsigned char*>(w_r) + bid * 7200, 7200, bars + B_PIN * 8);
            bulk_g2s(sb + 6 * SLOT + 7200, reinterpret_cast<const unsigned char*>(w_i) + bid * 7200, 7200, bars + B_PIN * 8);
          }
          const uint32_t fb = bars + (B_FULL + i) * 8;
          mbar_expect(fb, SLOT);
          tma2d(sb + i * SLOT, &tm_g, c64, i * 64, fb);
          tma2d(sb + i * SLOT + 8192, &tm_u, c64, i * 64, fb);
          PROF(3, 4 + i);
        }
      }
      if (elect()) {
        prefetch_tma2d(&tm_g, c64, 320); prefetch_tma2d(&tm_u, c64, 320);
        prefetch_tma2d(&tm_g, c64, 384); prefetch_tma2d(&tm_u, c64, 384);
      }
    } else if (warp == 14) {
      if (elect()) {
#pragma unroll
        for (int i = B_EMPTY; i < B_END; i++)
          if (i < B_XFULL || i >= B_XFREE) mbar_init(bars + i * 8, i >= B_PQFULL ? 1 : ((i == B_XFREE || i >= B_PUBW) ? 4 : 8));
        asm volatile("fence.mbarrier_init.release.cluster;" ::: "memory");
        fence_async_smem();
        mbar_expect(bars + B_RECV * 8, 64 * 112 * 4);
      }
      bar_arrive<0, NTHREADS - 64>();
    }
    const uint32_t epoch = ld_relaxed(&g_ep[bid]);
    if (warp == 13 && lane == 0) { PROFG(4, 0); PROF(4, 1); }
    bar_sync<1, 128>();
    asm volatile("barrier.cluster.arrive.relaxed.aligned;" ::: "memory");
    if (warp == 12) {
      int slot = 5, ph = 1;
      auto wait_slot = [&]() { mbar_wait(bars + (B_EMPTY + slot) * 8, ph ^ (slot >= 5)); };
      auto adv = [&]() { if (++slot == NSLOT) { slot = 0; ph ^= 1; } };
      const int c32 = 224 * j + ((j & 1) ? 0 : 192);
#pragma unroll 1
      for (int i = 5; i < 25; i++) {
        wait_slot();
        if (elect()) {
          const uint32_t dst = sb + slot * SLOT, fb = bars + (B_FULL + slot) * 8;
          const bool last = i >= 21;
          const int cc = last ? c32 : c64 + 64 * (i / 7), rr = last ? slot * 128 : slot * 64;
          mbar_expect(fb, SLOT);
          tma2d(dst, last ? &tm_g32 : &tm_g, cc, rr, fb);
          tma2d(dst + 8192, last ? &tm_u32 : &tm_u, cc, rr, fb);
        }
        adv();
      }
      if (lane == 0) PROF(3, 0);
      mbar_wait(bars + B_PREP * 8, 0);
      if (lane == 0) PROF(3, 1);
#pragma unroll 1
      for (int i = 4; i < 16; i++) {
        if (lane == 0) PROF(3, 16 + i);
        wait_slot();
        if (elect()) {
          const int bytes = i < 14 ? 14336 : G_IMG / 2;
          const unsigned char* src = i < 14 ? g_Wd + (size_t)j * WD_IMG + i * 14336 : g_G + (size_t)(n * 4 + i - 12) * (G_IMG / 2);
          mbar_expect(bars + (B_FULL + slot) * 8, bytes);
          bulk_g2s(sb + slot * SLOT, src, bytes, bars + (B_FULL + slot) * 8);
        }
        adv();
      }
      if (lane == 0) PROF(3, 2);
    } else if (warp == 13) {
#pragma unroll 1
      for (int u = 0; u < 3; u++) {
        mbar_wait(bars + (u ? B_PUBW - 1 + u : B_PUBX) * 8, 0);
        if (lane == 0) { PROF(4, 8 + u); red_release(&g_cnt[(u ? 8 - 2 * u : j >> 1) * 32]); PROF(4, 12 + u); }
        __syncwarp();
      }
      mbar_wait(bars + B_LFREE * 8, 0);
      if (elect()) {
        mbar_expect(bars + B_GFULL * 8, G_IMG);
        bulk_g2s(sb + OFF_R + 28672, g_G + (size_t)(n * 2) * G_IMG, G_IMG, bars + B_GFULL * 8);
      }
    } else if (warp == 14) {
#pragma unroll 1
      for (int u = 0; u < 2; u++) {
        wait_ge(&g_cnt[(6 - 2 * u) * 32], (epoch + 1) * 128);
        fence_async_global();
        if (lane == 0) { mbar_arrive(bars + (B_PREPW - u) * 8); PROF(5, 9 - u); }
      }
    } else {
      mbar_wait(bars + B_XFREE * 8, 0);
      if (elect()) {
        prefetch_l2(reinterpret_cast<const unsigned char*>(w_gate) + bid * 12544, 12544);
        prefetch_l2(reinterpret_cast<const unsigned char*>(w_up) + bid * 12544, 12544);
      }
      mbar_wait(bars + (B_XFREE + 1) * 8, 0);
      if (elect()) {
        mbar_expect(bars + B_RFULL * 8, 12544);
        bulk_g2s(sb + OFF_R, reinterpret_cast<const unsigned char*>(w_down) + bid * 12544, 12544, bars + B_RFULL * 8);
      }
      if (bid < 113) {
        const int sl = (bid == 112) ? 0 : bid;
        wait_ge(&g_cnt[((sl & 1) + 2 * ((sl >> 1) / 28)) * 32], (epoch + 1) * 32);
        fence_async_global();
        if (elect()) {
          PROF(5, 16);
          mbar_expect(bars + B_XCFULL * 8, 16384);
          bulk_g2s(sb + OFF_EXCH, g_Xc + sl * 2 * S_, 16384, bars + B_XCFULL * 8);
        }
        mbar_wait(bars + B_PREPW * 8, 0);
        if (elect()) {
          mbar_expect(bars + B_WFULL * 8, 16384);
          bulk_g2s(sb + OFF_WS, g_Wt + bid * S_, 16384, bars + B_WFULL * 8);
          PROF(5, 17);
        }
      }
      mbar_wait(bars + B_PREP * 8, 0);
      if (elect()) {
        mbar_expect(bars + B_RFULL * 8, HALF_XR);
        bulk_g2s(sb + OFF_R, g_Wd + (size_t)j * WD_IMG, HALF_XR, bars + B_RFULL * 8);
        PROF(5, 19);
      }
      wait_ge(&g_cnt[5 * 32], (epoch + 1) * 128);
      fence_async_global();
      if (elect()) {
        PROF(5, 18);
        mbar_expect(bars + B_PQFULL * 8, HALF_XR + 256);
        const unsigned char* src = g_PQ + (size_t)(m * 2 + kh) * HALF_XR;
        bulk_g2s(sb + OFF_PQ, src, 28672, bars + B_PQFULL * 8);
        bulk_g2s(sb + OFF_PQ + 28672, src + 28672, 28672, bars + B_PQFULL * 8);
        bulk_g2s(sb + OFF_G, g_gate + m * 128 + kh * 64, 256, bars + B_PQFULL * 8);
      }
    }
    __syncwarp();
    asm volatile("barrier.cluster.wait.aligned;" ::: "memory");
  }
}

typedef CUresult (*EncodeFn)(CUtensorMap*, CUtensorMapDataType, cuuint32_t, void*, const cuuint64_t*, const cuuint64_t*, const cuuint32_t*,
                             const cuuint32_t*, CUtensorMapInterleave, CUtensorMapSwizzle, CUtensorMapL2promotion, CUtensorMapFloatOOBfill);

void make_map(EncodeFn enc, CUtensorMap* tm, const void* base, int cols, int rows, int bc, int br, CUtensorMapSwizzle sw) {
  cuuint64_t gd[2] = {(cuuint64_t)cols, (cuuint64_t)rows};
  cuuint64_t gs[1] = {(cuuint64_t)cols * 2};
  cuuint32_t bd[2] = {(cuuint32_t)bc, (cuuint32_t)br};
  cuuint32_t es[2] = {1, 1};
  enc(tm, CU_TENSOR_MAP_DATA_TYPE_BFLOAT16, 2, const_cast<void*>(base), gd, gs, bd, es, CU_TENSOR_MAP_INTERLEAVE_NONE, sw,
      CU_TENSOR_MAP_L2_PROMOTION_L2_128B, CU_TENSOR_MAP_FLOAT_OOB_FILL_NONE);
}

}

extern "C" void kernel_launch(void* const* d_in, const int* in_sizes, int n_in, void* d_out, int out_size) {
  (void)in_sizes; (void)n_in; (void)out_size;
  const __nv_bfloat16* x = (const __nv_bfloat16*)d_in[0];
  const __nv_bfloat16* w_r = (const __nv_bfloat16*)d_in[1];
  const __nv_bfloat16* w_i = (const __nv_bfloat16*)d_in[2];
  const __nv_bfloat16* w_gate = (const __nv_bfloat16*)d_in[4];
  const __nv_bfloat16* w_up = (const __nv_bfloat16*)d_in[5];
  const __nv_bfloat16* w_down = (const __nv_bfloat16*)d_in[6];
  const __nv_bfloat16* gate_w = (const __nv_bfloat16*)d_in[7];
  static EncodeFn enc = nullptr;
  static bool ok = false;
  if (!enc) {
    cudaDriverEntryPointQueryResult qr;
    cudaGetDriverEntryPoint("cuTensorMapEncodeTiled", (void**)&enc, cudaEnableDefault, &qr);
    cudaFuncSetAttribute(fused_kernel, cudaFuncAttributeMaxDynamicSharedMemorySize, SMEM_BYTES);
    cudaFuncAttributes fa;
    cudaFuncGetAttributes(&fa, fused_kernel);
    ok = (fa.numRegs == 128);
  }
  if (!ok) return;
  CUtensorMap tx, tg, tu, tg32, tu32;
  {
    cuuint64_t gd[3] = {64, (cuuint64_t)S_, 7};
    cuuint64_t gs[2] = {(cuuint64_t)D_ * 2, 128};
    cuuint32_t bd[3] = {64, 64, 7};
    cuuint32_t es[3] = {1, 1, 1};
    enc(&tx, CU_TENSOR_MAP_DATA_TYPE_BFLOAT16, 3, const_cast<__nv_bfloat16*>(x), gd, gs, bd, es, CU_TENSOR_MAP_INTERLEAVE_NONE, CU_TENSOR_MAP_SWIZZLE_128B,
        CU_TENSOR_MAP_L2_PROMOTION_L2_128B, CU_TENSOR_MAP_FLOAT_OOB_FILL_NONE);
  }
  make_map(enc, &tg, w_gate, F_, D_, 64, 64, CU_TENSOR_MAP_SWIZZLE_128B);
  make_map(enc, &tu, w_up, F_, D_, 64, 64, CU_TENSOR_MAP_SWIZZLE_128B);
  make_map(enc, &tg32, w_gate, F_, D_, 32, 128, CU_TENSOR_MAP_SWIZZLE_64B);
  make_map(enc, &tu32, w_up, F_, D_, 32, 128, CU_TENSOR_MAP_SWIZZLE_64B);
  fused_kernel<<<128, NTHREADS, SMEM_BYTES>>>(tx, tg, tu, tg32, tu32, w_r, w_i, w_gate, w_up, w_down, gate_w, (__nv_bfloat16*)d_out);
}
```

```cpp
#include <cuda_runtime.h>
#include <cuda_bf16.h>
#include <cuda.h>
#include <stdint.h>

namespace {

constexpr int S_ = 2048, D_ = 448, F_ = 1792;
constexpr int NTHREADS = 512;
constexpr int SLOT = 16384, NSLOT = 7;
constexpr int HALF_XR = 57344;
constexpr int OFF_PQ = NSLOT * SLOT;
constexpr int OFF_R = OFF_PQ + HALF_XR;
constexpr int OFF_EXCH = OFF_PQ;
constexpr int OFF_WS = OFF_EXCH + 18432;
constexpr int OFF_TW = OFF_WS + 16384;
constexpr int OFF_MISC = OFF_R + HALF_XR;
constexpr int OFF_G = OFF_MISC;
constexpr int OFF_BAR = OFF_MISC + 512;
constexpr int SMEM_BYTES = OFF_BAR + 512;
constexpr int B_FULL = 0, B_EMPTY = 7, B_XFULL = 14  ;
constexpr int B_XFREE = 16  , B_PUBX = 18, B_RFREE = 19, B_LFREE = 20;
constexpr int B_PUBW = 21, B_PUBD = 22;
constexpr int B_PQFULL = 23, B_RECV = 24, B_WFULL = 25, B_XCFULL = 26, B_PREP = 27, B_PREPW = 28, B_RFULL = 29, B_GFULL = 30, B_END = 31, B_PIN = 31;

constexpr int WD_IMG = 896 * 112 * 2;
constexpr int G_IMG = 224 * 56 * 2;

__device__ __align__(1024) uint32_t g_Xc[112 * 2 * S_];
__device__ __align__(1024) unsigned char g_H[32 * 56 * 4096];
__device__ __align__(1024) unsigned char g_PQ[32 * HALF_XR];
__device__ __align__(1024) unsigned char g_Wd[8 * WD_IMG];
__device__ __align__(1024) unsigned char g_G[8 * G_IMG];
__device__ __align__(1024) uint2 g_Wt[113 * S_];
__device__ __align__(1024) float g_gate[S_];
__device__ __align__(128) unsigned int g_ep[128];
__device__ __align__(128) unsigned int g_cnt[8 * 32];

#define PROF(role, idx) do {} while (0)
#define PROFG(role, idx) do {} while (0)

__device__ __forceinline__ uint32_t s2u(const void* p) { return (uint32_t)__cvta_generic_to_shared(p); }
__device__ __forceinline__ void mbar_init(uint32_t b, int c) { asm volatile("mbarrier.init.shared::cta.b64 [%0], %1;" :: "r"(b), "r"(c) : "memory"); }
__device__ __forceinline__ void mbar_expect(uint32_t b, int bytes) { asm volatile("mbarrier.arrive.expect_tx.shared::cta.b64 _, [%0], %1;" :: "r"(b), "r"(bytes) : "memory"); }
__device__ __forceinline__ void mbar_arrive(uint32_t b) { asm volatile("mbarrier.arrive.shared::cta.b64 _, [%0];" :: "r"(b) : "memory"); }
__device__ __forceinline__ void mbar_wait(uint32_t b, int ph) {
  asm volatile("{\n.reg .pred p;\n.reg .u32 c;\nmov.u32 c, 0;\nL_WAIT:\nmbarrier.try_wait.parity.shared::cta.b64 p, [%0], %1;\n@p bra.uni L_DONE;\n"
               "add.u32 c, c, 1;\nsetp.lt.u32 p, c, 4194304;\n@p bra.uni L_WAIT;\ntrap;\nL_DONE:\n}" :: "r"(b), "r"(ph) : "memory");
}
__device__ __forceinline__ void mbar_wait_cluster(uint32_t b, int ph) {
  asm volatile("{\n.reg .pred p;\n.reg .u32 c;\nmov.u32 c, 0;\nL_WAIT:\nmbarrier.try_wait.parity.acquire.cluster.shared::cta.b64 p, [%0], %1;\n@p bra.uni L_DONE;\n"
               "add.u32 c, c, 1;\nsetp.lt.u32 p, c, 4194304;\n@p bra.uni L_WAIT;\ntrap;\nL_DONE:\n}" :: "r"(b), "r"(ph) : "memory");
}
__device__ __forceinline__ uint32_t ld_acquire(const unsigned int* p) { uint32_t v; asm volatile("ld.acquire.gpu.global.u32 %0, [%1];" : "=r"(v) : "l"(p) : "memory"); return v; }
__device__ __forceinline__ uint32_t ld_relaxed(const unsigned int* p) { uint32_t v; asm volatile("ld.relaxed.gpu.global.u32 %0, [%1];" : "=r"(v) : "l"(p) : "memory"); return v; }
__device__ __forceinline__ void wait_ge(const unsigned int* p, uint32_t target) {
#pragma unroll 1
  for (int i = 0; i < (1 << 22); i++) { if ((int)(ld_acquire(p) - target) >= 0) return; }
  __trap();
}
__device__ __forceinline__ void red_release(unsigned int* p) { asm volatile("red.release.gpu.global.add.u32 [%0], 1;" :: "l"(p) : "memory"); }
__device__ __forceinline__ void red_relaxed(unsigned int* p) { asm volatile("red.relaxed.gpu.global.add.u32 [%0], 1;" :: "l"(p) : "memory"); }
__device__ __forceinline__ bool elect() { uint32_t p; asm volatile("{\n.reg .pred p;\nelect.sync _|p, 0xffffffff;\nselp.u32 %0, 1, 0, p;\n}" : "=r"(p)); return p; }
__device__ __forceinline__ void fence_async_smem() { asm volatile("fence.proxy.async.shared::cta;" ::: "memory"); }
__device__ __forceinline__ void fence_async_global() { asm volatile("fence.proxy.async.global;" ::: "memory"); }
template <int ID, int N> __device__ __forceinline__ void bar_sync() { asm volatile("bar.sync %0, %1;" :: "n"(ID), "n"(N) : "memory"); }
template <int ID, int N> __device__ __forceinline__ void bar_arrive() { asm volatile("bar.arrive %0, %1;" :: "n"(ID), "n"(N) : "memory"); }
__device__ __forceinline__ void tma2d(uint32_t dst, const CUtensorMap* tm, int c0, int c1, uint32_t bar) {
  asm volatile("cp.async.bulk.tensor.2d.shared::cluster.global.mbarrier::complete_tx::bytes [%0], [%1, {%3, %4}], [%2];"
               :: "r"(dst), "l"(tm), "r"(bar), "r"(c0), "r"(c1) : "memory");
}
__device__ __forceinline__ void tma3d(uint32_t dst, const CUtensorMap* tm, int c0, int c1, int c2, uint32_t bar) {
  asm volatile("cp.async.bulk.tensor.3d.shared::cluster.global.mbarrier::complete_tx::bytes [%0], [%1, {%3, %4, %5}], [%2];"
               :: "r"(dst), "l"(tm), "r"(bar), "r"(c0), "r"(c1), "r"(c2) : "memory");
}
__device__ __forceinline__ void bulk_g2s(uint32_t dst, const void* src, int bytes, uint32_t bar) {
  asm volatile("cp.async.bulk.shared::cluster.global.mbarrier::complete_tx::bytes [%0], [%1], %2, [%3];"
               :: "r"(dst), "l"(src), "r"(bytes), "r"(bar) : "memory");
}
__device__ __forceinline__ void prefetch_l2(const void* src, int bytes) {
  asm volatile("cp.async.bulk.prefetch.L2.global [%0], %1;" :: "l"(src), "r"(bytes) : "memory");
}
__device__ __forceinline__ void prefetch_tma2d(const CUtensorMap* tm, int c0, int c1) {
  asm volatile("cp.async.bulk.prefetch.tensor.2d.L2.global [%0, {%1, %2}];" :: "l"(tm), "r"(c0), "r"(c1) : "memory");
}
__device__ __forceinline__ uint64_t mkdesc(uint32_t addr, uint32_t lbo, uint32_t sbo, uint32_t mode) {
  return (uint64_t)((addr & 0x3FFFF) >> 4) | ((uint64_t)(lbo >> 4) << 16) | ((uint64_t)(sbo >> 4) << 32) | ((uint64_t)mode << 62);
}
__device__ __forceinline__ void wg_fence() { asm volatile("wgmma.fence.sync.aligned;" ::: "memory"); }
__device__ __forceinline__ void wg_commit() { asm volatile("wgmma.commit_group.sync.aligned;" ::: "memory"); }
template <int N> __device__ __forceinline__ void wg_wait() { asm volatile("wgmma.wait_group.sync.aligned %0;" :: "n"(N) : "memory"); }
template <int N> __device__ __forceinline__ void keep(float (&d)[N]) {
#pragma unroll
  for (int i = 0; i < N; i++) asm volatile("" : "+f"(d[i]) :: "memory");
}
__device__ __forceinline__ uint32_t pack_bf16(float lo, float hi) { uint32_t r; asm("cvt.rn.bf16x2.f32 %0, %1, %2;" : "=r"(r) : "f"(hi), "f"(lo)); return r; }
__device__ __forceinline__ float bf16_round(float v) { return __bfloat162float(__float2bfloat16_rn(v)); }
__device__ __forceinline__ void sts128(uint32_t a, uint32_t x, uint32_t y, uint32_t z, uint32_t w) { asm volatile("st.shared.v4.b32 [%0], {%1,%2,%3,%4};" :: "r"(a), "r"(x), "r"(y), "r"(z), "r"(w) : "memory"); }
__device__ __forceinline__ float4 lds128f(uint32_t a) { float4 v; asm volatile("ld.shared.v4.f32 {%0,%1,%2,%3}, [%4];" : "=f"(v.x), "=f"(v.y), "=f"(v.z), "=f"(v.w) : "r"(a) : "memory"); return v; }

__device__ __forceinline__ uint2 lds64(uint32_t a) { uint2 v; asm volatile("ld.shared.v2.b32 {%0,%1}, [%2];" : "=r"(v.x), "=r"(v.y) : "r"(a) : "memory"); return v; }
__device__ __forceinline__ float bf_lo(uint32_t w) { return __uint_as_float(w << 16); }
__device__ __forceinline__ float bf_hi(uint32_t w) { return __uint_as_float(w & 0xffff0000u); }
__device__ __forceinline__ uint32_t opaque(uint32_t v) { asm volatile("" : "+r"(v)); return v; }
__device__ __forceinline__ uint4 ldg128(const void* p) { uint4 v; asm volatile("ld.global.nc.v4.b32 {%0,%1,%2,%3}, [%4];" : "=r"(v.x), "=r"(v.y), "=r"(v.z), "=r"(v.w) : "l"(p)); return v; }
__device__ __forceinline__ void stg128(void* p, uint32_t x, uint32_t y, uint32_t z, uint32_t w) { asm volatile("st.global.v4.b32 [%0], {%1,%2,%3,%4};" :: "l"(p), "r"(x), "r"(y), "r"(z), "r"(w) : "memory"); }
__device__ __forceinline__ void stg128_l2(void* p, uint32_t x, uint32_t y, uint32_t z, uint32_t w) { asm volatile("st.relaxed.gpu.global.v4.b32 [%0], {%1,%2,%3,%4};" :: "l"(p), "r"(x), "r"(y), "r"(z), "r"(w) : "memory"); }
__device__ __forceinline__ void ldg128_na(uint32_t (&v)[4], const void* p) { asm volatile("ld.global.L1::no_allocate.v4.b32 {%0,%1,%2,%3}, [%4];" : "=r"(v[0]), "=r"(v[1]), "=r"(v[2]), "=r"(v[3]) : "l"(p) : "memory"); }
__device__ __forceinline__ void ldg128_l2(uint32_t (&v)[4], const void* p) { asm volatile("ld.relaxed.gpu.global.v4.b32 {%0,%1,%2,%3}, [%4];" : "=r"(v[0]), "=r"(v[1]), "=r"(v[2]), "=r"(v[3]) : "l"(p) : "memory"); }
__device__ __forceinline__ uint4 lds128(uint32_t a) { uint4 v; asm volatile("ld.shared.v4.b32 {%0,%1,%2,%3}, [%4];" : "=r"(v.x), "=r"(v.y), "=r"(v.z), "=r"(v.w) : "r"(a) : "memory"); return v; }
__device__ __forceinline__ uint32_t lds16(uint32_t a) { uint32_t v; asm volatile("ld.shared.u16 %0, [%1];" : "=r"(v) : "r"(a) : "memory"); return v; }
__device__ __forceinline__ void sts64(uint32_t a, uint32_t x, uint32_t y) { asm volatile("st.shared.v2.b32 [%0], {%1,%2};" :: "r"(a), "r"(x), "r"(y) : "memory"); }
template <int TB> __device__ __forceinline__ void wgmma_rs_128(float (&d)[64], const uint32_t (&a)[4], uint64_t db, int sc) {
  asm volatile("{\n.reg .pred p;\nsetp.ne.b32 p, %69, 0;\n"
    "wgmma.mma_async.sync.aligned.m64n128k16.f32.bf16.bf16 {%0, %1, %2, %3, %4, %5, %6, %7, %8, %9, %10, %11, %12, %13, %14, %15, %16, %17, %18, %19, %20, %21, %22, %23, %24, %25, %26, %27, %28, %29, %30, %31, %32, %33, %34, %35, %36, %37, %38, %39, %40, %41, %42, %43, %44, %45, %46, %47, %48, %49, %50, %51, %52, %53, %54, %55, %56, %57, %58, %59, %60, %61, %62, %63}, {%64, %65, %66, %67}, %68, p, 1, 1, %70;\n}\n"
    : "+f"(d[0]), "+f"(d[1]), "+f"(d[2]), "+f"(d[3]), "+f"(d[4]), "+f"(d[5]), "+f"(d[6]), "+f"(d[7]), "+f"(d[8]), "+f"(d[9]), "+f"(d[10]), "+f"(d[11]), "+f"(d[12]), "+f"(d[13]), "+f"(d[14]), "+f"(d[15]), "+f"(d[16]), "+f"(d[17]), "+f"(d[18]), "+f"(d[19]), "+f"(d[20]), "+f"(d[21]), "+f"(d[22]), "+f"(d[23]), "+f"(d[24]), "+f"(d[25]), "+f"(d[26]), "+f"(d[27]), "+f"(d[28]), "+f"(d[29]), "+f"(d[30]), "+f"(d[31]), "+f"(d[32]), "+f"(d[33]), "+f"(d[34]), "+f"(d[35]), "+f"(d[36]), "+f"(d[37]), "+f"(d[38]), "+f"(d[39]), "+f"(d[40]), "+f"(d[41]), "+f"(d[42]), "+f"(d[43]), "+f"(d[44]), "+f"(d[45]), "+f"(d[46]), "+f"(d[47]), "+f"(d[48]), "+f"(d[49]), "+f"(d[50]), "+f"(d[51]), "+f"(d[52]), "+f"(d[53]), "+f"(d[54]), "+f"(d[55]), "+f"(d[56]), "+f"(d[57]), "+f"(d[58]), "+f"(d[59]), "+f"(d[60]), "+f"(d[61]), "+f"(d[62]), "+f"(d[63])
    : "r"(a[0]), "r"(a[1]), "r"(a[2]), "r"(a[3]), "l"(db), "r"(sc), "n"(TB));
}
template <int TB> __device__ __forceinline__ void wgmma_rs_64(float (&d)[32], const uint32_t (&a)[4], uint64_t db, int sc) {
  asm volatile("{\n.reg .pred p;\nsetp.ne.b32 p, %37, 0;\n"
    "wgmma.mma_async.sync.aligned.m64n64k16.f32.bf16.bf16 {%0, %1, %2, %3, %4, %5, %6, %7, %8, %9, %10, %11, %12, %13, %14, %15, %16, %17, %18, %19, %20, %21, %22, %23, %24, %25, %26, %27, %28, %29, %30, %31}, {%32, %33, %34, %35}, %36, p, 1, 1, %38;\n}\n"
    : "+f"(d[0]), "+f"(d[1]), "+f"(d[2]), "+f"(d[3]), "+f"(d[4]), "+f"(d[5]), "+f"(d[6]), "+f"(d[7]), "+f"(d[8]), "+f"(d[9]), "+f"(d[10]), "+f"(d[11]), "+f"(d[12]), "+f"(d[13]), "+f"(d[14]), "+f"(d[15]), "+f"(d[16]), "+f"(d[17]), "+f"(d[18]), "+f"(d[19]), "+f"(d[20]), "+f"(d[21]), "+f"(d[22]), "+f"(d[23]), "+f"(d[24]), "+f"(d[25]), "+f"(d[26]), "+f"(d[27]), "+f"(d[28]), "+f"(d[29]), "+f"(d[30]), "+f"(d[31])
    : "r"(a[0]), "r"(a[1]), "r"(a[2]), "r"(a[3]), "l"(db), "r"(sc), "n"(TB));
}
template <int TB> __device__ __forceinline__ void wgmma_rs_56(float (&d)[28], const uint32_t (&a)[4], uint64_t db, int sc) {
  asm volatile("{\n.reg .pred p;\nsetp.ne.b32 p, %33, 0;\n"
    "wgmma.mma_async.sync.aligned.m64n56k16.f32.bf16.bf16 {%0, %1, %2, %3, %4, %5, %6, %7, %8, %9, %10, %11, %12, %13, %14, %15, %16, %17, %18, %19, %20, %21, %22, %23, %24, %25, %26, %27}, {%28, %29, %30, %31}, %32, p, 1, 1, %34;\n}\n"
    : "+f"(d[0]), "+f"(d[1]), "+f"(d[2]), "+f"(d[3]), "+f"(d[4]), "+f"(d[5]), "+f"(d[6]), "+f"(d[7]), "+f"(d[8]), "+f"(d[9]), "+f"(d[10]), "+f"(d[11]), "+f"(d[12]), "+f"(d[13]), "+f"(d[14]), "+f"(d[15]), "+f"(d[16]), "+f"(d[17]), "+f"(d[18]), "+f"(d[19]), "+f"(d[20]), "+f"(d[21]), "+f"(d[22]), "+f"(d[23]), "+f"(d[24]), "+f"(d[25]), "+f"(d[26]), "+f"(d[27])
    : "r"(a[0]), "r"(a[1]), "r"(a[2]), "r"(a[3]), "l"(db), "r"(sc), "n"(TB));
}
template <int TB> __device__ __forceinline__ void wgmma_rs_112(float (&d)[56], const uint32_t (&a)[4], uint64_t db, int sc) {
  asm volatile("{\n.reg .pred p;\nsetp.ne.b32 p, %61, 0;\n"
    "wgmma.mma_async.sync.aligned.m64n112k16.f32.bf16.bf16 {%0, %1, %2, %3, %4, %5, %6, %7, %8, %9, %10, %11, %12, %13, %14, %15, %16, %17, %18, %19, %20, %21, %22, %23, %24, %25, %26, %27, %28, %29, %30, %31, %32, %33, %34, %35, %36, %37, %38, %39, %40, %41, %42, %43, %44, %45, %46, %47, %48, %49, %50, %51, %52, %53, %54, %55}, {%56, %57, %58, %59}, %60, p, 1, 1, %62;\n}\n"
    : "+f"(d[0]), "+f"(d[1]), "+f"(d[2]), "+f"(d[3]), "+f"(d[4]), "+f"(d[5]), "+f"(d[6]), "+f"(d[7]), "+f"(d[8]), "+f"(d[9]), "+f"(d[10]), "+f"(d[11]), "+f"(d[12]), "+f"(d[13]), "+f"(d[14]), "+f"(d[15]), "+f"(d[16]), "+f"(d[17]), "+f"(d[18]), "+f"(d[19]), "+f"(d[20]), "+f"(d[21]), "+f"(d[22]), "+f"(d[23]), "+f"(d[24]), "+f"(d[25]), "+f"(d[26]), "+f"(d[27]), "+f"(d[28]), "+f"(d[29]), "+f"(d[30]), "+f"(d[31]), "+f"(d[32]), "+f"(d[33]), "+f"(d[34]), "+f"(d[35]), "+f"(d[36]), "+f"(d[37]), "+f"(d[38]), "+f"(d[39]), "+f"(d[40]), "+f"(d[41]), "+f"(d[42]), "+f"(d[43]), "+f"(d[44]), "+f"(d[45]), "+f"(d[46]), "+f"(d[47]), "+f"(d[48]), "+f"(d[49]), "+f"(d[50]), "+f"(d[51]), "+f"(d[52]), "+f"(d[53]), "+f"(d[54]), "+f"(d[55])
    : "r"(a[0]), "r"(a[1]), "r"(a[2]), "r"(a[3]), "l"(db), "r"(sc), "n"(TB));
}
template <int TA, int TB> __device__ __forceinline__ void wgmma_ss_56(float (&d)[28], uint64_t da, uint64_t db, int sc) {
  asm volatile("{\n.reg .pred p;\nsetp.ne.b32 p, %30, 0;\n"
    "wgmma.mma_async.sync.aligned.m64n56k16.f32.bf16.bf16 {%0, %1, %2, %3, %4, %5, %6, %7, %8, %9, %10, %11, %12, %13, %14, %15, %16, %17, %18, %19, %20, %21, %22, %23, %24, %25, %26, %27}, %28, %29, p, 1, 1, %31, %32;\n}\n"
    : "+f"(d[0]), "+f"(d[1]), "+f"(d[2]), "+f"(d[3]), "+f"(d[4]), "+f"(d[5]), "+f"(d[6]), "+f"(d[7]), "+f"(d[8]), "+f"(d[9]), "+f"(d[10]), "+f"(d[11]), "+f"(d[12]), "+f"(d[13]), "+f"(d[14]), "+f"(d[15]), "+f"(d[16]), "+f"(d[17]), "+f"(d[18]), "+f"(d[19]), "+f"(d[20]), "+f"(d[21]), "+f"(d[22]), "+f"(d[23]), "+f"(d[24]), "+f"(d[25]), "+f"(d[26]), "+f"(d[27])
    : "l"(da), "l"(db), "r"(sc), "n"(TA), "n"(TB));
}

__device__ __forceinline__ uint32_t cis(float a) { return pack_bf16(__cosf(a), __sinf(a)); }

typedef __nv_bfloat162 b2;
struct c2 { b2 x, y; };
__device__ __forceinline__ b2 as_b2(uint32_t u) { return *reinterpret_cast<b2*>(&u); }
__device__ __forceinline__ uint32_t as_u(b2 v) { return *reinterpret_cast<uint32_t*>(&v); }
__device__ __forceinline__ c2 mk(b2 x, b2 y) { c2 r; r.x = x; r.y = y; return r; }
__device__ __forceinline__ c2 cmul(c2 a, b2 wr, b2 wi) { return mk(__hfma2(a.x, wr, __hneg2(__hmul2(a.y, wi))), __hfma2(a.x, wi, __hmul2(a.y, wr))); }
__device__ __forceinline__ void fft4(c2& a0, c2& a1, c2& a2, c2& a3) {
  c2 t0 = mk(__hadd2(a0.x, a2.x), __hadd2(a0.y, a2.y)), t1 = mk(__hsub2(a0.x, a2.x), __hsub2(a0.y, a2.y));
  c2 t2 = mk(__hadd2(a1.x, a3.x), __hadd2(a1.y, a3.y)), t3 = mk(__hsub2(a1.x, a3.x), __hsub2(a1.y, a3.y));
  a0 = mk(__hadd2(t0.x, t2.x), __hadd2(t0.y, t2.y)); a2 = mk(__hsub2(t0.x, t2.x), __hsub2(t0.y, t2.y));
  a1 = mk(__hadd2(t1.x, t3.y), __hsub2(t1.y, t3.x)); a3 = mk(__hsub2(t1.x, t3.y), __hadd2(t1.y, t3.x));
}
__device__ __forceinline__ void fft4_s2(c2& a0, c2& a1, c2& a2, c2& a3, b2 r) {
  const b2 nr = __hneg2(r);
  c2 t0 = mk(__hfma2(a2.x, r, a0.x), __hfma2(a2.y, r, a0.y)), t1 = mk(__hfma2(a2.x, nr, a0.x), __hfma2(a2.y, nr, a0.y));
  c2 t2 = mk(__hadd2(a1.x, a3.x), __hadd2(a1.y, a3.y)), t3 = mk(__hsub2(a1.x, a3.x), __hsub2(a1.y, a3.y));
  a0 = mk(__hadd2(t0.x, t2.x), __hadd2(t0.y, t2.y)); a2 = mk(__hsub2(t0.x, t2.x), __hsub2(t0.y, t2.y));
  a1 = mk(__hadd2(t1.x, t3.y), __hsub2(t1.y, t3.x)); a3 = mk(__hsub2(t1.x, t3.y), __hadd2(t1.y, t3.x));
}
__device__ __forceinline__ void fft4_s13(c2& a0, c2& a1, c2& a2, c2& a3, b2 r) {
  const b2 nr = __hneg2(r);
  c2 t0 = mk(__hadd2(a0.x, a2.x), __hadd2(a0.y, a2.y)), t1 = mk(__hsub2(a0.x, a2.x), __hsub2(a0.y, a2.y));
  c2 t2 = mk(__hadd2(a1.x, a3.x), __hadd2(a1.y, a3.y)), t3 = mk(__hsub2(a1.x, a3.x), __hsub2(a1.y, a3.y));
  a0 = mk(__hfma2(t2.x, r, t0.x), __hfma2(t2.y, r, t0.y)); a2 = mk(__hfma2(t2.x, nr, t0.x), __hfma2(t2.y, nr, t0.y));
  a1 = mk(__hfma2(t3.y, r, t1.x), __hfma2(t3.x, nr, t1.y)); a3 = mk(__hfma2(t3.y, nr, t1.x), __hfma2(t3.x, r, t1.y));
}
__device__ __forceinline__ c2 rot1(c2 a) { return mk(__hadd2(a.x, a.y), __hsub2(a.y, a.x)); }
__device__ __forceinline__ c2 rot3(c2 a) { return mk(__hsub2(a.y, a.x), __hneg2(__hadd2(a.x, a.y))); }
__device__ __forceinline__ c2 mul_mi(c2 a) { return mk(a.y, __hneg2(a.x)); }
template <int O> __device__ __forceinline__ void fft8(c2 (&v)[16]) {
  const b2 r = as_b2(0x3F353F35u), nr = as_b2(0xBF35BF35u);
  fft4(v[O], v[O + 4], v[O + 8], v[O + 12]);
  fft4(v[O + 2], v[O + 6], v[O + 10], v[O + 14]);
  const c2 o0 = v[O + 2], o1 = rot1(v[O + 6]), o2 = v[O + 10], o3 = rot1(v[O + 14]);
  const c2 e0 = v[O], e1 = v[O + 4], e2 = v[O + 8], e3 = v[O + 12];
  v[O] = mk(__hadd2(e0.x, o0.x), __hadd2(e0.y, o0.y));              v[O + 8] = mk(__hsub2(e0.x, o0.x), __hsub2(e0.y, o0.y));
  v[O + 2] = mk(__hfma2(o1.x, r, e1.x), __hfma2(o1.y, r, e1.y));    v[O + 10] = mk(__hfma2(o1.x, nr, e1.x), __hfma2(o1.y, nr, e1.y));
  v[O + 4] = mk(__hadd2(e2.x, o2.y), __hsub2(e2.y, o2.x));          v[O + 12] = mk(__hsub2(e2.x, o2.y), __hadd2(e2.y, o2.x));
  v[O + 6] = mk(__hfma2(o3.y, r, e3.x), __hfma2(o3.x, nr, e3.y));   v[O + 14] = mk(__hfma2(o3.y, nr, e3.x), __hfma2(o3.x, r, e3.y));
}
__device__ __forceinline__ void fft16(c2 (&v)[16]) {
  const b2 r = as_b2(0x3F353F35u), c1 = as_b2(0x3F6D3F6Du), s1 = as_b2(0x3EC43EC4u), nc1 = as_b2(0xBF6DBF6Du), ns1 = as_b2(0xBEC4BEC4u);
#pragma unroll
  for (int a = 0; a < 4; a++) fft4(v[a], v[a + 4], v[a + 8], v[a + 12]);
  v[5] = cmul(v[5], c1, ns1); v[6] = rot1(v[6]); v[7] = cmul(v[7], s1, nc1);
  v[9] = rot1(v[9]); v[10] = mul_mi(v[10]); v[11] = rot3(v[11]);
  v[13] = cmul(v[13], s1, nc1); v[14] = rot3(v[14]); v[15] = cmul(v[15], nc1, s1);
  fft4(v[0], v[1], v[2], v[3]); fft4_s2(v[4], v[5], v[6], v[7], r); fft4_s13(v[8], v[9], v[10], v[11], r); fft4_s2(v[12], v[13], v[14], v[15], r);
  c2 t;
  t = v[1]; v[1] = v[4]; v[4] = t;  t = v[2]; v[2] = v[8]; v[8] = t;  t = v[3]; v[3] = v[12]; v[12] = t;
  t = v[6]; v[6] = v[9]; v[9] = t;  t = v[7]; v[7] = v[13]; v[13] = t; t = v[11]; v[11] = v[14]; v[14] = t;
}

__device__ __forceinline__ void columns(c2 (&v)[16], uint32_t sb, int t) {
  const int l16 = t & 15;
  const uint32_t row = sb + OFF_EXCH + (t >> 4) * 2304;
  const uint32_t pos = sb + OFF_EXCH + (t >> 3) * 144 + (t & 7) * 16;
#pragma unroll 1
  for (int ps = 0; ps < 6; ps++) {
    if (ps == 0 || ps == 5) { fft8<0>(v); fft8<1>(v); } else fft16(v);
    if (ps == 5) break;
    if (ps == 2) {
      const uint32_t ws = sb + OFF_WS + (l16 >> 1) * 128 + ((((t >> 4) + (l16 >> 1)) & 7) * 2 + (l16 & 1)) * 8;
      mbar_wait(sb + OFF_BAR + B_WFULL * 8, 0);
#pragma unroll
      for (int q = 0; q < 16; q++) {
        const uint2 w = lds64(ws + q * 1024);
        const c2 z = cmul(v[q], as_b2(w.x), as_b2(w.y));
        v[q] = mk(z.y, z.x);
      }
      continue;
    }
    {
      const bool full = ps == 0 || ps == 4;
      const uint32_t tw = sb + OFF_TW + (full ? ps * 2048 + t * 16 : 16384 + l16 * 16);
      const uint32_t st = full ? 2048 : 256;
#pragma unroll
      for (int i = 0; i < 4; i++) {
        const uint4 w4 = lds128(tw + i * st);
        const uint32_t w[4] = {w4.x, w4.y, w4.z, w4.w};
#pragma unroll
        for (int e = 0; e < 4; e++) v[4 * i + e] = cmul(v[4 * i + e], __low2bfloat162(as_b2(w[e])), __high2bfloat162(as_b2(w[e])));
      }
    }
    if (ps == 0) {
      bar_sync<3, 128>();
#pragma unroll
      for (int q = 0; q < 8; q++) sts128(pos + q * 2304, as_u(v[2 * q].x), as_u(v[2 * q].y), as_u(v[2 * q + 1].x), as_u(v[2 * q + 1].y));
      bar_sync<3, 128>();
#pragma unroll
      for (int q = 0; q < 16; q++) { const uint2 a = lds64(row + q * 144 + l16 * 8); v[q] = mk(as_b2(a.x), as_b2(a.y)); }
    } else {
      __syncwarp();
#pragma unroll
      for (int q = 0; q < 16; q++) sts64(row + q * 144 + l16 * 8, as_u(v[q].x), as_u(v[q].y));
      if (ps == 4) bar_sync<3, 128>(); else __syncwarp();
      const uint32_t src = ps == 4 ? pos : row + l16 * 144, st = ps == 4 ? 2304 : 16;
#pragma unroll
      for (int q = 0; q < 8; q++) { const uint4 a = lds128(src + q * st); v[2 * q] = mk(as_b2(a.x), as_b2(a.y)); v[2 * q + 1] = mk(as_b2(a.z), as_b2(a.w)); }
    }
  }
}

template <int NH> __device__ __forceinline__ void h_epilogue(float (&acc)[NH * 8], unsigned char* gdst, uint32_t tag) {
#pragma unroll
  for (int c = 0; c < NH / 2; c++) {
    uint32_t pk[4];
#pragma unroll
    for (int i = 0; i < 4; i++) {
      float hv[2];
#pragma unroll
      for (int e = 0; e < 2; e++) {
        float hg = 0.5f * acc[c * 8 + i * 2 + e], up = acc[NH * 4 + c * 8 + i * 2 + e];
        float th; asm("tanh.approx.f32 %0, %1;" : "=f"(th) : "f"(hg));
        hv[e] = fmaf(hg, th, hg) * up;
      }
      pk[i] = pack_bf16(hv[0], hv[1]);
    }
    stg128_l2(gdst + c * 4096, (pk[0] & ~1u) | tag, pk[1], pk[2], pk[3]);
  }
}

__device__ __forceinline__ void frag_ready(uint32_t (&a)[4], uint32_t (&b)[4], uint32_t (&c)[4], uint32_t (&d)[4], const unsigned char* p, uint32_t tag) {
  asm volatile("{\n.reg .pred p;\n.reg .u32 c, m, q;\nmov.u32 c, 0;\nL_TRY:\n"
               "lop3.b32 m, %0, %4, %17, 0x7E;\nlop3.b32 q, %8, %12, %17, 0x7E;\nlop3.b32 m, m, q, 1, 0xA8;\nsetp.ne.u32 p, m, 0;\n"
               "vote.sync.any.pred p, p, 0xffffffff;\n@!p bra.uni L_OK;\n"
               "ld.relaxed.gpu.global.v4.b32 {%0,%1,%2,%3}, [%16];\nld.relaxed.gpu.global.v4.b32 {%4,%5,%6,%7}, [%16+4096];\n"
               "ld.relaxed.gpu.global.v4.b32 {%8,%9,%10,%11}, [%16+8192];\nld.relaxed.gpu.global.v4.b32 {%12,%13,%14,%15}, [%16+12288];\n"
               "add.u32 c, c, 1;\nsetp.lt.u32 p, c, 262144;\n@p bra.uni L_TRY;\ntrap;\nL_OK:\n}"
               : "+r"(a[0]), "+r"(a[1]), "+r"(a[2]), "+r"(a[3]), "+r"(b[0]), "+r"(b[1]), "+r"(b[2]), "+r"(b[3]),
                 "+r"(c[0]), "+r"(c[1]), "+r"(c[2]), "+r"(c[3]), "+r"(d[0]), "+r"(d[1]), "+r"(d[2]), "+r"(d[3])
               : "l"(p), "r"(tag) : "memory");
}

#define LDH ldg128_na
#define MAP 0
#define WPOS 0
#define XPRI 0
#define LEAD2 1
#define LEAD1 3

__global__ void __cluster_dims__(2, 1, 1) __launch_bounds__(NTHREADS, 1)
fused_kernel(const __grid_constant__ CUtensorMap tm_x, const __grid_constant__ CUtensorMap tm_g, const __grid_constant__ CUtensorMap tm_u,
             const __grid_constant__ CUtensorMap tm_g32, const __grid_constant__ CUtensorMap tm_u32,
             const __nv_bfloat16* __restrict__ w_r, const __nv_bfloat16* __restrict__ w_i,
             const __nv_bfloat16* __restrict__ w_gate, const __nv_bfloat16* __restrict__ w_up,
             const __nv_bfloat16* __restrict__ w_down, const __nv_bfloat16* __restrict__ gate_w, __nv_bfloat16* __restrict__ out) {
  extern __shared__ __align__(1024) unsigned char smem[];
  const uint32_t sb = s2u(smem);
  const uint32_t bars = sb + OFF_BAR;
  const int tid = threadIdx.x, warp = __shfl_sync(0xffffffffu, tid >> 5, 0), lane = tid & 31;
  const int cl = blockIdx.x >> 1, kh = blockIdx.x & 1;
  const int n0 = cl < 4 ? cl : (cl < 36 ? (cl - 4) >> 3 : (cl - 36) / 7);
  const int m0 = cl < 4 ? 15 : (cl < 36 ? (cl - 4) & 7 : cl - 28 - 7 * n0);
  const int n = MAP == 0 ? n0 : (MAP == 1 ? (m0 & 3) : ((n0 & 1) | ((m0 & 1) << 1)));
  const int m = MAP == 0 ? m0 : (MAP == 1 ? ((m0 & 12) | n0) : ((m0 & 14) | (n0 >> 1)));
  const int j = kh * 4 + n, bid = m * 8 + n * 2 + kh;

  const int c64 = 224 * j + (j & 1) * 32;
  if (warp < 8) {
    asm volatile("setmaxnreg.inc.sync.aligned.u32 208;");
    const int wg = warp >> 2, w4 = warp & 3, g = lane >> 2, t = lane & 3;
    const int rh = wg ^ kh ^ 1;
    const int p = j & 1, r = (j >> 1) & 1, hh = j >> 2;
    const uint32_t epoch = ld_relaxed(&g_ep[bid]);
    if ((tid & 127) == 0) PROF(wg, 30);
#pragma unroll 1
    for (int it = tid; it < 392; it += 256) {
      const int kc = it / 28, sg = it - kc * 28;
      const int k = 2 * (28 * hh + sg) + r;
      const float kf = (float)k * (-6.283185307179586f / 448.0f), a0 = (float)(16 * kc + p) * kf;
      uint32_t c[4], s[4];
#pragma unroll
      for (int q = 0; q < 4; q++) {
        const float a1 = fmaf((float)(2 * q), kf, a0), a2 = fmaf((float)(2 * q + 8), kf, a0);
        c[q] = pack_bf16(__cosf(a1), __cosf(a2)); s[q] = pack_bf16(__sinf(a1), __sinf(a2));
        if (k == 0) s[q] = ((q ^ p) & 1) ? 0xBF80BF80u : 0x3F803F80u;
      }
      const uint32_t a = sb + 5 * SLOT + (kc * 56 + 2 * sg) * 16;
      sts128(a, c[0], c[1], c[2], c[3]);
      sts128(a + 16, s[0], s[1], s[2], s[3]);
    }
    if ((tid & 127) == 0) PROF(wg, 31);
    fence_async_smem();
    bar_sync<0, NTHREADS - 64>();
    asm volatile("barrier.cluster.arrive.relaxed.aligned;" ::: "memory");
    if ((tid & 127) == 0) PROF(wg, 1);

    uint32_t xa[28][4];
    {
      const uint32_t xb = sb + OFF_PQ + wg * HALF_XR + (w4 * 16 + (lane & 15)) * 128;
      mbar_wait(bars + (B_XFULL + wg) * 8, 0);
      if (XPRI && wg) mbar_wait(bars + B_XFREE * 8, 0);
      if ((tid & 127) == 0) PROF(wg, 2);
#pragma unroll
      for (int kb = 0; kb < 7; kb++) {
#pragma unroll
        for (int kk = 0; kk < 4; kk++) {
          uint32_t a = xb + kb * 8192 + (((2 * kk + (lane >> 4)) ^ (lane & 7)) << 4);
          asm volatile("ldmatrix.sync.aligned.m8n8.x4.shared.b16 {%0,%1,%2,%3}, [%4];"
                       : "=r"(xa[kb * 4 + kk][0]), "=r"(xa[kb * 4 + kk][1]), "=r"(xa[kb * 4 + kk][2]), "=r"(xa[kb * 4 + kk][3]) : "r"(a) : "memory");
        }
      }
    }
    {
      uint32_t ad[7][4];
      const uint32_t sel = p ? 0x7632 : 0x5410;
      const uint32_t sgn = r ? 0xBF80BF80u : 0x3F803F80u;
#pragma unroll
      for (int jj = 0; jj < 7; jj++) {
#pragma unroll
        for (int i = 0; i < 4; i++) {
          int ks = 2 * jj + (i >> 1), rr = i & 1;
          uint32_t lo = __byte_perm(xa[ks][rr], xa[ks][rr + 2], sel);
          uint32_t hi = __byte_perm(xa[ks + 14][rr], xa[ks + 14][rr + 2], sel);
          asm("fma.rn.bf16x2 %0, %1, %2, %3;" : "=r"(ad[jj][i]) : "r"(hi), "r"(sgn), "r"(lo));
        }
      }
      __syncwarp();
      if (lane == 0) mbar_arrive(bars + (B_XFREE + wg) * 8);
      float acc[28];
      wg_fence();
      uint64_t db = mkdesc(sb + 5 * SLOT, 896, 128, 0);
#pragma unroll
      for (int jj = 0; jj < 7; jj++) wgmma_rs_56<0>(acc, ad[jj], db + jj * 112, jj != 0);
      wg_commit();
      wg_wait<0>(); keep(acc);
      if (lane == 0) mbar_arrive(bars + (B_EMPTY + 5) * 8);
      uint32_t* xc = g_Xc + (size_t)((2 * (28 * hh + t) + r) * 2 + p) * S_ + m * 128 + rh * 64 + w4 * 16 + g;
#pragma unroll
      for (int i = 0; i < 7; i++) {
        xc[i * 16 * S_] = pack_bf16(acc[4 * i], acc[4 * i + 1]);
        xc[i * 16 * S_ + 8] = pack_bf16(acc[4 * i + 2], acc[4 * i + 3]);
      }
      __syncwarp();
      if (lane == 0) mbar_arrive(bars + B_PUBX * 8);
    }
    if ((tid & 127) == 0) PROF(wg, 3);
    const uint32_t tag = ~epoch & 1;
    unsigned char* const hbase = g_H + (size_t)(m * 2 + kh) * (56 * 4096) + rh * 2048 + (tid & 127) * 16;
#pragma unroll 1
    for (int u = 0; u < 3; u++) {
      float acc[64];
      if (wg == 1) { if (u & 1) bar_sync<6, 256>(); else bar_sync<2, 256>(); }
      const uint32_t sbu = opaque(sb);
#pragma unroll
      for (int kb = 0; kb < 7; kb++) {
        mbar_wait(sbu + OFF_BAR + (B_FULL + kb) * 8, u & 1);
        wg_fence();
        uint64_t db = mkdesc(sbu + kb * SLOT, 8192, 1024, 1);
#pragma unroll
        for (int kk = 0; kk < 4; kk++) wgmma_rs_128<1>(acc, xa[kb * 4 + kk], db + kk * 128, (kb | kk) != 0);
        wg_commit();
        if (kb == LEAD1 && wg == 0) { if (u & 1) bar_arrive<6, 256>(); else bar_arrive<2, 256>(); }
        if (kb > 0) { wg_wait<1>(); if (lane == 0) mbar_arrive(sbu + OFF_BAR + (B_EMPTY + kb - 1) * 8); }
      }
      wg_wait<0>(); keep(acc);
      if (lane == 0) mbar_arrive(sbu + OFF_BAR + (B_EMPTY + 6) * 8);
      if ((tid & 127) == 0) PROF(wg, 4 + 2 * u);
      h_epilogue<8>(acc, hbase + (u * 16 + n * 4) * 4096, tag);
      if ((tid & 127) == 0) PROF(wg, 5 + 2 * u);
    }
    {
      float acc[32];
      if (wg == 1) bar_sync<6, 256>();
      const uint32_t sbu = opaque(sb);
#pragma unroll
      for (int it = 0; it < 4; it++) {
        mbar_wait(sbu + OFF_BAR + (B_FULL + it) * 8, 1);
        wg_fence();
        uint64_t db = mkdesc(sbu + it * SLOT, 8192, 512, 2);
#pragma unroll
        for (int kk = 0; kk < 8; kk++) if (it * 8 + kk < 28) wgmma_rs_64<1>(acc, xa[it * 8 + kk], db + kk * 64, (it | kk) != 0);
        wg_commit();
        if (it == 2 && wg == 0) bar_arrive<6, 256>();
        if (it > 0) {
          wg_wait<1>();
          if (lane == 0) mbar_arrive(sbu + OFF_BAR + (B_EMPTY + it - 1) * 8);
#pragma unroll
          for (int i = it * 8 - 8; i < it * 8; i++) LDH(xa[i], hbase + i * 4096);
        }
      }
      wg_wait<0>(); keep(acc);
      if (lane == 0) mbar_arrive(sbu + OFF_BAR + (B_EMPTY + 3) * 8);
      if ((tid & 127) == 0) PROF(wg, 10);
      h_epilogue<4>(acc, hbase + (48 + n * 2) * 4096, tag);
    }
    asm volatile("barrier.cluster.wait.aligned;" ::: "memory");
    if ((tid & 127) == 0) PROF(wg, 11);

    float acc[56];
    auto check = [&](int b0, int b1) {
#pragma unroll
      for (int b = b0; b < b1; b++) frag_ready(xa[b % 7 * 4], xa[b % 7 * 4 + 1], xa[b % 7 * 4 + 2], xa[b % 7 * 4 + 3], hbase + b * 16384, tag);
    };
    auto load = [&](int b) {
#pragma unroll
      for (int kk = 0; kk < 4; kk++) LDH(xa[b % 7 * 4 + kk], hbase + (b * 4 + kk) * 4096);
    };
    check(0, 6);
    if (wg == 1) bar_sync<2, 256>();
#pragma unroll
    for (int b = 0; b < 14; b++) {
      if ((tid & 127) == 0) PROF(wg, 16 + b);
      if (b >= 4) mbar_wait(bars + (B_FULL + b % 7) * 8, b < 7);
      else if (b == 0) mbar_wait(bars + B_RFULL * 8, 1);
      if (b == 6 || b == 9) check(b, b + 3);
      if (b == 12) check(12, 14);
      wg_fence();
      const uint64_t db = mkdesc(b < 4 ? sb + OFF_R + b * 14336 : sb + b % 7 * SLOT, 1792, 128, 0);
#pragma unroll
      for (int kk = 0; kk < 4; kk++) wgmma_rs_112<1>(acc, xa[b % 7 * 4 + kk], db + kk * 224, (b | kk) != 0);
      wg_commit();
      if (b == LEAD2 && wg == 0) bar_arrive<2, 256>();
      if (b == 0) load(6);
      if (b == 2 || b == 3) load(b + 5);
      if (b == 6) { load(9); load(10); load(11); }
      if (b == 9) { load(12); load(13); }
      if (b > 0) wg_wait<1>();
      if (lane == 0) {
        if (b >= 5 && b <= 9) mbar_arrive(bars + (B_EMPTY + (b + 6) % 7) * 8);
        if (b == 4) {
          mbar_arrive(bars + B_LFREE * 8);
          asm volatile("{\n.reg .b32 ra;\nmapa.shared::cluster.u32 ra, %0, %1;\nmbarrier.arrive.relaxed.cluster.shared::cluster.b64 _, [ra];\n}"
                       :: "r"(bars + B_RFREE * 8), "r"(kh ^ 1) : "memory");
        }
      }
    }
    const int t128 = tid & 127;
    wg_wait<0>(); keep(acc);
    if (wg == 0) {
      if (t128 == 0) PROF(wg, 12);
      mbar_wait_cluster(bars + B_RFREE * 8, 0);
      uint32_t rdst, rbar;
      asm volatile("mapa.shared::cluster.u32 %0, %1, %2;" : "=r"(rdst) : "r"(sb + OFF_R + t128 * 16), "r"(kh ^ 1));
      asm volatile("mapa.shared::cluster.u32 %0, %1, %2;" : "=r"(rbar) : "r"(bars + B_RECV * 8), "r"(kh ^ 1));
#pragma unroll
      for (int i = 0; i < 14; i++)
        asm volatile("st.async.weak.shared::cluster.mbarrier::complete_tx::bytes.v4.f32 [%0], {%1,%2,%3,%4}, [%5];"
                     :: "r"(rdst + i * 2048), "f"(acc[4 * i]), "f"(acc[4 * i + 1]), "f"(acc[4 * i + 2]), "f"(acc[4 * i + 3]), "r"(rbar) : "memory");
    } else {
      float spec[2][28];
      if (t128 == 0) PROF(wg, 12);
      mbar_wait(bars + B_PQFULL * 8, 0);
      if (t128 == 0) { PROF(wg, 13); g_ep[bid] = epoch + 1; }
#pragma unroll
      for (int i = 0; i < 4; i++) {
        if (i == 0) mbar_wait(bars + B_GFULL * 8, 0);
        if (i >= 2) mbar_wait(bars + (B_FULL + i - 2) * 8, 1);
        wg_fence();
        const uint64_t da = mkdesc(sb + OFF_PQ + i * 14336, 1024, 1024, 1);
        const uint64_t db = mkdesc(i < 2 ? sb + OFF_R + 28672 + i * (G_IMG / 2) : sb + (i - 2) * SLOT, 896, 128, 0);
#pragma unroll
        for (int kk = 0; kk < 7; kk++) wgmma_ss_56<1, 0>(spec[i >> 1], da + kk * 128, db + kk * 112, ((i & 1) | kk) != 0);
        wg_commit();
      }
      const float* gs = reinterpret_cast<const float*>(smem + OFF_G) + w4 * 16 + g;
      const float o0 = bf16_round(1.0f - gs[0]), o1 = bf16_round(1.0f - gs[8]);
      const float g0 = gs[0] * (1.0f / (float)(S_ * D_)), g1 = gs[8] * (1.0f / (float)(S_ * D_));
      wg_wait<0>(); keep(spec[0]); keep(spec[1]);
      if (t128 == 0) PROF(wg, 14);
      mbar_wait_cluster(bars + B_RECV * 8, 0);
      if (t128 == 0) PROF(wg, 0);
      float4 o[14];
#pragma unroll
      for (int i = 0; i < 14; i++) o[i] = lds128f(sb + OFF_R + t128 * 16 + i * 2048);
      bar_sync<5, 128>();
      const uint32_t st = sb + OFF_PQ + w4 * 3840;
#pragma unroll
      for (int i = 0; i < 7; i++) {
        uint32_t pk[4];
#pragma unroll
        for (int e = 0; e < 2; e++) {
          const int c = 2 * i + e, si = i * 4 + e;
          pk[2 * e] = pack_bf16(fmaf(acc[4 * c] + o[c].x, o0, g0 * spec[0][si]), fmaf(acc[4 * c + 1] + o[c].y, o0, g0 * spec[1][si]));
          pk[2 * e + 1] = pack_bf16(fmaf(acc[4 * c + 2] + o[c].z, o1, g1 * spec[0][si + 2]), fmaf(acc[4 * c + 3] + o[c].w, o1, g1 * spec[1][si + 2]));
        }
        asm volatile("stmatrix.sync.aligned.m8n8.x4.shared.b16 [%0], {%1,%2,%3,%4};"
                     :: "r"(st + (lane & 15) * 240 + (lane >> 4) * 16 + i * 32), "r"(pk[0]), "r"(pk[1]), "r"(pk[2]), "r"(pk[3]) : "memory");
      }
      __syncwarp();
      if (lane < 28) {
        const int r2 = lane >= 14, cc = lane - r2 * 14;
        unsigned char* ob = reinterpret_cast<unsigned char*>(out) + (size_t)(m * 128 + kh * 64 + w4 * 16 + r2) * (D_ * 2) + n * 224 + cc * 16;
        float4 v[8];
#pragma unroll
        for (int i = 0; i < 8; i++) v[i] = lds128f(st + r2 * 240 + cc * 16 + i * 480);
#pragma unroll
        for (int i = 0; i < 8; i++) stg128(ob + i * (D_ * 4), __float_as_uint(v[i].x), __float_as_uint(v[i].y), __float_as_uint(v[i].z), __float_as_uint(v[i].w));
      }
    }
    if (t128 == 0) { PROF(wg, 15); if (wg) { PROFG(4, 30); PROF(4, 31); } }
  } else if (warp < 12) {
    asm volatile("setmaxnreg.dec.sync.aligned.u32 72;");
    const int t = tid - 256;
    const int k = bid;
    if (t == 0) PROF(2, 0);
    uint4 gv[7];
#pragma unroll
    for (int i = 0; i < 7; i++) gv[i] = ldg128(reinterpret_cast<const uint4*>(gate_w) + i * 8 + (t & 7));
    if (t < 98) {
      int cid = m * 98 + t, kc = cid / 56, nn = cid - kc * 56;
      int d = 112 * n + 8 * (2 * (nn >> 3) + (nn & 1)) + (nn & 6) + kh;
      int dr = d > 224 ? d - 448 : d;
      const float df = (float)dr * (-6.283185307179586f / 448.0f);
      uint32_t pk[4];
#pragma unroll
      for (int e = 0; e < 4; e++) {
        const float a = (float)(4 * kc + e) * df;
        pk[e] = pack_bf16(2.0f * __cosf(a), 2.0f * __sinf(a));
      }
      if (kc == 0) pk[0] = (((d >> 1) ^ kh) & 1) ? 0xBF803F80u : 0x3F803F80u;
      stg128(g_G + (size_t)(n * 2 + kh) * G_IMG + cid * 16, pk[0], pk[1], pk[2], pk[3]);
    }
    bar_sync<0, NTHREADS - 64>();
    asm volatile("barrier.cluster.arrive.relaxed.aligned;" ::: "memory");
    {
      const int row = n * 16 + (t >> 3), l8 = t & 7;
      mbar_wait(bars + (B_XFULL + 1) * 8, 0);
      float sum = 0.f;
#pragma unroll
      for (int i = 0; i < 7; i++) {
        const uint4 a = lds128(sb + OFF_R + i * 8192 + row * 128 + ((l8 ^ (row & 7)) << 4));
        const uint32_t aa[4] = {a.x, a.y, a.z, a.w}, bb[4] = {gv[i].x, gv[i].y, gv[i].z, gv[i].w};
#pragma unroll
        for (int e = 0; e < 4; e++) {
          const uint32_t pr = as_u(__hmul2(as_b2(aa[e]), as_b2(bb[e])));
          sum += bf_lo(pr) + bf_hi(pr);
        }
      }
      sum += __shfl_xor_sync(0xffffffffu, sum, 1); sum += __shfl_xor_sync(0xffffffffu, sum, 2); sum += __shfl_xor_sync(0xffffffffu, sum, 4);
      if (lane == 0) mbar_arrive(bars + (B_XFREE + 1) * 8);
      if (l8 == 0) g_gate[m * 128 + kh * 64 + row] = bf16_round(__fdividef(1.0f, 1.0f + __expf(-bf16_round(sum))));
    }
    if (t == 0) PROF(2, 11);
    mbar_wait(bars + B_PIN * 8, 0);
    if (t == 0) PROF(2, 4);
    {
      const uint32_t wa = sb + 6 * SLOT + (((t & 7) - bid) & 7) * 450 + (t >> 3) * 2, wc = wa + 448 - (t >> 3) * 4;
      uint2* dst = g_Wt + (t >> 3) * S_ + 16 * bid + 2 * (t & 7);
#pragma unroll 1
      for (int h = 0; h < 2; h++) {
        uint32_t w[4][8];
#pragma unroll
        for (int i = 0; i < 4; i++) {
#pragma unroll
          for (int e = 0; e < 4; e++) { w[i][2 * e] = lds16(wa + h * 128 + i * 32 + e * 3600); w[i][2 * e + 1] = lds16(wc - h * 128 - i * 32 + e * 3600); }
        }
        if (h == 1) {
          const uint32_t z = __reduce_or_sync(0xffffffffu, w[3][7] | w[3][6]) >> 16;
          if (lane < 2) mbar_arrive(bars + (B_EMPTY + 6) * 8 + z);
        }
#pragma unroll
        for (int i = 0; i < 4; i++)
          if (i < 3 || h == 0 || t < 8)
            stg128(dst + (h * 64 + i * 16) * S_, __byte_perm(w[i][0], w[i][1], 0x5410), __byte_perm(w[i][4], w[i][5], 0x5410), __byte_perm(w[i][2], w[i][3], 0x5410), __byte_perm(w[i][6], w[i][7], 0x5410));
      }
    }
    __syncwarp();
    if (lane == 0) mbar_arrive(bars + B_PUBW * 8);
    if (t == 0) PROF(2, 6);
    mbar_wait(bars + B_XFREE * 8, 0);
    if (k < 113) {
      const float u = -6.283185307179586f / 2048.0f, t2 = (float)(2 * t) * u, rr = (float)(t >> 4) * u;
#pragma unroll 1
      for (int i = 0; i < 4; i++) {
        const float q = (float)(2 * i), l = (float)((t & 15) + 64 * i);
        sts128(sb + OFF_TW + i * 2048 + t * 16, cis(t2 * q), cis((t2 + u) * q), cis(t2 * (q + 1.0f)), cis((t2 + u) * (q + 1.0f)));
        sts128(sb + OFF_TW + 8192 + i * 2048 + t * 16, cis(rr * l), cis(rr * (l + 16.0f)), cis(rr * (l + 32.0f)), cis(rr * (l + 48.0f)));
      }
      const float l = (float)((t >> 1) & 15) * (8.0f * u), jj = (float)((t >> 5) * 4 + (t & 1) * 2);
      sts64(sb + OFF_TW + 16384 + t * 8, cis(l * jj), cis(l * (jj + 1.0f)));
    }
    if (t == 0) PROF(2, 9);
    mbar_wait(bars + B_RFULL * 8, 0);
    if (t < 112) {
      const int js = bid >> 4, nn = (t >> 1) / 14, cc = (t >> 1) - nn * 14;
      unsigned char* wdst = g_Wd + (size_t)((js >> 2) * 4 + nn) * WD_IMG + cc * 128 + (t & 1) * 16;
      uint4 v[7];
#pragma unroll
      for (int i = 0; i < 7; i++) v[i] = lds128(sb + OFF_R + i * 1792 + (t & 1) * 896 + (t >> 1) * 16);
#pragma unroll
      for (int i = 0; i < 7; i++) {
        int col = 14 * (bid & 15) + 2 * i - (js & 1) * 32;
        if (col < 0) col += 224;
        const int kpos = col < 192 ? (col >> 6) * 256 + (js & 3) * 64 + (col & 63) : 576 + (js & 3) * 32 + col;
        stg128(wdst + (kpos >> 3) * 1792 + (kpos & 7) * 16, v[i].x, v[i].y, v[i].z, v[i].w);
      }
    }
    __syncwarp();
    if (lane == 0) mbar_arrive(bars + B_PUBD * 8);
    bar_sync<3, 128>();
    if (k < 113) {
      if (t == 0) PROF(2, 2);
      mbar_wait(bars + B_XCFULL * 8, 0);
      if (t == 0) PROF(2, 3);
      c2 v[16];
      const uint32_t se = k == 0 ? 0x4410 : (k == 112 ? 0x4432 : 0x3210), so = k == 0 ? 0x4410 : (k == 112 ? 0x3244 : 0x3210);
#pragma unroll
      for (int jj = 0; jj < 8; jj++) {
        const uint2 e2 = lds64(sb + OFF_EXCH + jj * 1024 + t * 8), o2 = lds64(sb + OFF_EXCH + 8192 + jj * 1024 + t * 8);
#pragma unroll
        for (int h = 0; h < 2; h++) {
          const b2 e = as_b2(__byte_perm(h ? e2.y : e2.x, 0, se)), o = as_b2(__byte_perm(h ? o2.y : o2.x, 0, so));
          const uint32_t s = as_u(__hadd2(e, o)), d = as_u(__hsub2(e, o)) ^ 0x80000000u;
          v[2 * jj + h] = mk(as_b2(__byte_perm(s, d, 0x5410)), as_b2(__byte_perm(s, d, 0x7632)));
        }
      }
      if (t == 0) PROF(2, 12);
      columns(v, sb, t);
      if (t == 0) PROF(2, 14);
      const int pre = (k == 112) ? 1 : 2 * k, pim = (k == 112) ? 1 : 2 * k + 1;
      uint32_t* pq = reinterpret_cast<uint32_t*>(g_PQ) + (t >> 5) * 14336;
      uint32_t* pr = pq + pre * 32 + ((((lane >> 2) ^ pre) & 7) << 2) + (lane & 3);
      uint32_t* pi = pq + pim * 32 + ((((lane >> 2) ^ pim) & 7) << 2) + (lane & 3);
#pragma unroll
      for (int jj = 0; jj < 8; jj++) {
        const b2 ar = as_b2(__byte_perm(as_u(v[2 * jj].y), as_u(v[2 * jj + 1].y), 0x5410)), br = as_b2(__byte_perm(as_u(v[2 * jj].y), as_u(v[2 * jj + 1].y), 0x7632));
        const b2 ai = as_b2(__byte_perm(as_u(v[2 * jj].x), as_u(v[2 * jj + 1].x), 0x5410)), bi = as_b2(__byte_perm(as_u(v[2 * jj].x), as_u(v[2 * jj + 1].x), 0x7632));
        pr[jj * 57344] = as_u(__hadd2(ar, br));
        if (k != 112) pr[jj * 57344 + 7168] = as_u(__hsub2(ar, br));
        if (k != 0) pi[jj * 57344 + 7168] = as_u(__hadd2(ai, bi));
        if (k != 0 && k != 112) pi[jj * 57344] = as_u(__hsub2(ai, bi));
      }
      fence_async_smem();
    }
    bar_sync<3, 128>();
    if (t == 0) { PROF(2, 5); red_release(&g_cnt[5 * 32]); PROF(2, 7); }
    __syncwarp();
    asm volatile("barrier.cluster.wait.aligned;" ::: "memory");
  } else {
    asm volatile("setmaxnreg.dec.sync.aligned.u32 24;");
    if (warp == 12) {
      if (elect()) {
        mbar_init(bars + B_XFULL * 8, 1); mbar_init(bars + (B_XFULL + 1) * 8, 1);
        fence_async_smem();
#pragma unroll
        for (int w = 0; w < 2; w++) {
          mbar_expect(bars + (B_XFULL + w) * 8, HALF_XR);
          tma3d(sb + OFF_PQ + w * HALF_XR, &tm_x, 0, m * 128 + (w ^ kh ^ 1) * 64, 0, bars + (B_XFULL + w) * 8);
        }
        PROF(3, 3);
#pragma unroll
        for (int i = 0; i < NSLOT; i++) mbar_init(bars + (B_FULL + i) * 8, 1);
        mbar_init(bars + B_PIN * 8, 1);
        fence_async_smem();
      }
      bar_arrive<0, NTHREADS - 64>();
#pragma unroll 1
      for (int i = 0; i < 5; i++) {
        if (elect()) {
          if (i == WPOS) {
            mbar_expect(bars + B_PIN * 8, 14400);
            bulk_g2s(sb + 6 * SLOT, reinterpret_cast<const unsigned char*>(w_r) + bid * 7200, 7200, bars + B_PIN * 8);
            bulk_g2s(sb + 6 * SLOT + 7200, reinterpret_cast<const unsigned char*>(w_i) + bid * 7200, 7200, bars + B_PIN * 8);
          }
          const uint32_t fb = bars + (B_FULL + i) * 8;
          mbar_expect(fb, SLOT);
          tma2d(sb + i * SLOT, &tm_g, c64, i * 64, fb);
          tma2d(sb + i * SLOT + 8192, &tm_u, c64, i * 64, fb);
          PROF(3, 4 + i);
        }
      }
      if (elect()) {
        prefetch_tma2d(&tm_g, c64, 320); prefetch_tma2d(&tm_u, c64, 320);
        prefetch_tma2d(&tm_g, c64, 384); prefetch_tma2d(&tm_u, c64, 384);
      }
    } else if (warp == 14) {
      if (elect()) {
#pragma unroll
        for (int i = B_EMPTY; i < B_END; i++)
          if (i < B_XFULL || i >= B_XFREE) mbar_init(bars + i * 8, i >= B_PQFULL ? 1 : ((i == B_XFREE || i >= B_PUBW) ? 4 : 8));
        asm volatile("fence.mbarrier_init.release.cluster;" ::: "memory");
        fence_async_smem();
        mbar_expect(bars + B_RECV * 8, 64 * 112 * 4);
      }
      bar_arrive<0, NTHREADS - 64>();
    }
    const uint32_t epoch = ld_relaxed(&g_ep[bid]);
    if (warp == 13 && lane == 0) { PROFG(4, 0); PROF(4, 1); }
    bar_sync<1, 128>();
    asm volatile("barrier.cluster.arrive.relaxed.aligned;" ::: "memory");
    if (warp == 12) {
      int slot = 5, ph = 1;
      auto wait_slot = [&]() { mbar_wait(bars + (B_EMPTY + slot) * 8, ph ^ (slot >= 5)); };
      auto adv = [&]() { if (++slot == NSLOT) { slot = 0; ph ^= 1; } };
      const int c32 = 224 * j + ((j & 1) ? 0 : 192);
#pragma unroll 1
      for (int i = 5; i < 25; i++) {
        wait_slot();
        if (elect()) {
          const uint32_t dst = sb + slot * SLOT, fb = bars + (B_FULL + slot) * 8;
          const bool last = i >= 21;
          const int cc = last ? c32 : c64 + 64 * (i / 7), rr = last ? slot * 128 : slot * 64;
          mbar_expect(fb, SLOT);
          tma2d(dst, last ? &tm_g32 : &tm_g, cc, rr, fb);
          tma2d(dst + 8192, last ? &tm_u32 : &tm_u, cc, rr, fb);
        }
        adv();
      }
      if (lane == 0) PROF(3, 0);
      mbar_wait(bars + B_PREP * 8, 0);
      if (lane == 0) PROF(3, 1);
#pragma unroll 1
      for (int i = 4; i < 16; i++) {
        if (lane == 0) PROF(3, 16 + i);
        wait_slot();
        if (elect()) {
          const int bytes = i < 14 ? 14336 : G_IMG / 2;
          const unsigned char* src = i < 14 ? g_Wd + (size_t)j * WD_IMG + i * 14336 : g_G + (size_t)(n * 4 + i - 12) * (G_IMG / 2);
          mbar_expect(bars + (B_FULL + slot) * 8, bytes);
          bulk_g2s(sb + slot * SLOT, src, bytes, bars + (B_FULL + slot) * 8);
        }
        adv();
      }
      if (lane == 0) PROF(3, 2);
    } else if (warp == 13) {
#pragma unroll 1
      for (int u = 0; u < 3; u++) {
        mbar_wait(bars + (u ? B_PUBW - 1 + u : B_PUBX) * 8, 0);
        if (lane == 0) { PROF(4, 8 + u); red_release(&g_cnt[(u ? 8 - 2 * u : j >> 1) * 32]); PROF(4, 12 + u); }
        __syncwarp();
      }
      mbar_wait(bars + B_LFREE * 8, 0);
      if (elect()) {
        mbar_expect(bars + B_GFULL * 8, G_IMG);
        bulk_g2s(sb + OFF_R + 28672, g_G + (size_t)(n * 2) * G_IMG, G_IMG, bars + B_GFULL * 8);
      }
    } else if (warp == 14) {
#pragma unroll 1
      for (int u = 0; u < 2; u++) {
        wait_ge(&g_cnt[(6 - 2 * u) * 32], (epoch + 1) * 128);
        fence_async_global();
        if (lane == 0) { mbar_arrive(bars + (B_PREPW - u) * 8); PROF(5, 9 - u); }
      }
    } else {
      mbar_wait(bars + B_XFREE * 8, 0);
      if (elect()) {
        prefetch_l2(reinterpret_cast<const unsigned char*>(w_gate) + bid * 12544, 12544);
        prefetch_l2(reinterpret_cast<const unsigned char*>(w_up) + bid * 12544, 12544);
      }
      mbar_wait(bars + (B_XFREE + 1) * 8, 0);
      if (elect()) {
        mbar_expect(bars + B_RFULL * 8, 12544);
        bulk_g2s(sb + OFF_R, reinterpret_cast<const unsigned char*>(w_down) + bid * 12544, 12544, bars + B_RFULL * 8);
      }
      if (bid < 113) {
        const int sl = (bid == 112) ? 0 : bid;
        wait_ge(&g_cnt[((sl & 1) + 2 * ((sl >> 1) / 28)) * 32], (epoch + 1) * 32);
        fence_async_global();
        if (elect()) {
          PROF(5, 16);
          mbar_expect(bars + B_XCFULL * 8, 16384);
          bulk_g2s(sb + OFF_EXCH, g_Xc + sl * 2 * S_, 16384, bars + B_XCFULL * 8);
        }
        mbar_wait(bars + B_PREPW * 8, 0);
        if (elect()) {
          mbar_expect(bars + B_WFULL * 8, 16384);
          bulk_g2s(sb + OFF_WS, g_Wt + bid * S_, 16384, bars + B_WFULL * 8);
          PROF(5, 17);
        }
      }
      mbar_wait(bars + B_PREP * 8, 0);
      if (elect()) {
        mbar_expect(bars + B_RFULL * 8, HALF_XR);
        bulk_g2s(sb + OFF_R, g_Wd + (size_t)j * WD_IMG, HALF_XR, bars + B_RFULL * 8);
        PROF(5, 19);
      }
      wait_ge(&g_cnt[5 * 32], (epoch + 1) * 128);
      fence_async_global();
      if (elect()) {
        PROF(5, 18);
        mbar_expect(bars + B_PQFULL * 8, HALF_XR + 256);
        const unsigned char* src = g_PQ + (size_t)(m * 2 + kh) * HALF_XR;
        bulk_g2s(sb + OFF_PQ, src, 28672, bars + B_PQFULL * 8);
        bulk_g2s(sb + OFF_PQ + 28672, src + 28672, 28672, bars + B_PQFULL * 8);
        bulk_g2s(sb + OFF_G, g_gate + m * 128 + kh * 64, 256, bars + B_PQFULL * 8);
      }
    }
    __syncwarp();
    asm volatile("barrier.cluster.wait.aligned;" ::: "memory");
  }
}

typedef CUresult (*EncodeFn)(CUtensorMap*, CUtensorMapDataType, cuuint32_t, void*, const cuuint64_t*, const cuuint64_t*, const cuuint32_t*,
                             const cuuint32_t*, CUtensorMapInterleave, CUtensorMapSwizzle, CUtensorMapL2promotion, CUtensorMapFloatOOBfill);

void make_map(EncodeFn enc, CUtensorMap* tm, const void* base, int cols, int rows, int bc, int br, CUtensorMapSwizzle sw) {
  cuuint64_t gd[2] = {(cuuint64_t)cols, (cuuint64_t)rows};
  cuuint64_t gs[1] = {(cuuint64_t)cols * 2};
  cuuint32_t bd[2] = {(cuuint32_t)bc, (cuuint32_t)br};
  cuuint32_t es[2] = {1, 1};
  enc(tm, CU_TENSOR_MAP_DATA_TYPE_BFLOAT16, 2, const_cast<void*>(base), gd, gs, bd, es, CU_TENSOR_MAP_INTERLEAVE_NONE, sw,
      CU_TENSOR_MAP_L2_PROMOTION_L2_128B, CU_TENSOR_MAP_FLOAT_OOB_FILL_NONE);
}

}

extern "C" void kernel_launch(void* const* d_in, const int* in_sizes, int n_in, void* d_out, int out_size) {
  (void)in_sizes; (void)n_in; (void)out_size;
  const __nv_bfloat16* x = (const __nv_bfloat16*)d_in[0];
  const __nv_bfloat16* w_r = (const __nv_bfloat16*)d_in[1];
  const __nv_bfloat16* w_i = (const __nv_bfloat16*)d_in[2];
  const __nv_bfloat16* w_gate = (const __nv_bfloat16*)d_in[4];
  const __nv_bfloat16* w_up = (const __nv_bfloat16*)d_in[5];
  const __nv_bfloat16* w_down = (const __nv_bfloat16*)d_in[6];
  const __nv_bfloat16* gate_w = (const __nv_bfloat16*)d_in[7];
  static EncodeFn enc = nullptr;
  static bool ok = false;
  if (!enc) {
    cudaDriverEntryPointQueryResult qr;
    cudaGetDriverEntryPoint("cuTensorMapEncodeTiled", (void**)&enc, cudaEnableDefault, &qr);
    cudaFuncSetAttribute(fused_kernel, cudaFuncAttributeMaxDynamicSharedMemorySize, SMEM_BYTES);
    cudaFuncAttributes fa;
    cudaFuncGetAttributes(&fa, fused_kernel);
    ok = (fa.numRegs == 128);
  }
  if (!ok) return;
  CUtensorMap tx, tg, tu, tg32, tu32;
  {
    cuuint64_t gd[3] = {64, (cuuint64_t)S_, 7};
    cuuint64_t gs[2] = {(cuuint64_t)D_ * 2, 128};
    cuuint32_t bd[3] = {64, 64, 7};
    cuuint32_t es[3] = {1, 1, 1};
    enc(&tx, CU_TENSOR_MAP_DATA_TYPE_BFLOAT16, 3, const_cast<__nv_bfloat16*>(x), gd, gs, bd, es, CU_TENSOR_MAP_INTERLEAVE_NONE, CU_TENSOR_MAP_SWIZZLE_128B,
        CU_TENSOR_MAP_L2_PROMOTION_L2_128B, CU_TENSOR_MAP_FLOAT_OOB_FILL_NONE);
  }
  make_map(enc, &tg, w_gate, F_, D_, 64, 64, CU_TENSOR_MAP_SWIZZLE_128B);
  make_map(enc, &tu, w_up, F_, D_, 64, 64, CU_TENSOR_MAP_SWIZZLE_128B);
  make_map(enc, &tg32, w_gate, F_, D_, 32, 128, CU_TENSOR_MAP_SWIZZLE_64B);
  make_map(enc, &tu32, w_up, F_, D_, 32, 128, CU_TENSOR_MAP_SWIZZLE_64B);
  fused_kernel<<<128, NTHREADS, SMEM_BYTES>>>(tx, tg, tu, tg32, tu32, w_r, w_i, w_gate, w_up, w_down, gate_w, (__nv_bfloat16*)d_out);
}
```

```cpp
#include <cuda_runtime.h>
#include <cuda_bf16.h>
#include <cuda.h>
#include <stdint.h>

namespace {

constexpr int S_ = 2048, D_ = 448, F_ = 1792;
constexpr int NTHREADS = 512;
constexpr int SLOT = 16384, NSLOT = 7;
constexpr int HALF_XR = 57344;
constexpr int OFF_PQ = NSLOT * SLOT;
constexpr int OFF_R = OFF_PQ + HALF_XR;
constexpr int OFF_EXCH = OFF_PQ;
constexpr int OFF_WS = OFF_EXCH + 18432;
constexpr int OFF_TW = OFF_WS + 16384;
constexpr int OFF_MISC = OFF_R + HALF_XR;
constexpr int OFF_G = OFF_MISC;
constexpr int OFF_BAR = OFF_MISC + 512;
constexpr int SMEM_BYTES = OFF_BAR + 512;
constexpr int B_FULL = 0, B_EMPTY = 7, B_XFULL = 14  ;
constexpr int B_XFREE = 16  , B_PUBX = 18, B_RFREE = 19, B_LFREE = 20;
constexpr int B_PUBW = 21, B_PUBD = 22;
constexpr int B_PQFULL = 23, B_RECV = 24, B_WFULL = 25, B_XCFULL = 26, B_PREP = 27, B_PREPW = 28, B_RFULL = 29, B_GFULL = 30, B_END = 31, B_PIN = 31;

constexpr int WD_IMG = 896 * 112 * 2;
constexpr int G_IMG = 224 * 56 * 2;

__device__ __align__(1024) uint32_t g_Xc[112 * 2 * S_];
__device__ __align__(1024) unsigned char g_H[32 * 56 * 4096];
__device__ __align__(1024) unsigned char g_PQ[32 * HALF_XR];
__device__ __align__(1024) unsigned char g_Wd[8 * WD_IMG];
__device__ __align__(1024) unsigned char g_G[8 * G_IMG];
__device__ __align__(1024) uint2 g_Wt[113 * S_];
__device__ __align__(1024) float g_gate[S_];
__device__ __align__(128) unsigned int g_ep[128];
__device__ __align__(128) unsigned int g_cnt[8 * 32];

#define PROF(role, idx) do {} while (0)
#define PROFG(role, idx) do {} while (0)

__device__ __forceinline__ uint32_t s2u(const void* p) { return (uint32_t)__cvta_generic_to_shared(p); }
__device__ __forceinline__ void mbar_init(uint32_t b, int c) { asm volatile("mbarrier.init.shared::cta.b64 [%0], %1;" :: "r"(b), "r"(c) : "memory"); }
__device__ __forceinline__ void mbar_expect(uint32_t b, int bytes) { asm volatile("mbarrier.arrive.expect_tx.shared::cta.b64 _, [%0], %1;" :: "r"(b), "r"(bytes) : "memory"); }
__device__ __forceinline__ void mbar_arrive(uint32_t b) { asm volatile("mbarrier.arrive.shared::cta.b64 _, [%0];" :: "r"(b) : "memory"); }
__device__ __forceinline__ void mbar_wait(uint32_t b, int ph) {
  asm volatile("{\n.reg .pred p;\n.reg .u32 c;\nmov.u32 c, 0;\nL_WAIT:\nmbarrier.try_wait.parity.shared::cta.b64 p, [%0], %1;\n@p bra.uni L_DONE;\n"
               "add.u32 c, c, 1;\nsetp.lt.u32 p, c, 4194304;\n@p bra.uni L_WAIT;\ntrap;\nL_DONE:\n}" :: "r"(b), "r"(ph) : "memory");
}
__device__ __forceinline__ void mbar_wait_cluster(uint32_t b, int ph) {
  asm volatile("{\n.reg .pred p;\n.reg .u32 c;\nmov.u32 c, 0;\nL_WAIT:\nmbarrier.try_wait.parity.acquire.cluster.shared::cta.b64 p, [%0], %1;\n@p bra.uni L_DONE;\n"
               "add.u32 c, c, 1;\nsetp.lt.u32 p, c, 4194304;\n@p bra.uni L_WAIT;\ntrap;\nL_DONE:\n}" :: "r"(b), "r"(ph) : "memory");
}
__device__ __forceinline__ uint32_t ld_acquire(const unsigned int* p) { uint32_t v; asm volatile("ld.acquire.gpu.global.u32 %0, [%1];" : "=r"(v) : "l"(p) : "memory"); return v; }
__device__ __forceinline__ uint32_t ld_relaxed(const unsigned int* p) { uint32_t v; asm volatile("ld.relaxed.gpu.global.u32 %0, [%1];" : "=r"(v) : "l"(p) : "memory"); return v; }
__device__ __forceinline__ void wait_ge(const unsigned int* p, uint32_t target) {
#pragma unroll 1
  for (int i = 0; i < (1 << 22); i++) { if ((int)(ld_acquire(p) - target) >= 0) return; }
  __trap();
}
__device__ __forceinline__ void red_release(unsigned int* p) { asm volatile("red.release.gpu.global.add.u32 [%0], 1;" :: "l"(p) : "memory"); }
__device__ __forceinline__ bool elect() { uint32_t p; asm volatile("{\n.reg .pred p;\nelect.sync _|p, 0xffffffff;\nselp.u32 %0, 1, 0, p;\n}" : "=r"(p)); return p; }
__device__ __forceinline__ void fence_async_smem() { asm volatile("fence.proxy.async.shared::cta;" ::: "memory"); }
__device__ __forceinline__ void fence_async_global() { asm volatile("fence.proxy.async.global;" ::: "memory"); }
template <int ID, int N> __device__ __forceinline__ void bar_sync() { asm volatile("bar.sync %0, %1;" :: "n"(ID), "n"(N) : "memory"); }
template <int ID, int N> __device__ __forceinline__ void bar_arrive() { asm volatile("bar.arrive %0, %1;" :: "n"(ID), "n"(N) : "memory"); }
__device__ __forceinline__ void tma2d(uint32_t dst, const CUtensorMap* tm, int c0, int c1, uint32_t bar) {
  asm volatile("cp.async.bulk.tensor.2d.shared::cluster.global.mbarrier::complete_tx::bytes [%0], [%1, {%3, %4}], [%2];"
               :: "r"(dst), "l"(tm), "r"(bar), "r"(c0), "r"(c1) : "memory");
}
__device__ __forceinline__ void tma3d(uint32_t dst, const CUtensorMap* tm, int c0, int c1, int c2, uint32_t bar) {
  asm volatile("cp.async.bulk.tensor.3d.shared::cluster.global.mbarrier::complete_tx::bytes [%0], [%1, {%3, %4, %5}], [%2];"
               :: "r"(dst), "l"(tm), "r"(bar), "r"(c0), "r"(c1), "r"(c2) : "memory");
}
__device__ __forceinline__ void bulk_g2s(uint32_t dst, const void* src, int bytes, uint32_t bar) {
  asm volatile("cp.async.bulk.shared::cluster.global.mbarrier::complete_tx::bytes [%0], [%1], %2, [%3];"
               :: "r"(dst), "l"(src), "r"(bytes), "r"(bar) : "memory");
}
__device__ __forceinline__ void prefetch_l2(const void* src, int bytes) {
  asm volatile("cp.async.bulk.prefetch.L2.global [%0], %1;" :: "l"(src), "r"(bytes) : "memory");
}
__device__ __forceinline__ void prefetch_tma2d(const CUtensorMap* tm, int c0, int c1) {
  asm volatile("cp.async.bulk.prefetch.tensor.2d.L2.global [%0, {%1, %2}];" :: "l"(tm), "r"(c0), "r"(c1) : "memory");
}
__device__ __forceinline__ uint64_t mkdesc(uint32_t addr, uint32_t lbo, uint32_t sbo, uint32_t mode) {
  return (uint64_t)((addr & 0x3FFFF) >> 4) | ((uint64_t)(lbo >> 4) << 16) | ((uint64_t)(sbo >> 4) << 32) | ((uint64_t)mode << 62);
}
__device__ __forceinline__ void wg_fence() { asm volatile("wgmma.fence.sync.aligned;" ::: "memory"); }
__device__ __forceinline__ void wg_commit() { asm volatile("wgmma.commit_group.sync.aligned;" ::: "memory"); }
template <int N> __device__ __forceinline__ void wg_wait() { asm volatile("wgmma.wait_group.sync.aligned %0;" :: "n"(N) : "memory"); }
template <int N> __device__ __forceinline__ void keep(float (&d)[N]) {
#pragma unroll
  for (int i = 0; i < N; i++) asm volatile("" : "+f"(d[i]) :: "memory");
}
__device__ __forceinline__ uint32_t pack_bf16(float lo, float hi) { uint32_t r; asm("cvt.rn.bf16x2.f32 %0, %1, %2;" : "=r"(r) : "f"(hi), "f"(lo)); return r; }
__device__ __forceinline__ float bf16_round(float v) { return __bfloat162float(__float2bfloat16_rn(v)); }
__device__ __forceinline__ void sts128(uint32_t a, uint32_t x, uint32_t y, uint32_t z, uint32_t w) { asm volatile("st.shared.v4.b32 [%0], {%1,%2,%3,%4};" :: "r"(a), "r"(x), "r"(y), "r"(z), "r"(w) : "memory"); }
__device__ __forceinline__ float4 lds128f(uint32_t a) { float4 v; asm volatile("ld.shared.v4.f32 {%0,%1,%2,%3}, [%4];" : "=f"(v.x), "=f"(v.y), "=f"(v.z), "=f"(v.w) : "r"(a) : "memory"); return v; }

__device__ __forceinline__ uint2 lds64(uint32_t a) { uint2 v; asm volatile("ld.shared.v2.b32 {%0,%1}, [%2];" : "=r"(v.x), "=r"(v.y) : "r"(a) : "memory"); return v; }
__device__ __forceinline__ float bf_lo(uint32_t w) { return __uint_as_float(w << 16); }
__device__ __forceinline__ float bf_hi(uint32_t w) { return __uint_as_float(w & 0xffff0000u); }
__device__ __forceinline__ uint32_t opaque(uint32_t v) { asm volatile("" : "+r"(v)); return v; }
__device__ __forceinline__ uint4 ldg128(const void* p) { uint4 v; asm volatile("ld.global.nc.v4.b32 {%0,%1,%2,%3}, [%4];" : "=r"(v.x), "=r"(v.y), "=r"(v.z), "=r"(v.w) : "l"(p)); return v; }
__device__ __forceinline__ void stg128(void* p, uint32_t x, uint32_t y, uint32_t z, uint32_t w) { asm volatile("st.global.v4.b32 [%0], {%1,%2,%3,%4};" :: "l"(p), "r"(x), "r"(y), "r"(z), "r"(w) : "memory"); }
__device__ __forceinline__ void stg128_l2(void* p, uint32_t x, uint32_t y, uint32_t z, uint32_t w) { asm volatile("st.relaxed.gpu.global.v4.b32 [%0], {%1,%2,%3,%4};" :: "l"(p), "r"(x), "r"(y), "r"(z), "r"(w) : "memory"); }
__device__ __forceinline__ uint2 ldg64_l2(const void* p) { uint2 v; asm volatile("ld.relaxed.gpu.global.v2.b32 {%0,%1}, [%2];" : "=r"(v.x), "=r"(v.y) : "l"(p) : "memory"); return v; }
__device__ __forceinline__ void ldg128_l2(uint32_t (&v)[4], const void* p) { asm volatile("ld.relaxed.gpu.global.v4.b32 {%0,%1,%2,%3}, [%4];" : "=r"(v[0]), "=r"(v[1]), "=r"(v[2]), "=r"(v[3]) : "l"(p) : "memory"); }
__device__ __forceinline__ uint4 lds128(uint32_t a) { uint4 v; asm volatile("ld.shared.v4.b32 {%0,%1,%2,%3}, [%4];" : "=r"(v.x), "=r"(v.y), "=r"(v.z), "=r"(v.w) : "r"(a) : "memory"); return v; }
__device__ __forceinline__ uint32_t lds16(uint32_t a) { uint32_t v; asm volatile("ld.shared.u16 %0, [%1];" : "=r"(v) : "r"(a) : "memory"); return v; }
__device__ __forceinline__ void sts64(uint32_t a, uint32_t x, uint32_t y) { asm volatile("st.shared.v2.b32 [%0], {%1,%2};" :: "r"(a), "r"(x), "r"(y) : "memory"); }
template <int TB> __device__ __forceinline__ void wgmma_rs_128(float (&d)[64], const uint32_t (&a)[4], uint64_t db, int sc) {
  asm volatile("{\n.reg .pred p;\nsetp.ne.b32 p, %69, 0;\n"
    "wgmma.mma_async.sync.aligned.m64n128k16.f32.bf16.bf16 {%0, %1, %2, %3, %4, %5, %6, %7, %8, %9, %10, %11, %12, %13, %14, %15, %16, %17, %18, %19, %20, %21, %22, %23, %24, %25, %26, %27, %28, %29, %30, %31, %32, %33, %34, %35, %36, %37, %38, %39, %40, %41, %42, %43, %44, %45, %46, %47, %48, %49, %50, %51, %52, %53, %54, %55, %56, %57, %58, %59, %60, %61, %62, %63}, {%64, %65, %66, %67}, %68, p, 1, 1, %70;\n}\n"
    : "+f"(d[0]), "+f"(d[1]), "+f"(d[2]), "+f"(d[3]), "+f"(d[4]), "+f"(d[5]), "+f"(d[6]), "+f"(d[7]), "+f"(d[8]), "+f"(d[9]), "+f"(d[10]), "+f"(d[11]), "+f"(d[12]), "+f"(d[13]), "+f"(d[14]), "+f"(d[15]), "+f"(d[16]), "+f"(d[17]), "+f"(d[18]), "+f"(d[19]), "+f"(d[20]), "+f"(d[21]), "+f"(d[22]), "+f"(d[23]), "+f"(d[24]), "+f"(d[25]), "+f"(d[26]), "+f"(d[27]), "+f"(d[28]), "+f"(d[29]), "+f"(d[30]), "+f"(d[31]), "+f"(d[32]), "+f"(d[33]), "+f"(d[34]), "+f"(d[35]), "+f"(d[36]), "+f"(d[37]), "+f"(d[38]), "+f"(d[39]), "+f"(d[40]), "+f"(d[41]), "+f"(d[42]), "+f"(d[43]), "+f"(d[44]), "+f"(d[45]), "+f"(d[46]), "+f"(d[47]), "+f"(d[48]), "+f"(d[49]), "+f"(d[50]), "+f"(d[51]), "+f"(d[52]), "+f"(d[53]), "+f"(d[54]), "+f"(d[55]), "+f"(d[56]), "+f"(d[57]), "+f"(d[58]), "+f"(d[59]), "+f"(d[60]), "+f"(d[61]), "+f"(d[62]), "+f"(d[63])
    : "r"(a[0]), "r"(a[1]), "r"(a[2]), "r"(a[3]), "l"(db), "r"(sc), "n"(TB));
}
template <int TB> __device__ __forceinline__ void wgmma_rs_64(float (&d)[32], const uint32_t (&a)[4], uint64_t db, int sc) {
  asm volatile("{\n.reg .pred p;\nsetp.ne.b32 p, %37, 0;\n"
    "wgmma.mma_async.sync.aligned.m64n64k16.f32.bf16.bf16 {%0, %1, %2, %3, %4, %5, %6, %7, %8, %9, %10, %11, %12, %13, %14, %15, %16, %17, %18, %19, %20, %21, %22, %23, %24, %25, %26, %27, %28, %29, %30, %31}, {%32, %33, %34, %35}, %36, p, 1, 1, %38;\n}\n"
    : "+f"(d[0]), "+f"(d[1]), "+f"(d[2]), "+f"(d[3]), "+f"(d[4]), "+f"(d[5]), "+f"(d[6]), "+f"(d[7]), "+f"(d[8]), "+f"(d[9]), "+f"(d[10]), "+f"(d[11]), "+f"(d[12]), "+f"(d[13]), "+f"(d[14]), "+f"(d[15]), "+f"(d[16]), "+f"(d[17]), "+f"(d[18]), "+f"(d[19]), "+f"(d[20]), "+f"(d[21]), "+f"(d[22]), "+f"(d[23]), "+f"(d[24]), "+f"(d[25]), "+f"(d[26]), "+f"(d[27]), "+f"(d[28]), "+f"(d[29]), "+f"(d[30]), "+f"(d[31])
    : "r"(a[0]), "r"(a[1]), "r"(a[2]), "r"(a[3]), "l"(db), "r"(sc), "n"(TB));
}
template <int TB> __device__ __forceinline__ void wgmma_rs_56(float (&d)[28], const uint32_t (&a)[4], uint64_t db, int sc) {
  asm volatile("{\n.reg .pred p;\nsetp.ne.b32 p, %33, 0;\n"
    "wgmma.mma_async.sync.aligned.m64n56k16.f32.bf16.bf16 {%0, %1, %2, %3, %4, %5, %6, %7, %8, %9, %10, %11, %12, %13, %14, %15, %16, %17, %18, %19, %20, %21, %22, %23, %24, %25, %26, %27}, {%28, %29, %30, %31}, %32, p, 1, 1, %34;\n}\n"
    : "+f"(d[0]), "+f"(d[1]), "+f"(d[2]), "+f"(d[3]), "+f"(d[4]), "+f"(d[5]), "+f"(d[6]), "+f"(d[7]), "+f"(d[8]), "+f"(d[9]), "+f"(d[10]), "+f"(d[11]), "+f"(d[12]), "+f"(d[13]), "+f"(d[14]), "+f"(d[15]), "+f"(d[16]), "+f"(d[17]), "+f"(d[18]), "+f"(d[19]), "+f"(d[20]), "+f"(d[21]), "+f"(d[22]), "+f"(d[23]), "+f"(d[24]), "+f"(d[25]), "+f"(d[26]), "+f"(d[27])
    : "r"(a[0]), "r"(a[1]), "r"(a[2]), "r"(a[3]), "l"(db), "r"(sc), "n"(TB));
}
template <int TB> __device__ __forceinline__ void wgmma_rs_112(float (&d)[56], const uint32_t (&a)[4], uint64_t db, int sc) {
  asm volatile("{\n.reg .pred p;\nsetp.ne.b32 p, %61, 0;\n"
    "wgmma.mma_async.sync.aligned.m64n112k16.f32.bf16.bf16 {%0, %1, %2, %3, %4, %5, %6, %7, %8, %9, %10, %11, %12, %13, %14, %15, %16, %17, %18, %19, %20, %21, %22, %23, %24, %25, %26, %27, %28, %29, %30, %31, %32, %33, %34, %35, %36, %37, %38, %39, %40, %41, %42, %43, %44, %45, %46, %47, %48, %49, %50, %51, %52, %53, %54, %55}, {%56, %57, %58, %59}, %60, p, 1, 1, %62;\n}\n"
    : "+f"(d[0]), "+f"(d[1]), "+f"(d[2]), "+f"(d[3]), "+f"(d[4]), "+f"(d[5]), "+f"(d[6]), "+f"(d[7]), "+f"(d[8]), "+f"(d[9]), "+f"(d[10]), "+f"(d[11]), "+f"(d[12]), "+f"(d[13]), "+f"(d[14]), "+f"(d[15]), "+f"(d[16]), "+f"(d[17]), "+f"(d[18]), "+f"(d[19]), "+f"(d[20]), "+f"(d[21]), "+f"(d[22]), "+f"(d[23]), "+f"(d[24]), "+f"(d[25]), "+f"(d[26]), "+f"(d[27]), "+f"(d[28]), "+f"(d[29]), "+f"(d[30]), "+f"(d[31]), "+f"(d[32]), "+f"(d[33]), "+f"(d[34]), "+f"(d[35]), "+f"(d[36]), "+f"(d[37]), "+f"(d[38]), "+f"(d[39]), "+f"(d[40]), "+f"(d[41]), "+f"(d[42]), "+f"(d[43]), "+f"(d[44]), "+f"(d[45]), "+f"(d[46]), "+f"(d[47]), "+f"(d[48]), "+f"(d[49]), "+f"(d[50]), "+f"(d[51]), "+f"(d[52]), "+f"(d[53]), "+f"(d[54]), "+f"(d[55])
    : "r"(a[0]), "r"(a[1]), "r"(a[2]), "r"(a[3]), "l"(db), "r"(sc), "n"(TB));
}
template <int TA, int TB> __device__ __forceinline__ void wgmma_ss_56(float (&d)[28], uint64_t da, uint64_t db, int sc) {
  asm volatile("{\n.reg .pred p;\nsetp.ne.b32 p, %30, 0;\n"
    "wgmma.mma_async.sync.aligned.m64n56k16.f32.bf16.bf16 {%0, %1, %2, %3, %4, %5, %6, %7, %8, %9, %10, %11, %12, %13, %14, %15, %16, %17, %18, %19, %20, %21, %22, %23, %24, %25, %26, %27}, %28, %29, p, 1, 1, %31, %32;\n}\n"
    : "+f"(d[0]), "+f"(d[1]), "+f"(d[2]), "+f"(d[3]), "+f"(d[4]), "+f"(d[5]), "+f"(d[6]), "+f"(d[7]), "+f"(d[8]), "+f"(d[9]), "+f"(d[10]), "+f"(d[11]), "+f"(d[12]), "+f"(d[13]), "+f"(d[14]), "+f"(d[15]), "+f"(d[16]), "+f"(d[17]), "+f"(d[18]), "+f"(d[19]), "+f"(d[20]), "+f"(d[21]), "+f"(d[22]), "+f"(d[23]), "+f"(d[24]), "+f"(d[25]), "+f"(d[26]), "+f"(d[27])
    : "l"(da), "l"(db), "r"(sc), "n"(TA), "n"(TB));
}

__device__ __forceinline__ uint32_t cis(float a) { return pack_bf16(__cosf(a), __sinf(a)); }

typedef __nv_bfloat162 b2;
struct c2 { b2 x, y; };
__device__ __forceinline__ b2 as_b2(uint32_t u) { return *reinterpret_cast<b2*>(&u); }
__device__ __forceinline__ uint32_t as_u(b2 v) { return *reinterpret_cast<uint32_t*>(&v); }
__device__ __forceinline__ c2 mk(b2 x, b2 y) { c2 r; r.x = x; r.y = y; return r; }
__device__ __forceinline__ c2 cmul(c2 a, b2 wr, b2 wi) { return mk(__hfma2(a.x, wr, __hneg2(__hmul2(a.y, wi))), __hfma2(a.x, wi, __hmul2(a.y, wr))); }
__device__ __forceinline__ void fft4(c2& a0, c2& a1, c2& a2, c2& a3) {
  c2 t0 = mk(__hadd2(a0.x, a2.x), __hadd2(a0.y, a2.y)), t1 = mk(__hsub2(a0.x, a2.x), __hsub2(a0.y, a2.y));
  c2 t2 = mk(__hadd2(a1.x, a3.x), __hadd2(a1.y, a3.y)), t3 = mk(__hsub2(a1.x, a3.x), __hsub2(a1.y, a3.y));
  a0 = mk(__hadd2(t0.x, t2.x), __hadd2(t0.y, t2.y)); a2 = mk(__hsub2(t0.x, t2.x), __hsub2(t0.y, t2.y));
  a1 = mk(__hadd2(t1.x, t3.y), __hsub2(t1.y, t3.x)); a3 = mk(__hsub2(t1.x, t3.y), __hadd2(t1.y, t3.x));
}
__device__ __forceinline__ void fft4_s2(c2& a0, c2& a1, c2& a2, c2& a3, b2 r) {
  const b2 nr = __hneg2(r);
  c2 t0 = mk(__hfma2(a2.x, r, a0.x), __hfma2(a2.y, r, a0.y)), t1 = mk(__hfma2(a2.x, nr, a0.x), __hfma2(a2.y, nr, a0.y));
  c2 t2 = mk(__hadd2(a1.x, a3.x), __hadd2(a1.y, a3.y)), t3 = mk(__hsub2(a1.x, a3.x), __hsub2(a1.y, a3.y));
  a0 = mk(__hadd2(t0.x, t2.x), __hadd2(t0.y, t2.y)); a2 = mk(__hsub2(t0.x, t2.x), __hsub2(t0.y, t2.y));
  a1 = mk(__hadd2(t1.x, t3.y), __hsub2(t1.y, t3.x)); a3 = mk(__hsub2(t1.x, t3.y), __hadd2(t1.y, t3.x));
}
__device__ __forceinline__ void fft4_s13(c2& a0, c2& a1, c2& a2, c2& a3, b2 r) {
  const b2 nr = __hneg2(r);
  c2 t0 = mk(__hadd2(a0.x, a2.x), __hadd2(a0.y, a2.y)), t1 = mk(__hsub2(a0.x, a2.x), __hsub2(a0.y, a2.y));
  c2 t2 = mk(__hadd2(a1.x, a3.x), __hadd2(a1.y, a3.y)), t3 = mk(__hsub2(a1.x, a3.x), __hsub2(a1.y, a3.y));
  a0 = mk(__hfma2(t2.x, r, t0.x), __hfma2(t2.y, r, t0.y)); a2 = mk(__hfma2(t2.x, nr, t0.x), __hfma2(t2.y, nr, t0.y));
  a1 = mk(__hfma2(t3.y, r, t1.x), __hfma2(t3.x, nr, t1.y)); a3 = mk(__hfma2(t3.y, nr, t1.x), __hfma2(t3.x, r, t1.y));
}
__device__ __forceinline__ c2 rot1(c2 a) { return mk(__hadd2(a.x, a.y), __hsub2(a.y, a.x)); }
__device__ __forceinline__ c2 rot3(c2 a) { return mk(__hsub2(a.y, a.x), __hneg2(__hadd2(a.x, a.y))); }
__device__ __forceinline__ c2 mul_mi(c2 a) { return mk(a.y, __hneg2(a.x)); }
template <int O> __device__ __forceinline__ void fft8(c2 (&v)[16]) {
  const b2 r = as_b2(0x3F353F35u), nr = as_b2(0xBF35BF35u);
  fft4(v[O], v[O + 4], v[O + 8], v[O + 12]);
  fft4(v[O + 2], v[O + 6], v[O + 10], v[O + 14]);
  const c2 o0 = v[O + 2], o1 = rot1(v[O + 6]), o2 = v[O + 10], o3 = rot1(v[O + 14]);
  const c2 e0 = v[O], e1 = v[O + 4], e2 = v[O + 8], e3 = v[O + 12];
  v[O] = mk(__hadd2(e0.x, o0.x), __hadd2(e0.y, o0.y));              v[O + 8] = mk(__hsub2(e0.x, o0.x), __hsub2(e0.y, o0.y));
  v[O + 2] = mk(__hfma2(o1.x, r, e1.x), __hfma2(o1.y, r, e1.y));    v[O + 10] = mk(__hfma2(o1.x, nr, e1.x), __hfma2(o1.y, nr, e1.y));
  v[O + 4] = mk(__hadd2(e2.x, o2.y), __hsub2(e2.y, o2.x));          v[O + 12] = mk(__hsub2(e2.x, o2.y), __hadd2(e2.y, o2.x));
  v[O + 6] = mk(__hfma2(o3.y, r, e3.x), __hfma2(o3.x, nr, e3.y));   v[O + 14] = mk(__hfma2(o3.y, nr, e3.x), __hfma2(o3.x, r, e3.y));
}
__device__ __forceinline__ void fft16(c2 (&v)[16]) {
  const b2 r = as_b2(0x3F353F35u), c1 = as_b2(0x3F6D3F6Du), s1 = as_b2(0x3EC43EC4u), nc1 = as_b2(0xBF6DBF6Du), ns1 = as_b2(0xBEC4BEC4u);
#pragma unroll
  for (int a = 0; a < 4; a++) fft4(v[a], v[a + 4], v[a + 8], v[a + 12]);
  v[5] = cmul(v[5], c1, ns1); v[6] = rot1(v[6]); v[7] = cmul(v[7], s1, nc1);
  v[9] = rot1(v[9]); v[10] = mul_mi(v[10]); v[11] = rot3(v[11]);
  v[13] = cmul(v[13], s1, nc1); v[14] = rot3(v[14]); v[15] = cmul(v[15], nc1, s1);
  fft4(v[0], v[1], v[2], v[3]); fft4_s2(v[4], v[5], v[6], v[7], r); fft4_s13(v[8], v[9], v[10], v[11], r); fft4_s2(v[12], v[13], v[14], v[15], r);
  c2 t;
  t = v[1]; v[1] = v[4]; v[4] = t;  t = v[2]; v[2] = v[8]; v[8] = t;  t = v[3]; v[3] = v[12]; v[12] = t;
  t = v[6]; v[6] = v[9]; v[9] = t;  t = v[7]; v[7] = v[13]; v[13] = t; t = v[11]; v[11] = v[14]; v[14] = t;
}

__device__ __forceinline__ void columns(c2 (&v)[16], uint32_t sb, int t) {
  const int l16 = t & 15;
  const uint32_t row = sb + OFF_EXCH + (t >> 4) * 2304;
  const uint32_t pos = sb + OFF_EXCH + (t >> 3) * 144 + (t & 7) * 16;
#pragma unroll 1
  for (int ps = 0; ps < 6; ps++) {
    if (ps == 0 || ps == 5) { fft8<0>(v); fft8<1>(v); } else fft16(v);
    if (ps == 5) break;
    if (ps == 2) {
      const uint32_t ws = sb + OFF_WS + (l16 >> 1) * 128 + ((((t >> 4) + (l16 >> 1)) & 7) * 2 + (l16 & 1)) * 8;
      mbar_wait(sb + OFF_BAR + B_WFULL * 8, 0);
#pragma unroll
      for (int q = 0; q < 16; q++) {
        const uint2 w = lds64(ws + q * 1024);
        const c2 z = cmul(v[q], as_b2(w.x), as_b2(w.y));
        v[q] = mk(z.y, z.x);
      }
      continue;
    }
    {
      const bool full = ps == 0 || ps == 4;
      const uint32_t tw = sb + OFF_TW + (full ? ps * 2048 + t * 16 : 16384 + l16 * 16);
      const uint32_t st = full ? 2048 : 256;
#pragma unroll
      for (int i = 0; i < 4; i++) {
        const uint4 w4 = lds128(tw + i * st);
        const uint32_t w[4] = {w4.x, w4.y, w4.z, w4.w};
#pragma unroll
        for (int e = 0; e < 4; e++) v[4 * i + e] = cmul(v[4 * i + e], __low2bfloat162(as_b2(w[e])), __high2bfloat162(as_b2(w[e])));
      }
    }
    if (ps == 0) {
      bar_sync<3, 128>();
#pragma unroll
      for (int q = 0; q < 8; q++) sts128(pos + q * 2304, as_u(v[2 * q].x), as_u(v[2 * q].y), as_u(v[2 * q + 1].x), as_u(v[2 * q + 1].y));
      bar_sync<3, 128>();
#pragma unroll
      for (int q = 0; q < 16; q++) { const uint2 a = lds64(row + q * 144 + l16 * 8); v[q] = mk(as_b2(a.x), as_b2(a.y)); }
    } else {
      __syncwarp();
#pragma unroll
      for (int q = 0; q < 16; q++) sts64(row + q * 144 + l16 * 8, as_u(v[q].x), as_u(v[q].y));
      if (ps == 4) bar_sync<3, 128>(); else __syncwarp();
      const uint32_t src = ps == 4 ? pos : row + l16 * 144, st = ps == 4 ? 2304 : 16;
#pragma unroll
      for (int q = 0; q < 8; q++) { const uint4 a = lds128(src + q * st); v[2 * q] = mk(as_b2(a.x), as_b2(a.y)); v[2 * q + 1] = mk(as_b2(a.z), as_b2(a.w)); }
    }
  }
}

template <int NH> __device__ __forceinline__ void h_epilogue(float (&acc)[NH * 8], unsigned char* gdst, uint32_t tag) {
#pragma unroll
  for (int c = 0; c < NH / 2; c++) {
    uint32_t pk[4];
#pragma unroll
    for (int i = 0; i < 4; i++) {
      float hv[2];
#pragma unroll
      for (int e = 0; e < 2; e++) {
        float hg = 0.5f * acc[c * 8 + i * 2 + e], up = acc[NH * 4 + c * 8 + i * 2 + e];
        float th; asm("tanh.approx.f32 %0, %1;" : "=f"(th) : "f"(hg));
        hv[e] = fmaf(hg, th, hg) * up;
      }
      pk[i] = pack_bf16(hv[0], hv[1]);
    }
    stg128_l2(gdst + c * 4096, (pk[0] & ~1u) | tag, pk[1], pk[2], pk[3]);
  }
}

__device__ __forceinline__ void frag_ready(uint32_t (&a)[4], uint32_t (&b)[4], uint32_t (&c)[4], uint32_t (&d)[4], const unsigned char* p, uint32_t tag) {
  asm volatile("{\n.reg .pred p;\n.reg .u32 c, m, q;\nmov.u32 c, 0;\nL_TRY:\n"
               "lop3.b32 m, %0, %4, %17, 0x7E;\nlop3.b32 q, %8, %12, %17, 0x7E;\nlop3.b32 m, m, q, 1, 0xA8;\nsetp.ne.u32 p, m, 0;\n"
               "vote.sync.any.pred p, p, 0xffffffff;\n@!p bra.uni L_OK;\n"
               "ld.relaxed.gpu.global.v4.b32 {%0,%1,%2,%3}, [%16];\nld.relaxed.gpu.global.v4.b32 {%4,%5,%6,%7}, [%16+4096];\n"
               "ld.relaxed.gpu.global.v4.b32 {%8,%9,%10,%11}, [%16+8192];\nld.relaxed.gpu.global.v4.b32 {%12,%13,%14,%15}, [%16+12288];\n"
               "add.u32 c, c, 1;\nsetp.lt.u32 p, c, 262144;\n@p bra.uni L_TRY;\ntrap;\nL_OK:\n}"
               : "+r"(a[0]), "+r"(a[1]), "+r"(a[2]), "+r"(a[3]), "+r"(b[0]), "+r"(b[1]), "+r"(b[2]), "+r"(b[3]),
                 "+r"(c[0]), "+r"(c[1]), "+r"(c[2]), "+r"(c[3]), "+r"(d[0]), "+r"(d[1]), "+r"(d[2]), "+r"(d[3])
               : "l"(p), "r"(tag) : "memory");
}

#define MAP 0
#define LEAD2 0
#define LEAD1 3

__global__ void __cluster_dims__(2, 1, 1) __launch_bounds__(NTHREADS, 1)
fused_kernel(const __grid_constant__ CUtensorMap tm_x, const __grid_constant__ CUtensorMap tm_g, const __grid_constant__ CUtensorMap tm_u,
             const __grid_constant__ CUtensorMap tm_g32, const __grid_constant__ CUtensorMap tm_u32,
             const __nv_bfloat16* __restrict__ w_r, const __nv_bfloat16* __restrict__ w_i,
             const __nv_bfloat16* __restrict__ w_gate, const __nv_bfloat16* __restrict__ w_up,
             const __nv_bfloat16* __restrict__ w_down, const __nv_bfloat16* __restrict__ gate_w, __nv_bfloat16* __restrict__ out) {
  extern __shared__ __align__(1024) unsigned char smem[];
  const uint32_t sb = s2u(smem);
  const uint32_t bars = sb + OFF_BAR;
  const int tid = threadIdx.x, warp = __shfl_sync(0xffffffffu, tid >> 5, 0), lane = tid & 31;
  const int cl = blockIdx.x >> 1, kh = blockIdx.x & 1;
  const int n0 = cl < 4 ? cl : (cl < 36 ? (cl - 4) >> 3 : (cl - 36) / 7);
  const int m0 = cl < 4 ? 15 : (cl < 36 ? (cl - 4) & 7 : cl - 28 - 7 * n0);
  const int n = MAP == 0 ? n0 : (MAP == 1 ? (m0 & 3) : ((n0 & 1) | ((m0 & 1) << 1)));
  const int m = MAP == 0 ? m0 : (MAP == 1 ? ((m0 & 12) | n0) : ((m0 & 14) | (n0 >> 1)));
  const int j = kh * 4 + n, bid = m * 8 + n * 2 + kh;

  const int c64 = 224 * j + (j & 1) * 32;
  if (warp < 8) {
    asm volatile("setmaxnreg.inc.sync.aligned.u32 208;");
    const int wg = warp >> 2, w4 = warp & 3, g = lane >> 2, t = lane & 3;
    const int rh = wg ^ kh ^ 1;
    const int p = j & 1, r = (j >> 1) & 1, hh = j >> 2;
    const uint32_t epoch = ld_relaxed(&g_ep[bid]);
    if ((tid & 127) == 0) PROF(wg, 30);
#pragma unroll 1
    for (int it = tid; it < 392; it += 256) {
      const int kc = it / 28, sg = it - kc * 28;
      const int k = 2 * (28 * hh + sg) + r;
      const float kf = (float)k * (-6.283185307179586f / 448.0f), a0 = (float)(16 * kc + p) * kf;
      uint32_t c[4], s[4];
#pragma unroll
      for (int q = 0; q < 4; q++) {
        const float a1 = fmaf((float)(2 * q), kf, a0), a2 = fmaf((float)(2 * q + 8), kf, a0);
        c[q] = pack_bf16(__cosf(a1), __cosf(a2)); s[q] = pack_bf16(__sinf(a1), __sinf(a2));
        if (k == 0) s[q] = ((q ^ p) & 1) ? 0xBF80BF80u : 0x3F803F80u;
      }
      const uint32_t a = sb + 6 * SLOT + (kc * 56 + 2 * sg) * 16;
      sts128(a, c[0], c[1], c[2], c[3]);
      sts128(a + 16, s[0], s[1], s[2], s[3]);
    }
    if ((tid & 127) == 0) PROF(wg, 31);
    fence_async_smem();
    bar_sync<0, NTHREADS - 64>();
    asm volatile("barrier.cluster.arrive.relaxed.aligned;" ::: "memory");
    if ((tid & 127) == 0) PROF(wg, 1);

    uint32_t xa[28][4];
    {
      const uint32_t xb = sb + OFF_PQ + wg * HALF_XR + (w4 * 16 + (lane & 15)) * 128;
      mbar_wait(bars + (B_XFULL + wg) * 8, 0);
      if ((tid & 127) == 0) PROF(wg, 2);
#pragma unroll
      for (int kb = 0; kb < 7; kb++) {
#pragma unroll
        for (int kk = 0; kk < 4; kk++) {
          uint32_t a = xb + kb * 8192 + (((2 * kk + (lane >> 4)) ^ (lane & 7)) << 4);
          asm volatile("ldmatrix.sync.aligned.m8n8.x4.shared.b16 {%0,%1,%2,%3}, [%4];"
                       : "=r"(xa[kb * 4 + kk][0]), "=r"(xa[kb * 4 + kk][1]), "=r"(xa[kb * 4 + kk][2]), "=r"(xa[kb * 4 + kk][3]) : "r"(a) : "memory");
        }
      }
    }
    {
      uint32_t ad[7][4];
      const uint32_t sel = p ? 0x7632 : 0x5410;
      const uint32_t sgn = r ? 0xBF80BF80u : 0x3F803F80u;
#pragma unroll
      for (int jj = 0; jj < 7; jj++) {
#pragma unroll
        for (int i = 0; i < 4; i++) {
          int ks = 2 * jj + (i >> 1), rr = i & 1;
          uint32_t lo = __byte_perm(xa[ks][rr], xa[ks][rr + 2], sel);
          uint32_t hi = __byte_perm(xa[ks + 14][rr], xa[ks + 14][rr + 2], sel);
          asm("fma.rn.bf16x2 %0, %1, %2, %3;" : "=r"(ad[jj][i]) : "r"(hi), "r"(sgn), "r"(lo));
        }
      }
      __syncwarp();
      if (lane == 0) mbar_arrive(bars + (B_XFREE + wg) * 8);
      float acc[28];
      wg_fence();
      uint64_t db = mkdesc(sb + 6 * SLOT, 896, 128, 0);
#pragma unroll
      for (int jj = 0; jj < 7; jj++) wgmma_rs_56<0>(acc, ad[jj], db + jj * 112, jj != 0);
      wg_commit();
      wg_wait<0>(); keep(acc);
      if (lane == 0) mbar_arrive(bars + (B_EMPTY + 6) * 8);
      uint32_t* xc = g_Xc + (size_t)((2 * (28 * hh + t) + r) * 2 + p) * S_ + m * 128 + rh * 64 + w4 * 16 + g;
#pragma unroll
      for (int i = 0; i < 7; i++) {
        xc[i * 16 * S_] = pack_bf16(acc[4 * i], acc[4 * i + 1]);
        xc[i * 16 * S_ + 8] = pack_bf16(acc[4 * i + 2], acc[4 * i + 3]);
      }
      __syncwarp();
      if (lane == 0) mbar_arrive(bars + B_PUBX * 8);
    }
    if ((tid & 127) == 0) PROF(wg, 3);
    const uint32_t tag = ~epoch & 1;
    unsigned char* const hbase = g_H + (size_t)(m * 2 + kh) * (56 * 4096) + rh * 2048 + (tid & 127) * 16;
#pragma unroll 1
    for (int u = 0; u < 3; u++) {
      float acc[64];
      if (wg == 1) { if (u & 1) bar_sync<6, 256>(); else bar_sync<2, 256>(); }
      const uint32_t sbu = opaque(sb);
#pragma unroll
      for (int kb = 0; kb < 7; kb++) {
        mbar_wait(sbu + OFF_BAR + (B_FULL + kb) * 8, u & 1);
        wg_fence();
        uint64_t db = mkdesc(sbu + kb * SLOT, 8192, 1024, 1);
#pragma unroll
        for (int kk = 0; kk < 4; kk++) wgmma_rs_128<1>(acc, xa[kb * 4 + kk], db + kk * 128, (kb | kk) != 0);
        wg_commit();
        if (kb == LEAD1 && wg == 0) { if (u & 1) bar_arrive<6, 256>(); else bar_arrive<2, 256>(); }
        if (kb > 0) { wg_wait<1>(); if (lane == 0) mbar_arrive(sbu + OFF_BAR + (B_EMPTY + kb - 1) * 8); }
      }
      wg_wait<0>(); keep(acc);
      if (lane == 0) mbar_arrive(sbu + OFF_BAR + (B_EMPTY + 6) * 8);
      if ((tid & 127) == 0) PROF(wg, 4 + 2 * u);
      h_epilogue<8>(acc, hbase + (u * 16 + n * 4) * 4096, tag);
      if ((tid & 127) == 0) PROF(wg, 5 + 2 * u);
    }
    uint32_t ha[14][4][4];
    auto check = [&](int b0, int b1) {
#pragma unroll
      for (int b = b0; b < b1; b++) frag_ready(ha[b][0], ha[b][1], ha[b][2], ha[b][3], hbase + b * 16384, tag);
    };
    auto load = [&](int b0, int b1) {
#pragma unroll
      for (int i = b0 * 4; i < b1 * 4; i++) ldg128_l2(ha[i >> 2][i & 3], hbase + i * 4096);
    };
    {
      float acc[32];
      load(0, 2);
      if (wg == 1) bar_sync<6, 256>();
      const uint32_t sbu = opaque(sb);
#pragma unroll
      for (int it = 0; it < 4; it++) {
        mbar_wait(sbu + OFF_BAR + (B_FULL + it) * 8, 1);
        wg_fence();
        uint64_t db = mkdesc(sbu + it * SLOT, 8192, 512, 2);
#pragma unroll
        for (int kk = 0; kk < 8; kk++) if (it * 8 + kk < 28) wgmma_rs_64<1>(acc, xa[it * 8 + kk], db + kk * 64, (it | kk) != 0);
        wg_commit();
        if (it == 2 && wg == 0) bar_arrive<6, 256>();
        if (it > 0) {
          wg_wait<1>();
          if (lane == 0) mbar_arrive(sbu + OFF_BAR + (B_EMPTY + it - 1) * 8);
          if (it == 1) load(2, 4);
          if (it == 2) load(4, 5);
        }
      }
      wg_wait<0>(); keep(acc);
      if (lane == 0) mbar_arrive(sbu + OFF_BAR + (B_EMPTY + 3) * 8);
      if ((tid & 127) == 0) PROF(wg, 10);
      h_epilogue<4>(acc, hbase + (48 + n * 2) * 4096, tag);
    }
    asm volatile("barrier.cluster.wait.aligned;" ::: "memory");
    if ((tid & 127) == 0) PROF(wg, 11);

    float acc[56];
    check(0, 5);
    if (wg == 1) bar_sync<2, 256>();
#pragma unroll
    for (int b = 0; b < 14; b++) {
      if ((tid & 127) == 0) PROF(wg, 16 + b);
      if (b >= 4) mbar_wait(bars + (B_FULL + b % 7) * 8, b < 7);
      else if (b == 0) mbar_wait(bars + B_RFULL * 8, 1);
      if (b == 5) check(5, 8);
      if (b == 8) check(8, 12);
      if (b == 12) check(12, 14);
      wg_fence();
      const uint64_t db = mkdesc(b < 4 ? sb + OFF_R + b * 14336 : sb + b % 7 * SLOT, 1792, 128, 0);
#pragma unroll
      for (int kk = 0; kk < 4; kk++) wgmma_rs_112<1>(acc, ha[b][kk], db + kk * 224, (b | kk) != 0);
      wg_commit();
      if (b == LEAD2 && wg == 0) bar_arrive<2, 256>();
      if (b == 0) load(5, 7);
      if (b == 2) load(7, 8);
      if (b == 5) load(8, 10);
      if (b == 6) load(10, 12);
      if (b == 8 || b == 9) load(b + 4, b + 5);
      if (b > 0) wg_wait<1>();
      if (lane == 0) {
        if (b >= 5 && b <= 9) mbar_arrive(bars + (B_EMPTY + (b + 6) % 7) * 8);
        if (b == 4) {
          mbar_arrive(bars + B_LFREE * 8);
          asm volatile("{\n.reg .b32 ra;\nmapa.shared::cluster.u32 ra, %0, %1;\nmbarrier.arrive.relaxed.cluster.shared::cluster.b64 _, [ra];\n}"
                       :: "r"(bars + B_RFREE * 8), "r"(kh ^ 1) : "memory");
        }
      }
    }
    const int t128 = tid & 127;
    wg_wait<0>(); keep(acc);
    if (wg == 0) {
      if (t128 == 0) PROF(wg, 12);
      mbar_wait_cluster(bars + B_RFREE * 8, 0);
      uint32_t rdst, rbar;
      asm volatile("mapa.shared::cluster.u32 %0, %1, %2;" : "=r"(rdst) : "r"(sb + OFF_R + t128 * 16), "r"(kh ^ 1));
      asm volatile("mapa.shared::cluster.u32 %0, %1, %2;" : "=r"(rbar) : "r"(bars + B_RECV * 8), "r"(kh ^ 1));
#pragma unroll
      for (int i = 0; i < 14; i++)
        asm volatile("st.async.weak.shared::cluster.mbarrier::complete_tx::bytes.v4.f32 [%0], {%1,%2,%3,%4}, [%5];"
                     :: "r"(rdst + i * 2048), "f"(acc[4 * i]), "f"(acc[4 * i + 1]), "f"(acc[4 * i + 2]), "f"(acc[4 * i + 3]), "r"(rbar) : "memory");
    } else {
      float spec[2][28];
      if (t128 == 0) PROF(wg, 12);
      mbar_wait(bars + B_PQFULL * 8, 0);
      if (t128 == 0) { PROF(wg, 13); g_ep[bid] = epoch + 1; }
#pragma unroll
      for (int i = 0; i < 4; i++) {
        if (i == 0) mbar_wait(bars + B_GFULL * 8, 0);
        if (i >= 2) mbar_wait(bars + (B_FULL + i - 2) * 8, 1);
        wg_fence();
        const uint64_t da = mkdesc(sb + OFF_PQ + i * 14336, 1024, 1024, 1);
        const uint64_t db = mkdesc(i < 2 ? sb + OFF_R + 28672 + i * (G_IMG / 2) : sb + (i - 2) * SLOT, 896, 128, 0);
#pragma unroll
        for (int kk = 0; kk < 7; kk++) wgmma_ss_56<1, 0>(spec[i >> 1], da + kk * 128, db + kk * 112, ((i & 1) | kk) != 0);
        wg_commit();
      }
      const float* gs = reinterpret_cast<const float*>(smem + OFF_G) + w4 * 16 + g;
      const float o0 = bf16_round(1.0f - gs[0]), o1 = bf16_round(1.0f - gs[8]);
      const float g0 = gs[0] * (1.0f / (float)(S_ * D_)), g1 = gs[8] * (1.0f / (float)(S_ * D_));
      wg_wait<0>(); keep(spec[0]); keep(spec[1]);
      if (t128 == 0) PROF(wg, 14);
      mbar_wait_cluster(bars + B_RECV * 8, 0);
      if (t128 == 0) PROF(wg, 0);
      float4 o[14];
#pragma unroll
      for (int i = 0; i < 14; i++) o[i] = lds128f(sb + OFF_R + t128 * 16 + i * 2048);
      bar_sync<5, 128>();
      const uint32_t st = sb + OFF_PQ + w4 * 3840;
#pragma unroll
      for (int i = 0; i < 7; i++) {
        uint32_t pk[4];
#pragma unroll
        for (int e = 0; e < 2; e++) {
          const int c = 2 * i + e, si = i * 4 + e;
          pk[2 * e] = pack_bf16(fmaf(acc[4 * c] + o[c].x, o0, g0 * spec[0][si]), fmaf(acc[4 * c + 1] + o[c].y, o0, g0 * spec[1][si]));
          pk[2 * e + 1] = pack_bf16(fmaf(acc[4 * c + 2] + o[c].z, o1, g1 * spec[0][si + 2]), fmaf(acc[4 * c + 3] + o[c].w, o1, g1 * spec[1][si + 2]));
        }
        asm volatile("stmatrix.sync.aligned.m8n8.x4.shared.b16 [%0], {%1,%2,%3,%4};"
                     :: "r"(st + (lane & 15) * 240 + (lane >> 4) * 16 + i * 32), "r"(pk[0]), "r"(pk[1]), "r"(pk[2]), "r"(pk[3]) : "memory");
      }
      __syncwarp();
      if (lane < 28) {
        const int r2 = lane >= 14, cc = lane - r2 * 14;
        unsigned char* ob = reinterpret_cast<unsigned char*>(out) + (size_t)(m * 128 + kh * 64 + w4 * 16 + r2) * (D_ * 2) + n * 224 + cc * 16;
        float4 v[8];
#pragma unroll
        for (int i = 0; i < 8; i++) v[i] = lds128f(st + r2 * 240 + cc * 16 + i * 480);
#pragma unroll
        for (int i = 0; i < 8; i++) stg128(ob + i * (D_ * 4), __float_as_uint(v[i].x), __float_as_uint(v[i].y), __float_as_uint(v[i].z), __float_as_uint(v[i].w));
      }
    }
    if (t128 == 0) { PROF(wg, 15); if (wg) { PROFG(4, 30); PROF(4, 31); } }
  } else if (warp < 12) {
    asm volatile("setmaxnreg.dec.sync.aligned.u32 72;");
    const int t = tid - 256;
    const int k = bid;
    if (t == 0) PROF(2, 0);
    uint4 gv[7];
#pragma unroll
    for (int i = 0; i < 7; i++) gv[i] = ldg128(reinterpret_cast<const uint4*>(gate_w) + i * 8 + (t & 7));
    if (t < 98) {
      int cid = m * 98 + t, kc = cid / 56, nn = cid - kc * 56;
      int d = 112 * n + 8 * (2 * (nn >> 3) + (nn & 1)) + (nn & 6) + kh;
      int dr = d > 224 ? d - 448 : d;
      const float df = (float)dr * (-6.283185307179586f / 448.0f);
      uint32_t pk[4];
#pragma unroll
      for (int e = 0; e < 4; e++) {
        const float a = (float)(4 * kc + e) * df;
        pk[e] = pack_bf16(2.0f * __cosf(a), 2.0f * __sinf(a));
      }
      if (kc == 0) pk[0] = (((d >> 1) ^ kh) & 1) ? 0xBF803F80u : 0x3F803F80u;
      stg128(g_G + (size_t)(n * 2 + kh) * G_IMG + cid * 16, pk[0], pk[1], pk[2], pk[3]);
    }
    bar_sync<0, NTHREADS - 64>();
    asm volatile("barrier.cluster.arrive.relaxed.aligned;" ::: "memory");
    {
      const int row = n * 16 + (t >> 3), l8 = t & 7;
      mbar_wait(bars + (B_XFULL + 1) * 8, 0);
      float sum = 0.f;
#pragma unroll
      for (int i = 0; i < 7; i++) {
        const uint4 a = lds128(sb + OFF_R + i * 8192 + row * 128 + ((l8 ^ (row & 7)) << 4));
        const uint32_t aa[4] = {a.x, a.y, a.z, a.w}, bb[4] = {gv[i].x, gv[i].y, gv[i].z, gv[i].w};
#pragma unroll
        for (int e = 0; e < 4; e++) {
          const uint32_t pr = as_u(__hmul2(as_b2(aa[e]), as_b2(bb[e])));
          sum += bf_lo(pr) + bf_hi(pr);
        }
      }
      sum += __shfl_xor_sync(0xffffffffu, sum, 1); sum += __shfl_xor_sync(0xffffffffu, sum, 2); sum += __shfl_xor_sync(0xffffffffu, sum, 4);
      if (lane == 0) mbar_arrive(bars + (B_XFREE + 1) * 8);
      if (l8 == 0) g_gate[m * 128 + kh * 64 + row] = bf16_round(__fdividef(1.0f, 1.0f + __expf(-bf16_round(sum))));
    }
    if (t == 0) PROF(2, 11);
    mbar_wait(bars + B_XFREE * 8, 0);
    if (k < 113) {
      const float u = -6.283185307179586f / 2048.0f, t2 = (float)(2 * t) * u, rr = (float)(t >> 4) * u;
#pragma unroll 1
      for (int i = 0; i < 4; i++) {
        const float q = (float)(2 * i), l = (float)((t & 15) + 64 * i);
        sts128(sb + OFF_TW + i * 2048 + t * 16, cis(t2 * q), cis((t2 + u) * q), cis(t2 * (q + 1.0f)), cis((t2 + u) * (q + 1.0f)));
        sts128(sb + OFF_TW + 8192 + i * 2048 + t * 16, cis(rr * l), cis(rr * (l + 16.0f)), cis(rr * (l + 32.0f)), cis(rr * (l + 48.0f)));
      }
      const float l = (float)((t >> 1) & 15) * (8.0f * u), jj = (float)((t >> 5) * 4 + (t & 1) * 2);
      sts64(sb + OFF_TW + 16384 + t * 8, cis(l * jj), cis(l * (jj + 1.0f)));
    }
    if (t == 0) PROF(2, 9);
    mbar_wait(bars + B_PIN * 8, 0);
    if (t == 0) PROF(2, 4);
    {
      const uint32_t wa = sb + OFF_WS + (((t & 7) - bid) & 7) * 450 + (t >> 3) * 2, wc = wa + 448 - (t >> 3) * 4;
      uint2* dst = g_Wt + (t >> 3) * S_ + 16 * bid + 2 * (t & 7);
#pragma unroll 1
      for (int h = 0; h < 2; h++) {
        uint32_t w[4][8];
#pragma unroll
        for (int i = 0; i < 4; i++) {
#pragma unroll
          for (int e = 0; e < 4; e++) { w[i][2 * e] = lds16(wa + h * 128 + i * 32 + e * 3600); w[i][2 * e + 1] = lds16(wc - h * 128 - i * 32 + e * 3600); }
        }
#pragma unroll
        for (int i = 0; i < 4; i++)
          if (i < 3 || h == 0 || t < 8)
            stg128(dst + (h * 64 + i * 16) * S_, __byte_perm(w[i][0], w[i][1], 0x5410), __byte_perm(w[i][4], w[i][5], 0x5410), __byte_perm(w[i][2], w[i][3], 0x5410), __byte_perm(w[i][6], w[i][7], 0x5410));
      }
    }
    __syncwarp();
    if (lane == 0) mbar_arrive(bars + B_PUBW * 8);
    if (t == 0) PROF(2, 6);
    mbar_wait(bars + B_RFULL * 8, 0);
    if (t < 112) {
      const int js = bid >> 4, nn = (t >> 1) / 14, cc = (t >> 1) - nn * 14;
      unsigned char* wdst = g_Wd + (size_t)((js >> 2) * 4 + nn) * WD_IMG + cc * 128 + (t & 1) * 16;
      uint4 v[7];
#pragma unroll
      for (int i = 0; i < 7; i++) v[i] = lds128(sb + OFF_R + i * 1792 + (t & 1) * 896 + (t >> 1) * 16);
#pragma unroll
      for (int i = 0; i < 7; i++) {
        int col = 14 * (bid & 15) + 2 * i - (js & 1) * 32;
        if (col < 0) col += 224;
        const int kpos = col < 192 ? (col >> 6) * 256 + (js & 3) * 64 + (col & 63) : 576 + (js & 3) * 32 + col;
        stg128(wdst + (kpos >> 3) * 1792 + (kpos & 7) * 16, v[i].x, v[i].y, v[i].z, v[i].w);
      }
    }
    __syncwarp();
    if (lane == 0) mbar_arrive(bars + B_PUBD * 8);
    bar_sync<3, 128>();
    if (k < 113) {
      if (t == 0) PROF(2, 2);
      mbar_wait(bars + B_XCFULL * 8, 0);
      if (t == 0) PROF(2, 3);
      c2 v[16];
      uint2 xe[8], xo[8];
      const uint32_t* xs = g_Xc + (k == 112 ? 0 : k) * 2 * S_ + 2 * t;
#pragma unroll
      for (int jj = 0; jj < 8; jj++) { xe[jj] = ldg64_l2(xs + jj * 256); xo[jj] = ldg64_l2(xs + S_ + jj * 256); }
      const uint32_t se = k == 0 ? 0x4410 : (k == 112 ? 0x4432 : 0x3210), so = k == 0 ? 0x4410 : (k == 112 ? 0x3244 : 0x3210);
#pragma unroll
      for (int jj = 0; jj < 8; jj++) {
        const uint2 e2 = xe[jj], o2 = xo[jj];
#pragma unroll
        for (int h = 0; h < 2; h++) {
          const b2 e = as_b2(__byte_perm(h ? e2.y : e2.x, 0, se)), o = as_b2(__byte_perm(h ? o2.y : o2.x, 0, so));
          const uint32_t s = as_u(__hadd2(e, o)), d = as_u(__hsub2(e, o)) ^ 0x80000000u;
          v[2 * jj + h] = mk(as_b2(__byte_perm(s, d, 0x5410)), as_b2(__byte_perm(s, d, 0x7632)));
        }
      }
      if (t == 0) PROF(2, 12);
      columns(v, sb, t);
      if (t == 0) PROF(2, 14);
      const int pre = (k == 112) ? 1 : 2 * k, pim = (k == 112) ? 1 : 2 * k + 1;
      uint32_t* pq = reinterpret_cast<uint32_t*>(g_PQ) + (t >> 5) * 14336;
      uint32_t* pr = pq + pre * 32 + ((((lane >> 2) ^ pre) & 7) << 2) + (lane & 3);
      uint32_t* pi = pq + pim * 32 + ((((lane >> 2) ^ pim) & 7) << 2) + (lane & 3);
#pragma unroll
      for (int jj = 0; jj < 8; jj++) {
        const b2 ar = as_b2(__byte_perm(as_u(v[2 * jj].y), as_u(v[2 * jj + 1].y), 0x5410)), br = as_b2(__byte_perm(as_u(v[2 * jj].y), as_u(v[2 * jj + 1].y), 0x7632));
        const b2 ai = as_b2(__byte_perm(as_u(v[2 * jj].x), as_u(v[2 * jj + 1].x), 0x5410)), bi = as_b2(__byte_perm(as_u(v[2 * jj].x), as_u(v[2 * jj + 1].x), 0x7632));
        pr[jj * 57344] = as_u(__hadd2(ar, br));
        if (k != 112) pr[jj * 57344 + 7168] = as_u(__hsub2(ar, br));
        if (k != 0) pi[jj * 57344 + 7168] = as_u(__hadd2(ai, bi));
        if (k != 0 && k != 112) pi[jj * 57344] = as_u(__hsub2(ai, bi));
      }
      fence_async_smem();
    }
    bar_sync<3, 128>();
    if (t == 0) { PROF(2, 5); red_release(&g_cnt[5 * 32]); PROF(2, 7); }
    __syncwarp();
    asm volatile("barrier.cluster.wait.aligned;" ::: "memory");
  } else {
    asm volatile("setmaxnreg.dec.sync.aligned.u32 24;");
    if (warp == 12) {
      if (elect()) {
        mbar_init(bars + B_XFULL * 8, 1); mbar_init(bars + (B_XFULL + 1) * 8, 1);
        fence_async_smem();
#pragma unroll
        for (int w = 0; w < 2; w++) {
          mbar_expect(bars + (B_XFULL + w) * 8, HALF_XR);
          tma3d(sb + OFF_PQ + w * HALF_XR, &tm_x, 0, m * 128 + (w ^ kh ^ 1) * 64, 0, bars + (B_XFULL + w) * 8);
        }
        PROF(3, 3);
#pragma unroll
        for (int i = 0; i < NSLOT; i++) mbar_init(bars + (B_FULL + i) * 8, 1);
        mbar_init(bars + B_PIN * 8, 1);
        fence_async_smem();
      }
      bar_arrive<0, NTHREADS - 64>();
#pragma unroll 1
      for (int i = 0; i < 6; i++) {
        if (elect()) {
          const uint32_t fb = bars + (B_FULL + i) * 8;
          mbar_expect(fb, SLOT);
          tma2d(sb + i * SLOT, &tm_g, c64, i * 64, fb);
          tma2d(sb + i * SLOT + 8192, &tm_u, c64, i * 64, fb);
          PROF(3, 4 + i);
        }
      }
      if (elect()) {
        prefetch_l2(reinterpret_cast<const unsigned char*>(w_r) + bid * 7200, 7200);
        prefetch_l2(reinterpret_cast<const unsigned char*>(w_i) + bid * 7200, 7200);
        prefetch_tma2d(&tm_g, c64, 384); prefetch_tma2d(&tm_u, c64, 384);
      }
    } else if (warp == 14) {
      if (elect()) {
#pragma unroll
        for (int i = B_EMPTY; i < B_END; i++)
          if (i < B_XFULL || i >= B_XFREE) mbar_init(bars + i * 8, i >= B_PQFULL ? 1 : ((i == B_XFREE || i >= B_PUBW) ? 4 : 8));
        asm volatile("fence.mbarrier_init.release.cluster;" ::: "memory");
        fence_async_smem();
        mbar_expect(bars + B_RECV * 8, 64 * 112 * 4);
      }
      bar_arrive<0, NTHREADS - 64>();
    }
    const uint32_t epoch = ld_relaxed(&g_ep[bid]);
    if (warp == 13 && lane == 0) { PROFG(4, 0); PROF(4, 1); }
    bar_sync<1, 128>();
    asm volatile("barrier.cluster.arrive.relaxed.aligned;" ::: "memory");
    if (warp == 12) {
      int slot = 6, ph = 1;
      auto wait_slot = [&]() { mbar_wait(bars + (B_EMPTY + slot) * 8, ph ^ (slot == 6)); };
      auto adv = [&]() { if (++slot == NSLOT) { slot = 0; ph ^= 1; } };
      const int c32 = 224 * j + ((j & 1) ? 0 : 192);
#pragma unroll 1
      for (int i = 6; i < 25; i++) {
        wait_slot();
        if (elect()) {
          const uint32_t dst = sb + slot * SLOT, fb = bars + (B_FULL + slot) * 8;
          const bool last = i >= 21;
          const int cc = last ? c32 : c64 + 64 * (i / 7), rr = last ? slot * 128 : slot * 64;
          mbar_expect(fb, SLOT);
          tma2d(dst, last ? &tm_g32 : &tm_g, cc, rr, fb);
          tma2d(dst + 8192, last ? &tm_u32 : &tm_u, cc, rr, fb);
        }
        adv();
      }
      if (lane == 0) PROF(3, 0);
      mbar_wait(bars + B_PREP * 8, 0);
      if (lane == 0) PROF(3, 1);
#pragma unroll 1
      for (int i = 4; i < 16; i++) {
        if (lane == 0) PROF(3, 16 + i);
        wait_slot();
        if (elect()) {
          const int bytes = i < 14 ? 14336 : G_IMG / 2;
          const unsigned char* src = i < 14 ? g_Wd + (size_t)j * WD_IMG + i * 14336 : g_G + (size_t)(n * 4 + i - 12) * (G_IMG / 2);
          mbar_expect(bars + (B_FULL + slot) * 8, bytes);
          bulk_g2s(sb + slot * SLOT, src, bytes, bars + (B_FULL + slot) * 8);
        }
        adv();
      }
      if (lane == 0) PROF(3, 2);
    } else if (warp == 13) {
#pragma unroll 1
      for (int u = 0; u < 3; u++) {
        mbar_wait(bars + (u ? B_PUBW - 1 + u : B_PUBX) * 8, 0);
        if (lane == 0) { PROF(4, 8 + u); red_release(&g_cnt[(u ? 8 - 2 * u : j >> 1) * 32]); PROF(4, 12 + u); }
        __syncwarp();
      }
      mbar_wait(bars + B_LFREE * 8, 0);
      if (elect()) {
        mbar_expect(bars + B_GFULL * 8, G_IMG);
        bulk_g2s(sb + OFF_R + 28672, g_G + (size_t)(n * 2) * G_IMG, G_IMG, bars + B_GFULL * 8);
      }
    } else if (warp == 14) {
#pragma unroll 1
      for (int u = 0; u < 2; u++) {
        wait_ge(&g_cnt[(6 - 2 * u) * 32], (epoch + 1) * 128);
        fence_async_global();
        if (lane == 0) { mbar_arrive(bars + (B_PREPW - u) * 8); PROF(5, 9 - u); }
      }
    } else {
      mbar_wait(bars + B_XFREE * 8, 0);
      if (elect()) {
        mbar_expect(bars + B_PIN * 8, 14400);
        bulk_g2s(sb + OFF_WS, reinterpret_cast<const unsigned char*>(w_r) + bid * 7200, 7200, bars + B_PIN * 8);
        bulk_g2s(sb + OFF_WS + 7200, reinterpret_cast<const unsigned char*>(w_i) + bid * 7200, 7200, bars + B_PIN * 8);
        prefetch_l2(reinterpret_cast<const unsigned char*>(w_gate) + bid * 12544, 12544);
        prefetch_l2(reinterpret_cast<const unsigned char*>(w_up) + bid * 12544, 12544);
      }
      mbar_wait(bars + (B_XFREE + 1) * 8, 0);
      if (elect()) {
        mbar_expect(bars + B_RFULL * 8, 12544);
        bulk_g2s(sb + OFF_R, reinterpret_cast<const unsigned char*>(w_down) + bid * 12544, 12544, bars + B_RFULL * 8);
      }
      if (bid < 113) {
        const int sl = (bid == 112) ? 0 : bid;
        wait_ge(&g_cnt[((sl & 1) + 2 * ((sl >> 1) / 28)) * 32], (epoch + 1) * 32);
        if (elect()) { PROF(5, 16); mbar_arrive(bars + B_XCFULL * 8); }
        mbar_wait(bars + B_PREPW * 8, 0);
        if (elect()) {
          mbar_expect(bars + B_WFULL * 8, 16384);
          bulk_g2s(sb + OFF_WS, g_Wt + bid * S_, 16384, bars + B_WFULL * 8);
          PROF(5, 17);
        }
      }
      mbar_wait(bars + B_PREP * 8, 0);
      if (elect()) {
        mbar_expect(bars + B_RFULL * 8, HALF_XR);
        bulk_g2s(sb + OFF_R, g_Wd + (size_t)j * WD_IMG, HALF_XR, bars + B_RFULL * 8);
        PROF(5, 19);
      }
      wait_ge(&g_cnt[5 * 32], (epoch + 1) * 128);
      fence_async_global();
      if (elect()) {
        PROF(5, 18);
        mbar_expect(bars + B_PQFULL * 8, HALF_XR + 256);
        const unsigned char* src = g_PQ + (size_t)(m * 2 + kh) * HALF_XR;
        bulk_g2s(sb + OFF_PQ, src, 28672, bars + B_PQFULL * 8);
        bulk_g2s(sb + OFF_PQ + 28672, src + 28672, 28672, bars + B_PQFULL * 8);
        bulk_g2s(sb + OFF_G, g_gate + m * 128 + kh * 64, 256, bars + B_PQFULL * 8);
      }
    }
    __syncwarp();
    asm volatile("barrier.cluster.wait.aligned;" ::: "memory");
  }
}

typedef CUresult (*EncodeFn)(CUtensorMap*, CUtensorMapDataType, cuuint32_t, void*, const cuuint64_t*, const cuuint64_t*, const cuuint32_t*,
                             const cuuint32_t*, CUtensorMapInterleave, CUtensorMapSwizzle, CUtensorMapL2promotion, CUtensorMapFloatOOBfill);

void make_map(EncodeFn enc, CUtensorMap* tm, const void* base, int cols, int rows, int bc, int br, CUtensorMapSwizzle sw) {
  cuuint64_t gd[2] = {(cuuint64_t)cols, (cuuint64_t)rows};
  cuuint64_t gs[1] = {(cuuint64_t)cols * 2};
  cuuint32_t bd[2] = {(cuuint32_t)bc, (cuuint32_t)br};
  cuuint32_t es[2] = {1, 1};
  enc(tm, CU_TENSOR_MAP_DATA_TYPE_BFLOAT16, 2, const_cast<void*>(base), gd, gs, bd, es, CU_TENSOR_MAP_INTERLEAVE_NONE, sw,
      CU_TENSOR_MAP_L2_PROMOTION_L2_128B, CU_TENSOR_MAP_FLOAT_OOB_FILL_NONE);
}

}

extern "C" void kernel_launch(void* const* d_in, const int* in_sizes, int n_in, void* d_out, int out_size) {
  (void)in_sizes; (void)n_in; (void)out_size;
  const __nv_bfloat16* x = (const __nv_bfloat16*)d_in[0];
  const __nv_bfloat16* w_r = (const __nv_bfloat16*)d_in[1];
  const __nv_bfloat16* w_i = (const __nv_bfloat16*)d_in[2];
  const __nv_bfloat16* w_gate = (const __nv_bfloat16*)d_in[4];
  const __nv_bfloat16* w_up = (const __nv_bfloat16*)d_in[5];
  const __nv_bfloat16* w_down = (const __nv_bfloat16*)d_in[6];
  const __nv_bfloat16* gate_w = (const __nv_bfloat16*)d_in[7];
  static EncodeFn enc = nullptr;
  static bool ok = false;
  if (!enc) {
    cudaDriverEntryPointQueryResult qr;
    cudaGetDriverEntryPoint("cuTensorMapEncodeTiled", (void**)&enc, cudaEnableDefault, &qr);
    cudaFuncSetAttribute(fused_kernel, cudaFuncAttributeMaxDynamicSharedMemorySize, SMEM_BYTES);
    cudaFuncAttributes fa;
    cudaFuncGetAttributes(&fa, fused_kernel);
    ok = (fa.numRegs == 128);
  }
  if (!ok) return;
  CUtensorMap tx, tg, tu, tg32, tu32;
  {
    cuuint64_t gd[3] = {64, (cuuint64_t)S_, 7};
    cuuint64_t gs[2] = {(cuuint64_t)D_ * 2, 128};
    cuuint32_t bd[3] = {64, 64, 7};
    cuuint32_t es[3] = {1, 1, 1};
    enc(&tx, CU_TENSOR_MAP_DATA_TYPE_BFLOAT16, 3, const_cast<__nv_bfloat16*>(x), gd, gs, bd, es, CU_TENSOR_MAP_INTERLEAVE_NONE, CU_TENSOR_MAP_SWIZZLE_128B,
        CU_TENSOR_MAP_L2_PROMOTION_L2_128B, CU_TENSOR_MAP_FLOAT_OOB_FILL_NONE);
  }
  make_map(enc, &tg, w_gate, F_, D_, 64, 64, CU_TENSOR_MAP_SWIZZLE_128B);
  make_map(enc, &tu, w_up, F_, D_, 64, 64, CU_TENSOR_MAP_SWIZZLE_128B);
  make_map(enc, &tg32, w_gate, F_, D_, 32, 128, CU_TENSOR_MAP_SWIZZLE_64B);
  make_map(enc, &tu32, w_up, F_, D_, 32, 128, CU_TENSOR_MAP_SWIZZLE_64B);
  fused_kernel<<<128, NTHREADS, SMEM_BYTES>>>(tx, tg, tu, tg32, tu32, w_r, w_i, w_gate, w_up, w_down, gate_w, (__nv_bfloat16*)d_out);
}
```

```cpp
#include <cuda_runtime.h>
#include <cuda_bf16.h>
#include <cuda.h>
#include <stdint.h>

namespace {

constexpr int S_ = 2048, D_ = 448, F_ = 1792;
constexpr int NTHREADS = 512;
constexpr int SLOT = 16384, NSLOT = 7;
constexpr int HALF_XR = 57344;
constexpr int OFF_PQ = NSLOT * SLOT;
constexpr int OFF_R = OFF_PQ + HALF_XR;
constexpr int OFF_EXCH = OFF_PQ;
constexpr int OFF_WS = OFF_EXCH + 18432;
constexpr int OFF_TW = OFF_WS + 16384;
constexpr int OFF_MISC = OFF_R + HALF_XR;
constexpr int OFF_G = OFF_MISC;
constexpr int OFF_BAR = OFF_MISC + 512;
constexpr int SMEM_BYTES = OFF_BAR + 512;
constexpr int B_FULL = 0, B_EMPTY = 7, B_XFULL = 14  ;
constexpr int B_XFREE = 16  , B_PUBX = 18, B_RFREE = 19, B_LFREE = 20;
constexpr int B_PUBW = 21, B_PUBD = 22;
constexpr int B_PQFULL = 23, B_RECV = 24, B_WFULL = 25, B_XCFULL = 26, B_PREP = 27, B_PREPW = 28, B_RFULL = 29, B_GFULL = 30, B_END = 31, B_PIN = 31;

constexpr int WD_IMG = 896 * 112 * 2;
constexpr int G_IMG = 224 * 56 * 2;

__device__ __align__(1024) uint32_t g_Xc[112 * 2 * S_];
__device__ __align__(1024) unsigned char g_H[32 * 56 * 4096];
__device__ __align__(1024) unsigned char g_PQ[32 * HALF_XR];
__device__ __align__(1024) unsigned char g_Wd[8 * WD_IMG];
__device__ __align__(1024) unsigned char g_G[8 * G_IMG];
__device__ __align__(1024) uint2 g_Wt[113 * S_];
__device__ __align__(1024) float g_gate[S_];
__device__ __align__(128) unsigned int g_ep[128];
__device__ __align__(128) unsigned int g_cnt[8 * 32];

#define PROF(role, idx) do {} while (0)
#define PROFG(role, idx) do {} while (0)

__device__ __forceinline__ uint32_t s2u(const void* p) { return (uint32_t)__cvta_generic_to_shared(p); }
__device__ __forceinline__ void mbar_init(uint32_t b, int c) { asm volatile("mbarrier.init.shared::cta.b64 [%0], %1;" :: "r"(b), "r"(c) : "memory"); }
__device__ __forceinline__ void mbar_expect(uint32_t b, int bytes) { asm volatile("mbarrier.arrive.expect_tx.shared::cta.b64 _, [%0], %1;" :: "r"(b), "r"(bytes) : "memory"); }
__device__ __forceinline__ void mbar_arrive(uint32_t b) { asm volatile("mbarrier.arrive.shared::cta.b64 _, [%0];" :: "r"(b) : "memory"); }
__device__ __forceinline__ void mbar_wait(uint32_t b, int ph) {
  asm volatile("{\n.reg .pred p;\n.reg .u32 c;\nmov.u32 c, 0;\nL_WAIT:\nmbarrier.try_wait.parity.shared::cta.b64 p, [%0], %1;\n@p bra.uni L_DONE;\n"
               "add.u32 c, c, 1;\nsetp.lt.u32 p, c, 4194304;\n@p bra.uni L_WAIT;\ntrap;\nL_DONE:\n}" :: "r"(b), "r"(ph) : "memory");
}
__device__ __forceinline__ void mbar_wait_cluster(uint32_t b, int ph) {
  asm volatile("{\n.reg .pred p;\n.reg .u32 c;\nmov.u32 c, 0;\nL_WAIT:\nmbarrier.try_wait.parity.acquire.cluster.shared::cta.b64 p, [%0], %1;\n@p bra.uni L_DONE;\n"
               "add.u32 c, c, 1;\nsetp.lt.u32 p, c, 4194304;\n@p bra.uni L_WAIT;\ntrap;\nL_DONE:\n}" :: "r"(b), "r"(ph) : "memory");
}
__device__ __forceinline__ uint32_t ld_acquire(const unsigned int* p) { uint32_t v; asm volatile("ld.acquire.gpu.global.u32 %0, [%1];" : "=r"(v) : "l"(p) : "memory"); return v; }
__device__ __forceinline__ uint32_t ld_relaxed(const unsigned int* p) { uint32_t v; asm volatile("ld.relaxed.gpu.global.u32 %0, [%1];" : "=r"(v) : "l"(p) : "memory"); return v; }
__device__ __forceinline__ void wait_ge(const unsigned int* p, uint32_t target) {
#pragma unroll 1
  for (int i = 0; i < (1 << 22); i++) { if ((int)(ld_acquire(p) - target) >= 0) return; }
  __trap();
}
__device__ __forceinline__ void red_release(unsigned int* p) { asm volatile("red.release.gpu.global.add.u32 [%0], 1;" :: "l"(p) : "memory"); }
__device__ __forceinline__ bool elect() { uint32_t p; asm volatile("{\n.reg .pred p;\nelect.sync _|p, 0xffffffff;\nselp.u32 %0, 1, 0, p;\n}" : "=r"(p)); return p; }
__device__ __forceinline__ void fence_async_smem() { asm volatile("fence.proxy.async.shared::cta;" ::: "memory"); }
__device__ __forceinline__ void fence_async_global() { asm volatile("fence.proxy.async.global;" ::: "memory"); }
template <int ID, int N> __device__ __forceinline__ void bar_sync() { asm volatile("bar.sync %0, %1;" :: "n"(ID), "n"(N) : "memory"); }
template <int ID, int N> __device__ __forceinline__ void bar_arrive() { asm volatile("bar.arrive %0, %1;" :: "n"(ID), "n"(N) : "memory"); }
__device__ __forceinline__ void tma2d(uint32_t dst, const CUtensorMap* tm, int c0, int c1, uint32_t bar) {
  asm volatile("cp.async.bulk.tensor.2d.shared::cluster.global.mbarrier::complete_tx::bytes [%0], [%1, {%3, %4}], [%2];"
               :: "r"(dst), "l"(tm), "r"(bar), "r"(c0), "r"(c1) : "memory");
}
__device__ __forceinline__ void tma3d(uint32_t dst, const CUtensorMap* tm, int c0, int c1, int c2, uint32_t bar) {
  asm volatile("cp.async.bulk.tensor.3d.shared::cluster.global.mbarrier::complete_tx::bytes [%0], [%1, {%3, %4, %5}], [%2];"
               :: "r"(dst), "l"(tm), "r"(bar), "r"(c0), "r"(c1), "r"(c2) : "memory");
}
__device__ __forceinline__ void bulk_g2s(uint32_t dst, const void* src, int bytes, uint32_t bar) {
  asm volatile("cp.async.bulk.shared::cluster.global.mbarrier::complete_tx::bytes [%0], [%1], %2, [%3];"
               :: "r"(dst), "l"(src), "r"(bytes), "r"(bar) : "memory");
}
__device__ __forceinline__ void prefetch_l2(const void* src, int bytes) {
  asm volatile("cp.async.bulk.prefetch.L2.global [%0], %1;" :: "l"(src), "r"(bytes) : "memory");
}
__device__ __forceinline__ void prefetch_tma2d(const CUtensorMap* tm, int c0, int c1) {
  asm volatile("cp.async.bulk.prefetch.tensor.2d.L2.global [%0, {%1, %2}];" :: "l"(tm), "r"(c0), "r"(c1) : "memory");
}
__device__ __forceinline__ uint64_t mkdesc(uint32_t addr, uint32_t lbo, uint32_t sbo, uint32_t mode) {
  return (uint64_t)((addr & 0x3FFFF) >> 4) | ((uint64_t)(lbo >> 4) << 16) | ((uint64_t)(sbo >> 4) << 32) | ((uint64_t)mode << 62);
}
__device__ __forceinline__ void wg_fence() { asm volatile("wgmma.fence.sync.aligned;" ::: "memory"); }
__device__ __forceinline__ void wg_commit() { asm volatile("wgmma.commit_group.sync.aligned;" ::: "memory"); }
template <int N> __device__ __forceinline__ void wg_wait() { asm volatile("wgmma.wait_group.sync.aligned %0;" :: "n"(N) : "memory"); }
template <int N> __device__ __forceinline__ void keep(float (&d)[N]) {
#pragma unroll
  for (int i = 0; i < N; i++) asm volatile("" : "+f"(d[i]) :: "memory");
}
__device__ __forceinline__ uint32_t pack_bf16(float lo, float hi) { uint32_t r; asm("cvt.rn.bf16x2.f32 %0, %1, %2;" : "=r"(r) : "f"(hi), "f"(lo)); return r; }
__device__ __forceinline__ float bf16_round(float v) { return __bfloat162float(__float2bfloat16_rn(v)); }
__device__ __forceinline__ void sts128(uint32_t a, uint32_t x, uint32_t y, uint32_t z, uint32_t w) { asm volatile("st.shared.v4.b32 [%0], {%1,%2,%3,%4};" :: "r"(a), "r"(x), "r"(y), "r"(z), "r"(w) : "memory"); }
__device__ __forceinline__ float4 lds128f(uint32_t a) { float4 v; asm volatile("ld.shared.v4.f32 {%0,%1,%2,%3}, [%4];" : "=f"(v.x), "=f"(v.y), "=f"(v.z), "=f"(v.w) : "r"(a) : "memory"); return v; }

__device__ __forceinline__ uint2 lds64(uint32_t a) { uint2 v; asm volatile("ld.shared.v2.b32 {%0,%1}, [%2];" : "=r"(v.x), "=r"(v.y) : "r"(a) : "memory"); return v; }
__device__ __forceinline__ float bf_lo(uint32_t w) { return __uint_as_float(w << 16); }
__device__ __forceinline__ float bf_hi(uint32_t w) { return __uint_as_float(w & 0xffff0000u); }
__device__ __forceinline__ uint32_t opaque(uint32_t v) { asm volatile("" : "+r"(v)); return v; }
__device__ __forceinline__ uint4 ldg128(const void* p) { uint4 v; asm volatile("ld.global.nc.v4.b32 {%0,%1,%2,%3}, [%4];" : "=r"(v.x), "=r"(v.y), "=r"(v.z), "=r"(v.w) : "l"(p)); return v; }
__device__ __forceinline__ void stg128(void* p, uint32_t x, uint32_t y, uint32_t z, uint32_t w) { asm volatile("st.global.v4.b32 [%0], {%1,%2,%3,%4};" :: "l"(p), "r"(x), "r"(y), "r"(z), "r"(w) : "memory"); }
__device__ __forceinline__ void stg128_l2(void* p, uint32_t x, uint32_t y, uint32_t z, uint32_t w) { asm volatile("st.relaxed.gpu.global.v4.b32 [%0], {%1,%2,%3,%4};" :: "l"(p), "r"(x), "r"(y), "r"(z), "r"(w) : "memory"); }
__device__ __forceinline__ uint2 ldg64_l2(const void* p) { uint2 v; asm volatile("ld.relaxed.gpu.global.v2.b32 {%0,%1}, [%2];" : "=r"(v.x), "=r"(v.y) : "l"(p) : "memory"); return v; }
__device__ __forceinline__ void ldg128_l2(uint32_t (&v)[4], const void* p) { asm volatile("ld.relaxed.gpu.global.v4.b32 {%0,%1,%2,%3}, [%4];" : "=r"(v[0]), "=r"(v[1]), "=r"(v[2]), "=r"(v[3]) : "l"(p) : "memory"); }
__device__ __forceinline__ uint4 lds128(uint32_t a) { uint4 v; asm volatile("ld.shared.v4.b32 {%0,%1,%2,%3}, [%4];" : "=r"(v.x), "=r"(v.y), "=r"(v.z), "=r"(v.w) : "r"(a) : "memory"); return v; }
__device__ __forceinline__ uint32_t lds16(uint32_t a) { uint32_t v; asm volatile("ld.shared.u16 %0, [%1];" : "=r"(v) : "r"(a) : "memory"); return v; }
__device__ __forceinline__ void sts64(uint32_t a, uint32_t x, uint32_t y) { asm volatile("st.shared.v2.b32 [%0], {%1,%2};" :: "r"(a), "r"(x), "r"(y) : "memory"); }
template <int TB> __device__ __forceinline__ void wgmma_rs_128(float (&d)[64], const uint32_t (&a)[4], uint64_t db, int sc) {
  asm volatile("{\n.reg .pred p;\nsetp.ne.b32 p, %69, 0;\n"
    "wgmma.mma_async.sync.aligned.m64n128k16.f32.bf16.bf16 {%0, %1, %2, %3, %4, %5, %6, %7, %8, %9, %10, %11, %12, %13, %14, %15, %16, %17, %18, %19, %20, %21, %22, %23, %24, %25, %26, %27, %28, %29, %30, %31, %32, %33, %34, %35, %36, %37, %38, %39, %40, %41, %42, %43, %44, %45, %46, %47, %48, %49, %50, %51, %52, %53, %54, %55, %56, %57, %58, %59, %60, %61, %62, %63}, {%64, %65, %66, %67}, %68, p, 1, 1, %70;\n}\n"
    : "+f"(d[0]), "+f"(d[1]), "+f"(d[2]), "+f"(d[3]), "+f"(d[4]), "+f"(d[5]), "+f"(d[6]), "+f"(d[7]), "+f"(d[8]), "+f"(d[9]), "+f"(d[10]), "+f"(d[11]), "+f"(d[12]), "+f"(d[13]), "+f"(d[14]), "+f"(d[15]), "+f"(d[16]), "+f"(d[17]), "+f"(d[18]), "+f"(d[19]), "+f"(d[20]), "+f"(d[21]), "+f"(d[22]), "+f"(d[23]), "+f"(d[24]), "+f"(d[25]), "+f"(d[26]), "+f"(d[27]), "+f"(d[28]), "+f"(d[29]), "+f"(d[30]), "+f"(d[31]), "+f"(d[32]), "+f"(d[33]), "+f"(d[34]), "+f"(d[35]), "+f"(d[36]), "+f"(d[37]), "+f"(d[38]), "+f"(d[39]), "+f"(d[40]), "+f"(d[41]), "+f"(d[42]), "+f"(d[43]), "+f"(d[44]), "+f"(d[45]), "+f"(d[46]), "+f"(d[47]), "+f"(d[48]), "+f"(d[49]), "+f"(d[50]), "+f"(d[51]), "+f"(d[52]), "+f"(d[53]), "+f"(d[54]), "+f"(d[55]), "+f"(d[56]), "+f"(d[57]), "+f"(d[58]), "+f"(d[59]), "+f"(d[60]), "+f"(d[61]), "+f"(d[62]), "+f"(d[63])
    : "r"(a[0]), "r"(a[1]), "r"(a[2]), "r"(a[3]), "l"(db), "r"(sc), "n"(TB));
}
template <int TB> __device__ __forceinline__ void wgmma_rs_64(float (&d)[32], const uint32_t (&a)[4], uint64_t db, int sc) {
  asm volatile("{\n.reg .pred p;\nsetp.ne.b32 p, %37, 0;\n"
    "wgmma.mma_async.sync.aligned.m64n64k16.f32.bf16.bf16 {%0, %1, %2, %3, %4, %5, %6, %7, %8, %9, %10, %11, %12, %13, %14, %15, %16, %17, %18, %19, %20, %21, %22, %23, %24, %25, %26, %27, %28, %29, %30, %31}, {%32, %33, %34, %35}, %36, p, 1, 1, %38;\n}\n"
    : "+f"(d[0]), "+f"(d[1]), "+f"(d[2]), "+f"(d[3]), "+f"(d[4]), "+f"(d[5]), "+f"(d[6]), "+f"(d[7]), "+f"(d[8]), "+f"(d[9]), "+f"(d[10]), "+f"(d[11]), "+f"(d[12]), "+f"(d[13]), "+f"(d[14]), "+f"(d[15]), "+f"(d[16]), "+f"(d[17]), "+f"(d[18]), "+f"(d[19]), "+f"(d[20]), "+f"(d[21]), "+f"(d[22]), "+f"(d[23]), "+f"(d[24]), "+f"(d[25]), "+f"(d[26]), "+f"(d[27]), "+f"(d[28]), "+f"(d[29]), "+f"(d[30]), "+f"(d[31])
    : "r"(a[0]), "r"(a[1]), "r"(a[2]), "r"(a[3]), "l"(db), "r"(sc), "n"(TB));
}
template <int TB> __device__ __forceinline__ void wgmma_rs_56(float (&d)[28], const uint32_t (&a)[4], uint64_t db, int sc) {
  asm volatile("{\n.reg .pred p;\nsetp.ne.b32 p, %33, 0;\n"
    "wgmma.mma_async.sync.aligned.m64n56k16.f32.bf16.bf16 {%0, %1, %2, %3, %4, %5, %6, %7, %8, %9, %10, %11, %12, %13, %14, %15, %16, %17, %18, %19, %20, %21, %22, %23, %24, %25, %26, %27}, {%28, %29, %30, %31}, %32, p, 1, 1, %34;\n}\n"
    : "+f"(d[0]), "+f"(d[1]), "+f"(d[2]), "+f"(d[3]), "+f"(d[4]), "+f"(d[5]), "+f"(d[6]), "+f"(d[7]), "+f"(d[8]), "+f"(d[9]), "+f"(d[10]), "+f"(d[11]), "+f"(d[12]), "+f"(d[13]), "+f"(d[14]), "+f"(d[15]), "+f"(d[16]), "+f"(d[17]), "+f"(d[18]), "+f"(d[19]), "+f"(d[20]), "+f"(d[21]), "+f"(d[22]), "+f"(d[23]), "+f"(d[24]), "+f"(d[25]), "+f"(d[26]), "+f"(d[27])
    : "r"(a[0]), "r"(a[1]), "r"(a[2]), "r"(a[3]), "l"(db), "r"(sc), "n"(TB));
}
template <int TB> __device__ __forceinline__ void wgmma_rs_112(float (&d)[56], const uint32_t (&a)[4], uint64_t db, int sc) {
  asm volatile("{\n.reg .pred p;\nsetp.ne.b32 p, %61, 0;\n"
    "wgmma.mma_async.sync.aligned.m64n112k16.f32.bf16.bf16 {%0, %1, %2, %3, %4, %5, %6, %7, %8, %9, %10, %11, %12, %13, %14, %15, %16, %17, %18, %19, %20, %21, %22, %23, %24, %25, %26, %27, %28, %29, %30, %31, %32, %33, %34, %35, %36, %37, %38, %39, %40, %41, %42, %43, %44, %45, %46, %47, %48, %49, %50, %51, %52, %53, %54, %55}, {%56, %57, %58, %59}, %60, p, 1, 1, %62;\n}\n"
    : "+f"(d[0]), "+f"(d[1]), "+f"(d[2]), "+f"(d[3]), "+f"(d[4]), "+f"(d[5]), "+f"(d[6]), "+f"(d[7]), "+f"(d[8]), "+f"(d[9]), "+f"(d[10]), "+f"(d[11]), "+f"(d[12]), "+f"(d[13]), "+f"(d[14]), "+f"(d[15]), "+f"(d[16]), "+f"(d[17]), "+f"(d[18]), "+f"(d[19]), "+f"(d[20]), "+f"(d[21]), "+f"(d[22]), "+f"(d[23]), "+f"(d[24]), "+f"(d[25]), "+f"(d[26]), "+f"(d[27]), "+f"(d[28]), "+f"(d[29]), "+f"(d[30]), "+f"(d[31]), "+f"(d[32]), "+f"(d[33]), "+f"(d[34]), "+f"(d[35]), "+f"(d[36]), "+f"(d[37]), "+f"(d[38]), "+f"(d[39]), "+f"(d[40]), "+f"(d[41]), "+f"(d[42]), "+f"(d[43]), "+f"(d[44]), "+f"(d[45]), "+f"(d[46]), "+f"(d[47]), "+f"(d[48]), "+f"(d[49]), "+f"(d[50]), "+f"(d[51]), "+f"(d[52]), "+f"(d[53]), "+f"(d[54]), "+f"(d[55])
    : "r"(a[0]), "r"(a[1]), "r"(a[2]), "r"(a[3]), "l"(db), "r"(sc), "n"(TB));
}
template <int TA, int TB> __device__ __forceinline__ void wgmma_ss_56(float (&d)[28], uint64_t da, uint64_t db, int sc) {
  asm volatile("{\n.reg .pred p;\nsetp.ne.b32 p, %30, 0;\n"
    "wgmma.mma_async.sync.aligned.m64n56k16.f32.bf16.bf16 {%0, %1, %2, %3, %4, %5, %6, %7, %8, %9, %10, %11, %12, %13, %14, %15, %16, %17, %18, %19, %20, %21, %22, %23, %24, %25, %26, %27}, %28, %29, p, 1, 1, %31, %32;\n}\n"
    : "+f"(d[0]), "+f"(d[1]), "+f"(d[2]), "+f"(d[3]), "+f"(d[4]), "+f"(d[5]), "+f"(d[6]), "+f"(d[7]), "+f"(d[8]), "+f"(d[9]), "+f"(d[10]), "+f"(d[11]), "+f"(d[12]), "+f"(d[13]), "+f"(d[14]), "+f"(d[15]), "+f"(d[16]), "+f"(d[17]), "+f"(d[18]), "+f"(d[19]), "+f"(d[20]), "+f"(d[21]), "+f"(d[22]), "+f"(d[23]), "+f"(d[24]), "+f"(d[25]), "+f"(d[26]), "+f"(d[27])
    : "l"(da), "l"(db), "r"(sc), "n"(TA), "n"(TB));
}

__device__ __forceinline__ uint32_t cis(float a) { return pack_bf16(__cosf(a), __sinf(a)); }

typedef __nv_bfloat162 b2;
struct c2 { b2 x, y; };
__device__ __forceinline__ b2 as_b2(uint32_t u) { return *reinterpret_cast<b2*>(&u); }
__device__ __forceinline__ uint32_t as_u(b2 v) { return *reinterpret_cast<uint32_t*>(&v); }
__device__ __forceinline__ c2 mk(b2 x, b2 y) { c2 r; r.x = x; r.y = y; return r; }
__device__ __forceinline__ c2 cmul(c2 a, b2 wr, b2 wi) { return mk(__hfma2(a.x, wr, __hneg2(__hmul2(a.y, wi))), __hfma2(a.x, wi, __hmul2(a.y, wr))); }
__device__ __forceinline__ void fft4(c2& a0, c2& a1, c2& a2, c2& a3) {
  c2 t0 = mk(__hadd2(a0.x, a2.x), __hadd2(a0.y, a2.y)), t1 = mk(__hsub2(a0.x, a2.x), __hsub2(a0.y, a2.y));
  c2 t2 = mk(__hadd2(a1.x, a3.x), __hadd2(a1.y, a3.y)), t3 = mk(__hsub2(a1.x, a3.x), __hsub2(a1.y, a3.y));
  a0 = mk(__hadd2(t0.x, t2.x), __hadd2(t0.y, t2.y)); a2 = mk(__hsub2(t0.x, t2.x), __hsub2(t0.y, t2.y));
  a1 = mk(__hadd2(t1.x, t3.y), __hsub2(t1.y, t3.x)); a3 = mk(__hsub2(t1.x, t3.y), __hadd2(t1.y, t3.x));
}
__device__ __forceinline__ void fft4_s2(c2& a0, c2& a1, c2& a2, c2& a3, b2 r) {
  const b2 nr = __hneg2(r);
  c2 t0 = mk(__hfma2(a2.x, r, a0.x), __hfma2(a2.y, r, a0.y)), t1 = mk(__hfma2(a2.x, nr, a0.x), __hfma2(a2.y, nr, a0.y));
  c2 t2 = mk(__hadd2(a1.x, a3.x), __hadd2(a1.y, a3.y)), t3 = mk(__hsub2(a1.x, a3.x), __hsub2(a1.y, a3.y));
  a0 = mk(__hadd2(t0.x, t2.x), __hadd2(t0.y, t2.y)); a2 = mk(__hsub2(t0.x, t2.x), __hsub2(t0.y, t2.y));
  a1 = mk(__hadd2(t1.x, t3.y), __hsub2(t1.y, t3.x)); a3 = mk(__hsub2(t1.x, t3.y), __hadd2(t1.y, t3.x));
}
__device__ __forceinline__ void fft4_s13(c2& a0, c2& a1, c2& a2, c2& a3, b2 r) {
  const b2 nr = __hneg2(r);
  c2 t0 = mk(__hadd2(a0.x, a2.x), __hadd2(a0.y, a2.y)), t1 = mk(__hsub2(a0.x, a2.x), __hsub2(a0.y, a2.y));
  c2 t2 = mk(__hadd2(a1.x, a3.x), __hadd2(a1.y, a3.y)), t3 = mk(__hsub2(a1.x, a3.x), __hsub2(a1.y, a3.y));
  a0 = mk(__hfma2(t2.x, r, t0.x), __hfma2(t2.y, r, t0.y)); a2 = mk(__hfma2(t2.x, nr, t0.x), __hfma2(t2.y, nr, t0.y));
  a1 = mk(__hfma2(t3.y, r, t1.x), __hfma2(t3.x, nr, t1.y)); a3 = mk(__hfma2(t3.y, nr, t1.x), __hfma2(t3.x, r, t1.y));
}
__device__ __forceinline__ c2 rot1(c2 a) { return mk(__hadd2(a.x, a.y), __hsub2(a.y, a.x)); }
__device__ __forceinline__ c2 rot3(c2 a) { return mk(__hsub2(a.y, a.x), __hneg2(__hadd2(a.x, a.y))); }
__device__ __forceinline__ c2 mul_mi(c2 a) { return mk(a.y, __hneg2(a.x)); }
template <int O> __device__ __forceinline__ void fft8(c2 (&v)[16]) {
  const b2 r = as_b2(0x3F353F35u), nr = as_b2(0xBF35BF35u);
  fft4(v[O], v[O + 4], v[O + 8], v[O + 12]);
  fft4(v[O + 2], v[O + 6], v[O + 10], v[O + 14]);
  const c2 o0 = v[O + 2], o1 = rot1(v[O + 6]), o2 = v[O + 10], o3 = rot1(v[O + 14]);
  const c2 e0 = v[O], e1 = v[O + 4], e2 = v[O + 8], e3 = v[O + 12];
  v[O] = mk(__hadd2(e0.x, o0.x), __hadd2(e0.y, o0.y));              v[O + 8] = mk(__hsub2(e0.x, o0.x), __hsub2(e0.y, o0.y));
  v[O + 2] = mk(__hfma2(o1.x, r, e1.x), __hfma2(o1.y, r, e1.y));    v[O + 10] = mk(__hfma2(o1.x, nr, e1.x), __hfma2(o1.y, nr, e1.y));
  v[O + 4] = mk(__hadd2(e2.x, o2.y), __hsub2(e2.y, o2.x));          v[O + 12] = mk(__hsub2(e2.x, o2.y), __hadd2(e2.y, o2.x));
  v[O + 6] = mk(__hfma2(o3.y, r, e3.x), __hfma2(o3.x, nr, e3.y));   v[O + 14] = mk(__hfma2(o3.y, nr, e3.x), __hfma2(o3.x, r, e3.y));
}
__device__ __forceinline__ void fft16(c2 (&v)[16]) {
  const b2 r = as_b2(0x3F353F35u), c1 = as_b2(0x3F6D3F6Du), s1 = as_b2(0x3EC43EC4u), nc1 = as_b2(0xBF6DBF6Du), ns1 = as_b2(0xBEC4BEC4u);
#pragma unroll
  for (int a = 0; a < 4; a++) fft4(v[a], v[a + 4], v[a + 8], v[a + 12]);
  v[5] = cmul(v[5], c1, ns1); v[6] = rot1(v[6]); v[7] = cmul(v[7], s1, nc1);
  v[9] = rot1(v[9]); v[10] = mul_mi(v[10]); v[11] = rot3(v[11]);
  v[13] = cmul(v[13], s1, nc1); v[14] = rot3(v[14]); v[15] = cmul(v[15], nc1, s1);
  fft4(v[0], v[1], v[2], v[3]); fft4_s2(v[4], v[5], v[6], v[7], r); fft4_s13(v[8], v[9], v[10], v[11], r); fft4_s2(v[12], v[13], v[14], v[15], r);
  c2 t;
  t = v[1]; v[1] = v[4]; v[4] = t;  t = v[2]; v[2] = v[8]; v[8] = t;  t = v[3]; v[3] = v[12]; v[12] = t;
  t = v[6]; v[6] = v[9]; v[9] = t;  t = v[7]; v[7] = v[13]; v[13] = t; t = v[11]; v[11] = v[14]; v[14] = t;
}

__device__ __forceinline__ void columns(c2 (&v)[16], uint32_t sb, int t) {
  const int l16 = t & 15;
  const uint32_t row = sb + OFF_EXCH + (t >> 4) * 2304;
  const uint32_t pos = sb + OFF_EXCH + (t >> 3) * 144 + (t & 7) * 16;
#pragma unroll 1
  for (int ps = 0; ps < 6; ps++) {
    if (ps == 0 || ps == 5) { fft8<0>(v); fft8<1>(v); } else fft16(v);
    if (ps == 5) break;
    if (ps == 2) {
      const uint32_t ws = sb + OFF_WS + (l16 >> 1) * 128 + ((((t >> 4) + (l16 >> 1)) & 7) * 2 + (l16 & 1)) * 8;
      mbar_wait(sb + OFF_BAR + B_WFULL * 8, 0);
#pragma unroll
      for (int q = 0; q < 16; q++) {
        const uint2 w = lds64(ws + q * 1024);
        const c2 z = cmul(v[q], as_b2(w.x), as_b2(w.y));
        v[q] = mk(z.y, z.x);
      }
      continue;
    }
    {
      const bool full = ps == 0 || ps == 4;
      const uint32_t tw = sb + OFF_TW + (full ? ps * 2048 + t * 16 : 16384 + l16 * 16);
      const uint32_t st = full ? 2048 : 256;
#pragma unroll
      for (int i = 0; i < 4; i++) {
        const uint4 w4 = lds128(tw + i * st);
        const uint32_t w[4] = {w4.x, w4.y, w4.z, w4.w};
#pragma unroll
        for (int e = 0; e < 4; e++) v[4 * i + e] = cmul(v[4 * i + e], __low2bfloat162(as_b2(w[e])), __high2bfloat162(as_b2(w[e])));
      }
    }
    if (ps == 0) {
#pragma unroll
      for (int q = 0; q < 8; q++) sts128(pos + q * 2304, as_u(v[2 * q].x), as_u(v[2 * q].y), as_u(v[2 * q + 1].x), as_u(v[2 * q + 1].y));
      bar_sync<3, 128>();
#pragma unroll
      for (int q = 0; q < 16; q++) { const uint2 a = lds64(row + q * 144 + l16 * 8); v[q] = mk(as_b2(a.x), as_b2(a.y)); }
    } else {
      __syncwarp();
#pragma unroll
      for (int q = 0; q < 16; q++) sts64(row + q * 144 + l16 * 8, as_u(v[q].x), as_u(v[q].y));
      if (ps == 4) bar_sync<3, 128>(); else __syncwarp();
      const uint32_t src = ps == 4 ? pos : row + l16 * 144, st = ps == 4 ? 2304 : 16;
#pragma unroll
      for (int q = 0; q < 8; q++) { const uint4 a = lds128(src + q * st); v[2 * q] = mk(as_b2(a.x), as_b2(a.y)); v[2 * q + 1] = mk(as_b2(a.z), as_b2(a.w)); }
    }
  }
}

template <int NH> __device__ __forceinline__ void h_epilogue(float (&acc)[NH * 8], unsigned char* gdst, uint32_t tag) {
#pragma unroll
  for (int c = 0; c < NH / 2; c++) {
    uint32_t pk[4];
#pragma unroll
    for (int i = 0; i < 4; i++) {
      float hv[2];
#pragma unroll
      for (int e = 0; e < 2; e++) {
        float hg = 0.5f * acc[c * 8 + i * 2 + e], up = acc[NH * 4 + c * 8 + i * 2 + e];
        float th; asm("tanh.approx.f32 %0, %1;" : "=f"(th) : "f"(hg));
        hv[e] = fmaf(hg, th, hg) * up;
      }
      pk[i] = pack_bf16(hv[0], hv[1]);
    }
    stg128_l2(gdst + c * 4096, (pk[0] & ~1u) | tag, pk[1], pk[2], pk[3]);
  }
}

__device__ __forceinline__ void frag_ready(uint32_t (&a)[4], uint32_t (&b)[4], uint32_t (&c)[4], uint32_t (&d)[4], const unsigned char* p, uint32_t tag) {
  asm volatile("{\n.reg .pred p;\n.reg .u32 c, m, q;\nmov.u32 c, 0;\nL_TRY:\n"
               "lop3.b32 m, %0, %4, %17, 0x7E;\nlop3.b32 q, %8, %12, %17, 0x7E;\nlop3.b32 m, m, q, 1, 0xA8;\nsetp.ne.u32 p, m, 0;\n"
               "vote.sync.any.pred p, p, 0xffffffff;\n@!p bra.uni L_OK;\n"
               "ld.relaxed.gpu.global.v4.b32 {%0,%1,%2,%3}, [%16];\nld.relaxed.gpu.global.v4.b32 {%4,%5,%6,%7}, [%16+4096];\n"
               "ld.relaxed.gpu.global.v4.b32 {%8,%9,%10,%11}, [%16+8192];\nld.relaxed.gpu.global.v4.b32 {%12,%13,%14,%15}, [%16+12288];\n"
               "add.u32 c, c, 1;\nsetp.lt.u32 p, c, 262144;\n@p bra.uni L_TRY;\ntrap;\nL_OK:\n}"
               : "+r"(a[0]), "+r"(a[1]), "+r"(a[2]), "+r"(a[3]), "+r"(b[0]), "+r"(b[1]), "+r"(b[2]), "+r"(b[3]),
                 "+r"(c[0]), "+r"(c[1]), "+r"(c[2]), "+r"(c[3]), "+r"(d[0]), "+r"(d[1]), "+r"(d[2]), "+r"(d[3])
               : "l"(p), "r"(tag) : "memory");
}

#define MAP 0
#define LEAD2 0
#define LEAD1 3

__global__ void __cluster_dims__(2, 1, 1) __launch_bounds__(NTHREADS, 1)
fused_kernel(const __grid_constant__ CUtensorMap tm_x, const __grid_constant__ CUtensorMap tm_g, const __grid_constant__ CUtensorMap tm_u,
             const __grid_constant__ CUtensorMap tm_g32, const __grid_constant__ CUtensorMap tm_u32,
             const __nv_bfloat16* __restrict__ w_r, const __nv_bfloat16* __restrict__ w_i,
             const __nv_bfloat16* __restrict__ w_gate, const __nv_bfloat16* __restrict__ w_up,
             const __nv_bfloat16* __restrict__ w_down, const __nv_bfloat16* __restrict__ gate_w, __nv_bfloat16* __restrict__ out) {
  extern __shared__ __align__(1024) unsigned char smem[];
  const uint32_t sb = s2u(smem);
  const uint32_t bars = sb + OFF_BAR;
  const int tid = threadIdx.x, warp = __shfl_sync(0xffffffffu, tid >> 5, 0), lane = tid & 31;
  const int cl = blockIdx.x >> 1, kh = blockIdx.x & 1;
  const int n0 = cl < 4 ? cl : (cl < 36 ? (cl - 4) >> 3 : (cl - 36) / 7);
  const int m0 = cl < 4 ? 15 : (cl < 36 ? (cl - 4) & 7 : cl - 28 - 7 * n0);
  const int n = MAP == 0 ? n0 : (MAP == 1 ? (m0 & 3) : ((n0 & 1) | ((m0 & 1) << 1)));
  const int m = MAP == 0 ? m0 : (MAP == 1 ? ((m0 & 12) | n0) : ((m0 & 14) | (n0 >> 1)));
  const int j = kh * 4 + n, bid = m * 8 + n * 2 + kh;

  const int c64 = 224 * j + (j & 1) * 32;
  if (warp < 8) {
    asm volatile("setmaxnreg.inc.sync.aligned.u32 208;");
    const int wg = warp >> 2, w4 = warp & 3, g = lane >> 2, t = lane & 3;
    const int rh = wg ^ kh ^ 1;
    const int p = j & 1, r = (j >> 1) & 1, hh = j >> 2;
    const uint32_t epoch = ld_relaxed(&g_ep[bid]);
    if ((tid & 127) == 0) PROF(wg, 30);
#pragma unroll 1
    for (int it = tid; it < 392; it += 256) {
      const int kc = it / 28, sg = it - kc * 28;
      const int k = 2 * (28 * hh + sg) + r;
      const float kf = (float)k * (-6.283185307179586f / 448.0f), a0 = (float)(16 * kc + p) * kf;
      uint32_t c[4], s[4];
#pragma unroll
      for (int q = 0; q < 4; q++) {
        const float a1 = fmaf((float)(2 * q), kf, a0), a2 = fmaf((float)(2 * q + 8), kf, a0);
        c[q] = pack_bf16(__cosf(a1), __cosf(a2)); s[q] = pack_bf16(__sinf(a1), __sinf(a2));
        if (k == 0) s[q] = ((q ^ p) & 1) ? 0xBF80BF80u : 0x3F803F80u;
      }
      const uint32_t a = sb + 6 * SLOT + (kc * 56 + 2 * sg) * 16;
      sts128(a, c[0], c[1], c[2], c[3]);
      sts128(a + 16, s[0], s[1], s[2], s[3]);
    }
    if ((tid & 127) == 0) PROF(wg, 31);
    fence_async_smem();
    bar_sync<0, NTHREADS - 64>();
    asm volatile("barrier.cluster.arrive.relaxed.aligned;" ::: "memory");
    if ((tid & 127) == 0) PROF(wg, 1);

    uint32_t xa[28][4];
    {
      const uint32_t xb = sb + OFF_PQ + wg * HALF_XR + (w4 * 16 + (lane & 15)) * 128;
      mbar_wait(bars + (B_XFULL + wg) * 8, 0);
      if ((tid & 127) == 0) PROF(wg, 2);
#pragma unroll
      for (int kb = 0; kb < 7; kb++) {
#pragma unroll
        for (int kk = 0; kk < 4; kk++) {
          uint32_t a = xb + kb * 8192 + (((2 * kk + (lane >> 4)) ^ (lane & 7)) << 4);
          asm volatile("ldmatrix.sync.aligned.m8n8.x4.shared.b16 {%0,%1,%2,%3}, [%4];"
                       : "=r"(xa[kb * 4 + kk][0]), "=r"(xa[kb * 4 + kk][1]), "=r"(xa[kb * 4 + kk][2]), "=r"(xa[kb * 4 + kk][3]) : "r"(a) : "memory");
        }
      }
    }
    {
      uint32_t ad[7][4];
      const uint32_t sel = p ? 0x7632 : 0x5410;
      const uint32_t sgn = r ? 0xBF80BF80u : 0x3F803F80u;
#pragma unroll
      for (int jj = 0; jj < 7; jj++) {
#pragma unroll
        for (int i = 0; i < 4; i++) {
          int ks = 2 * jj + (i >> 1), rr = i & 1;
          uint32_t lo = __byte_perm(xa[ks][rr], xa[ks][rr + 2], sel);
          uint32_t hi = __byte_perm(xa[ks + 14][rr], xa[ks + 14][rr + 2], sel);
          asm("fma.rn.bf16x2 %0, %1, %2, %3;" : "=r"(ad[jj][i]) : "r"(hi), "r"(sgn), "r"(lo));
        }
      }
      __syncwarp();
      if (lane == 0) mbar_arrive(bars + (B_XFREE + wg) * 8);
      float acc[28];
      wg_fence();
      uint64_t db = mkdesc(sb + 6 * SLOT, 896, 128, 0);
#pragma unroll
      for (int jj = 0; jj < 7; jj++) wgmma_rs_56<0>(acc, ad[jj], db + jj * 112, jj != 0);
      wg_commit();
      wg_wait<0>(); keep(acc);
      if (lane == 0) mbar_arrive(bars + (B_EMPTY + 6) * 8);
      uint32_t* xc = g_Xc + (size_t)((2 * (28 * hh + t) + r) * 2 + p) * S_ + m * 128 + rh * 64 + w4 * 16 + g;
#pragma unroll
      for (int i = 0; i < 7; i++) {
        xc[i * 16 * S_] = pack_bf16(acc[4 * i], acc[4 * i + 1]);
        xc[i * 16 * S_ + 8] = pack_bf16(acc[4 * i + 2], acc[4 * i + 3]);
      }
      __syncwarp();
      if (lane == 0) mbar_arrive(bars + B_PUBX * 8);
    }
    if ((tid & 127) == 0) PROF(wg, 3);
    const uint32_t tag = ~epoch & 1;
    unsigned char* const hbase = g_H + (size_t)(m * 2 + kh) * (56 * 4096) + rh * 2048 + (tid & 127) * 16;
#pragma unroll 1
    for (int u = 0; u < 3; u++) {
      float acc[64];
      if (wg == 1) { if (u & 1) bar_sync<6, 256>(); else bar_sync<2, 256>(); }
      const uint32_t sbu = opaque(sb);
#pragma unroll
      for (int kb = 0; kb < 7; kb++) {
        mbar_wait(sbu + OFF_BAR + (B_FULL + kb) * 8, u & 1);
        wg_fence();
        uint64_t db = mkdesc(sbu + kb * SLOT, 8192, 1024, 1);
#pragma unroll
        for (int kk = 0; kk < 4; kk++) wgmma_rs_128<1>(acc, xa[kb * 4 + kk], db + kk * 128, (kb | kk) != 0);
        wg_commit();
        if (kb == LEAD1 && wg == 0) { if (u & 1) bar_arrive<6, 256>(); else bar_arrive<2, 256>(); }
        if (kb > 0) { wg_wait<1>(); if (lane == 0) mbar_arrive(sbu + OFF_BAR + (B_EMPTY + kb - 1) * 8); }
      }
      wg_wait<0>(); keep(acc);
      if (lane == 0) mbar_arrive(sbu + OFF_BAR + (B_EMPTY + 6) * 8);
      if ((tid & 127) == 0) PROF(wg, 4 + 2 * u);
      h_epilogue<8>(acc, hbase + (u * 16 + n * 4) * 4096, tag);
      if ((tid & 127) == 0) PROF(wg, 5 + 2 * u);
    }
    uint32_t ha[14][4][4];
    auto check = [&](int b0, int b1) {
#pragma unroll
      for (int b = b0; b < b1; b++) frag_ready(ha[b][0], ha[b][1], ha[b][2], ha[b][3], hbase + b * 16384, tag);
    };
    auto load = [&](int b0, int b1) {
#pragma unroll
      for (int i = b0; i < b1; i++) ldg128_l2(ha[i >> 2][i & 3], hbase + i * 4096);
    };
    {
      float acc[32];
      load(0, 3);
      if (wg == 1) bar_sync<6, 256>();
      const uint32_t sbu = opaque(sb);
#pragma unroll
      for (int it = 0; it < 4; it++) {
        mbar_wait(sbu + OFF_BAR + (B_FULL + it) * 8, 1);
        wg_fence();
        uint64_t db = mkdesc(sbu + it * SLOT, 8192, 512, 2);
#pragma unroll
        for (int kk = 0; kk < 8; kk++) if (it * 8 + kk < 28) wgmma_rs_64<1>(acc, xa[it * 8 + kk], db + kk * 64, (it | kk) != 0);
        wg_commit();
        if (it == 2 && wg == 0) bar_arrive<6, 256>();
        if (it > 0) {
          wg_wait<1>();
          if (lane == 0) mbar_arrive(sbu + OFF_BAR + (B_EMPTY + it - 1) * 8);
          if (it == 1) load(3, 11);
          if (it == 2) load(11, 16);
        }
      }
      wg_wait<0>(); keep(acc);
      if (lane == 0) mbar_arrive(sbu + OFF_BAR + (B_EMPTY + 3) * 8);
      if ((tid & 127) == 0) PROF(wg, 10);
      h_epilogue<4>(acc, hbase + (48 + n * 2) * 4096, tag);
    }
    asm volatile("barrier.cluster.wait.aligned;" ::: "memory");
    if ((tid & 127) == 0) PROF(wg, 11);

    float acc[56];
    check(0, 4);
    if (wg == 1) bar_sync<2, 256>();
#pragma unroll
    for (int b = 0; b < 14; b++) {
      if ((tid & 127) == 0) PROF(wg, 16 + b);
      if (b >= 4) mbar_wait(bars + (B_FULL + b % 7) * 8, b < 7);
      else if (b == 0) mbar_wait(bars + B_RFULL * 8, 1);
      if (b == 4) check(4, 7);
      if (b == 7) check(7, 11);
      if (b == 11) check(11, 14);
      wg_fence();
      const uint64_t db = mkdesc(b < 4 ? sb + OFF_R + b * 14336 : sb + b % 7 * SLOT, 1792, 128, 0);
#pragma unroll
      for (int kk = 0; kk < 4; kk++) wgmma_rs_112<1>(acc, ha[b][kk], db + kk * 224, (b | kk) != 0);
      wg_commit();
      if (b == LEAD2 && wg == 0) bar_arrive<2, 256>();
      if (b == 0) load(16, 24);
      if (b == 1) load(24, 28);
      if (b == 4 || b == 5) load(8 * b - 4, 8 * b + 4);
      if (b == 7) load(44, 52);
      if (b == 8) load(52, 56);
      if (b > 0) wg_wait<1>();
      if (lane == 0) {
        if (b >= 5 && b <= 9) mbar_arrive(bars + (B_EMPTY + (b + 6) % 7) * 8);
        if (b == 4) {
          mbar_arrive(bars + B_LFREE * 8);
          asm volatile("{\n.reg .b32 ra;\nmapa.shared::cluster.u32 ra, %0, %1;\nmbarrier.arrive.relaxed.cluster.shared::cluster.b64 _, [ra];\n}"
                       :: "r"(bars + B_RFREE * 8), "r"(kh ^ 1) : "memory");
        }
      }
    }
    const int t128 = tid & 127;
    wg_wait<0>(); keep(acc);
    if (wg == 0) {
      if (t128 == 0) PROF(wg, 12);
      mbar_wait_cluster(bars + B_RFREE * 8, 0);
      uint32_t rdst, rbar;
      asm volatile("mapa.shared::cluster.u32 %0, %1, %2;" : "=r"(rdst) : "r"(sb + OFF_R + t128 * 16), "r"(kh ^ 1));
      asm volatile("mapa.shared::cluster.u32 %0, %1, %2;" : "=r"(rbar) : "r"(bars + B_RECV * 8), "r"(kh ^ 1));
#pragma unroll
      for (int i = 0; i < 14; i++)
        asm volatile("st.async.weak.shared::cluster.mbarrier::complete_tx::bytes.v4.f32 [%0], {%1,%2,%3,%4}, [%5];"
                     :: "r"(rdst + i * 2048), "f"(acc[4 * i]), "f"(acc[4 * i + 1]), "f"(acc[4 * i + 2]), "f"(acc[4 * i + 3]), "r"(rbar) : "memory");
    } else {
      float spec[2][28];
      if (t128 == 0) PROF(wg, 12);
      mbar_wait(bars + B_PQFULL * 8, 0);
      if (t128 == 0) { PROF(wg, 13); g_ep[bid] = epoch + 1; }
#pragma unroll
      for (int i = 0; i < 4; i++) {
        if (i == 0) mbar_wait(bars + B_GFULL * 8, 0);
        if (i >= 2) mbar_wait(bars + (B_FULL + i - 2) * 8, 1);
        wg_fence();
        const uint64_t da = mkdesc(sb + OFF_PQ + i * 14336, 1024, 1024, 1);
        const uint64_t db = mkdesc(i < 2 ? sb + OFF_R + 28672 + i * (G_IMG / 2) : sb + (i - 2) * SLOT, 896, 128, 0);
#pragma unroll
        for (int kk = 0; kk < 7; kk++) wgmma_ss_56<1, 0>(spec[i >> 1], da + kk * 128, db + kk * 112, ((i & 1) | kk) != 0);
        wg_commit();
      }
      const float* gs = reinterpret_cast<const float*>(smem + OFF_G) + w4 * 16 + g;
      const float o0 = bf16_round(1.0f - gs[0]), o1 = bf16_round(1.0f - gs[8]);
      const float g0 = gs[0] * (1.0f / (float)(S_ * D_)), g1 = gs[8] * (1.0f / (float)(S_ * D_));
      wg_wait<0>(); keep(spec[0]); keep(spec[1]);
      if (t128 == 0) PROF(wg, 14);
      mbar_wait_cluster(bars + B_RECV * 8, 0);
      if (t128 == 0) PROF(wg, 0);
      float4 o[14];
#pragma unroll
      for (int i = 0; i < 14; i++) o[i] = lds128f(sb + OFF_R + t128 * 16 + i * 2048);
      bar_sync<5, 128>();
      const uint32_t st = sb + OFF_PQ + w4 * 3840;
#pragma unroll
      for (int i = 0; i < 7; i++) {
        uint32_t pk[4];
#pragma unroll
        for (int e = 0; e < 2; e++) {
          const int c = 2 * i + e, si = i * 4 + e;
          pk[2 * e] = pack_bf16(fmaf(acc[4 * c] + o[c].x, o0, g0 * spec[0][si]), fmaf(acc[4 * c + 1] + o[c].y, o0, g0 * spec[1][si]));
          pk[2 * e + 1] = pack_bf16(fmaf(acc[4 * c + 2] + o[c].z, o1, g1 * spec[0][si + 2]), fmaf(acc[4 * c + 3] + o[c].w, o1, g1 * spec[1][si + 2]));
        }
        asm volatile("stmatrix.sync.aligned.m8n8.x4.shared.b16 [%0], {%1,%2,%3,%4};"
                     :: "r"(st + (lane & 15) * 240 + (lane >> 4) * 16 + i * 32), "r"(pk[0]), "r"(pk[1]), "r"(pk[2]), "r"(pk[3]) : "memory");
      }
      __syncwarp();
      if (lane < 28) {
        const int r2 = lane >= 14, cc = lane - r2 * 14;
        unsigned char* ob = reinterpret_cast<unsigned char*>(out) + (size_t)(m * 128 + kh * 64 + w4 * 16 + r2) * (D_ * 2) + n * 224 + cc * 16;
        float4 v[8];
#pragma unroll
        for (int i = 0; i < 8; i++) v[i] = lds128f(st + r2 * 240 + cc * 16 + i * 480);
#pragma unroll
        for (int i = 0; i < 8; i++) stg128(ob + i * (D_ * 4), __float_as_uint(v[i].x), __float_as_uint(v[i].y), __float_as_uint(v[i].z), __float_as_uint(v[i].w));
      }
    }
    if (t128 == 0) { PROF(wg, 15); if (wg) { PROFG(4, 30); PROF(4, 31); } }
  } else if (warp < 12) {
    asm volatile("setmaxnreg.dec.sync.aligned.u32 72;");
    const int t = tid - 256;
    const int k = bid;
    if (t == 0) PROF(2, 0);
    uint4 gv[7];
#pragma unroll
    for (int i = 0; i < 7; i++) gv[i] = ldg128(reinterpret_cast<const uint4*>(gate_w) + i * 8 + (t & 7));
    if (t < 98) {
      int cid = m * 98 + t, kc = cid / 56, nn = cid - kc * 56;
      int d = 112 * n + 8 * (2 * (nn >> 3) + (nn & 1)) + (nn & 6) + kh;
      int dr = d > 224 ? d - 448 : d;
      const float df = (float)dr * (-6.283185307179586f / 448.0f);
      uint32_t pk[4];
#pragma unroll
      for (int e = 0; e < 4; e++) {
        const float a = (float)(4 * kc + e) * df;
        pk[e] = pack_bf16(2.0f * __cosf(a), 2.0f * __sinf(a));
      }
      if (kc == 0) pk[0] = (((d >> 1) ^ kh) & 1) ? 0xBF803F80u : 0x3F803F80u;
      stg128(g_G + (size_t)(n * 2 + kh) * G_IMG + cid * 16, pk[0], pk[1], pk[2], pk[3]);
    }
    bar_sync<0, NTHREADS - 64>();
    asm volatile("barrier.cluster.arrive.relaxed.aligned;" ::: "memory");
    {
      const int row = n * 16 + (t >> 3), l8 = t & 7;
      mbar_wait(bars + (B_XFULL + 1) * 8, 0);
      float sum = 0.f;
#pragma unroll
      for (int i = 0; i < 7; i++) {
        const uint4 a = lds128(sb + OFF_R + i * 8192 + row * 128 + ((l8 ^ (row & 7)) << 4));
        const uint32_t aa[4] = {a.x, a.y, a.z, a.w}, bb[4] = {gv[i].x, gv[i].y, gv[i].z, gv[i].w};
#pragma unroll
        for (int e = 0; e < 4; e++) {
          const uint32_t pr = as_u(__hmul2(as_b2(aa[e]), as_b2(bb[e])));
          sum += bf_lo(pr) + bf_hi(pr);
        }
      }
      sum += __shfl_xor_sync(0xffffffffu, sum, 1); sum += __shfl_xor_sync(0xffffffffu, sum, 2); sum += __shfl_xor_sync(0xffffffffu, sum, 4);
      if (lane == 0) mbar_arrive(bars + (B_XFREE + 1) * 8);
      if (l8 == 0) g_gate[m * 128 + kh * 64 + row] = bf16_round(__fdividef(1.0f, 1.0f + __expf(-bf16_round(sum))));
    }
    if (t == 0) PROF(2, 11);
    mbar_wait(bars + B_XFREE * 8, 0);
    if (k < 113) {
      const float u = -6.283185307179586f / 2048.0f, t2 = (float)(2 * t) * u, rr = (float)(t >> 4) * u;
#pragma unroll 1
      for (int i = 0; i < 4; i++) {
        const float q = (float)(2 * i), l = (float)((t & 15) + 64 * i);
        sts128(sb + OFF_TW + i * 2048 + t * 16, cis(t2 * q), cis((t2 + u) * q), cis(t2 * (q + 1.0f)), cis((t2 + u) * (q + 1.0f)));
        sts128(sb + OFF_TW + 8192 + i * 2048 + t * 16, cis(rr * l), cis(rr * (l + 16.0f)), cis(rr * (l + 32.0f)), cis(rr * (l + 48.0f)));
      }
      const float l = (float)((t >> 1) & 15) * (8.0f * u), jj = (float)((t >> 5) * 4 + (t & 1) * 2);
      sts64(sb + OFF_TW + 16384 + t * 8, cis(l * jj), cis(l * (jj + 1.0f)));
    }
    if (t == 0) PROF(2, 9);
    mbar_wait(bars + B_PIN * 8, 0);
    if (t == 0) PROF(2, 4);
    {
      const uint32_t wa = sb + OFF_WS + (((t & 7) - bid) & 7) * 450 + (t >> 3) * 2, wc = wa + 448 - (t >> 3) * 4;
      uint2* dst = g_Wt + (t >> 3) * S_ + 16 * bid + 2 * (t & 7);
#pragma unroll 1
      for (int h = 0; h < 2; h++) {
        uint32_t w[4][8];
#pragma unroll
        for (int i = 0; i < 4; i++) {
#pragma unroll
          for (int e = 0; e < 4; e++) { w[i][2 * e] = lds16(wa + h * 128 + i * 32 + e * 3600); w[i][2 * e + 1] = lds16(wc - h * 128 - i * 32 + e * 3600); }
        }
#pragma unroll
        for (int i = 0; i < 4; i++)
          if (i < 3 || h == 0 || t < 8)
            stg128(dst + (h * 64 + i * 16) * S_, __byte_perm(w[i][0], w[i][1], 0x5410), __byte_perm(w[i][4], w[i][5], 0x5410), __byte_perm(w[i][2], w[i][3], 0x5410), __byte_perm(w[i][6], w[i][7], 0x5410));
      }
    }
    __syncwarp();
    if (lane == 0) mbar_arrive(bars + B_PUBW * 8);
    if (t == 0) PROF(2, 6);
    mbar_wait(bars + B_RFULL * 8, 0);
    if (t < 112) {
      const int js = bid >> 4, nn = (t >> 1) / 14, cc = (t >> 1) - nn * 14;
      unsigned char* wdst = g_Wd + (size_t)((js >> 2) * 4 + nn) * WD_IMG + cc * 128 + (t & 1) * 16;
      uint4 v[7];
#pragma unroll
      for (int i = 0; i < 7; i++) v[i] = lds128(sb + OFF_R + i * 1792 + (t & 1) * 896 + (t >> 1) * 16);
#pragma unroll
      for (int i = 0; i < 7; i++) {
        int col = 14 * (bid & 15) + 2 * i - (js & 1) * 32;
        if (col < 0) col += 224;
        const int kpos = col < 192 ? (col >> 6) * 256 + (js & 3) * 64 + (col & 63) : 576 + (js & 3) * 32 + col;
        stg128(wdst + (kpos >> 3) * 1792 + (kpos & 7) * 16, v[i].x, v[i].y, v[i].z, v[i].w);
      }
    }
    __syncwarp();
    if (lane == 0) mbar_arrive(bars + B_PUBD * 8);
    bar_sync<3, 128>();
    if (k < 113) {
      if (t == 0) PROF(2, 2);
      mbar_wait(bars + B_XCFULL * 8, 0);
      if (t == 0) PROF(2, 3);
      c2 v[16];
      uint2 xe[8], xo[8];
      const uint32_t* xs = g_Xc + (k == 112 ? 0 : k) * 2 * S_ + 2 * t;
#pragma unroll
      for (int jj = 0; jj < 8; jj++) { xe[jj] = ldg64_l2(xs + jj * 256); xo[jj] = ldg64_l2(xs + S_ + jj * 256); }
      const uint32_t se = k == 0 ? 0x4410 : (k == 112 ? 0x4432 : 0x3210), so = k == 0 ? 0x4410 : (k == 112 ? 0x3244 : 0x3210);
#pragma unroll
      for (int jj = 0; jj < 8; jj++) {
        const uint2 e2 = xe[jj], o2 = xo[jj];
#pragma unroll
        for (int h = 0; h < 2; h++) {
          const b2 e = as_b2(__byte_perm(h ? e2.y : e2.x, 0, se)), o = as_b2(__byte_perm(h ? o2.y : o2.x, 0, so));
          const uint32_t s = as_u(__hadd2(e, o)), d = as_u(__hsub2(e, o)) ^ 0x80000000u;
          v[2 * jj + h] = mk(as_b2(__byte_perm(s, d, 0x5410)), as_b2(__byte_perm(s, d, 0x7632)));
        }
      }
      if (t == 0) PROF(2, 12);
      columns(v, sb, t);
      if (t == 0) PROF(2, 14);
      const int pre = (k == 112) ? 1 : 2 * k, pim = (k == 112) ? 1 : 2 * k + 1;
      uint32_t* pq = reinterpret_cast<uint32_t*>(g_PQ) + (t >> 5) * 14336;
      uint32_t* pr = pq + pre * 32 + ((((lane >> 2) ^ pre) & 7) << 2) + (lane & 3);
      uint32_t* pi = pq + pim * 32 + ((((lane >> 2) ^ pim) & 7) << 2) + (lane & 3);
#pragma unroll
      for (int jj = 0; jj < 8; jj++) {
        const b2 ar = as_b2(__byte_perm(as_u(v[2 * jj].y), as_u(v[2 * jj + 1].y), 0x5410)), br = as_b2(__byte_perm(as_u(v[2 * jj].y), as_u(v[2 * jj + 1].y), 0x7632));
        const b2 ai = as_b2(__byte_perm(as_u(v[2 * jj].x), as_u(v[2 * jj + 1].x), 0x5410)), bi = as_b2(__byte_perm(as_u(v[2 * jj].x), as_u(v[2 * jj + 1].x), 0x7632));
        pr[jj * 57344] = as_u(__hadd2(ar, br));
        if (k != 112) pr[jj * 57344 + 7168] = as_u(__hsub2(ar, br));
        if (k != 0) pi[jj * 57344 + 7168] = as_u(__hadd2(ai, bi));
        if (k != 0 && k != 112) pi[jj * 57344] = as_u(__hsub2(ai, bi));
      }
      fence_async_smem();
    }
    bar_sync<3, 128>();
    if (t == 0) { PROF(2, 5); red_release(&g_cnt[5 * 32]); PROF(2, 7); }
    __syncwarp();
    asm volatile("barrier.cluster.wait.aligned;" ::: "memory");
  } else {
    asm volatile("setmaxnreg.dec.sync.aligned.u32 24;");
    if (warp == 12) {
      if (elect()) {
        mbar_init(bars + B_XFULL * 8, 1); mbar_init(bars + (B_XFULL + 1) * 8, 1);
        fence_async_smem();
#pragma unroll
        for (int w = 0; w < 2; w++) {
          mbar_expect(bars + (B_XFULL + w) * 8, HALF_XR);
          tma3d(sb + OFF_PQ + w * HALF_XR, &tm_x, 0, m * 128 + (w ^ kh ^ 1) * 64, 0, bars + (B_XFULL + w) * 8);
        }
        PROF(3, 3);
#pragma unroll
        for (int i = 0; i < NSLOT; i++) mbar_init(bars + (B_FULL + i) * 8, 1);
        mbar_init(bars + B_PIN * 8, 1);
        fence_async_smem();
      }
      bar_arrive<0, NTHREADS - 64>();
#pragma unroll 1
      for (int i = 0; i < 6; i++) {
        if (elect()) {
          const uint32_t fb = bars + (B_FULL + i) * 8;
          mbar_expect(fb, SLOT);
          tma2d(sb + i * SLOT, &tm_g, c64, i * 64, fb);
          tma2d(sb + i * SLOT + 8192, &tm_u, c64, i * 64, fb);
          PROF(3, 4 + i);
        }
      }
      if (elect()) {
        prefetch_l2(reinterpret_cast<const unsigned char*>(w_r) + bid * 7200, 7200);
        prefetch_l2(reinterpret_cast<const unsigned char*>(w_i) + bid * 7200, 7200);
        prefetch_tma2d(&tm_g, c64, 384); prefetch_tma2d(&tm_u, c64, 384);
      }
    } else if (warp == 14) {
      if (elect()) {
#pragma unroll
        for (int i = B_EMPTY; i < B_END; i++)
          if (i < B_XFULL || i >= B_XFREE) mbar_init(bars + i * 8, i >= B_PQFULL ? 1 : ((i == B_XFREE || i >= B_PUBW) ? 4 : 8));
        asm volatile("fence.mbarrier_init.release.cluster;" ::: "memory");
        fence_async_smem();
        mbar_expect(bars + B_RECV * 8, 64 * 112 * 4);
      }
      bar_arrive<0, NTHREADS - 64>();
    }
    const uint32_t epoch = ld_relaxed(&g_ep[bid]);
    if (warp == 13 && lane == 0) { PROFG(4, 0); PROF(4, 1); }
    bar_sync<1, 128>();
    asm volatile("barrier.cluster.arrive.relaxed.aligned;" ::: "memory");
    if (warp == 12) {
      int slot = 6, ph = 1;
      auto wait_slot = [&]() { mbar_wait(bars + (B_EMPTY + slot) * 8, ph ^ (slot == 6)); };
      auto adv = [&]() { if (++slot == NSLOT) { slot = 0; ph ^= 1; } };
      const int c32 = 224 * j + ((j & 1) ? 0 : 192);
#pragma unroll 1
      for (int i = 6; i < 25; i++) {
        wait_slot();
        if (elect()) {
          const uint32_t dst = sb + slot * SLOT, fb = bars + (B_FULL + slot) * 8;
          const bool last = i >= 21;
          const int cc = last ? c32 : c64 + 64 * (i / 7), rr = last ? slot * 128 : slot * 64;
          mbar_expect(fb, SLOT);
          tma2d(dst, last ? &tm_g32 : &tm_g, cc, rr, fb);
          tma2d(dst + 8192, last ? &tm_u32 : &tm_u, cc, rr, fb);
        }
        adv();
      }
      if (lane == 0) PROF(3, 0);
      mbar_wait(bars + B_PREP * 8, 0);
      if (lane == 0) PROF(3, 1);
#pragma unroll 1
      for (int i = 4; i < 16; i++) {
        if (lane == 0) PROF(3, 16 + i);
        wait_slot();
        if (elect()) {
          const int bytes = i < 14 ? 14336 : G_IMG / 2;
          const unsigned char* src = i < 14 ? g_Wd + (size_t)j * WD_IMG + i * 14336 : g_G + (size_t)(n * 4 + i - 12) * (G_IMG / 2);
          mbar_expect(bars + (B_FULL + slot) * 8, bytes);
          bulk_g2s(sb + slot * SLOT, src, bytes, bars + (B_FULL + slot) * 8);
        }
        adv();
      }
      if (lane == 0) PROF(3, 2);
    } else if (warp == 13) {
#pragma unroll 1
      for (int u = 0; u < 3; u++) {
        mbar_wait(bars + (u ? B_PUBW - 1 + u : B_PUBX) * 8, 0);
        if (lane == 0) { PROF(4, 8 + u); red_release(&g_cnt[(u ? 8 - 2 * u : j >> 1) * 32]); PROF(4, 12 + u); }
        __syncwarp();
      }
      mbar_wait(bars + B_LFREE * 8, 0);
      if (elect()) {
        mbar_expect(bars + B_GFULL * 8, G_IMG);
        bulk_g2s(sb + OFF_R + 28672, g_G + (size_t)(n * 2) * G_IMG, G_IMG, bars + B_GFULL * 8);
      }
    } else if (warp == 14) {
#pragma unroll 1
      for (int u = 0; u < 2; u++) {
        wait_ge(&g_cnt[(6 - 2 * u) * 32], (epoch + 1) * 128);
        fence_async_global();
        if (lane == 0) { mbar_arrive(bars + (B_PREPW - u) * 8); PROF(5, 9 - u); }
      }
    } else {
      mbar_wait(bars + B_XFREE * 8, 0);
      if (elect()) {
        mbar_expect(bars + B_PIN * 8, 14400);
        bulk_g2s(sb + OFF_WS, reinterpret_cast<const unsigned char*>(w_r) + bid * 7200, 7200, bars + B_PIN * 8);
        bulk_g2s(sb + OFF_WS + 7200, reinterpret_cast<const unsigned char*>(w_i) + bid * 7200, 7200, bars + B_PIN * 8);
        PROF(5, 1);
      }
      mbar_wait(bars + (B_XFREE + 1) * 8, 0);
      if (elect()) {
        mbar_expect(bars + B_RFULL * 8, 12544);
        bulk_g2s(sb + OFF_R, reinterpret_cast<const unsigned char*>(w_down) + bid * 12544, 12544, bars + B_RFULL * 8);
        prefetch_l2(reinterpret_cast<const unsigned char*>(w_gate) + bid * 12544, 12544);
        prefetch_l2(reinterpret_cast<const unsigned char*>(w_up) + bid * 12544, 12544);
        PROF(5, 2);
      }
      if (bid < 113) {
        const int sl = (bid == 112) ? 0 : bid;
        wait_ge(&g_cnt[((sl & 1) + 2 * ((sl >> 1) / 28)) * 32], (epoch + 1) * 32);
        if (elect()) { PROF(5, 16); mbar_arrive(bars + B_XCFULL * 8); }
        mbar_wait(bars + B_PREPW * 8, 0);
        if (elect()) {
          mbar_expect(bars + B_WFULL * 8, 16384);
          bulk_g2s(sb + OFF_WS, g_Wt + bid * S_, 16384, bars + B_WFULL * 8);
          PROF(5, 17);
        }
      }
      mbar_wait(bars + B_PREP * 8, 0);
      if (elect()) {
        mbar_expect(bars + B_RFULL * 8, HALF_XR);
        bulk_g2s(sb + OFF_R, g_Wd + (size_t)j * WD_IMG, HALF_XR, bars + B_RFULL * 8);
        PROF(5, 19);
      }
      wait_ge(&g_cnt[5 * 32], (epoch + 1) * 128);
      fence_async_global();
      if (elect()) {
        PROF(5, 18);
        mbar_expect(bars + B_PQFULL * 8, HALF_XR + 256);
        const unsigned char* src = g_PQ + (size_t)(m * 2 + kh) * HALF_XR;
        bulk_g2s(sb + OFF_PQ, src, 28672, bars + B_PQFULL * 8);
        bulk_g2s(sb + OFF_PQ + 28672, src + 28672, 28672, bars + B_PQFULL * 8);
        bulk_g2s(sb + OFF_G, g_gate + m * 128 + kh * 64, 256, bars + B_PQFULL * 8);
      }
    }
    __syncwarp();
    asm volatile("barrier.cluster.wait.aligned;" ::: "memory");
  }
}

typedef CUresult (*EncodeFn)(CUtensorMap*, CUtensorMapDataType, cuuint32_t, void*, const cuuint64_t*, const cuuint64_t*, const cuuint32_t*,
                             const cuuint32_t*, CUtensorMapInterleave, CUtensorMapSwizzle, CUtensorMapL2promotion, CUtensorMapFloatOOBfill);

void make_map(EncodeFn enc, CUtensorMap* tm, const void* base, int cols, int rows, int bc, int br, CUtensorMapSwizzle sw) {
  cuuint64_t gd[2] = {(cuuint64_t)cols, (cuuint64_t)rows};
  cuuint64_t gs[1] = {(cuuint64_t)cols * 2};
  cuuint32_t bd[2] = {(cuuint32_t)bc, (cuuint32_t)br};
  cuuint32_t es[2] = {1, 1};
  enc(tm, CU_TENSOR_MAP_DATA_TYPE_BFLOAT16, 2, const_cast<void*>(base), gd, gs, bd, es, CU_TENSOR_MAP_INTERLEAVE_NONE, sw,
      CU_TENSOR_MAP_L2_PROMOTION_L2_128B, CU_TENSOR_MAP_FLOAT_OOB_FILL_NONE);
}

}

extern "C" void kernel_launch(void* const* d_in, const int* in_sizes, int n_in, void* d_out, int out_size) {
  (void)in_sizes; (void)n_in; (void)out_size;
  const __nv_bfloat16* x = (const __nv_bfloat16*)d_in[0];
  const __nv_bfloat16* w_r = (const __nv_bfloat16*)d_in[1];
  const __nv_bfloat16* w_i = (const __nv_bfloat16*)d_in[2];
  const __nv_bfloat16* w_gate = (const __nv_bfloat16*)d_in[4];
  const __nv_bfloat16* w_up = (const __nv_bfloat16*)d_in[5];
  const __nv_bfloat16* w_down = (const __nv_bfloat16*)d_in[6];
  const __nv_bfloat16* gate_w = (const __nv_bfloat16*)d_in[7];
  static EncodeFn enc = nullptr;
  static bool ok = false;
  if (!enc) {
    cudaDriverEntryPointQueryResult qr;
    cudaGetDriverEntryPoint("cuTensorMapEncodeTiled", (void**)&enc, cudaEnableDefault, &qr);
    cudaFuncSetAttribute(fused_kernel, cudaFuncAttributeMaxDynamicSharedMemorySize, SMEM_BYTES);
    cudaFuncAttributes fa;
    cudaFuncGetAttributes(&fa, fused_kernel);
    ok = (fa.numRegs == 128);
  }
  if (!ok) return;
  CUtensorMap tx, tg, tu, tg32, tu32;
  {
    cuuint64_t gd[3] = {64, (cuuint64_t)S_, 7};
    cuuint64_t gs[2] = {(cuuint64_t)D_ * 2, 128};
    cuuint32_t bd[3] = {64, 64, 7};
    cuuint32_t es[3] = {1, 1, 1};
    enc(&tx, CU_TENSOR_MAP_DATA_TYPE_BFLOAT16, 3, const_cast<__nv_bfloat16*>(x), gd, gs, bd, es, CU_TENSOR_MAP_INTERLEAVE_NONE, CU_TENSOR_MAP_SWIZZLE_128B,
        CU_TENSOR_MAP_L2_PROMOTION_L2_128B, CU_TENSOR_MAP_FLOAT_OOB_FILL_NONE);
  }
  make_map(enc, &tg, w_gate, F_, D_, 64, 64, CU_TENSOR_MAP_SWIZZLE_128B);
  make_map(enc, &tu, w_up, F_, D_, 64, 64, CU_TENSOR_MAP_SWIZZLE_128B);
  make_map(enc, &tg32, w_gate, F_, D_, 32, 128, CU_TENSOR_MAP_SWIZZLE_64B);
  make_map(enc, &tu32, w_up, F_, D_, 32, 128, CU_TENSOR_MAP_SWIZZLE_64B);
  fused_kernel<<<128, NTHREADS, SMEM_BYTES>>>(tx, tg, tu, tg32, tu32, w_r, w_i, w_gate, w_up, w_down, gate_w, (__nv_bfloat16*)d_out);
}
```

```cpp
#include <cuda_runtime.h>
#include <cuda_bf16.h>
#include <cuda.h>
#include <stdint.h>

namespace {

constexpr int S_ = 2048, D_ = 448, F_ = 1792;
constexpr int NTHREADS = 512;
constexpr int SLOT = 16384, NSLOT = 7;
constexpr int HALF_XR = 57344;
constexpr int OFF_PQ = NSLOT * SLOT;
constexpr int OFF_R = OFF_PQ + HALF_XR;
constexpr int OFF_EXCH = OFF_PQ;
constexpr int OFF_WS = OFF_EXCH + 18432;
constexpr int OFF_TW = OFF_WS + 16384;
constexpr int OFF_MISC = OFF_R + HALF_XR;
constexpr int OFF_G = OFF_MISC;
constexpr int OFF_BAR = OFF_MISC + 512;
constexpr int SMEM_BYTES = OFF_BAR + 512;
constexpr int B_FULL = 0, B_EMPTY = 7, B_XFULL = 14  ;
constexpr int B_XFREE = 16  , B_PUBX = 18, B_RFREE = 19, B_LFREE = 20;
constexpr int B_PUBW = 21;
constexpr int B_PQFULL = 22  , B_RECV = 26, B_WFULL = 27, B_XCFULL = 28, B_PREP = 29, B_RFULL = 30, B_GFULL = 31, B_END = 32, B_PIN = 32;

constexpr int G_IMG = 224 * 56 * 2;

__device__ __align__(1024) uint32_t g_Xc[112 * 2 * S_];
__device__ __align__(1024) unsigned char g_H[32 * 56 * 4096];
__device__ __align__(1024) unsigned char g_PQ[32 * HALF_XR];
__device__ __align__(1024) unsigned char g_G[8 * G_IMG];
__device__ __align__(1024) uint2 g_Wt[113 * S_];
__device__ __align__(1024) float g_gate[S_];
__device__ __align__(128) unsigned int g_ep[128];
__device__ __align__(128) unsigned int g_cnt[8 * 32];

#define PROF(role, idx) do {} while (0)
#define PROFG(role, idx) do {} while (0)

__device__ __forceinline__ uint32_t s2u(const void* p) { return (uint32_t)__cvta_generic_to_shared(p); }
__device__ __forceinline__ void mbar_init(uint32_t b, int c) { asm volatile("mbarrier.init.shared::cta.b64 [%0], %1;" :: "r"(b), "r"(c) : "memory"); }
__device__ __forceinline__ void mbar_expect(uint32_t b, int bytes) { asm volatile("mbarrier.arrive.expect_tx.shared::cta.b64 _, [%0], %1;" :: "r"(b), "r"(bytes) : "memory"); }
__device__ __forceinline__ void mbar_arrive(uint32_t b) { asm volatile("mbarrier.arrive.shared::cta.b64 _, [%0];" :: "r"(b) : "memory"); }
__device__ __forceinline__ void mbar_wait(uint32_t b, int ph) {
  asm volatile("{\n.reg .pred p;\n.reg .u32 c;\nmov.u32 c, 0;\nL_WAIT:\nmbarrier.try_wait.parity.shared::cta.b64 p, [%0], %1;\n@p bra.uni L_DONE;\n"
               "add.u32 c, c, 1;\nsetp.lt.u32 p, c, 4194304;\n@p bra.uni L_WAIT;\ntrap;\nL_DONE:\n}" :: "r"(b), "r"(ph) : "memory");
}
__device__ __forceinline__ void mbar_wait_cluster(uint32_t b, int ph) {
  asm volatile("{\n.reg .pred p;\n.reg .u32 c;\nmov.u32 c, 0;\nL_WAIT:\nmbarrier.try_wait.parity.acquire.cluster.shared::cta.b64 p, [%0], %1;\n@p bra.uni L_DONE;\n"
               "add.u32 c, c, 1;\nsetp.lt.u32 p, c, 4194304;\n@p bra.uni L_WAIT;\ntrap;\nL_DONE:\n}" :: "r"(b), "r"(ph) : "memory");
}
__device__ __forceinline__ uint32_t ld_acquire(const unsigned int* p) { uint32_t v; asm volatile("ld.acquire.gpu.global.u32 %0, [%1];" : "=r"(v) : "l"(p) : "memory"); return v; }
__device__ __forceinline__ uint32_t ld_relaxed(const unsigned int* p) { uint32_t v; asm volatile("ld.relaxed.gpu.global.u32 %0, [%1];" : "=r"(v) : "l"(p) : "memory"); return v; }
__device__ __forceinline__ void wait_ge(const unsigned int* p, uint32_t target) {
#pragma unroll 1
  for (int i = 0; i < (1 << 22); i++) { if ((int)(ld_acquire(p) - target) >= 0) return; }
  __trap();
}
__device__ __forceinline__ void red_release(unsigned int* p) { asm volatile("red.release.gpu.global.add.u32 [%0], 1;" :: "l"(p) : "memory"); }
__device__ __forceinline__ bool elect() { uint32_t p; asm volatile("{\n.reg .pred p;\nelect.sync _|p, 0xffffffff;\nselp.u32 %0, 1, 0, p;\n}" : "=r"(p)); return p; }
__device__ __forceinline__ void fence_async_smem() { asm volatile("fence.proxy.async.shared::cta;" ::: "memory"); }
__device__ __forceinline__ void fence_async_global() { asm volatile("fence.proxy.async.global;" ::: "memory"); }
template <int ID, int N> __device__ __forceinline__ void bar_sync() { asm volatile("bar.sync %0, %1;" :: "n"(ID), "n"(N) : "memory"); }
template <int ID, int N> __device__ __forceinline__ void bar_arrive() { asm volatile("bar.arrive %0, %1;" :: "n"(ID), "n"(N) : "memory"); }
__device__ __forceinline__ void tma2d(uint32_t dst, const CUtensorMap* tm, int c0, int c1, uint32_t bar) {
  asm volatile("cp.async.bulk.tensor.2d.shared::cluster.global.mbarrier::complete_tx::bytes [%0], [%1, {%3, %4}], [%2];"
               :: "r"(dst), "l"(tm), "r"(bar), "r"(c0), "r"(c1) : "memory");
}
__device__ __forceinline__ void tma3d(uint32_t dst, const CUtensorMap* tm, int c0, int c1, int c2, uint32_t bar) {
  asm volatile("cp.async.bulk.tensor.3d.shared::cluster.global.mbarrier::complete_tx::bytes [%0], [%1, {%3, %4, %5}], [%2];"
               :: "r"(dst), "l"(tm), "r"(bar), "r"(c0), "r"(c1), "r"(c2) : "memory");
}
__device__ __forceinline__ void bulk_g2s(uint32_t dst, const void* src, int bytes, uint32_t bar) {
  asm volatile("cp.async.bulk.shared::cluster.global.mbarrier::complete_tx::bytes [%0], [%1], %2, [%3];"
               :: "r"(dst), "l"(src), "r"(bytes), "r"(bar) : "memory");
}
__device__ __forceinline__ void prefetch_l2(const void* src, int bytes) {
  asm volatile("cp.async.bulk.prefetch.L2.global [%0], %1;" :: "l"(src), "r"(bytes) : "memory");
}
__device__ __forceinline__ void prefetch_tma2d(const CUtensorMap* tm, int c0, int c1) {
  asm volatile("cp.async.bulk.prefetch.tensor.2d.L2.global [%0, {%1, %2}];" :: "l"(tm), "r"(c0), "r"(c1) : "memory");
}
__device__ __forceinline__ uint64_t mkdesc(uint32_t addr, uint32_t lbo, uint32_t sbo, uint32_t mode) {
  return (uint64_t)((addr & 0x3FFFF) >> 4) | ((uint64_t)(lbo >> 4) << 16) | ((uint64_t)(sbo >> 4) << 32) | ((uint64_t)mode << 62);
}
__device__ __forceinline__ void wg_fence() { asm volatile("wgmma.fence.sync.aligned;" ::: "memory"); }
__device__ __forceinline__ void wg_commit() { asm volatile("wgmma.commit_group.sync.aligned;" ::: "memory"); }
template <int N> __device__ __forceinline__ void wg_wait() { asm volatile("wgmma.wait_group.sync.aligned %0;" :: "n"(N) : "memory"); }
template <int N> __device__ __forceinline__ void keep(float (&d)[N]) {
#pragma unroll
  for (int i = 0; i < N; i++) asm volatile("" : "+f"(d[i]) :: "memory");
}
__device__ __forceinline__ uint32_t pack_bf16(float lo, float hi) { uint32_t r; asm("cvt.rn.bf16x2.f32 %0, %1, %2;" : "=r"(r) : "f"(hi), "f"(lo)); return r; }
__device__ __forceinline__ float bf16_round(float v) { return __bfloat162float(__float2bfloat16_rn(v)); }
__device__ __forceinline__ void sts128(uint32_t a, uint32_t x, uint32_t y, uint32_t z, uint32_t w) { asm volatile("st.shared.v4.b32 [%0], {%1,%2,%3,%4};" :: "r"(a), "r"(x), "r"(y), "r"(z), "r"(w) : "memory"); }
__device__ __forceinline__ float4 lds128f(uint32_t a) { float4 v; asm volatile("ld.shared.v4.f32 {%0,%1,%2,%3}, [%4];" : "=f"(v.x), "=f"(v.y), "=f"(v.z), "=f"(v.w) : "r"(a) : "memory"); return v; }

__device__ __forceinline__ uint2 lds64(uint32_t a) { uint2 v; asm volatile("ld.shared.v2.b32 {%0,%1}, [%2];" : "=r"(v.x), "=r"(v.y) : "r"(a) : "memory"); return v; }
__device__ __forceinline__ float bf_lo(uint32_t w) { return __uint_as_float(w << 16); }
__device__ __forceinline__ float bf_hi(uint32_t w) { return __uint_as_float(w & 0xffff0000u); }
__device__ __forceinline__ uint32_t opaque(uint32_t v) { asm volatile("" : "+r"(v)); return v; }
__device__ __forceinline__ uint4 ldg128(const void* p) { uint4 v; asm volatile("ld.global.nc.v4.b32 {%0,%1,%2,%3}, [%4];" : "=r"(v.x), "=r"(v.y), "=r"(v.z), "=r"(v.w) : "l"(p)); return v; }
__device__ __forceinline__ void stg128(void* p, uint32_t x, uint32_t y, uint32_t z, uint32_t w) { asm volatile("st.global.v4.b32 [%0], {%1,%2,%3,%4};" :: "l"(p), "r"(x), "r"(y), "r"(z), "r"(w) : "memory"); }
__device__ __forceinline__ void stg128_l2(void* p, uint32_t x, uint32_t y, uint32_t z, uint32_t w) { asm volatile("st.relaxed.gpu.global.v4.b32 [%0], {%1,%2,%3,%4};" :: "l"(p), "r"(x), "r"(y), "r"(z), "r"(w) : "memory"); }
__device__ __forceinline__ uint2 ldg64_l2(const void* p) { uint2 v; asm volatile("ld.relaxed.gpu.global.v2.b32 {%0,%1}, [%2];" : "=r"(v.x), "=r"(v.y) : "l"(p) : "memory"); return v; }
__device__ __forceinline__ void ldg128_l2(uint32_t (&v)[4], const void* p) { asm volatile("ld.relaxed.gpu.global.v4.b32 {%0,%1,%2,%3}, [%4];" : "=r"(v[0]), "=r"(v[1]), "=r"(v[2]), "=r"(v[3]) : "l"(p) : "memory"); }
__device__ __forceinline__ uint4 lds128(uint32_t a) { uint4 v; asm volatile("ld.shared.v4.b32 {%0,%1,%2,%3}, [%4];" : "=r"(v.x), "=r"(v.y), "=r"(v.z), "=r"(v.w) : "r"(a) : "memory"); return v; }
__device__ __forceinline__ uint32_t lds16(uint32_t a) { uint32_t v; asm volatile("ld.shared.u16 %0, [%1];" : "=r"(v) : "r"(a) : "memory"); return v; }
__device__ __forceinline__ void sts64(uint32_t a, uint32_t x, uint32_t y) { asm volatile("st.shared.v2.b32 [%0], {%1,%2};" :: "r"(a), "r"(x), "r"(y) : "memory"); }
template <int TB> __device__ __forceinline__ void wgmma_rs_128(float (&d)[64], const uint32_t (&a)[4], uint64_t db, int sc) {
  asm volatile("{\n.reg .pred p;\nsetp.ne.b32 p, %69, 0;\n"
    "wgmma.mma_async.sync.aligned.m64n128k16.f32.bf16.bf16 {%0, %1, %2, %3, %4, %5, %6, %7, %8, %9, %10, %11, %12, %13, %14, %15, %16, %17, %18, %19, %20, %21, %22, %23, %24, %25, %26, %27, %28, %29, %30, %31, %32, %33, %34, %35, %36, %37, %38, %39, %40, %41, %42, %43, %44, %45, %46, %47, %48, %49, %50, %51, %52, %53, %54, %55, %56, %57, %58, %59, %60, %61, %62, %63}, {%64, %65, %66, %67}, %68, p, 1, 1, %70;\n}\n"
    : "+f"(d[0]), "+f"(d[1]), "+f"(d[2]), "+f"(d[3]), "+f"(d[4]), "+f"(d[5]), "+f"(d[6]), "+f"(d[7]), "+f"(d[8]), "+f"(d[9]), "+f"(d[10]), "+f"(d[11]), "+f"(d[12]), "+f"(d[13]), "+f"(d[14]), "+f"(d[15]), "+f"(d[16]), "+f"(d[17]), "+f"(d[18]), "+f"(d[19]), "+f"(d[20]), "+f"(d[21]), "+f"(d[22]), "+f"(d[23]), "+f"(d[24]), "+f"(d[25]), "+f"(d[26]), "+f"(d[27]), "+f"(d[28]), "+f"(d[29]), "+f"(d[30]), "+f"(d[31]), "+f"(d[32]), "+f"(d[33]), "+f"(d[34]), "+f"(d[35]), "+f"(d[36]), "+f"(d[37]), "+f"(d[38]), "+f"(d[39]), "+f"(d[40]), "+f"(d[41]), "+f"(d[42]), "+f"(d[43]), "+f"(d[44]), "+f"(d[45]), "+f"(d[46]), "+f"(d[47]), "+f"(d[48]), "+f"(d[49]), "+f"(d[50]), "+f"(d[51]), "+f"(d[52]), "+f"(d[53]), "+f"(d[54]), "+f"(d[55]), "+f"(d[56]), "+f"(d[57]), "+f"(d[58]), "+f"(d[59]), "+f"(d[60]), "+f"(d[61]), "+f"(d[62]), "+f"(d[63])
    : "r"(a[0]), "r"(a[1]), "r"(a[2]), "r"(a[3]), "l"(db), "r"(sc), "n"(TB));
}
template <int TB> __device__ __forceinline__ void wgmma_rs_64(float (&d)[32], const uint32_t (&a)[4], uint64_t db, int sc) {
  asm volatile("{\n.reg .pred p;\nsetp.ne.b32 p, %37, 0;\n"
    "wgmma.mma_async.sync.aligned.m64n64k16.f32.bf16.bf16 {%0, %1, %2, %3, %4, %5, %6, %7, %8, %9, %10, %11, %12, %13, %14, %15, %16, %17, %18, %19, %20, %21, %22, %23, %24, %25, %26, %27, %28, %29, %30, %31}, {%32, %33, %34, %35}, %36, p, 1, 1, %38;\n}\n"
    : "+f"(d[0]), "+f"(d[1]), "+f"(d[2]), "+f"(d[3]), "+f"(d[4]), "+f"(d[5]), "+f"(d[6]), "+f"(d[7]), "+f"(d[8]), "+f"(d[9]), "+f"(d[10]), "+f"(d[11]), "+f"(d[12]), "+f"(d[13]), "+f"(d[14]), "+f"(d[15]), "+f"(d[16]), "+f"(d[17]), "+f"(d[18]), "+f"(d[19]), "+f"(d[20]), "+f"(d[21]), "+f"(d[22]), "+f"(d[23]), "+f"(d[24]), "+f"(d[25]), "+f"(d[26]), "+f"(d[27]), "+f"(d[28]), "+f"(d[29]), "+f"(d[30]), "+f"(d[31])
    : "r"(a[0]), "r"(a[1]), "r"(a[2]), "r"(a[3]), "l"(db), "r"(sc), "n"(TB));
}
template <int TB> __device__ __forceinline__ void wgmma_rs_56(float (&d)[28], const uint32_t (&a)[4], uint64_t db, int sc) {
  asm volatile("{\n.reg .pred p;\nsetp.ne.b32 p, %33, 0;\n"
    "wgmma.mma_async.sync.aligned.m64n56k16.f32.bf16.bf16 {%0, %1, %2, %3, %4, %5, %6, %7, %8, %9, %10, %11, %12, %13, %14, %15, %16, %17, %18, %19, %20, %21, %22, %23, %24, %25, %26, %27}, {%28, %29, %30, %31}, %32, p, 1, 1, %34;\n}\n"
    : "+f"(d[0]), "+f"(d[1]), "+f"(d[2]), "+f"(d[3]), "+f"(d[4]), "+f"(d[5]), "+f"(d[6]), "+f"(d[7]), "+f"(d[8]), "+f"(d[9]), "+f"(d[10]), "+f"(d[11]), "+f"(d[12]), "+f"(d[13]), "+f"(d[14]), "+f"(d[15]), "+f"(d[16]), "+f"(d[17]), "+f"(d[18]), "+f"(d[19]), "+f"(d[20]), "+f"(d[21]), "+f"(d[22]), "+f"(d[23]), "+f"(d[24]), "+f"(d[25]), "+f"(d[26]), "+f"(d[27])
    : "r"(a[0]), "r"(a[1]), "r"(a[2]), "r"(a[3]), "l"(db), "r"(sc), "n"(TB));
}
template <int TB> __device__ __forceinline__ void wgmma_rs_112(float (&d)[56], const uint32_t (&a)[4], uint64_t db, int sc) {
  asm volatile("{\n.reg .pred p;\nsetp.ne.b32 p, %61, 0;\n"
    "wgmma.mma_async.sync.aligned.m64n112k16.f32.bf16.bf16 {%0, %1, %2, %3, %4, %5, %6, %7, %8, %9, %10, %11, %12, %13, %14, %15, %16, %17, %18, %19, %20, %21, %22, %23, %24, %25, %26, %27, %28, %29, %30, %31, %32, %33, %34, %35, %36, %37, %38, %39, %40, %41, %42, %43, %44, %45, %46, %47, %48, %49, %50, %51, %52, %53, %54, %55}, {%56, %57, %58, %59}, %60, p, 1, 1, %62;\n}\n"
    : "+f"(d[0]), "+f"(d[1]), "+f"(d[2]), "+f"(d[3]), "+f"(d[4]), "+f"(d[5]), "+f"(d[6]), "+f"(d[7]), "+f"(d[8]), "+f"(d[9]), "+f"(d[10]), "+f"(d[11]), "+f"(d[12]), "+f"(d[13]), "+f"(d[14]), "+f"(d[15]), "+f"(d[16]), "+f"(d[17]), "+f"(d[18]), "+f"(d[19]), "+f"(d[20]), "+f"(d[21]), "+f"(d[22]), "+f"(d[23]), "+f"(d[24]), "+f"(d[25]), "+f"(d[26]), "+f"(d[27]), "+f"(d[28]), "+f"(d[29]), "+f"(d[30]), "+f"(d[31]), "+f"(d[32]), "+f"(d[33]), "+f"(d[34]), "+f"(d[35]), "+f"(d[36]), "+f"(d[37]), "+f"(d[38]), "+f"(d[39]), "+f"(d[40]), "+f"(d[41]), "+f"(d[42]), "+f"(d[43]), "+f"(d[44]), "+f"(d[45]), "+f"(d[46]), "+f"(d[47]), "+f"(d[48]), "+f"(d[49]), "+f"(d[50]), "+f"(d[51]), "+f"(d[52]), "+f"(d[53]), "+f"(d[54]), "+f"(d[55])
    : "r"(a[0]), "r"(a[1]), "r"(a[2]), "r"(a[3]), "l"(db), "r"(sc), "n"(TB));
}
template <int TA, int TB> __device__ __forceinline__ void wgmma_ss_56(float (&d)[28], uint64_t da, uint64_t db, int sc) {
  asm volatile("{\n.reg .pred p;\nsetp.ne.b32 p, %30, 0;\n"
    "wgmma.mma_async.sync.aligned.m64n56k16.f32.bf16.bf16 {%0, %1, %2, %3, %4, %5, %6, %7, %8, %9, %10, %11, %12, %13, %14, %15, %16, %17, %18, %19, %20, %21, %22, %23, %24, %25, %26, %27}, %28, %29, p, 1, 1, %31, %32;\n}\n"
    : "+f"(d[0]), "+f"(d[1]), "+f"(d[2]), "+f"(d[3]), "+f"(d[4]), "+f"(d[5]), "+f"(d[6]), "+f"(d[7]), "+f"(d[8]), "+f"(d[9]), "+f"(d[10]), "+f"(d[11]), "+f"(d[12]), "+f"(d[13]), "+f"(d[14]), "+f"(d[15]), "+f"(d[16]), "+f"(d[17]), "+f"(d[18]), "+f"(d[19]), "+f"(d[20]), "+f"(d[21]), "+f"(d[22]), "+f"(d[23]), "+f"(d[24]), "+f"(d[25]), "+f"(d[26]), "+f"(d[27])
    : "l"(da), "l"(db), "r"(sc), "n"(TA), "n"(TB));
}

__device__ __forceinline__ uint32_t cis(float a) { return pack_bf16(__cosf(a), __sinf(a)); }

typedef __nv_bfloat162 b2;
struct c2 { b2 x, y; };
__device__ __forceinline__ b2 as_b2(uint32_t u) { return *reinterpret_cast<b2*>(&u); }
__device__ __forceinline__ uint32_t as_u(b2 v) { return *reinterpret_cast<uint32_t*>(&v); }
__device__ __forceinline__ c2 mk(b2 x, b2 y) { c2 r; r.x = x; r.y = y; return r; }
__device__ __forceinline__ c2 cmul(c2 a, b2 wr, b2 wi) { return mk(__hfma2(a.x, wr, __hneg2(__hmul2(a.y, wi))), __hfma2(a.x, wi, __hmul2(a.y, wr))); }
__device__ __forceinline__ void fft4(c2& a0, c2& a1, c2& a2, c2& a3) {
  c2 t0 = mk(__hadd2(a0.x, a2.x), __hadd2(a0.y, a2.y)), t1 = mk(__hsub2(a0.x, a2.x), __hsub2(a0.y, a2.y));
  c2 t2 = mk(__hadd2(a1.x, a3.x), __hadd2(a1.y, a3.y)), t3 = mk(__hsub2(a1.x, a3.x), __hsub2(a1.y, a3.y));
  a0 = mk(__hadd2(t0.x, t2.x), __hadd2(t0.y, t2.y)); a2 = mk(__hsub2(t0.x, t2.x), __hsub2(t0.y, t2.y));
  a1 = mk(__hadd2(t1.x, t3.y), __hsub2(t1.y, t3.x)); a3 = mk(__hsub2(t1.x, t3.y), __hadd2(t1.y, t3.x));
}
__device__ __forceinline__ void fft4_s2(c2& a0, c2& a1, c2& a2, c2& a3, b2 r) {
  const b2 nr = __hneg2(r);
  c2 t0 = mk(__hfma2(a2.x, r, a0.x), __hfma2(a2.y, r, a0.y)), t1 = mk(__hfma2(a2.x, nr, a0.x), __hfma2(a2.y, nr, a0.y));
  c2 t2 = mk(__hadd2(a1.x, a3.x), __hadd2(a1.y, a3.y)), t3 = mk(__hsub2(a1.x, a3.x), __hsub2(a1.y, a3.y));
  a0 = mk(__hadd2(t0.x, t2.x), __hadd2(t0.y, t2.y)); a2 = mk(__hsub2(t0.x, t2.x), __hsub2(t0.y, t2.y));
  a1 = mk(__hadd2(t1.x, t3.y), __hsub2(t1.y, t3.x)); a3 = mk(__hsub2(t1.x, t3.y), __hadd2(t1.y, t3.x));
}
__device__ __forceinline__ void fft4_s13(c2& a0, c2& a1, c2& a2, c2& a3, b2 r) {
  const b2 nr = __hneg2(r);
  c2 t0 = mk(__hadd2(a0.x, a2.x), __hadd2(a0.y, a2.y)), t1 = mk(__hsub2(a0.x, a2.x), __hsub2(a0.y, a2.y));
  c2 t2 = mk(__hadd2(a1.x, a3.x), __hadd2(a1.y, a3.y)), t3 = mk(__hsub2(a1.x, a3.x), __hsub2(a1.y, a3.y));
  a0 = mk(__hfma2(t2.x, r, t0.x), __hfma2(t2.y, r, t0.y)); a2 = mk(__hfma2(t2.x, nr, t0.x), __hfma2(t2.y, nr, t0.y));
  a1 = mk(__hfma2(t3.y, r, t1.x), __hfma2(t3.x, nr, t1.y)); a3 = mk(__hfma2(t3.y, nr, t1.x), __hfma2(t3.x, r, t1.y));
}
__device__ __forceinline__ c2 rot1(c2 a) { return mk(__hadd2(a.x, a.y), __hsub2(a.y, a.x)); }
__device__ __forceinline__ c2 rot3(c2 a) { return mk(__hsub2(a.y, a.x), __hneg2(__hadd2(a.x, a.y))); }
__device__ __forceinline__ c2 mul_mi(c2 a) { return mk(a.y, __hneg2(a.x)); }
template <int O> __device__ __forceinline__ void fft8(c2 (&v)[16]) {
  const b2 r = as_b2(0x3F353F35u), nr = as_b2(0xBF35BF35u);
  fft4(v[O], v[O + 4], v[O + 8], v[O + 12]);
  fft4(v[O + 2], v[O + 6], v[O + 10], v[O + 14]);
  const c2 o0 = v[O + 2], o1 = rot1(v[O + 6]), o2 = v[O + 10], o3 = rot1(v[O + 14]);
  const c2 e0 = v[O], e1 = v[O + 4], e2 = v[O + 8], e3 = v[O + 12];
  v[O] = mk(__hadd2(e0.x, o0.x), __hadd2(e0.y, o0.y));              v[O + 8] = mk(__hsub2(e0.x, o0.x), __hsub2(e0.y, o0.y));
  v[O + 2] = mk(__hfma2(o1.x, r, e1.x), __hfma2(o1.y, r, e1.y));    v[O + 10] = mk(__hfma2(o1.x, nr, e1.x), __hfma2(o1.y, nr, e1.y));
  v[O + 4] = mk(__hadd2(e2.x, o2.y), __hsub2(e2.y, o2.x));          v[O + 12] = mk(__hsub2(e2.x, o2.y), __hadd2(e2.y, o2.x));
  v[O + 6] = mk(__hfma2(o3.y, r, e3.x), __hfma2(o3.x, nr, e3.y));   v[O + 14] = mk(__hfma2(o3.y, nr, e3.x), __hfma2(o3.x, r, e3.y));
}
__device__ __forceinline__ void fft16(c2 (&v)[16]) {
  const b2 r = as_b2(0x3F353F35u), c1 = as_b2(0x3F6D3F6Du), s1 = as_b2(0x3EC43EC4u), nc1 = as_b2(0xBF6DBF6Du), ns1 = as_b2(0xBEC4BEC4u);
#pragma unroll
  for (int a = 0; a < 4; a++) fft4(v[a], v[a + 4], v[a + 8], v[a + 12]);
  v[5] = cmul(v[5], c1, ns1); v[6] = rot1(v[6]); v[7] = cmul(v[7], s1, nc1);
  v[9] = rot1(v[9]); v[10] = mul_mi(v[10]); v[11] = rot3(v[11]);
  v[13] = cmul(v[13], s1, nc1); v[14] = rot3(v[14]); v[15] = cmul(v[15], nc1, s1);
  fft4(v[0], v[1], v[2], v[3]); fft4_s2(v[4], v[5], v[6], v[7], r); fft4_s13(v[8], v[9], v[10], v[11], r); fft4_s2(v[12], v[13], v[14], v[15], r);
  c2 t;
  t = v[1]; v[1] = v[4]; v[4] = t;  t = v[2]; v[2] = v[8]; v[8] = t;  t = v[3]; v[3] = v[12]; v[12] = t;
  t = v[6]; v[6] = v[9]; v[9] = t;  t = v[7]; v[7] = v[13]; v[13] = t; t = v[11]; v[11] = v[14]; v[14] = t;
}

__device__ __forceinline__ void columns(c2 (&v)[16], uint32_t sb, int t) {
  const int l16 = t & 15;
  const uint32_t row = sb + OFF_EXCH + (t >> 4) * 2304;
  const uint32_t pos = sb + OFF_EXCH + (t >> 3) * 144 + (t & 7) * 16;
#pragma unroll 1
  for (int ps = 0; ps < 6; ps++) {
    if (ps == 0 || ps == 5) { fft8<0>(v); fft8<1>(v); } else fft16(v);
    if (ps == 5) break;
    if (ps == 2) {
      const uint32_t ws = sb + OFF_WS + (l16 >> 1) * 128 + ((((t >> 4) + (l16 >> 1)) & 7) * 2 + (l16 & 1)) * 8;
      mbar_wait(sb + OFF_BAR + B_WFULL * 8, 0);
#pragma unroll
      for (int q = 0; q < 16; q++) {
        const uint2 w = lds64(ws + q * 1024);
        const c2 z = cmul(v[q], as_b2(w.x), as_b2(w.y));
        v[q] = mk(z.y, z.x);
      }
      continue;
    }
    {
      const bool full = ps == 0 || ps == 4;
      const uint32_t tw = sb + OFF_TW + (full ? ps * 2048 + t * 16 : 16384 + l16 * 16);
      const uint32_t st = full ? 2048 : 256;
#pragma unroll
      for (int i = 0; i < 4; i++) {
        const uint4 w4 = lds128(tw + i * st);
        const uint32_t w[4] = {w4.x, w4.y, w4.z, w4.w};
#pragma unroll
        for (int e = 0; e < 4; e++) v[4 * i + e] = cmul(v[4 * i + e], __low2bfloat162(as_b2(w[e])), __high2bfloat162(as_b2(w[e])));
      }
    }
    if (ps == 0) {
#pragma unroll
      for (int q = 0; q < 8; q++) sts128(pos + q * 2304, as_u(v[2 * q].x), as_u(v[2 * q].y), as_u(v[2 * q + 1].x), as_u(v[2 * q + 1].y));
      bar_sync<3, 128>();
#pragma unroll
      for (int q = 0; q < 16; q++) { const uint2 a = lds64(row + q * 144 + l16 * 8); v[q] = mk(as_b2(a.x), as_b2(a.y)); }
    } else {
      __syncwarp();
#pragma unroll
      for (int q = 0; q < 16; q++) sts64(row + q * 144 + l16 * 8, as_u(v[q].x), as_u(v[q].y));
      if (ps == 4) bar_sync<3, 128>(); else __syncwarp();
      const uint32_t src = ps == 4 ? pos : row + l16 * 144, st = ps == 4 ? 2304 : 16;
#pragma unroll
      for (int q = 0; q < 8; q++) { const uint4 a = lds128(src + q * st); v[2 * q] = mk(as_b2(a.x), as_b2(a.y)); v[2 * q + 1] = mk(as_b2(a.z), as_b2(a.w)); }
    }
  }
}

template <int NH> __device__ __forceinline__ void h_epilogue(float (&acc)[NH * 8], unsigned char* gdst, uint32_t tag) {
#pragma unroll
  for (int c = 0; c < NH / 2; c++) {
    uint32_t pk[4];
#pragma unroll
    for (int i = 0; i < 4; i++) {
      float hv[2];
#pragma unroll
      for (int e = 0; e < 2; e++) {
        float hg = 0.5f * acc[c * 8 + i * 2 + e], up = acc[NH * 4 + c * 8 + i * 2 + e];
        float th; asm("tanh.approx.f32 %0, %1;" : "=f"(th) : "f"(hg));
        hv[e] = fmaf(hg, th, hg) * up;
      }
      pk[i] = pack_bf16(hv[0], hv[1]);
    }
    stg128_l2(gdst + c * 4096, (pk[0] & ~1u) | tag, pk[1], pk[2], pk[3]);
  }
}

__device__ __forceinline__ void frag_ready(uint32_t (&a)[4], uint32_t (&b)[4], uint32_t (&c)[4], uint32_t (&d)[4], const unsigned char* p, uint32_t tag) {
  asm volatile("{\n.reg .pred p;\n.reg .u32 c, m, q;\nmov.u32 c, 0;\nL_TRY:\n"
               "lop3.b32 m, %0, %4, %17, 0x7E;\nlop3.b32 q, %8, %12, %17, 0x7E;\nlop3.b32 m, m, q, 1, 0xA8;\nsetp.ne.u32 p, m, 0;\n"
               "vote.sync.any.pred p, p, 0xffffffff;\n@!p bra.uni L_OK;\n"
               "ld.relaxed.gpu.global.v4.b32 {%0,%1,%2,%3}, [%16];\nld.relaxed.gpu.global.v4.b32 {%4,%5,%6,%7}, [%16+4096];\n"
               "ld.relaxed.gpu.global.v4.b32 {%8,%9,%10,%11}, [%16+8192];\nld.relaxed.gpu.global.v4.b32 {%12,%13,%14,%15}, [%16+12288];\n"
               "add.u32 c, c, 1;\nsetp.lt.u32 p, c, 262144;\n@p bra.uni L_TRY;\ntrap;\nL_OK:\n}"
               : "+r"(a[0]), "+r"(a[1]), "+r"(a[2]), "+r"(a[3]), "+r"(b[0]), "+r"(b[1]), "+r"(b[2]), "+r"(b[3]),
                 "+r"(c[0]), "+r"(c[1]), "+r"(c[2]), "+r"(c[3]), "+r"(d[0]), "+r"(d[1]), "+r"(d[2]), "+r"(d[3])
               : "l"(p), "r"(tag) : "memory");
}

#define MAP 0
#define LEAD2 0
#define LEAD1 3

__global__ void __cluster_dims__(2, 1, 1) __launch_bounds__(NTHREADS, 1)
fused_kernel(const __grid_constant__ CUtensorMap tm_x, const __grid_constant__ CUtensorMap tm_g, const __grid_constant__ CUtensorMap tm_u,
             const __grid_constant__ CUtensorMap tm_g32, const __grid_constant__ CUtensorMap tm_u32, const __grid_constant__ CUtensorMap tm_d,
             const __nv_bfloat16* __restrict__ w_r, const __nv_bfloat16* __restrict__ w_i,
             const __nv_bfloat16* __restrict__ w_gate, const __nv_bfloat16* __restrict__ w_up,
             const __nv_bfloat16* __restrict__ w_down, const __nv_bfloat16* __restrict__ gate_w, __nv_bfloat16* __restrict__ out) {
  extern __shared__ __align__(1024) unsigned char smem[];
  const uint32_t sb = s2u(smem);
  const uint32_t bars = sb + OFF_BAR;
  const int tid = threadIdx.x, warp = __shfl_sync(0xffffffffu, tid >> 5, 0), lane = tid & 31;
  const int cl = blockIdx.x >> 1, kh = blockIdx.x & 1;
  const int n0 = cl < 4 ? cl : (cl < 36 ? (cl - 4) >> 3 : (cl - 36) / 7);
  const int m0 = cl < 4 ? 15 : (cl < 36 ? (cl - 4) & 7 : cl - 28 - 7 * n0);
  const int n = MAP == 0 ? n0 : (MAP == 1 ? (m0 & 3) : ((n0 & 1) | ((m0 & 1) << 1)));
  const int m = MAP == 0 ? m0 : (MAP == 1 ? ((m0 & 12) | n0) : ((m0 & 14) | (n0 >> 1)));
  const int j = kh * 4 + n, bid = m * 8 + n * 2 + kh;

  const int c64 = 224 * j + (j & 1) * 32;
  if (warp < 8) {
    asm volatile("setmaxnreg.inc.sync.aligned.u32 208;");
    const int wg = warp >> 2, w4 = warp & 3, g = lane >> 2, t = lane & 3;
    const int rh = wg ^ kh ^ 1;
    const int p = j & 1, r = (j >> 1) & 1, hh = j >> 2;
    const uint32_t epoch = ld_relaxed(&g_ep[bid]);
    if ((tid & 127) == 0) PROF(wg, 30);
#pragma unroll 1
    for (int it = tid; it < 392; it += 256) {
      const int kc = it / 28, sg = it - kc * 28;
      const int k = 2 * (28 * hh + sg) + r;
      const float kf = (float)k * (-6.283185307179586f / 448.0f), a0 = (float)(16 * kc + p) * kf;
      uint32_t c[4], s[4];
#pragma unroll
      for (int q = 0; q < 4; q++) {
        const float a1 = fmaf((float)(2 * q), kf, a0), a2 = fmaf((float)(2 * q + 8), kf, a0);
        c[q] = pack_bf16(__cosf(a1), __cosf(a2)); s[q] = pack_bf16(__sinf(a1), __sinf(a2));
        if (k == 0) s[q] = ((q ^ p) & 1) ? 0xBF80BF80u : 0x3F803F80u;
      }
      const uint32_t a = sb + 6 * SLOT + (kc * 56 + 2 * sg) * 16;
      sts128(a, c[0], c[1], c[2], c[3]);
      sts128(a + 16, s[0], s[1], s[2], s[3]);
    }
    if ((tid & 127) == 0) PROF(wg, 31);
    fence_async_smem();
    bar_sync<0, NTHREADS - 64>();
    asm volatile("barrier.cluster.arrive.relaxed.aligned;" ::: "memory");
    if ((tid & 127) == 0) PROF(wg, 1);

    uint32_t xa[28][4];
    {
      const uint32_t xb = sb + OFF_PQ + wg * HALF_XR + (w4 * 16 + (lane & 15)) * 128;
      mbar_wait(bars + (B_XFULL + wg) * 8, 0);
      if ((tid & 127) == 0) PROF(wg, 2);
#pragma unroll
      for (int kb = 0; kb < 7; kb++) {
#pragma unroll
        for (int kk = 0; kk < 4; kk++) {
          uint32_t a = xb + kb * 8192 + (((2 * kk + (lane >> 4)) ^ (lane & 7)) << 4);
          asm volatile("ldmatrix.sync.aligned.m8n8.x4.shared.b16 {%0,%1,%2,%3}, [%4];"
                       : "=r"(xa[kb * 4 + kk][0]), "=r"(xa[kb * 4 + kk][1]), "=r"(xa[kb * 4 + kk][2]), "=r"(xa[kb * 4 + kk][3]) : "r"(a) : "memory");
        }
      }
    }
    {
      uint32_t ad[7][4];
      const uint32_t sel = p ? 0x7632 : 0x5410;
      const uint32_t sgn = r ? 0xBF80BF80u : 0x3F803F80u;
#pragma unroll
      for (int jj = 0; jj < 7; jj++) {
#pragma unroll
        for (int i = 0; i < 4; i++) {
          int ks = 2 * jj + (i >> 1), rr = i & 1;
          uint32_t lo = __byte_perm(xa[ks][rr], xa[ks][rr + 2], sel);
          uint32_t hi = __byte_perm(xa[ks + 14][rr], xa[ks + 14][rr + 2], sel);
          asm("fma.rn.bf16x2 %0, %1, %2, %3;" : "=r"(ad[jj][i]) : "r"(hi), "r"(sgn), "r"(lo));
        }
      }
      __syncwarp();
      if (lane == 0) mbar_arrive(bars + (B_XFREE + wg) * 8);
      float acc[28];
      wg_fence();
      uint64_t db = mkdesc(sb + 6 * SLOT, 896, 128, 0);
#pragma unroll
      for (int jj = 0; jj < 7; jj++) wgmma_rs_56<0>(acc, ad[jj], db + jj * 112, jj != 0);
      wg_commit();
      wg_wait<0>(); keep(acc);
      if (lane == 0) mbar_arrive(bars + (B_EMPTY + 6) * 8);
      uint32_t* xc = g_Xc + (size_t)((2 * (28 * hh + t) + r) * 2 + p) * S_ + m * 128 + rh * 64 + w4 * 16 + g;
#pragma unroll
      for (int i = 0; i < 7; i++) {
        xc[i * 16 * S_] = pack_bf16(acc[4 * i], acc[4 * i + 1]);
        xc[i * 16 * S_ + 8] = pack_bf16(acc[4 * i + 2], acc[4 * i + 3]);
      }
      __syncwarp();
      if (lane == 0) mbar_arrive(bars + B_PUBX * 8);
    }
    if ((tid & 127) == 0) PROF(wg, 3);
    const uint32_t tag = ~epoch & 1;
    unsigned char* const hbase = g_H + (size_t)(m * 2 + kh) * (56 * 4096) + rh * 2048 + (tid & 127) * 16;
#pragma unroll 1
    for (int u = 0; u < 3; u++) {
      float acc[64];
      if (wg == 1) { if (u & 1) bar_sync<6, 256>(); else bar_sync<2, 256>(); }
      const uint32_t sbu = opaque(sb);
#pragma unroll
      for (int kb = 0; kb < 7; kb++) {
        mbar_wait(sbu + OFF_BAR + (B_FULL + kb) * 8, u & 1);
        wg_fence();
        uint64_t db = mkdesc(sbu + kb * SLOT, 8192, 1024, 1);
#pragma unroll
        for (int kk = 0; kk < 4; kk++) wgmma_rs_128<1>(acc, xa[kb * 4 + kk], db + kk * 128, (kb | kk) != 0);
        wg_commit();
        if (kb == LEAD1 && wg == 0) { if (u & 1) bar_arrive<6, 256>(); else bar_arrive<2, 256>(); }
        if (kb > 0) { wg_wait<1>(); if (lane == 0) mbar_arrive(sbu + OFF_BAR + (B_EMPTY + kb - 1) * 8); }
      }
      wg_wait<0>(); keep(acc);
      if (lane == 0) mbar_arrive(sbu + OFF_BAR + (B_EMPTY + 6) * 8);
      if ((tid & 127) == 0) PROF(wg, 4 + 2 * u);
      h_epilogue<8>(acc, hbase + (u * 16 + n * 4) * 4096, tag);
      if ((tid & 127) == 0) PROF(wg, 5 + 2 * u);
    }
    uint32_t ha[14][4][4];
    auto check = [&](int b0, int b1) {
#pragma unroll
      for (int b = b0; b < b1; b++) frag_ready(ha[b][0], ha[b][1], ha[b][2], ha[b][3], hbase + b * 16384, tag);
    };
    auto load = [&](int b0, int b1) {
#pragma unroll
      for (int i = b0; i < b1; i++) ldg128_l2(ha[i >> 2][i & 3], hbase + i * 4096);
    };
    {
      float acc[32];
      load(0, 3);
      if (wg == 1) bar_sync<6, 256>();
      const uint32_t sbu = opaque(sb);
#pragma unroll
      for (int it = 0; it < 4; it++) {
        mbar_wait(sbu + OFF_BAR + (B_FULL + it) * 8, 1);
        wg_fence();
        uint64_t db = mkdesc(sbu + it * SLOT, 8192, 512, 2);
#pragma unroll
        for (int kk = 0; kk < 8; kk++) if (it * 8 + kk < 28) wgmma_rs_64<1>(acc, xa[it * 8 + kk], db + kk * 64, (it | kk) != 0);
        wg_commit();
        if (it == 2 && wg == 0) bar_arrive<6, 256>();
        if (it > 0) {
          wg_wait<1>();
          if (lane == 0) mbar_arrive(sbu + OFF_BAR + (B_EMPTY + it - 1) * 8);
          if (it == 1) load(3, 11);
          if (it == 2) load(11, 16);
        }
      }
      wg_wait<0>(); keep(acc);
      if (lane == 0) mbar_arrive(sbu + OFF_BAR + (B_EMPTY + 3) * 8);
      if ((tid & 127) == 0) PROF(wg, 10);
      h_epilogue<4>(acc, hbase + (48 + n * 2) * 4096, tag);
    }
    asm volatile("barrier.cluster.wait.aligned;" ::: "memory");
    if ((tid & 127) == 0) PROF(wg, 11);

    float acc[56];
    check(0, 4);
    if (wg == 1) bar_sync<2, 256>();
#pragma unroll
    for (int b = 0; b < 14; b++) {
      if ((tid & 127) == 0) PROF(wg, 16 + b);
      if (b >= 3) mbar_wait(bars + (B_FULL + (b + 1) % 7) * 8, b < 6 || b == 13);
      else if (b == 0) mbar_wait(bars + B_RFULL * 8, 0);
      if (b == 4) check(4, 7);
      if (b == 7) check(7, 11);
      if (b == 11) check(11, 14);
      wg_fence();
      const uint64_t db = mkdesc(b < 3 ? sb + OFF_R + b * SLOT : sb + (b + 1) % 7 * SLOT, 8192, 1024, 1);
#pragma unroll
      for (int kk = 0; kk < 4; kk++) wgmma_rs_112<1>(acc, ha[b][kk], db + kk * 128, (b | kk) != 0);
      wg_commit();
      if (b == LEAD2 && wg == 0) bar_arrive<2, 256>();
      if (b == 0) load(16, 24);
      if (b == 1) load(24, 28);
      if (b == 4 || b == 5) load(8 * b - 4, 8 * b + 4);
      if (b == 7) load(44, 52);
      if (b == 8) load(52, 56);
      if (b > 0) wg_wait<1>();
      if (lane == 0) {
        if (b >= 4 && b <= 9) mbar_arrive(bars + (B_EMPTY + b % 7) * 8);
        if (b == 3) {
          mbar_arrive(bars + B_LFREE * 8);
          asm volatile("{\n.reg .b32 ra;\nmapa.shared::cluster.u32 ra, %0, %1;\nmbarrier.arrive.relaxed.cluster.shared::cluster.b64 _, [ra];\n}"
                       :: "r"(bars + B_RFREE * 8), "r"(kh ^ 1) : "memory");
        }
      }
    }
    const int t128 = tid & 127;
    wg_wait<0>(); keep(acc);
    if (wg == 0) {
      if (t128 == 0) PROF(wg, 12);
      mbar_wait_cluster(bars + B_RFREE * 8, 0);
      uint32_t rdst, rbar;
      asm volatile("mapa.shared::cluster.u32 %0, %1, %2;" : "=r"(rdst) : "r"(sb + OFF_R + t128 * 16), "r"(kh ^ 1));
      asm volatile("mapa.shared::cluster.u32 %0, %1, %2;" : "=r"(rbar) : "r"(bars + B_RECV * 8), "r"(kh ^ 1));
#pragma unroll
      for (int i = 0; i < 14; i++)
        asm volatile("st.async.weak.shared::cluster.mbarrier::complete_tx::bytes.v4.f32 [%0], {%1,%2,%3,%4}, [%5];"
                     :: "r"(rdst + i * 2048), "f"(acc[4 * i]), "f"(acc[4 * i + 1]), "f"(acc[4 * i + 2]), "f"(acc[4 * i + 3]), "r"(rbar) : "memory");
    } else {
      float spec[2][28];
      if (t128 == 0) PROF(wg, 12);
      mbar_wait_cluster(bars + B_RECV * 8, 0);
      if (t128 == 0) PROF(wg, 0);
#pragma unroll
      for (int i = 0; i < 14; i++) {
        const float4 o = lds128f(sb + OFF_R + t128 * 16 + i * 2048);
        acc[4 * i] += o.x; acc[4 * i + 1] += o.y; acc[4 * i + 2] += o.z; acc[4 * i + 3] += o.w;
      }
#pragma unroll
      for (int i = 0; i < 4; i++) {
        if (i == 0) mbar_wait(bars + B_GFULL * 8, 0);
        if (i >= 2) mbar_wait(bars + (B_FULL + i - 1) * 8, 1);
        mbar_wait(bars + (B_PQFULL + i) * 8, 0);
        if (i == 0 && t128 == 0) { PROF(wg, 13); g_ep[bid] = epoch + 1; }
        wg_fence();
        const uint64_t da = mkdesc(sb + OFF_PQ + i * 14336, 1024, 1024, 1);
        const uint64_t db = mkdesc(i < 2 ? sb + OFF_R + 28672 + i * (G_IMG / 2) : sb + (i - 1) * SLOT, 896, 128, 0);
#pragma unroll
        for (int kk = 0; kk < 7; kk++) wgmma_ss_56<1, 0>(spec[i >> 1], da + kk * 128, db + kk * 112, ((i & 1) | kk) != 0);
        wg_commit();
      }
      const float* gs = reinterpret_cast<const float*>(smem + OFF_G) + w4 * 16 + g;
      const float o0 = bf16_round(1.0f - gs[0]), o1 = bf16_round(1.0f - gs[8]);
      const float g0 = gs[0] * (1.0f / (float)(S_ * D_)), g1 = gs[8] * (1.0f / (float)(S_ * D_));
#pragma unroll
      for (int i = 0; i < 56; i++) acc[i] *= (i & 2) ? o1 : o0;
      keep(acc);
      wg_wait<0>(); keep(spec[0]); keep(spec[1]);
      if (t128 == 0) PROF(wg, 14);
      bar_sync<5, 128>();
      const uint32_t st = sb + OFF_PQ + w4 * 3840;
#pragma unroll
      for (int i = 0; i < 7; i++) {
        uint32_t pk[4];
#pragma unroll
        for (int e = 0; e < 2; e++) {
          const int c = 2 * i + e, si = i * 4 + e;
          pk[2 * e] = pack_bf16(fmaf(g0, spec[0][si], acc[4 * c]), fmaf(g0, spec[1][si], acc[4 * c + 1]));
          pk[2 * e + 1] = pack_bf16(fmaf(g1, spec[0][si + 2], acc[4 * c + 2]), fmaf(g1, spec[1][si + 2], acc[4 * c + 3]));
        }
        asm volatile("stmatrix.sync.aligned.m8n8.x4.shared.b16 [%0], {%1,%2,%3,%4};"
                     :: "r"(st + (lane & 15) * 240 + (lane >> 4) * 16 + i * 32), "r"(pk[0]), "r"(pk[1]), "r"(pk[2]), "r"(pk[3]) : "memory");
      }
      __syncwarp();
      if (lane < 28) {
        const int r2 = lane >= 14, cc = lane - r2 * 14;
        unsigned char* ob = reinterpret_cast<unsigned char*>(out) + (size_t)(m * 128 + kh * 64 + w4 * 16 + r2) * (D_ * 2) + n * 224 + cc * 16;
        float4 v[8];
#pragma unroll
        for (int i = 0; i < 8; i++) v[i] = lds128f(st + r2 * 240 + cc * 16 + i * 480);
#pragma unroll
        for (int i = 0; i < 8; i++) stg128(ob + i * (D_ * 4), __float_as_uint(v[i].x), __float_as_uint(v[i].y), __float_as_uint(v[i].z), __float_as_uint(v[i].w));
      }
    }
    if (t128 == 0) { PROF(wg, 15); if (wg) { PROFG(4, 30); PROF(4, 31); } }
  } else if (warp < 12) {
    asm volatile("setmaxnreg.dec.sync.aligned.u32 72;");
    const int t = tid - 256;
    const int k = bid;
    if (t == 0) PROF(2, 0);
    uint4 gv[7];
#pragma unroll
    for (int i = 0; i < 7; i++) gv[i] = ldg128(reinterpret_cast<const uint4*>(gate_w) + i * 8 + (t & 7));
    if (t < 98) {
      int cid = m * 98 + t, kc = cid / 56, nn = cid - kc * 56;
      int d = 112 * n + 8 * (2 * (nn >> 3) + (nn & 1)) + (nn & 6) + kh;
      int dr = d > 224 ? d - 448 : d;
      const float df = (float)dr * (-6.283185307179586f / 448.0f);
      uint32_t pk[4];
#pragma unroll
      for (int e = 0; e < 4; e++) {
        const float a = (float)(4 * kc + e) * df;
        pk[e] = pack_bf16(2.0f * __cosf(a), 2.0f * __sinf(a));
      }
      if (kc == 0) pk[0] = (((d >> 1) ^ kh) & 1) ? 0xBF803F80u : 0x3F803F80u;
      stg128(g_G + (size_t)(n * 2 + kh) * G_IMG + cid * 16, pk[0], pk[1], pk[2], pk[3]);
    }
    bar_sync<0, NTHREADS - 64>();
    asm volatile("barrier.cluster.arrive.relaxed.aligned;" ::: "memory");
    {
      const int row = n * 16 + (t >> 3), l8 = t & 7;
      mbar_wait(bars + (B_XFULL + 1) * 8, 0);
      float sum = 0.f;
#pragma unroll
      for (int i = 0; i < 7; i++) {
        const uint4 a = lds128(sb + OFF_R + i * 8192 + row * 128 + ((l8 ^ (row & 7)) << 4));
        const uint32_t aa[4] = {a.x, a.y, a.z, a.w}, bb[4] = {gv[i].x, gv[i].y, gv[i].z, gv[i].w};
#pragma unroll
        for (int e = 0; e < 4; e++) {
          const uint32_t pr = as_u(__hmul2(as_b2(aa[e]), as_b2(bb[e])));
          sum += bf_lo(pr) + bf_hi(pr);
        }
      }
      sum += __shfl_xor_sync(0xffffffffu, sum, 1); sum += __shfl_xor_sync(0xffffffffu, sum, 2); sum += __shfl_xor_sync(0xffffffffu, sum, 4);
      if (lane == 0) mbar_arrive(bars + (B_XFREE + 1) * 8);
      if (l8 == 0) g_gate[m * 128 + kh * 64 + row] = bf16_round(__fdividef(1.0f, 1.0f + __expf(-bf16_round(sum))));
    }
    if (t == 0) PROF(2, 11);
    mbar_wait(bars + B_XFREE * 8, 0);
    if (k < 113) {
      const float u = -6.283185307179586f / 2048.0f, t2 = (float)(2 * t) * u, rr = (float)(t >> 4) * u;
#pragma unroll 1
      for (int i = 0; i < 4; i++) {
        const float q = (float)(2 * i), l = (float)((t & 15) + 64 * i);
        sts128(sb + OFF_TW + i * 2048 + t * 16, cis(t2 * q), cis((t2 + u) * q), cis(t2 * (q + 1.0f)), cis((t2 + u) * (q + 1.0f)));
        sts128(sb + OFF_TW + 8192 + i * 2048 + t * 16, cis(rr * l), cis(rr * (l + 16.0f)), cis(rr * (l + 32.0f)), cis(rr * (l + 48.0f)));
      }
      const float l = (float)((t >> 1) & 15) * (8.0f * u), jj = (float)((t >> 5) * 4 + (t & 1) * 2);
      sts64(sb + OFF_TW + 16384 + t * 8, cis(l * jj), cis(l * (jj + 1.0f)));
    }
    if (t == 0) PROF(2, 9);
    mbar_wait(bars + B_PIN * 8, 0);
    if (t == 0) PROF(2, 4);
    {
      const uint32_t wa = sb + OFF_WS + (((t & 7) - bid) & 7) * 450 + (t >> 3) * 2, wc = wa + 448 - (t >> 3) * 4;
      uint2* dst = g_Wt + (t >> 3) * S_ + 16 * bid + 2 * (t & 7);
#pragma unroll 1
      for (int h = 0; h < 2; h++) {
        uint32_t w[4][8];
#pragma unroll
        for (int i = 0; i < 4; i++) {
#pragma unroll
          for (int e = 0; e < 4; e++) { w[i][2 * e] = lds16(wa + h * 128 + i * 32 + e * 3600); w[i][2 * e + 1] = lds16(wc - h * 128 - i * 32 + e * 3600); }
        }
#pragma unroll
        for (int i = 0; i < 4; i++)
          if (i < 3 || h == 0 || t < 8)
            stg128(dst + (h * 64 + i * 16) * S_, __byte_perm(w[i][0], w[i][1], 0x5410), __byte_perm(w[i][4], w[i][5], 0x5410), __byte_perm(w[i][2], w[i][3], 0x5410), __byte_perm(w[i][6], w[i][7], 0x5410));
      }
    }
    __syncwarp();
    if (lane == 0) mbar_arrive(bars + B_PUBW * 8);
    if (t == 0) PROF(2, 6);
    bar_sync<3, 128>();
    if (k < 113) {
      if (t == 0) PROF(2, 2);
      mbar_wait(bars + B_XCFULL * 8, 0);
      if (t == 0) PROF(2, 3);
      c2 v[16];
      uint2 xe[8], xo[8];
      const uint32_t* xs = g_Xc + (k == 112 ? 0 : k) * 2 * S_ + 2 * t;
#pragma unroll
      for (int jj = 0; jj < 8; jj++) { xe[jj] = ldg64_l2(xs + jj * 256); xo[jj] = ldg64_l2(xs + S_ + jj * 256); }
      const uint32_t se = k == 0 ? 0x4410 : (k == 112 ? 0x4432 : 0x3210), so = k == 0 ? 0x4410 : (k == 112 ? 0x3244 : 0x3210);
#pragma unroll
      for (int jj = 0; jj < 8; jj++) {
        const uint2 e2 = xe[jj], o2 = xo[jj];
#pragma unroll
        for (int h = 0; h < 2; h++) {
          const b2 e = as_b2(__byte_perm(h ? e2.y : e2.x, 0, se)), o = as_b2(__byte_perm(h ? o2.y : o2.x, 0, so));
          const uint32_t s = as_u(__hadd2(e, o)), d = as_u(__hsub2(e, o)) ^ 0x80000000u;
          v[2 * jj + h] = mk(as_b2(__byte_perm(s, d, 0x5410)), as_b2(__byte_perm(s, d, 0x7632)));
        }
      }
      if (t == 0) PROF(2, 12);
      columns(v, sb, t);
      if (t == 0) PROF(2, 14);
      const int pre = (k == 112) ? 1 : 2 * k, pim = (k == 112) ? 1 : 2 * k + 1;
      uint32_t* pq = reinterpret_cast<uint32_t*>(g_PQ) + (t >> 5) * 14336;
      uint32_t* pr = pq + pre * 32 + ((((lane >> 2) ^ pre) & 7) << 2) + (lane & 3);
      uint32_t* pi = pq + pim * 32 + ((((lane >> 2) ^ pim) & 7) << 2) + (lane & 3);
#pragma unroll
      for (int jj = 0; jj < 8; jj++) {
        const b2 ar = as_b2(__byte_perm(as_u(v[2 * jj].y), as_u(v[2 * jj + 1].y), 0x5410)), br = as_b2(__byte_perm(as_u(v[2 * jj].y), as_u(v[2 * jj + 1].y), 0x7632));
        const b2 ai = as_b2(__byte_perm(as_u(v[2 * jj].x), as_u(v[2 * jj + 1].x), 0x5410)), bi = as_b2(__byte_perm(as_u(v[2 * jj].x), as_u(v[2 * jj + 1].x), 0x7632));
        pr[jj * 57344] = as_u(__hadd2(ar, br));
        if (k != 112) pr[jj * 57344 + 7168] = as_u(__hsub2(ar, br));
        if (k != 0) pi[jj * 57344 + 7168] = as_u(__hadd2(ai, bi));
        if (k != 0 && k != 112) pi[jj * 57344] = as_u(__hsub2(ai, bi));
      }
      fence_async_smem();
    }
    bar_sync<3, 128>();
    if (t == 0) { PROF(2, 5); red_release(&g_cnt[5 * 32]); PROF(2, 7); }
    __syncwarp();
    asm volatile("barrier.cluster.wait.aligned;" ::: "memory");
  } else {
    asm volatile("setmaxnreg.dec.sync.aligned.u32 24;");
    auto wd_tile = [&](int b, uint32_t dst, uint32_t fb) {
#pragma unroll
      for (int hf = 0; hf < 2; hf++) {
        const int js = kh * 4 + (b < 12 ? (b & 3) : (b & 1) * 2 + hf);
        const int row = 224 * js + (b < 12 ? (js & 1) * 32 + (b >> 2) * 64 + hf * 32 : 192 - hf * 192);
        tma2d(dst + hf * 4096, &tm_d, 112 * n, row, fb);
        tma2d(dst + 8192 + hf * 4096, &tm_d, 112 * n + 64, row, fb);
      }
    };
    if (warp == 12) {
      if (elect()) {
        mbar_init(bars + B_XFULL * 8, 1); mbar_init(bars + (B_XFULL + 1) * 8, 1);
        fence_async_smem();
#pragma unroll
        for (int w = 0; w < 2; w++) {
          mbar_expect(bars + (B_XFULL + w) * 8, HALF_XR);
          tma3d(sb + OFF_PQ + w * HALF_XR, &tm_x, 0, m * 128 + (w ^ kh ^ 1) * 64, 0, bars + (B_XFULL + w) * 8);
        }
        PROF(3, 3);
#pragma unroll
        for (int i = 0; i < NSLOT; i++) mbar_init(bars + (B_FULL + i) * 8, 1);
        mbar_init(bars + B_PIN * 8, 1);
        fence_async_smem();
      }
      bar_arrive<0, NTHREADS - 64>();
#pragma unroll 1
      for (int i = 0; i < 6; i++) {
        if (elect()) {
          const uint32_t fb = bars + (B_FULL + i) * 8;
          mbar_expect(fb, SLOT);
          tma2d(sb + i * SLOT, &tm_g, c64, i * 64, fb);
          tma2d(sb + i * SLOT + 8192, &tm_u, c64, i * 64, fb);
          PROF(3, 4 + i);
        }
      }
      if (elect()) {
        prefetch_l2(reinterpret_cast<const unsigned char*>(w_r) + bid * 7200, 7200);
        prefetch_l2(reinterpret_cast<const unsigned char*>(w_i) + bid * 7200, 7200);
        prefetch_tma2d(&tm_g, c64, 384); prefetch_tma2d(&tm_u, c64, 384);
      }
    } else if (warp == 14) {
      if (elect()) {
#pragma unroll
        for (int i = B_EMPTY; i < B_END; i++)
          if (i < B_XFULL || i >= B_XFREE) mbar_init(bars + i * 8, i >= B_PQFULL ? 1 : ((i == B_XFREE || i >= B_PUBW) ? 4 : 8));
        asm volatile("fence.mbarrier_init.release.cluster;" ::: "memory");
        fence_async_smem();
        mbar_expect(bars + B_RECV * 8, 64 * 112 * 4);
      }
      bar_arrive<0, NTHREADS - 64>();
    }
    const uint32_t epoch = ld_relaxed(&g_ep[bid]);
    if (warp == 13 && lane == 0) { PROFG(4, 0); PROF(4, 1); }
    bar_sync<1, 128>();
    asm volatile("barrier.cluster.arrive.relaxed.aligned;" ::: "memory");
    if (warp == 12) {
      int slot = 6, ph = 1;
      auto wait_slot = [&]() { mbar_wait(bars + (B_EMPTY + slot) * 8, ph ^ (slot == 6)); };
      auto adv = [&]() { if (++slot == NSLOT) { slot = 0; ph ^= 1; } };
      const int c32 = 224 * j + ((j & 1) ? 0 : 192);
#pragma unroll 1
      for (int i = 6; i < 25; i++) {
        wait_slot();
        if (elect()) {
          const uint32_t dst = sb + slot * SLOT, fb = bars + (B_FULL + slot) * 8;
          const bool last = i >= 21;
          const int cc = last ? c32 : c64 + 64 * (i / 7), rr = last ? slot * 128 : slot * 64;
          mbar_expect(fb, SLOT);
          tma2d(dst, last ? &tm_g32 : &tm_g, cc, rr, fb);
          tma2d(dst + 8192, last ? &tm_u32 : &tm_u, cc, rr, fb);
        }
        adv();
      }
      if (lane == 0) PROF(3, 0);
#pragma unroll 1
      for (int i = 3; i < 16; i++) {
        if (lane == 0) PROF(3, 16 + i);
        if (i == 14) mbar_wait(bars + B_PREP * 8, 0);
        wait_slot();
        if (elect()) {
          const uint32_t fb = bars + (B_FULL + slot) * 8;
          mbar_expect(fb, i < 14 ? SLOT : G_IMG / 2);
          if (i < 14) wd_tile(i, sb + slot * SLOT, fb);
          else bulk_g2s(sb + slot * SLOT, g_G + (size_t)(n * 4 + i - 12) * (G_IMG / 2), G_IMG / 2, fb);
        }
        adv();
      }
      if (lane == 0) PROF(3, 2);
    } else if (warp == 13) {
#pragma unroll 1
      for (int u = 0; u < 2; u++) {
        mbar_wait(bars + (u ? B_PUBW : B_PUBX) * 8, 0);
        if (lane == 0) { PROF(4, 8 + u); red_release(&g_cnt[(u ? 4 : j >> 1) * 32]); PROF(4, 12 + u); }
        __syncwarp();
      }
      mbar_wait(bars + B_PREP * 8, 0);
      mbar_wait(bars + B_LFREE * 8, 0);
      if (elect()) {
        mbar_expect(bars + B_GFULL * 8, G_IMG);
        bulk_g2s(sb + OFF_R + 28672, g_G + (size_t)(n * 2) * G_IMG, G_IMG, bars + B_GFULL * 8);
      }
    } else if (warp == 14) {
      wait_ge(&g_cnt[4 * 32], (epoch + 1) * 128);
      fence_async_global();
      if (elect()) {
        mbar_arrive(bars + B_PREP * 8);
        if (bid < 113) {
          mbar_expect(bars + B_WFULL * 8, 16384);
          bulk_g2s(sb + OFF_WS, g_Wt + bid * S_, 16384, bars + B_WFULL * 8);
        }
        PROF(5, 17);
      }
    } else {
      mbar_wait(bars + B_XFREE * 8, 0);
      if (elect()) {
        mbar_expect(bars + B_PIN * 8, 14400);
        bulk_g2s(sb + OFF_WS, reinterpret_cast<const unsigned char*>(w_r) + bid * 7200, 7200, bars + B_PIN * 8);
        bulk_g2s(sb + OFF_WS + 7200, reinterpret_cast<const unsigned char*>(w_i) + bid * 7200, 7200, bars + B_PIN * 8);
        prefetch_l2(reinterpret_cast<const unsigned char*>(w_gate) + bid * 12544, 12544);
        prefetch_l2(reinterpret_cast<const unsigned char*>(w_up) + bid * 12544, 12544);
        prefetch_l2(reinterpret_cast<const unsigned char*>(w_down) + bid * 12544, 12544);
        PROF(5, 2);
      }
      if (bid < 113) {
        const int sl = (bid == 112) ? 0 : bid;
        wait_ge(&g_cnt[((sl & 1) + 2 * ((sl >> 1) / 28)) * 32], (epoch + 1) * 32);
        if (elect()) { PROF(5, 16); mbar_arrive(bars + B_XCFULL * 8); }
      }
      mbar_wait(bars + (B_XFREE + 1) * 8, 0);
      if (elect()) mbar_expect(bars + B_RFULL * 8, 3 * SLOT);
#pragma unroll 1
      for (int i = 0; i < 3; i++) {
        mbar_wait(bars + (B_FULL + 2 * i + 1) * 8, 1);
        if (elect()) wd_tile(i, sb + OFF_R + i * SLOT, bars + B_RFULL * 8);
      }
      if (lane == 0) PROF(5, 19);
      wait_ge(&g_cnt[5 * 32], (epoch + 1) * 128);
      fence_async_global();
      if (elect()) {
        PROF(5, 18);
        const unsigned char* src = g_PQ + (size_t)(m * 2 + kh) * HALF_XR;
#pragma unroll
        for (int i = 0; i < 4; i++) {
          mbar_expect(bars + (B_PQFULL + i) * 8, i ? 14336 : 14336 + 256);
          bulk_g2s(sb + OFF_PQ + i * 14336, src + i * 14336, 14336, bars + (B_PQFULL + i) * 8);
        }
        bulk_g2s(sb + OFF_G, g_gate + m * 128 + kh * 64, 256, bars + B_PQFULL * 8);
      }
    }
    __syncwarp();
    asm volatile("barrier.cluster.wait.aligned;" ::: "memory");
  }
}

typedef CUresult (*EncodeFn)(CUtensorMap*, CUtensorMapDataType, cuuint32_t, void*, const cuuint64_t*, const cuuint64_t*, const cuuint32_t*,
                             const cuuint32_t*, CUtensorMapInterleave, CUtensorMapSwizzle, CUtensorMapL2promotion, CUtensorMapFloatOOBfill);

void make_map(EncodeFn enc, CUtensorMap* tm, const void* base, int cols, int rows, int bc, int br, CUtensorMapSwizzle sw) {
  cuuint64_t gd[2] = {(cuuint64_t)cols, (cuuint64_t)rows};
  cuuint64_t gs[1] = {(cuuint64_t)cols * 2};
  cuuint32_t bd[2] = {(cuuint32_t)bc, (cuuint32_t)br};
  cuuint32_t es[2] = {1, 1};
  enc(tm, CU_TENSOR_MAP_DATA_TYPE_BFLOAT16, 2, const_cast<void*>(base), gd, gs, bd, es, CU_TENSOR_MAP_INTERLEAVE_NONE, sw,
      CU_TENSOR_MAP_L2_PROMOTION_L2_128B, CU_TENSOR_MAP_FLOAT_OOB_FILL_NONE);
}

}

extern "C" void kernel_launch(void* const* d_in, const int* in_sizes, int n_in, void* d_out, int out_size) {
  (void)in_sizes; (void)n_in; (void)out_size;
  const __nv_bfloat16* x = (const __nv_bfloat16*)d_in[0];
  const __nv_bfloat16* w_r = (const __nv_bfloat16*)d_in[1];
  const __nv_bfloat16* w_i = (const __nv_bfloat16*)d_in[2];
  const __nv_bfloat16* w_gate = (const __nv_bfloat16*)d_in[4];
  const __nv_bfloat16* w_up = (const __nv_bfloat16*)d_in[5];
  const __nv_bfloat16* w_down = (const __nv_bfloat16*)d_in[6];
  const __nv_bfloat16* gate_w = (const __nv_bfloat16*)d_in[7];
  static EncodeFn enc = nullptr;
  static bool ok = false;
  if (!enc) {
    cudaDriverEntryPointQueryResult qr;
    cudaGetDriverEntryPoint("cuTensorMapEncodeTiled", (void**)&enc, cudaEnableDefault, &qr);
    cudaFuncSetAttribute(fused_kernel, cudaFuncAttributeMaxDynamicSharedMemorySize, SMEM_BYTES);
    cudaFuncAttributes fa;
    cudaFuncGetAttributes(&fa, fused_kernel);
    ok = (fa.numRegs == 128);
  }
  if (!ok) return;
  CUtensorMap tx, tg, tu, tg32, tu32, td;
  {
    cuuint64_t gd[3] = {64, (cuuint64_t)S_, 7};
    cuuint64_t gs[2] = {(cuuint64_t)D_ * 2, 128};
    cuuint32_t bd[3] = {64, 64, 7};
    cuuint32_t es[3] = {1, 1, 1};
    enc(&tx, CU_TENSOR_MAP_DATA_TYPE_BFLOAT16, 3, const_cast<__nv_bfloat16*>(x), gd, gs, bd, es, CU_TENSOR_MAP_INTERLEAVE_NONE, CU_TENSOR_MAP_SWIZZLE_128B,
        CU_TENSOR_MAP_L2_PROMOTION_L2_128B, CU_TENSOR_MAP_FLOAT_OOB_FILL_NONE);
  }
  make_map(enc, &tg, w_gate, F_, D_, 64, 64, CU_TENSOR_MAP_SWIZZLE_128B);
  make_map(enc, &tu, w_up, F_, D_, 64, 64, CU_TENSOR_MAP_SWIZZLE_128B);
  make_map(enc, &tg32, w_gate, F_, D_, 32, 128, CU_TENSOR_MAP_SWIZZLE_64B);
  make_map(enc, &tu32, w_up, F_, D_, 32, 128, CU_TENSOR_MAP_SWIZZLE_64B);
  make_map(enc, &td, w_down, D_, F_, 64, 32, CU_TENSOR_MAP_SWIZZLE_128B);
  fused_kernel<<<128, NTHREADS, SMEM_BYTES>>>(tx, tg, tu, tg32, tu32, td, w_r, w_i, w_gate, w_up, w_down, gate_w, (__nv_bfloat16*)d_out);
}
```

```cpp
#include <cuda_runtime.h>
#include <cuda_bf16.h>
#include <cuda.h>
#include <stdint.h>

namespace {

constexpr int S_ = 2048, D_ = 448, F_ = 1792;
constexpr int NTHREADS = 512;
constexpr int SLOT = 16384, NSLOT = 7;
constexpr int HALF_XR = 57344;
constexpr int OFF_PQ = NSLOT * SLOT;
constexpr int OFF_R = OFF_PQ + HALF_XR;
constexpr int OFF_EXCH = OFF_PQ;
constexpr int OFF_WS = OFF_EXCH + 18432;
constexpr int OFF_TW = OFF_WS + 16384;
constexpr int OFF_MISC = OFF_R + HALF_XR;
constexpr int OFF_G = OFF_MISC;
constexpr int OFF_BAR = OFF_MISC + 512;
constexpr int SMEM_BYTES = OFF_BAR + 512;
constexpr int B_FULL = 0, B_EMPTY = 7, B_XFULL = 14  ;
constexpr int B_XFREE = 16  , B_PUBX = 18, B_RFREE = 19, B_LFREE = 20;
constexpr int B_PUBW = 21;
constexpr int B_PQFULL = 22  , B_RECV = 26, B_WFULL = 27, B_XCFULL = 28, B_PREP = 29, B_RFULL = 30, B_GFULL = 31, B_END = 32, B_PIN = 32;

constexpr int G_IMG = 224 * 56 * 2;

__device__ __align__(1024) uint32_t g_Xc[112 * 2 * S_];
__device__ __align__(1024) unsigned char g_H[32 * 56 * 4096];
__device__ __align__(1024) unsigned char g_PQ[32 * HALF_XR];
__device__ __align__(1024) unsigned char g_G[8 * G_IMG];
__device__ __align__(1024) uint2 g_Wt[113 * S_];
__device__ __align__(1024) float g_gate[S_];
__device__ __align__(128) unsigned int g_ep[128];
__device__ __align__(128) unsigned int g_cnt[8 * 32];

#define PROF(role, idx) do {} while (0)
#define PROFG(role, idx) do {} while (0)

__device__ __forceinline__ uint32_t s2u(const void* p) { return (uint32_t)__cvta_generic_to_shared(p); }
__device__ __forceinline__ void mbar_init(uint32_t b, int c) { asm volatile("mbarrier.init.shared::cta.b64 [%0], %1;" :: "r"(b), "r"(c) : "memory"); }
__device__ __forceinline__ void mbar_expect(uint32_t b, int bytes) { asm volatile("mbarrier.arrive.expect_tx.shared::cta.b64 _, [%0], %1;" :: "r"(b), "r"(bytes) : "memory"); }
__device__ __forceinline__ void mbar_arrive(uint32_t b) { asm volatile("mbarrier.arrive.shared::cta.b64 _, [%0];" :: "r"(b) : "memory"); }
__device__ __forceinline__ void mbar_wait(uint32_t b, int ph) {
  asm volatile("{\n.reg .pred p;\n.reg .u32 c;\nmov.u32 c, 0;\nL_WAIT:\nmbarrier.try_wait.parity.shared::cta.b64 p, [%0], %1;\n@p bra.uni L_DONE;\n"
               "add.u32 c, c, 1;\nsetp.lt.u32 p, c, 4194304;\n@p bra.uni L_WAIT;\ntrap;\nL_DONE:\n}" :: "r"(b), "r"(ph) : "memory");
}
__device__ __forceinline__ void mbar_wait_cluster(uint32_t b, int ph) {
  asm volatile("{\n.reg .pred p;\n.reg .u32 c;\nmov.u32 c, 0;\nL_WAIT:\nmbarrier.try_wait.parity.acquire.cluster.shared::cta.b64 p, [%0], %1;\n@p bra.uni L_DONE;\n"
               "add.u32 c, c, 1;\nsetp.lt.u32 p, c, 4194304;\n@p bra.uni L_WAIT;\ntrap;\nL_DONE:\n}" :: "r"(b), "r"(ph) : "memory");
}
__device__ __forceinline__ uint32_t ld_acquire(const unsigned int* p) { uint32_t v; asm volatile("ld.acquire.gpu.global.u32 %0, [%1];" : "=r"(v) : "l"(p) : "memory"); return v; }
__device__ __forceinline__ uint32_t ld_relaxed(const unsigned int* p) { uint32_t v; asm volatile("ld.relaxed.gpu.global.u32 %0, [%1];" : "=r"(v) : "l"(p) : "memory"); return v; }
__device__ __forceinline__ void wait_ge(const unsigned int* p, uint32_t target) {
#pragma unroll 1
  for (int i = 0; i < (1 << 22); i++) { if ((int)(ld_acquire(p) - target) >= 0) return; }
  __trap();
}
__device__ __forceinline__ void red_release(unsigned int* p) { asm volatile("red.release.gpu.global.add.u32 [%0], 1;" :: "l"(p) : "memory"); }
__device__ __forceinline__ void red_relaxed(unsigned int* p) { asm volatile("red.relaxed.gpu.global.add.u32 [%0], 1;" :: "l"(p) : "memory"); }
__device__ __forceinline__ bool elect() { uint32_t p; asm volatile("{\n.reg .pred p;\nelect.sync _|p, 0xffffffff;\nselp.u32 %0, 1, 0, p;\n}" : "=r"(p)); return p; }
__device__ __forceinline__ void fence_async_smem() { asm volatile("fence.proxy.async.shared::cta;" ::: "memory"); }
__device__ __forceinline__ void fence_async_global() { asm volatile("fence.proxy.async.global;" ::: "memory"); }
template <int ID, int N> __device__ __forceinline__ void bar_sync() { asm volatile("bar.sync %0, %1;" :: "n"(ID), "n"(N) : "memory"); }
template <int ID, int N> __device__ __forceinline__ void bar_arrive() { asm volatile("bar.arrive %0, %1;" :: "n"(ID), "n"(N) : "memory"); }
__device__ __forceinline__ void tma2d(uint32_t dst, const CUtensorMap* tm, int c0, int c1, uint32_t bar) {
  asm volatile("cp.async.bulk.tensor.2d.shared::cluster.global.mbarrier::complete_tx::bytes [%0], [%1, {%3, %4}], [%2];"
               :: "r"(dst), "l"(tm), "r"(bar), "r"(c0), "r"(c1) : "memory");
}
__device__ __forceinline__ void tma3d(uint32_t dst, const CUtensorMap* tm, int c0, int c1, int c2, uint32_t bar) {
  asm volatile("cp.async.bulk.tensor.3d.shared::cluster.global.mbarrier::complete_tx::bytes [%0], [%1, {%3, %4, %5}], [%2];"
               :: "r"(dst), "l"(tm), "r"(bar), "r"(c0), "r"(c1), "r"(c2) : "memory");
}
__device__ __forceinline__ void bulk_g2s(uint32_t dst, const void* src, int bytes, uint32_t bar) {
  asm volatile("cp.async.bulk.shared::cluster.global.mbarrier::complete_tx::bytes [%0], [%1], %2, [%3];"
               :: "r"(dst), "l"(src), "r"(bytes), "r"(bar) : "memory");
}
__device__ __forceinline__ void bulk_s2g128(void* dst, uint32_t src) {
  asm volatile("cp.async.bulk.global.shared::cta.bulk_group [%0], [%1], 128;\ncp.async.bulk.commit_group;" :: "l"(dst), "r"(src) : "memory");
}
__device__ __forceinline__ void bulk_done() { asm volatile("cp.async.bulk.wait_group 0;\nfence.proxy.async.global;" ::: "memory"); }
__device__ __forceinline__ void sts32(uint32_t a, uint32_t x) { asm volatile("st.shared.b32 [%0], %1;" :: "r"(a), "r"(x) : "memory"); }
__device__ __forceinline__ void prefetch_l2(const void* src, int bytes) {
  asm volatile("cp.async.bulk.prefetch.L2.global [%0], %1;" :: "l"(src), "r"(bytes) : "memory");
}
__device__ __forceinline__ void prefetch_tma2d(const CUtensorMap* tm, int c0, int c1) {
  asm volatile("cp.async.bulk.prefetch.tensor.2d.L2.global [%0, {%1, %2}];" :: "l"(tm), "r"(c0), "r"(c1) : "memory");
}
__device__ __forceinline__ uint64_t mkdesc(uint32_t addr, uint32_t lbo, uint32_t sbo, uint32_t mode) {
  return (uint64_t)((addr & 0x3FFFF) >> 4) | ((uint64_t)(lbo >> 4) << 16) | ((uint64_t)(sbo >> 4) << 32) | ((uint64_t)mode << 62);
}
__device__ __forceinline__ void wg_fence() { asm volatile("wgmma.fence.sync.aligned;" ::: "memory"); }
__device__ __forceinline__ void wg_commit() { asm volatile("wgmma.commit_group.sync.aligned;" ::: "memory"); }
template <int N> __device__ __forceinline__ void wg_wait() { asm volatile("wgmma.wait_group.sync.aligned %0;" :: "n"(N) : "memory"); }
template <int N> __device__ __forceinline__ void keep(float (&d)[N]) {
#pragma unroll
  for (int i = 0; i < N; i++) asm volatile("" : "+f"(d[i]) :: "memory");
}
__device__ __forceinline__ uint32_t pack_bf16(float lo, float hi) { uint32_t r; asm("cvt.rn.bf16x2.f32 %0, %1, %2;" : "=r"(r) : "f"(hi), "f"(lo)); return r; }
__device__ __forceinline__ float bf16_round(float v) { return __bfloat162float(__float2bfloat16_rn(v)); }
__device__ __forceinline__ void sts128(uint32_t a, uint32_t x, uint32_t y, uint32_t z, uint32_t w) { asm volatile("st.shared.v4.b32 [%0], {%1,%2,%3,%4};" :: "r"(a), "r"(x), "r"(y), "r"(z), "r"(w) : "memory"); }
__device__ __forceinline__ float4 lds128f(uint32_t a) { float4 v; asm volatile("ld.shared.v4.f32 {%0,%1,%2,%3}, [%4];" : "=f"(v.x), "=f"(v.y), "=f"(v.z), "=f"(v.w) : "r"(a) : "memory"); return v; }

__device__ __forceinline__ uint2 lds64(uint32_t a) { uint2 v; asm volatile("ld.shared.v2.b32 {%0,%1}, [%2];" : "=r"(v.x), "=r"(v.y) : "r"(a) : "memory"); return v; }
__device__ __forceinline__ float bf_lo(uint32_t w) { return __uint_as_float(w << 16); }
__device__ __forceinline__ float bf_hi(uint32_t w) { return __uint_as_float(w & 0xffff0000u); }
__device__ __forceinline__ uint32_t opaque(uint32_t v) { asm volatile("" : "+r"(v)); return v; }
__device__ __forceinline__ uint4 ldg128(const void* p) { uint4 v; asm volatile("ld.global.nc.v4.b32 {%0,%1,%2,%3}, [%4];" : "=r"(v.x), "=r"(v.y), "=r"(v.z), "=r"(v.w) : "l"(p)); return v; }
__device__ __forceinline__ void stg128(void* p, uint32_t x, uint32_t y, uint32_t z, uint32_t w) { asm volatile("st.global.v4.b32 [%0], {%1,%2,%3,%4};" :: "l"(p), "r"(x), "r"(y), "r"(z), "r"(w) : "memory"); }
__device__ __forceinline__ void stg128_l2(void* p, uint32_t x, uint32_t y, uint32_t z, uint32_t w) { asm volatile("st.relaxed.gpu.global.v4.b32 [%0], {%1,%2,%3,%4};" :: "l"(p), "r"(x), "r"(y), "r"(z), "r"(w) : "memory"); }
__device__ __forceinline__ uint2 ldg64_l2(const void* p) { uint2 v; asm volatile("ld.relaxed.gpu.global.v2.b32 {%0,%1}, [%2];" : "=r"(v.x), "=r"(v.y) : "l"(p) : "memory"); return v; }
__device__ __forceinline__ void ldg128_l2(uint32_t (&v)[4], const void* p) { asm volatile("ld.relaxed.gpu.global.v4.b32 {%0,%1,%2,%3}, [%4];" : "=r"(v[0]), "=r"(v[1]), "=r"(v[2]), "=r"(v[3]) : "l"(p) : "memory"); }
__device__ __forceinline__ uint4 lds128(uint32_t a) { uint4 v; asm volatile("ld.shared.v4.b32 {%0,%1,%2,%3}, [%4];" : "=r"(v.x), "=r"(v.y), "=r"(v.z), "=r"(v.w) : "r"(a) : "memory"); return v; }
__device__ __forceinline__ uint32_t lds16(uint32_t a) { uint32_t v; asm volatile("ld.shared.u16 %0, [%1];" : "=r"(v) : "r"(a) : "memory"); return v; }
__device__ __forceinline__ void sts64(uint32_t a, uint32_t x, uint32_t y) { asm volatile("st.shared.v2.b32 [%0], {%1,%2};" :: "r"(a), "r"(x), "r"(y) : "memory"); }
template <int TB> __device__ __forceinline__ void wgmma_rs_128(float (&d)[64], const uint32_t (&a)[4], uint64_t db, int sc) {
  asm volatile("{\n.reg .pred p;\nsetp.ne.b32 p, %69, 0;\n"
    "wgmma.mma_async.sync.aligned.m64n128k16.f32.bf16.bf16 {%0, %1, %2, %3, %4, %5, %6, %7, %8, %9, %10, %11, %12, %13, %14, %15, %16, %17, %18, %19, %20, %21, %22, %23, %24, %25, %26, %27, %28, %29, %30, %31, %32, %33, %34, %35, %36, %37, %38, %39, %40, %41, %42, %43, %44, %45, %46, %47, %48, %49, %50, %51, %52, %53, %54, %55, %56, %57, %58, %59, %60, %61, %62, %63}, {%64, %65, %66, %67}, %68, p, 1, 1, %70;\n}\n"
    : "+f"(d[0]), "+f"(d[1]), "+f"(d[2]), "+f"(d[3]), "+f"(d[4]), "+f"(d[5]), "+f"(d[6]), "+f"(d[7]), "+f"(d[8]), "+f"(d[9]), "+f"(d[10]), "+f"(d[11]), "+f"(d[12]), "+f"(d[13]), "+f"(d[14]), "+f"(d[15]), "+f"(d[16]), "+f"(d[17]), "+f"(d[18]), "+f"(d[19]), "+f"(d[20]), "+f"(d[21]), "+f"(d[22]), "+f"(d[23]), "+f"(d[24]), "+f"(d[25]), "+f"(d[26]), "+f"(d[27]), "+f"(d[28]), "+f"(d[29]), "+f"(d[30]), "+f"(d[31]), "+f"(d[32]), "+f"(d[33]), "+f"(d[34]), "+f"(d[35]), "+f"(d[36]), "+f"(d[37]), "+f"(d[38]), "+f"(d[39]), "+f"(d[40]), "+f"(d[41]), "+f"(d[42]), "+f"(d[43]), "+f"(d[44]), "+f"(d[45]), "+f"(d[46]), "+f"(d[47]), "+f"(d[48]), "+f"(d[49]), "+f"(d[50]), "+f"(d[51]), "+f"(d[52]), "+f"(d[53]), "+f"(d[54]), "+f"(d[55]), "+f"(d[56]), "+f"(d[57]), "+f"(d[58]), "+f"(d[59]), "+f"(d[60]), "+f"(d[61]), "+f"(d[62]), "+f"(d[63])
    : "r"(a[0]), "r"(a[1]), "r"(a[2]), "r"(a[3]), "l"(db), "r"(sc), "n"(TB));
}
template <int TB> __device__ __forceinline__ void wgmma_rs_64(float (&d)[32], const uint32_t (&a)[4], uint64_t db, int sc) {
  asm volatile("{\n.reg .pred p;\nsetp.ne.b32 p, %37, 0;\n"
    "wgmma.mma_async.sync.aligned.m64n64k16.f32.bf16.bf16 {%0, %1, %2, %3, %4, %5, %6, %7, %8, %9, %10, %11, %12, %13, %14, %15, %16, %17, %18, %19, %20, %21, %22, %23, %24, %25, %26, %27, %28, %29, %30, %31}, {%32, %33, %34, %35}, %36, p, 1, 1, %38;\n}\n"
    : "+f"(d[0]), "+f"(d[1]), "+f"(d[2]), "+f"(d[3]), "+f"(d[4]), "+f"(d[5]), "+f"(d[6]), "+f"(d[7]), "+f"(d[8]), "+f"(d[9]), "+f"(d[10]), "+f"(d[11]), "+f"(d[12]), "+f"(d[13]), "+f"(d[14]), "+f"(d[15]), "+f"(d[16]), "+f"(d[17]), "+f"(d[18]), "+f"(d[19]), "+f"(d[20]), "+f"(d[21]), "+f"(d[22]), "+f"(d[23]), "+f"(d[24]), "+f"(d[25]), "+f"(d[26]), "+f"(d[27]), "+f"(d[28]), "+f"(d[29]), "+f"(d[30]), "+f"(d[31])
    : "r"(a[0]), "r"(a[1]), "r"(a[2]), "r"(a[3]), "l"(db), "r"(sc), "n"(TB));
}
template <int TB> __device__ __forceinline__ void wgmma_rs_56(float (&d)[28], const uint32_t (&a)[4], uint64_t db, int sc) {
  asm volatile("{\n.reg .pred p;\nsetp.ne.b32 p, %33, 0;\n"
    "wgmma.mma_async.sync.aligned.m64n56k16.f32.bf16.bf16 {%0, %1, %2, %3, %4, %5, %6, %7, %8, %9, %10, %11, %12, %13, %14, %15, %16, %17, %18, %19, %20, %21, %22, %23, %24, %25, %26, %27}, {%28, %29, %30, %31}, %32, p, 1, 1, %34;\n}\n"
    : "+f"(d[0]), "+f"(d[1]), "+f"(d[2]), "+f"(d[3]), "+f"(d[4]), "+f"(d[5]), "+f"(d[6]), "+f"(d[7]), "+f"(d[8]), "+f"(d[9]), "+f"(d[10]), "+f"(d[11]), "+f"(d[12]), "+f"(d[13]), "+f"(d[14]), "+f"(d[15]), "+f"(d[16]), "+f"(d[17]), "+f"(d[18]), "+f"(d[19]), "+f"(d[20]), "+f"(d[21]), "+f"(d[22]), "+f"(d[23]), "+f"(d[24]), "+f"(d[25]), "+f"(d[26]), "+f"(d[27])
    : "r"(a[0]), "r"(a[1]), "r"(a[2]), "r"(a[3]), "l"(db), "r"(sc), "n"(TB));
}
template <int TB> __device__ __forceinline__ void wgmma_rs_112(float (&d)[56], const uint32_t (&a)[4], uint64_t db, int sc) {
  asm volatile("{\n.reg .pred p;\nsetp.ne.b32 p, %61, 0;\n"
    "wgmma.mma_async.sync.aligned.m64n112k16.f32.bf16.bf16 {%0, %1, %2, %3, %4, %5, %6, %7, %8, %9, %10, %11, %12, %13, %14, %15, %16, %17, %18, %19, %20, %21, %22, %23, %24, %25, %26, %27, %28, %29, %30, %31, %32, %33, %34, %35, %36, %37, %38, %39, %40, %41, %42, %43, %44, %45, %46, %47, %48, %49, %50, %51, %52, %53, %54, %55}, {%56, %57, %58, %59}, %60, p, 1, 1, %62;\n}\n"
    : "+f"(d[0]), "+f"(d[1]), "+f"(d[2]), "+f"(d[3]), "+f"(d[4]), "+f"(d[5]), "+f"(d[6]), "+f"(d[7]), "+f"(d[8]), "+f"(d[9]), "+f"(d[10]), "+f"(d[11]), "+f"(d[12]), "+f"(d[13]), "+f"(d[14]), "+f"(d[15]), "+f"(d[16]), "+f"(d[17]), "+f"(d[18]), "+f"(d[19]), "+f"(d[20]), "+f"(d[21]), "+f"(d[22]), "+f"(d[23]), "+f"(d[24]), "+f"(d[25]), "+f"(d[26]), "+f"(d[27]), "+f"(d[28]), "+f"(d[29]), "+f"(d[30]), "+f"(d[31]), "+f"(d[32]), "+f"(d[33]), "+f"(d[34]), "+f"(d[35]), "+f"(d[36]), "+f"(d[37]), "+f"(d[38]), "+f"(d[39]), "+f"(d[40]), "+f"(d[41]), "+f"(d[42]), "+f"(d[43]), "+f"(d[44]), "+f"(d[45]), "+f"(d[46]), "+f"(d[47]), "+f"(d[48]), "+f"(d[49]), "+f"(d[50]), "+f"(d[51]), "+f"(d[52]), "+f"(d[53]), "+f"(d[54]), "+f"(d[55])
    : "r"(a[0]), "r"(a[1]), "r"(a[2]), "r"(a[3]), "l"(db), "r"(sc), "n"(TB));
}
template <int TA, int TB> __device__ __forceinline__ void wgmma_ss_56(float (&d)[28], uint64_t da, uint64_t db, int sc) {
  asm volatile("{\n.reg .pred p;\nsetp.ne.b32 p, %30, 0;\n"
    "wgmma.mma_async.sync.aligned.m64n56k16.f32.bf16.bf16 {%0, %1, %2, %3, %4, %5, %6, %7, %8, %9, %10, %11, %12, %13, %14, %15, %16, %17, %18, %19, %20, %21, %22, %23, %24, %25, %26, %27}, %28, %29, p, 1, 1, %31, %32;\n}\n"
    : "+f"(d[0]), "+f"(d[1]), "+f"(d[2]), "+f"(d[3]), "+f"(d[4]), "+f"(d[5]), "+f"(d[6]), "+f"(d[7]), "+f"(d[8]), "+f"(d[9]), "+f"(d[10]), "+f"(d[11]), "+f"(d[12]), "+f"(d[13]), "+f"(d[14]), "+f"(d[15]), "+f"(d[16]), "+f"(d[17]), "+f"(d[18]), "+f"(d[19]), "+f"(d[20]), "+f"(d[21]), "+f"(d[22]), "+f"(d[23]), "+f"(d[24]), "+f"(d[25]), "+f"(d[26]), "+f"(d[27])
    : "l"(da), "l"(db), "r"(sc), "n"(TA), "n"(TB));
}

__device__ __forceinline__ uint32_t cis(float a) { return pack_bf16(__cosf(a), __sinf(a)); }

typedef __nv_bfloat162 b2;
struct c2 { b2 x, y; };
__device__ __forceinline__ b2 as_b2(uint32_t u) { return *reinterpret_cast<b2*>(&u); }
__device__ __forceinline__ uint32_t as_u(b2 v) { return *reinterpret_cast<uint32_t*>(&v); }
__device__ __forceinline__ c2 mk(b2 x, b2 y) { c2 r; r.x = x; r.y = y; return r; }
__device__ __forceinline__ c2 cmul(c2 a, b2 wr, b2 wi) { return mk(__hfma2(a.x, wr, __hneg2(__hmul2(a.y, wi))), __hfma2(a.x, wi, __hmul2(a.y, wr))); }
__device__ __forceinline__ void fft4(c2& a0, c2& a1, c2& a2, c2& a3) {
  c2 t0 = mk(__hadd2(a0.x, a2.x), __hadd2(a0.y, a2.y)), t1 = mk(__hsub2(a0.x, a2.x), __hsub2(a0.y, a2.y));
  c2 t2 = mk(__hadd2(a1.x, a3.x), __hadd2(a1.y, a3.y)), t3 = mk(__hsub2(a1.x, a3.x), __hsub2(a1.y, a3.y));
  a0 = mk(__hadd2(t0.x, t2.x), __hadd2(t0.y, t2.y)); a2 = mk(__hsub2(t0.x, t2.x), __hsub2(t0.y, t2.y));
  a1 = mk(__hadd2(t1.x, t3.y), __hsub2(t1.y, t3.x)); a3 = mk(__hsub2(t1.x, t3.y), __hadd2(t1.y, t3.x));
}
__device__ __forceinline__ void fft4_s2(c2& a0, c2& a1, c2& a2, c2& a3, b2 r) {
  const b2 nr = __hneg2(r);
  c2 t0 = mk(__hfma2(a2.x, r, a0.x), __hfma2(a2.y, r, a0.y)), t1 = mk(__hfma2(a2.x, nr, a0.x), __hfma2(a2.y, nr, a0.y));
  c2 t2 = mk(__hadd2(a1.x, a3.x), __hadd2(a1.y, a3.y)), t3 = mk(__hsub2(a1.x, a3.x), __hsub2(a1.y, a3.y));
  a0 = mk(__hadd2(t0.x, t2.x), __hadd2(t0.y, t2.y)); a2 = mk(__hsub2(t0.x, t2.x), __hsub2(t0.y, t2.y));
  a1 = mk(__hadd2(t1.x, t3.y), __hsub2(t1.y, t3.x)); a3 = mk(__hsub2(t1.x, t3.y), __hadd2(t1.y, t3.x));
}
__device__ __forceinline__ void fft4_s13(c2& a0, c2& a1, c2& a2, c2& a3, b2 r) {
  const b2 nr = __hneg2(r);
  c2 t0 = mk(__hadd2(a0.x, a2.x), __hadd2(a0.y, a2.y)), t1 = mk(__hsub2(a0.x, a2.x), __hsub2(a0.y, a2.y));
  c2 t2 = mk(__hadd2(a1.x, a3.x), __hadd2(a1.y, a3.y)), t3 = mk(__hsub2(a1.x, a3.x), __hsub2(a1.y, a3.y));
  a0 = mk(__hfma2(t2.x, r, t0.x), __hfma2(t2.y, r, t0.y)); a2 = mk(__hfma2(t2.x, nr, t0.x), __hfma2(t2.y, nr, t0.y));
  a1 = mk(__hfma2(t3.y, r, t1.x), __hfma2(t3.x, nr, t1.y)); a3 = mk(__hfma2(t3.y, nr, t1.x), __hfma2(t3.x, r, t1.y));
}
__device__ __forceinline__ c2 rot1(c2 a) { return mk(__hadd2(a.x, a.y), __hsub2(a.y, a.x)); }
__device__ __forceinline__ c2 rot3(c2 a) { return mk(__hsub2(a.y, a.x), __hneg2(__hadd2(a.x, a.y))); }
__device__ __forceinline__ c2 mul_mi(c2 a) { return mk(a.y, __hneg2(a.x)); }
template <int O> __device__ __forceinline__ void fft8(c2 (&v)[16]) {
  const b2 r = as_b2(0x3F353F35u), nr = as_b2(0xBF35BF35u);
  fft4(v[O], v[O + 4], v[O + 8], v[O + 12]);
  fft4(v[O + 2], v[O + 6], v[O + 10], v[O + 14]);
  const c2 o0 = v[O + 2], o1 = rot1(v[O + 6]), o2 = v[O + 10], o3 = rot1(v[O + 14]);
  const c2 e0 = v[O], e1 = v[O + 4], e2 = v[O + 8], e3 = v[O + 12];
  v[O] = mk(__hadd2(e0.x, o0.x), __hadd2(e0.y, o0.y));              v[O + 8] = mk(__hsub2(e0.x, o0.x), __hsub2(e0.y, o0.y));
  v[O + 2] = mk(__hfma2(o1.x, r, e1.x), __hfma2(o1.y, r, e1.y));    v[O + 10] = mk(__hfma2(o1.x, nr, e1.x), __hfma2(o1.y, nr, e1.y));
  v[O + 4] = mk(__hadd2(e2.x, o2.y), __hsub2(e2.y, o2.x));          v[O + 12] = mk(__hsub2(e2.x, o2.y), __hadd2(e2.y, o2.x));
  v[O + 6] = mk(__hfma2(o3.y, r, e3.x), __hfma2(o3.x, nr, e3.y));   v[O + 14] = mk(__hfma2(o3.y, nr, e3.x), __hfma2(o3.x, r, e3.y));
}
__device__ __forceinline__ void fft16(c2 (&v)[16]) {
  const b2 r = as_b2(0x3F353F35u), c1 = as_b2(0x3F6D3F6Du), s1 = as_b2(0x3EC43EC4u), nc1 = as_b2(0xBF6DBF6Du), ns1 = as_b2(0xBEC4BEC4u);
#pragma unroll
  for (int a = 0; a < 4; a++) fft4(v[a], v[a + 4], v[a + 8], v[a + 12]);
  v[5] = cmul(v[5], c1, ns1); v[6] = rot1(v[6]); v[7] = cmul(v[7], s1, nc1);
  v[9] = rot1(v[9]); v[10] = mul_mi(v[10]); v[11] = rot3(v[11]);
  v[13] = cmul(v[13], s1, nc1); v[14] = rot3(v[14]); v[15] = cmul(v[15], nc1, s1);
  fft4(v[0], v[1], v[2], v[3]); fft4_s2(v[4], v[5], v[6], v[7], r); fft4_s13(v[8], v[9], v[10], v[11], r); fft4_s2(v[12], v[13], v[14], v[15], r);
  c2 t;
  t = v[1]; v[1] = v[4]; v[4] = t;  t = v[2]; v[2] = v[8]; v[8] = t;  t = v[3]; v[3] = v[12]; v[12] = t;
  t = v[6]; v[6] = v[9]; v[9] = t;  t = v[7]; v[7] = v[13]; v[13] = t; t = v[11]; v[11] = v[14]; v[14] = t;
}

__device__ __forceinline__ void columns(c2 (&v)[16], uint32_t sb, int t) {
  const int l16 = t & 15;
  const uint32_t row = sb + OFF_EXCH + (t >> 4) * 2304;
  const uint32_t pos = sb + OFF_EXCH + (t >> 3) * 144 + (t & 7) * 16;
#pragma unroll 1
  for (int ps = 0; ps < 6; ps++) {
    if (ps == 0 || ps == 5) { fft8<0>(v); fft8<1>(v); } else fft16(v);
    if (ps == 5) break;
    if (ps == 2) {
      const uint32_t ws = sb + OFF_WS + (l16 >> 1) * 128 + ((((t >> 4) + (l16 >> 1)) & 7) * 2 + (l16 & 1)) * 8;
      mbar_wait(sb + OFF_BAR + B_WFULL * 8, 0);
#pragma unroll
      for (int q = 0; q < 16; q++) {
        const uint2 w = lds64(ws + q * 1024);
        const c2 z = cmul(v[q], as_b2(w.x), as_b2(w.y));
        v[q] = mk(z.y, z.x);
      }
      continue;
    }
    {
      const bool full = ps == 0 || ps == 4;
      const uint32_t tw = sb + OFF_TW + (full ? ps * 2048 + t * 16 : 16384 + l16 * 16);
      const uint32_t st = full ? 2048 : 256;
#pragma unroll
      for (int i = 0; i < 4; i++) {
        const uint4 w4 = lds128(tw + i * st);
        const uint32_t w[4] = {w4.x, w4.y, w4.z, w4.w};
#pragma unroll
        for (int e = 0; e < 4; e++) v[4 * i + e] = cmul(v[4 * i + e], __low2bfloat162(as_b2(w[e])), __high2bfloat162(as_b2(w[e])));
      }
    }
    if (ps == 0) {
#pragma unroll
      for (int q = 0; q < 8; q++) sts128(pos + q * 2304, as_u(v[2 * q].x), as_u(v[2 * q].y), as_u(v[2 * q + 1].x), as_u(v[2 * q + 1].y));
      bar_sync<3, 128>();
#pragma unroll
      for (int q = 0; q < 16; q++) { const uint2 a = lds64(row + q * 144 + l16 * 8); v[q] = mk(as_b2(a.x), as_b2(a.y)); }
    } else {
      __syncwarp();
#pragma unroll
      for (int q = 0; q < 16; q++) sts64(row + q * 144 + l16 * 8, as_u(v[q].x), as_u(v[q].y));
      if (ps == 4) bar_sync<3, 128>(); else __syncwarp();
      const uint32_t src = ps == 4 ? pos : row + l16 * 144, st = ps == 4 ? 2304 : 16;
#pragma unroll
      for (int q = 0; q < 8; q++) { const uint4 a = lds128(src + q * st); v[2 * q] = mk(as_b2(a.x), as_b2(a.y)); v[2 * q + 1] = mk(as_b2(a.z), as_b2(a.w)); }
    }
  }
}

template <int NH> __device__ __forceinline__ void h_epilogue(float (&acc)[NH * 8], unsigned char* gdst, uint32_t tag) {
#pragma unroll
  for (int c = 0; c < NH / 2; c++) {
    uint32_t pk[4];
#pragma unroll
    for (int i = 0; i < 4; i++) {
      float hv[2];
#pragma unroll
      for (int e = 0; e < 2; e++) {
        float hg = 0.5f * acc[c * 8 + i * 2 + e], up = acc[NH * 4 + c * 8 + i * 2 + e];
        float th; asm("tanh.approx.f32 %0, %1;" : "=f"(th) : "f"(hg));
        hv[e] = fmaf(hg, th, hg) * up;
      }
      pk[i] = pack_bf16(hv[0], hv[1]);
    }
    stg128_l2(gdst + c * 4096, (pk[0] & ~1u) | tag, pk[1], pk[2], pk[3]);
  }
}

__device__ __forceinline__ void frag_ready(uint32_t (&a)[4], uint32_t (&b)[4], uint32_t (&c)[4], uint32_t (&d)[4], const unsigned char* p, uint32_t tag) {
  asm volatile("{\n.reg .pred p;\n.reg .u32 c, m, q;\nmov.u32 c, 0;\nL_TRY:\n"
               "lop3.b32 m, %0, %4, %17, 0x7E;\nlop3.b32 q, %8, %12, %17, 0x7E;\nlop3.b32 m, m, q, 1, 0xA8;\nsetp.ne.u32 p, m, 0;\n"
               "vote.sync.any.pred p, p, 0xffffffff;\n@!p bra.uni L_OK;\n"
               "ld.relaxed.gpu.global.v4.b32 {%0,%1,%2,%3}, [%16];\nld.relaxed.gpu.global.v4.b32 {%4,%5,%6,%7}, [%16+4096];\n"
               "ld.relaxed.gpu.global.v4.b32 {%8,%9,%10,%11}, [%16+8192];\nld.relaxed.gpu.global.v4.b32 {%12,%13,%14,%15}, [%16+12288];\n"
               "add.u32 c, c, 1;\nsetp.lt.u32 p, c, 262144;\n@p bra.uni L_TRY;\ntrap;\nL_OK:\n}"
               : "+r"(a[0]), "+r"(a[1]), "+r"(a[2]), "+r"(a[3]), "+r"(b[0]), "+r"(b[1]), "+r"(b[2]), "+r"(b[3]),
                 "+r"(c[0]), "+r"(c[1]), "+r"(c[2]), "+r"(c[3]), "+r"(d[0]), "+r"(d[1]), "+r"(d[2]), "+r"(d[3])
               : "l"(p), "r"(tag) : "memory");
}

#define MAP 0
#define LEAD2 0
#define LEAD1 3

__global__ void __cluster_dims__(2, 1, 1) __launch_bounds__(NTHREADS, 1)
fused_kernel(const __grid_constant__ CUtensorMap tm_x, const __grid_constant__ CUtensorMap tm_g, const __grid_constant__ CUtensorMap tm_u,
             const __grid_constant__ CUtensorMap tm_g32, const __grid_constant__ CUtensorMap tm_u32, const __grid_constant__ CUtensorMap tm_d,
             const __nv_bfloat16* __restrict__ w_r, const __nv_bfloat16* __restrict__ w_i,
             const __nv_bfloat16* __restrict__ w_gate, const __nv_bfloat16* __restrict__ w_up,
             const __nv_bfloat16* __restrict__ w_down, const __nv_bfloat16* __restrict__ gate_w, __nv_bfloat16* __restrict__ out) {
  extern __shared__ __align__(1024) unsigned char smem[];
  const uint32_t sb = s2u(smem);
  const uint32_t bars = sb + OFF_BAR;
  const int tid = threadIdx.x, warp = __shfl_sync(0xffffffffu, tid >> 5, 0), lane = tid & 31;
  const int cl = blockIdx.x >> 1, kh = blockIdx.x & 1;
  const int n0 = cl < 4 ? cl : (cl < 36 ? (cl - 4) >> 3 : (cl - 36) / 7);
  const int m0 = cl < 4 ? 15 : (cl < 36 ? (cl - 4) & 7 : cl - 28 - 7 * n0);
  const int n = MAP == 0 ? n0 : (MAP == 1 ? (m0 & 3) : ((n0 & 1) | ((m0 & 1) << 1)));
  const int m = MAP == 0 ? m0 : (MAP == 1 ? ((m0 & 12) | n0) : ((m0 & 14) | (n0 >> 1)));
  const int j = kh * 4 + n, bid = m * 8 + n * 2 + kh;

  const int c64 = 224 * j + (j & 1) * 32;
  if (warp < 8) {
    asm volatile("setmaxnreg.inc.sync.aligned.u32 208;");
    const int wg = warp >> 2, w4 = warp & 3, g = lane >> 2, t = lane & 3;
    const int rh = wg ^ kh ^ 1;
    const int p = j & 1, r = (j >> 1) & 1, hh = j >> 2;
    const uint32_t epoch = ld_relaxed(&g_ep[bid]);
    if ((tid & 127) == 0) PROF(wg, 30);
#pragma unroll 1
    for (int it = tid; it < 392; it += 256) {
      const int kc = it / 28, sg = it - kc * 28;
      const int k = 2 * (28 * hh + sg) + r;
      const float kf = (float)k * (-6.283185307179586f / 448.0f), a0 = (float)(16 * kc + p) * kf;
      uint32_t c[4], s[4];
#pragma unroll
      for (int q = 0; q < 4; q++) {
        const float a1 = fmaf((float)(2 * q), kf, a0), a2 = fmaf((float)(2 * q + 8), kf, a0);
        c[q] = pack_bf16(__cosf(a1), __cosf(a2)); s[q] = pack_bf16(__sinf(a1), __sinf(a2));
        if (k == 0) s[q] = ((q ^ p) & 1) ? 0xBF80BF80u : 0x3F803F80u;
      }
      const uint32_t a = sb + 6 * SLOT + (kc * 56 + 2 * sg) * 16;
      sts128(a, c[0], c[1], c[2], c[3]);
      sts128(a + 16, s[0], s[1], s[2], s[3]);
    }
    if ((tid & 127) == 0) PROF(wg, 31);
    fence_async_smem();
    bar_sync<0, NTHREADS - 64>();
    asm volatile("barrier.cluster.arrive.relaxed.aligned;" ::: "memory");
    if ((tid & 127) == 0) PROF(wg, 1);

    uint32_t xa[28][4];
    {
      const uint32_t xb = sb + OFF_PQ + wg * HALF_XR + (w4 * 16 + (lane & 15)) * 128;
      mbar_wait(bars + (B_XFULL + wg) * 8, 0);
      if ((tid & 127) == 0) PROF(wg, 2);
#pragma unroll
      for (int kb = 0; kb < 7; kb++) {
#pragma unroll
        for (int kk = 0; kk < 4; kk++) {
          uint32_t a = xb + kb * 8192 + (((2 * kk + (lane >> 4)) ^ (lane & 7)) << 4);
          asm volatile("ldmatrix.sync.aligned.m8n8.x4.shared.b16 {%0,%1,%2,%3}, [%4];"
                       : "=r"(xa[kb * 4 + kk][0]), "=r"(xa[kb * 4 + kk][1]), "=r"(xa[kb * 4 + kk][2]), "=r"(xa[kb * 4 + kk][3]) : "r"(a) : "memory");
        }
      }
    }
    {
      uint32_t ad[7][4];
      const uint32_t sel = p ? 0x7632 : 0x5410;
      const uint32_t sgn = r ? 0xBF80BF80u : 0x3F803F80u;
#pragma unroll
      for (int jj = 0; jj < 7; jj++) {
#pragma unroll
        for (int i = 0; i < 4; i++) {
          int ks = 2 * jj + (i >> 1), rr = i & 1;
          uint32_t lo = __byte_perm(xa[ks][rr], xa[ks][rr + 2], sel);
          uint32_t hi = __byte_perm(xa[ks + 14][rr], xa[ks + 14][rr + 2], sel);
          asm("fma.rn.bf16x2 %0, %1, %2, %3;" : "=r"(ad[jj][i]) : "r"(hi), "r"(sgn), "r"(lo));
        }
      }
      __syncwarp();
      if (lane == 0) mbar_arrive(bars + (B_XFREE + wg) * 8);
      float acc[28];
      wg_fence();
      uint64_t db = mkdesc(sb + 6 * SLOT, 896, 128, 0);
#pragma unroll
      for (int jj = 0; jj < 7; jj++) wgmma_rs_56<0>(acc, ad[jj], db + jj * 112, jj != 0);
      wg_commit();
      wg_wait<0>(); keep(acc);
      if (lane == 0) mbar_arrive(bars + (B_EMPTY + 6) * 8);
      uint32_t* xc = g_Xc + (size_t)((2 * (28 * hh + t) + r) * 2 + p) * S_ + m * 128 + rh * 64 + w4 * 16 + g;
#pragma unroll
      for (int i = 0; i < 7; i++) {
        xc[i * 16 * S_] = pack_bf16(acc[4 * i], acc[4 * i + 1]);
        xc[i * 16 * S_ + 8] = pack_bf16(acc[4 * i + 2], acc[4 * i + 3]);
      }
      __syncwarp();
      if (lane == 0) mbar_arrive(bars + B_PUBX * 8);
    }
    if ((tid & 127) == 0) PROF(wg, 3);
    const uint32_t tag = ~epoch & 1;
    unsigned char* const hbase = g_H + (size_t)(m * 2 + kh) * (56 * 4096) + rh * 2048 + (tid & 127) * 16;
#pragma unroll 1
    for (int u = 0; u < 3; u++) {
      float acc[64];
      if (wg == 1) { if (u & 1) bar_sync<6, 256>(); else bar_sync<2, 256>(); }
      const uint32_t sbu = opaque(sb);
#pragma unroll
      for (int kb = 0; kb < 7; kb++) {
        mbar_wait(sbu + OFF_BAR + (B_FULL + kb) * 8, u & 1);
        wg_fence();
        uint64_t db = mkdesc(sbu + kb * SLOT, 8192, 1024, 1);
#pragma unroll
        for (int kk = 0; kk < 4; kk++) wgmma_rs_128<1>(acc, xa[kb * 4 + kk], db + kk * 128, (kb | kk) != 0);
        wg_commit();
        if (kb == LEAD1 && wg == 0) { if (u & 1) bar_arrive<6, 256>(); else bar_arrive<2, 256>(); }
        if (kb > 0) { wg_wait<1>(); if (lane == 0) mbar_arrive(sbu + OFF_BAR + (B_EMPTY + kb - 1) * 8); }
      }
      wg_wait<0>(); keep(acc);
      if (lane == 0) mbar_arrive(sbu + OFF_BAR + (B_EMPTY + 6) * 8);
      if ((tid & 127) == 0) PROF(wg, 4 + 2 * u);
      h_epilogue<8>(acc, hbase + (u * 16 + n * 4) * 4096, tag);
      if ((tid & 127) == 0) PROF(wg, 5 + 2 * u);
    }
    uint32_t ha[14][4][4];
    auto check = [&](int b0, int b1) {
#pragma unroll
      for (int b = b0; b < b1; b++) frag_ready(ha[b][0], ha[b][1], ha[b][2], ha[b][3], hbase + b * 16384, tag);
    };
    auto load = [&](int b0, int b1) {
#pragma unroll
      for (int i = b0; i < b1; i++) ldg128_l2(ha[i >> 2][i & 3], hbase + i * 4096);
    };
    {
      float acc[32];
      load(0, 3);
      if (wg == 1) bar_sync<6, 256>();
      const uint32_t sbu = opaque(sb);
#pragma unroll
      for (int it = 0; it < 4; it++) {
        mbar_wait(sbu + OFF_BAR + (B_FULL + it) * 8, 1);
        wg_fence();
        uint64_t db = mkdesc(sbu + it * SLOT, 8192, 512, 2);
#pragma unroll
        for (int kk = 0; kk < 8; kk++) if (it * 8 + kk < 28) wgmma_rs_64<1>(acc, xa[it * 8 + kk], db + kk * 64, (it | kk) != 0);
        wg_commit();
        if (it == 2 && wg == 0) bar_arrive<6, 256>();
        if (it > 0) {
          wg_wait<1>();
          if (lane == 0) mbar_arrive(sbu + OFF_BAR + (B_EMPTY + it - 1) * 8);
          if (it == 1) load(3, 11);
          if (it == 2) load(11, 16);
        }
      }
      wg_wait<0>(); keep(acc);
      if (lane == 0) mbar_arrive(sbu + OFF_BAR + (B_EMPTY + 3) * 8);
      if ((tid & 127) == 0) PROF(wg, 10);
      h_epilogue<4>(acc, hbase + (48 + n * 2) * 4096, tag);
    }
    asm volatile("barrier.cluster.wait.aligned;" ::: "memory");
    if ((tid & 127) == 0) PROF(wg, 11);

    float acc[56];
    check(0, 4);
    if (wg == 1) bar_sync<2, 256>();
#pragma unroll
    for (int b = 0; b < 14; b++) {
      if ((tid & 127) == 0) PROF(wg, 16 + b);
      if (b >= 3) mbar_wait(bars + (B_FULL + (b + 1) % 7) * 8, b < 6 || b == 13);
      else if (b == 0) mbar_wait(bars + B_RFULL * 8, 0);
      if (b == 4) check(4, 7);
      if (b == 7) check(7, 11);
      if (b == 11) check(11, 14);
      wg_fence();
      const uint64_t db = mkdesc(b < 3 ? sb + OFF_R + b * SLOT : sb + (b + 1) % 7 * SLOT, 8192, 1024, 1);
#pragma unroll
      for (int kk = 0; kk < 4; kk++) wgmma_rs_112<1>(acc, ha[b][kk], db + kk * 128, (b | kk) != 0);
      wg_commit();
      if (b == LEAD2 && wg == 0) bar_arrive<2, 256>();
      if (b == 0) load(16, 24);
      if (b == 1) load(24, 28);
      if (b == 4 || b == 5) load(8 * b - 4, 8 * b + 4);
      if (b == 7) load(44, 52);
      if (b == 8) load(52, 56);
      if (b > 0) wg_wait<1>();
      if (lane == 0) {
        if (b >= 4 && b <= 9) mbar_arrive(bars + (B_EMPTY + b % 7) * 8);
        if (b == 3) {
          mbar_arrive(bars + B_LFREE * 8);
          asm volatile("{\n.reg .b32 ra;\nmapa.shared::cluster.u32 ra, %0, %1;\nmbarrier.arrive.relaxed.cluster.shared::cluster.b64 _, [ra];\n}"
                       :: "r"(bars + B_RFREE * 8), "r"(kh ^ 1) : "memory");
        }
      }
    }
    const int t128 = tid & 127;
    wg_wait<0>(); keep(acc);
    if (wg == 0) {
      if (t128 == 0) PROF(wg, 12);
      mbar_wait_cluster(bars + B_RFREE * 8, 0);
      uint32_t rdst, rbar;
      asm volatile("mapa.shared::cluster.u32 %0, %1, %2;" : "=r"(rdst) : "r"(sb + OFF_R + t128 * 16), "r"(kh ^ 1));
      asm volatile("mapa.shared::cluster.u32 %0, %1, %2;" : "=r"(rbar) : "r"(bars + B_RECV * 8), "r"(kh ^ 1));
#pragma unroll
      for (int i = 0; i < 14; i++)
        asm volatile("st.async.weak.shared::cluster.mbarrier::complete_tx::bytes.v4.f32 [%0], {%1,%2,%3,%4}, [%5];"
                     :: "r"(rdst + i * 2048), "f"(acc[4 * i]), "f"(acc[4 * i + 1]), "f"(acc[4 * i + 2]), "f"(acc[4 * i + 3]), "r"(rbar) : "memory");
    } else {
      float spec[2][28];
      if (t128 == 0) PROF(wg, 12);
      mbar_wait_cluster(bars + B_RECV * 8, 0);
      if (t128 == 0) PROF(wg, 0);
#pragma unroll
      for (int i = 0; i < 14; i++) {
        const float4 o = lds128f(sb + OFF_R + t128 * 16 + i * 2048);
        acc[4 * i] += o.x; acc[4 * i + 1] += o.y; acc[4 * i + 2] += o.z; acc[4 * i + 3] += o.w;
      }
#pragma unroll
      for (int i = 0; i < 4; i++) {
        if (i == 0) mbar_wait(bars + B_GFULL * 8, 0);
        if (i >= 2) mbar_wait(bars + (B_FULL + i - 1) * 8, 1);
        mbar_wait(bars + (B_PQFULL + i) * 8, 0);
        if (i == 0 && t128 == 0) { PROF(wg, 13); g_ep[bid] = epoch + 1; }
        wg_fence();
        const uint64_t da = mkdesc(sb + OFF_PQ + i * 14336, 1024, 1024, 1);
        const uint64_t db = mkdesc(i < 2 ? sb + OFF_R + 28672 + i * (G_IMG / 2) : sb + (i - 1) * SLOT, 896, 128, 0);
#pragma unroll
        for (int kk = 0; kk < 7; kk++) wgmma_ss_56<1, 0>(spec[i >> 1], da + kk * 128, db + kk * 112, ((i & 1) | kk) != 0);
        wg_commit();
      }
      const float* gs = reinterpret_cast<const float*>(smem + OFF_G) + w4 * 16 + g;
      const float o0 = bf16_round(1.0f - gs[0]), o1 = bf16_round(1.0f - gs[8]);
      const float g0 = gs[0] * (1.0f / (float)(S_ * D_)), g1 = gs[8] * (1.0f / (float)(S_ * D_));
#pragma unroll
      for (int i = 0; i < 56; i++) acc[i] *= (i & 2) ? o1 : o0;
      keep(acc);
      wg_wait<0>(); keep(spec[0]); keep(spec[1]);
      if (t128 == 0) PROF(wg, 14);
      bar_sync<5, 128>();
      const uint32_t st = sb + OFF_PQ + w4 * 3840;
#pragma unroll
      for (int i = 0; i < 7; i++) {
        uint32_t pk[4];
#pragma unroll
        for (int e = 0; e < 2; e++) {
          const int c = 2 * i + e, si = i * 4 + e;
          pk[2 * e] = pack_bf16(fmaf(g0, spec[0][si], acc[4 * c]), fmaf(g0, spec[1][si], acc[4 * c + 1]));
          pk[2 * e + 1] = pack_bf16(fmaf(g1, spec[0][si + 2], acc[4 * c + 2]), fmaf(g1, spec[1][si + 2], acc[4 * c + 3]));
        }
        asm volatile("stmatrix.sync.aligned.m8n8.x4.shared.b16 [%0], {%1,%2,%3,%4};"
                     :: "r"(st + (lane & 15) * 240 + (lane >> 4) * 16 + i * 32), "r"(pk[0]), "r"(pk[1]), "r"(pk[2]), "r"(pk[3]) : "memory");
      }
      __syncwarp();
      if (lane < 28) {
        const int r2 = lane >= 14, cc = lane - r2 * 14;
        unsigned char* ob = reinterpret_cast<unsigned char*>(out) + (size_t)(m * 128 + kh * 64 + w4 * 16 + r2) * (D_ * 2) + n * 224 + cc * 16;
        float4 v[8];
#pragma unroll
        for (int i = 0; i < 8; i++) v[i] = lds128f(st + r2 * 240 + cc * 16 + i * 480);
#pragma unroll
        for (int i = 0; i < 8; i++) stg128(ob + i * (D_ * 4), __float_as_uint(v[i].x), __float_as_uint(v[i].y), __float_as_uint(v[i].z), __float_as_uint(v[i].w));
      }
    }
    if (t128 == 0) { PROF(wg, 15); if (wg) { PROFG(4, 30); PROF(4, 31); } }
  } else if (warp < 12) {
    asm volatile("setmaxnreg.dec.sync.aligned.u32 72;");
    const int t = tid - 256;
    const int k = bid;
    if (t == 0) PROF(2, 0);
    uint4 gv[7];
#pragma unroll
    for (int i = 0; i < 7; i++) gv[i] = ldg128(reinterpret_cast<const uint4*>(gate_w) + i * 8 + (t & 7));
    if (t < 98) {
      int cid = m * 98 + t, kc = cid / 56, nn = cid - kc * 56;
      int d = 112 * n + 8 * (2 * (nn >> 3) + (nn & 1)) + (nn & 6) + kh;
      int dr = d > 224 ? d - 448 : d;
      const float df = (float)dr * (-6.283185307179586f / 448.0f);
      uint32_t pk[4];
#pragma unroll
      for (int e = 0; e < 4; e++) {
        const float a = (float)(4 * kc + e) * df;
        pk[e] = pack_bf16(2.0f * __cosf(a), 2.0f * __sinf(a));
      }
      if (kc == 0) pk[0] = (((d >> 1) ^ kh) & 1) ? 0xBF803F80u : 0x3F803F80u;
      stg128(g_G + (size_t)(n * 2 + kh) * G_IMG + cid * 16, pk[0], pk[1], pk[2], pk[3]);
    }
    bar_sync<0, NTHREADS - 64>();
    asm volatile("barrier.cluster.arrive.relaxed.aligned;" ::: "memory");
    {
      const int row = n * 16 + (t >> 3), l8 = t & 7;
      mbar_wait(bars + (B_XFULL + 1) * 8, 0);
      float sum = 0.f;
#pragma unroll
      for (int i = 0; i < 7; i++) {
        const uint4 a = lds128(sb + OFF_R + i * 8192 + row * 128 + ((l8 ^ (row & 7)) << 4));
        const uint32_t aa[4] = {a.x, a.y, a.z, a.w}, bb[4] = {gv[i].x, gv[i].y, gv[i].z, gv[i].w};
#pragma unroll
        for (int e = 0; e < 4; e++) {
          const uint32_t pr = as_u(__hmul2(as_b2(aa[e]), as_b2(bb[e])));
          sum += bf_lo(pr) + bf_hi(pr);
        }
      }
      sum += __shfl_xor_sync(0xffffffffu, sum, 1); sum += __shfl_xor_sync(0xffffffffu, sum, 2); sum += __shfl_xor_sync(0xffffffffu, sum, 4);
      if (lane == 0) mbar_arrive(bars + (B_XFREE + 1) * 8);
      if (l8 == 0) g_gate[m * 128 + kh * 64 + row] = bf16_round(__fdividef(1.0f, 1.0f + __expf(-bf16_round(sum))));
    }
    __syncwarp();
    if (lane == 0) mbar_arrive(bars + B_PUBX * 8);
    if (t == 0) PROF(2, 11);
    mbar_wait(bars + B_XFREE * 8, 0);
    if (k < 113) {
      const float u = -6.283185307179586f / 2048.0f, t2 = (float)(2 * t) * u, rr = (float)(t >> 4) * u;
#pragma unroll 1
      for (int i = 0; i < 4; i++) {
        const float q = (float)(2 * i), l = (float)((t & 15) + 64 * i);
        sts128(sb + OFF_TW + i * 2048 + t * 16, cis(t2 * q), cis((t2 + u) * q), cis(t2 * (q + 1.0f)), cis((t2 + u) * (q + 1.0f)));
        sts128(sb + OFF_TW + 8192 + i * 2048 + t * 16, cis(rr * l), cis(rr * (l + 16.0f)), cis(rr * (l + 32.0f)), cis(rr * (l + 48.0f)));
      }
      const float l = (float)((t >> 1) & 15) * (8.0f * u), jj = (float)((t >> 5) * 4 + (t & 1) * 2);
      sts64(sb + OFF_TW + 16384 + t * 8, cis(l * jj), cis(l * (jj + 1.0f)));
    }
    if (t == 0) PROF(2, 9);
    mbar_wait(bars + B_PIN * 8, 0);
    if (t == 0) PROF(2, 4);
    {
      const uint32_t wa = sb + OFF_WS + (((t & 7) - bid) & 7) * 450 + (t >> 3) * 2, wc = wa + 448 - (t >> 3) * 4;
#pragma unroll 1
      for (int h = 0; h < 2; h++) {
        uint32_t w[4][8];
#pragma unroll
        for (int i = 0; i < 4; i++) {
#pragma unroll
          for (int e = 0; e < 4; e++) { w[i][2 * e] = lds16(wa + h * 128 + i * 32 + e * 3600); w[i][2 * e + 1] = lds16(wc - h * 128 - i * 32 + e * 3600); }
        }
#pragma unroll
        for (int i = 0; i < 4; i++)
          sts128(sb + OFF_EXCH + h * 8192 + i * 2048 + t * 16, __byte_perm(w[i][0], w[i][1], 0x5410), __byte_perm(w[i][4], w[i][5], 0x5410), __byte_perm(w[i][2], w[i][3], 0x5410), __byte_perm(w[i][6], w[i][7], 0x5410));
      }
    }
    fence_async_smem();
    bar_sync<3, 128>();
    if (t < 113) bulk_s2g128(g_Wt + t * S_ + 16 * bid, sb + OFF_EXCH + t * 128);
    if (t == 0) PROF(2, 6);
    bulk_done();
    __syncwarp();
    if (lane == 0) mbar_arrive(bars + B_PUBW * 8);
    bar_sync<3, 128>();
    if (k < 113) {
      if (t == 0) PROF(2, 2);
      mbar_wait(bars + B_XCFULL * 8, 0);
      if (t == 0) PROF(2, 3);
      c2 v[16];
      uint2 xe[8], xo[8];
      const uint32_t* xs = g_Xc + (k == 112 ? 0 : k) * 2 * S_ + 2 * t;
#pragma unroll
      for (int jj = 0; jj < 8; jj++) { xe[jj] = ldg64_l2(xs + jj * 256); xo[jj] = ldg64_l2(xs + S_ + jj * 256); }
      const uint32_t se = k == 0 ? 0x4410 : (k == 112 ? 0x4432 : 0x3210), so = k == 0 ? 0x4410 : (k == 112 ? 0x3244 : 0x3210);
#pragma unroll
      for (int jj = 0; jj < 8; jj++) {
        const uint2 e2 = xe[jj], o2 = xo[jj];
#pragma unroll
        for (int h = 0; h < 2; h++) {
          const b2 e = as_b2(__byte_perm(h ? e2.y : e2.x, 0, se)), o = as_b2(__byte_perm(h ? o2.y : o2.x, 0, so));
          const uint32_t s = as_u(__hadd2(e, o)), d = as_u(__hsub2(e, o)) ^ 0x80000000u;
          v[2 * jj + h] = mk(as_b2(__byte_perm(s, d, 0x5410)), as_b2(__byte_perm(s, d, 0x7632)));
        }
      }
      if (t == 0) PROF(2, 12);
      columns(v, sb, t);
      if (t == 0) PROF(2, 14);
      const int pre = (k == 112) ? 1 : 2 * k, pim = (k == 112) ? 1 : 2 * k + 1;
      const uint32_t pr = sb + OFF_EXCH + (t >> 5) * 256 + ((((lane >> 2) ^ pre) & 7) << 4) + (lane & 3) * 4;
      const uint32_t pi = sb + OFF_EXCH + 8192 + (t >> 5) * 256 + ((((lane >> 2) ^ pim) & 7) << 4) + (lane & 3) * 4;
      bar_sync<3, 128>();
#pragma unroll
      for (int jj = 0; jj < 8; jj++) {
        const b2 ar = as_b2(__byte_perm(as_u(v[2 * jj].y), as_u(v[2 * jj + 1].y), 0x5410)), br = as_b2(__byte_perm(as_u(v[2 * jj].y), as_u(v[2 * jj + 1].y), 0x7632));
        const b2 ai = as_b2(__byte_perm(as_u(v[2 * jj].x), as_u(v[2 * jj + 1].x), 0x5410)), bi = as_b2(__byte_perm(as_u(v[2 * jj].x), as_u(v[2 * jj + 1].x), 0x7632));
        sts32(pr + jj * 1024, as_u(__hadd2(ar, br)));
        sts32(pr + jj * 1024 + 128, as_u(__hsub2(ar, br)));
        sts32(pi + jj * 1024 + 128, as_u(__hadd2(ai, bi)));
        sts32(pi + jj * 1024, as_u(__hsub2(ai, bi)));
      }
      fence_async_smem();
      bar_sync<3, 128>();
      if (t == 0) PROF(2, 5);
      const bool im = t >= 64;
      if (k == 0 ? !im : (k != 112 || im == (t & 1))) bulk_s2g128(g_PQ + (t & 63) * 28672 + (im ? pim : pre) * 128, sb + OFF_EXCH + t * 128);
      bulk_done();
    }
    bar_sync<3, 128>();
    if (t == 0) { red_relaxed(&g_cnt[5 * 32]); PROF(2, 7); }
    __syncwarp();
    asm volatile("barrier.cluster.wait.aligned;" ::: "memory");
  } else {
    asm volatile("setmaxnreg.dec.sync.aligned.u32 24;");
    auto wd_tile = [&](int b, uint32_t dst, uint32_t fb) {
#pragma unroll
      for (int hf = 0; hf < 2; hf++) {
        const int js = kh * 4 + (b < 12 ? (b & 3) : (b & 1) * 2 + hf);
        const int row = 224 * js + (b < 12 ? (js & 1) * 32 + (b >> 2) * 64 + hf * 32 : 192 - hf * 192);
        tma2d(dst + hf * 4096, &tm_d, 112 * n, row, fb);
        tma2d(dst + 8192 + hf * 4096, &tm_d, 112 * n + 64, row, fb);
      }
    };
    if (warp == 12) {
      if (elect()) {
        mbar_init(bars + B_XFULL * 8, 1); mbar_init(bars + (B_XFULL + 1) * 8, 1);
        fence_async_smem();
#pragma unroll
        for (int w = 0; w < 2; w++) {
          mbar_expect(bars + (B_XFULL + w) * 8, HALF_XR);
          tma3d(sb + OFF_PQ + w * HALF_XR, &tm_x, 0, m * 128 + (w ^ kh ^ 1) * 64, 0, bars + (B_XFULL + w) * 8);
        }
        PROF(3, 3);
#pragma unroll
        for (int i = 0; i < NSLOT; i++) mbar_init(bars + (B_FULL + i) * 8, 1);
        mbar_init(bars + B_PIN * 8, 1);
        fence_async_smem();
      }
      bar_arrive<0, NTHREADS - 64>();
#pragma unroll 1
      for (int i = 0; i < 6; i++) {
        if (elect()) {
          const uint32_t fb = bars + (B_FULL + i) * 8;
          mbar_expect(fb, SLOT);
          tma2d(sb + i * SLOT, &tm_g, c64, i * 64, fb);
          tma2d(sb + i * SLOT + 8192, &tm_u, c64, i * 64, fb);
          PROF(3, 4 + i);
        }
      }
      if (elect()) {
        prefetch_l2(reinterpret_cast<const unsigned char*>(w_r) + bid * 7200, 7200);
        prefetch_l2(reinterpret_cast<const unsigned char*>(w_i) + bid * 7200, 7200);
        prefetch_tma2d(&tm_g, c64, 384); prefetch_tma2d(&tm_u, c64, 384);
      }
    } else if (warp == 14) {
      if (elect()) {
#pragma unroll
        for (int i = B_EMPTY; i < B_END; i++)
          if (i < B_XFULL || i >= B_XFREE) mbar_init(bars + i * 8, i >= B_PQFULL ? 1 : ((i == B_XFREE || i >= B_PUBW) ? 4 : (i == B_PUBX ? 12 : 8)));
        asm volatile("fence.mbarrier_init.release.cluster;" ::: "memory");
        fence_async_smem();
        mbar_expect(bars + B_RECV * 8, 64 * 112 * 4);
      }
      bar_arrive<0, NTHREADS - 64>();
    }
    const uint32_t epoch = ld_relaxed(&g_ep[bid]);
    if (warp == 13 && lane == 0) { PROFG(4, 0); PROF(4, 1); }
    bar_sync<1, 128>();
    asm volatile("barrier.cluster.arrive.relaxed.aligned;" ::: "memory");
    if (warp == 12) {
      int slot = 6, ph = 1;
      auto wait_slot = [&]() { mbar_wait(bars + (B_EMPTY + slot) * 8, ph ^ (slot == 6)); };
      auto adv = [&]() { if (++slot == NSLOT) { slot = 0; ph ^= 1; } };
      const int c32 = 224 * j + ((j & 1) ? 0 : 192);
#pragma unroll 1
      for (int i = 6; i < 25; i++) {
        wait_slot();
        if (elect()) {
          const uint32_t dst = sb + slot * SLOT, fb = bars + (B_FULL + slot) * 8;
          const bool last = i >= 21;
          const int cc = last ? c32 : c64 + 64 * (i / 7), rr = last ? slot * 128 : slot * 64;
          mbar_expect(fb, SLOT);
          tma2d(dst, last ? &tm_g32 : &tm_g, cc, rr, fb);
          tma2d(dst + 8192, last ? &tm_u32 : &tm_u, cc, rr, fb);
        }
        adv();
      }
      if (lane == 0) PROF(3, 0);
#pragma unroll 1
      for (int i = 3; i < 16; i++) {
        if (lane == 0) PROF(3, 16 + i);
        if (i == 14) mbar_wait(bars + B_PREP * 8, 0);
        wait_slot();
        if (elect()) {
          const uint32_t fb = bars + (B_FULL + slot) * 8;
          mbar_expect(fb, i < 14 ? SLOT : G_IMG / 2);
          if (i < 14) wd_tile(i, sb + slot * SLOT, fb);
          else bulk_g2s(sb + slot * SLOT, g_G + (size_t)(n * 4 + i - 12) * (G_IMG / 2), G_IMG / 2, fb);
        }
        adv();
      }
      if (lane == 0) PROF(3, 2);
    } else if (warp == 13) {
#pragma unroll 1
      for (int u = 0; u < 2; u++) {
        mbar_wait(bars + (u ? B_PUBW : B_PUBX) * 8, 0);
        if (lane == 0) { PROF(4, 8 + u); if (u) red_relaxed(&g_cnt[4 * 32]); else red_release(&g_cnt[(j >> 1) * 32]); PROF(4, 12 + u); }
        __syncwarp();
      }
      mbar_wait(bars + B_PREP * 8, 0);
      mbar_wait(bars + B_LFREE * 8, 0);
      if (elect()) {
        mbar_expect(bars + B_GFULL * 8, G_IMG);
        bulk_g2s(sb + OFF_R + 28672, g_G + (size_t)(n * 2) * G_IMG, G_IMG, bars + B_GFULL * 8);
      }
    } else if (warp == 14) {
      wait_ge(&g_cnt[4 * 32], (epoch + 1) * 128);
      fence_async_global();
      if (elect()) {
        mbar_arrive(bars + B_PREP * 8);
        if (bid < 113) {
          mbar_expect(bars + B_WFULL * 8, 16384);
          bulk_g2s(sb + OFF_WS, g_Wt + bid * S_, 16384, bars + B_WFULL * 8);
        }
        PROF(5, 17);
      }
    } else {
      mbar_wait(bars + B_XFREE * 8, 0);
      if (elect()) {
        mbar_expect(bars + B_PIN * 8, 14400);
        bulk_g2s(sb + OFF_WS, reinterpret_cast<const unsigned char*>(w_r) + bid * 7200, 7200, bars + B_PIN * 8);
        bulk_g2s(sb + OFF_WS + 7200, reinterpret_cast<const unsigned char*>(w_i) + bid * 7200, 7200, bars + B_PIN * 8);
        prefetch_l2(reinterpret_cast<const unsigned char*>(w_gate) + bid * 12544, 12544);
        prefetch_l2(reinterpret_cast<const unsigned char*>(w_up) + bid * 12544, 12544);
        prefetch_l2(reinterpret_cast<const unsigned char*>(w_down) + bid * 12544, 12544);
        PROF(5, 2);
      }
      if (bid < 113) {
        const int sl = (bid == 112) ? 0 : bid;
        wait_ge(&g_cnt[((sl & 1) + 2 * ((sl >> 1) / 28)) * 32], (epoch + 1) * 32);
        if (elect()) { PROF(5, 16); mbar_arrive(bars + B_XCFULL * 8); }
      }
      mbar_wait(bars + (B_XFREE + 1) * 8, 0);
      if (elect()) mbar_expect(bars + B_RFULL * 8, 3 * SLOT);
#pragma unroll 1
      for (int i = 0; i < 3; i++) {
        mbar_wait(bars + (B_FULL + 2 * i + 1) * 8, 1);
        if (elect()) wd_tile(i, sb + OFF_R + i * SLOT, bars + B_RFULL * 8);
      }
      if (lane == 0) PROF(5, 19);
      mbar_wait(bars + B_PREP * 8, 0);
      wait_ge(&g_cnt[5 * 32], (epoch + 1) * 128);
      fence_async_global();
      if (elect()) {
        PROF(5, 18);
        const unsigned char* src = g_PQ + (size_t)(m * 2 + kh) * HALF_XR;
#pragma unroll
        for (int i = 0; i < 4; i++) {
          mbar_expect(bars + (B_PQFULL + i) * 8, i ? 14336 : 14336 + 256);
          bulk_g2s(sb + OFF_PQ + i * 14336, src + i * 14336, 14336, bars + (B_PQFULL + i) * 8);
        }
        bulk_g2s(sb + OFF_G, g_gate + m * 128 + kh * 64, 256, bars + B_PQFULL * 8);
      }
    }
    __syncwarp();
    asm volatile("barrier.cluster.wait.aligned;" ::: "memory");
  }
}

typedef CUresult (*EncodeFn)(CUtensorMap*, CUtensorMapDataType, cuuint32_t, void*, const cuuint64_t*, const cuuint64_t*, const cuuint32_t*,
                             const cuuint32_t*, CUtensorMapInterleave, CUtensorMapSwizzle, CUtensorMapL2promotion, CUtensorMapFloatOOBfill);

void make_map(EncodeFn enc, CUtensorMap* tm, const void* base, int cols, int rows, int bc, int br, CUtensorMapSwizzle sw) {
  cuuint64_t gd[2] = {(cuuint64_t)cols, (cuuint64_t)rows};
  cuuint64_t gs[1] = {(cuuint64_t)cols * 2};
  cuuint32_t bd[2] = {(cuuint32_t)bc, (cuuint32_t)br};
  cuuint32_t es[2] = {1, 1};
  enc(tm, CU_TENSOR_MAP_DATA_TYPE_BFLOAT16, 2, const_cast<void*>(base), gd, gs, bd, es, CU_TENSOR_MAP_INTERLEAVE_NONE, sw,
      CU_TENSOR_MAP_L2_PROMOTION_L2_128B, CU_TENSOR_MAP_FLOAT_OOB_FILL_NONE);
}

}

extern "C" void kernel_launch(void* const* d_in, const int* in_sizes, int n_in, void* d_out, int out_size) {
  (void)in_sizes; (void)n_in; (void)out_size;
  const __nv_bfloat16* x = (const __nv_bfloat16*)d_in[0];
  const __nv_bfloat16* w_r = (const __nv_bfloat16*)d_in[1];
  const __nv_bfloat16* w_i = (const __nv_bfloat16*)d_in[2];
  const __nv_bfloat16* w_gate = (const __nv_bfloat16*)d_in[4];
  const __nv_bfloat16* w_up = (const __nv_bfloat16*)d_in[5];
  const __nv_bfloat16* w_down = (const __nv_bfloat16*)d_in[6];
  const __nv_bfloat16* gate_w = (const __nv_bfloat16*)d_in[7];
  static EncodeFn enc = nullptr;
  static bool ok = false;
  if (!enc) {
    cudaDriverEntryPointQueryResult qr;
    cudaGetDriverEntryPoint("cuTensorMapEncodeTiled", (void**)&enc, cudaEnableDefault, &qr);
    cudaFuncSetAttribute(fused_kernel, cudaFuncAttributeMaxDynamicSharedMemorySize, SMEM_BYTES);
    cudaFuncAttributes fa;
    cudaFuncGetAttributes(&fa, fused_kernel);
    ok = (fa.numRegs == 128);
  }
  if (!ok) return;
  CUtensorMap tx, tg, tu, tg32, tu32, td;
  {
    cuuint64_t gd[3] = {64, (cuuint64_t)S_, 7};
    cuuint64_t gs[2] = {(cuuint64_t)D_ * 2, 128};
    cuuint32_t bd[3] = {64, 64, 7};
    cuuint32_t es[3] = {1, 1, 1};
    enc(&tx, CU_TENSOR_MAP_DATA_TYPE_BFLOAT16, 3, const_cast<__nv_bfloat16*>(x), gd, gs, bd, es, CU_TENSOR_MAP_INTERLEAVE_NONE, CU_TENSOR_MAP_SWIZZLE_128B,
        CU_TENSOR_MAP_L2_PROMOTION_L2_128B, CU_TENSOR_MAP_FLOAT_OOB_FILL_NONE);
  }
  make_map(enc, &tg, w_gate, F_, D_, 64, 64, CU_TENSOR_MAP_SWIZZLE_128B);
  make_map(enc, &tu, w_up, F_, D_, 64, 64, CU_TENSOR_MAP_SWIZZLE_128B);
  make_map(enc, &tg32, w_gate, F_, D_, 32, 128, CU_TENSOR_MAP_SWIZZLE_64B);
  make_map(enc, &tu32, w_up, F_, D_, 32, 128, CU_TENSOR_MAP_SWIZZLE_64B);
  make_map(enc, &td, w_down, D_, F_, 64, 32, CU_TENSOR_MAP_SWIZZLE_128B);
  fused_kernel<<<128, NTHREADS, SMEM_BYTES>>>(tx, tg, tu, tg32, tu32, td, w_r, w_i, w_gate, w_up, w_down, gate_w, (__nv_bfloat16*)d_out);
}
```

```cpp
#include <cuda_runtime.h>
#include <cuda_bf16.h>
#include <cuda.h>
#include <stdint.h>

namespace {

constexpr int S_ = 2048, D_ = 448, F_ = 1792;
constexpr int NTHREADS = 512;
constexpr int SLOT = 16384, NSLOT = 7;
constexpr int HALF_XR = 57344;
constexpr int OFF_PQ = NSLOT * SLOT;
constexpr int OFF_R = OFF_PQ + HALF_XR;
constexpr int OFF_EXCH = OFF_PQ;
constexpr int OFF_WS = OFF_EXCH + 18432;
constexpr int OFF_TW = OFF_WS + 16384;
constexpr int OFF_MISC = OFF_R + HALF_XR;
constexpr int OFF_G = OFF_MISC;
constexpr int OFF_BAR = OFF_MISC + 512;
constexpr int SMEM_BYTES = OFF_BAR + 512;
constexpr int B_FULL = 0, B_EMPTY = 7, B_XFULL = 14  ;
constexpr int B_XFREE = 16  , B_PUBX = 18, B_RFREE = 19, B_LFREE = 20;
constexpr int B_PUBW = 21;
constexpr int B_PQFULL = 22  , B_RECV = 26, B_WFULL = 27, B_XCFULL = 28, B_PREP = 29, B_RFULL = 30, B_GFULL = 31, B_XDONE = 32, B_END = 33, B_PIN = 33;

constexpr int G_IMG = 224 * 56 * 2;

__device__ __align__(1024) unsigned char g_H[32 * 56 * 4096];
constexpr int XP = 28672;
__device__ __align__(1024) unsigned char g_X[448 * XP];
__device__ __align__(1024) unsigned char g_G[8 * G_IMG];
__device__ __align__(1024) float g_gate[S_];
__device__ __align__(128) unsigned int g_ep[128];
__device__ __align__(128) unsigned int g_cnt[8 * 32];

#define PROF(role, idx) do {} while (0)
#define PROFG(role, idx) do {} while (0)

__device__ __forceinline__ uint32_t s2u(const void* p) { return (uint32_t)__cvta_generic_to_shared(p); }
__device__ __forceinline__ void mbar_init(uint32_t b, int c) { asm volatile("mbarrier.init.shared::cta.b64 [%0], %1;" :: "r"(b), "r"(c) : "memory"); }
__device__ __forceinline__ void mbar_expect(uint32_t b, int bytes) { asm volatile("mbarrier.arrive.expect_tx.shared::cta.b64 _, [%0], %1;" :: "r"(b), "r"(bytes) : "memory"); }
__device__ __forceinline__ void mbar_arrive(uint32_t b) { asm volatile("mbarrier.arrive.shared::cta.b64 _, [%0];" :: "r"(b) : "memory"); }
__device__ __forceinline__ void mbar_wait(uint32_t b, int ph) {
  asm volatile("{\n.reg .pred p;\n.reg .u32 c;\nmov.u32 c, 0;\nL_WAIT:\nmbarrier.try_wait.parity.shared::cta.b64 p, [%0], %1;\n@p bra.uni L_DONE;\n"
               "add.u32 c, c, 1;\nsetp.lt.u32 p, c, 4194304;\n@p bra.uni L_WAIT;\ntrap;\nL_DONE:\n}" :: "r"(b), "r"(ph) : "memory");
}
__device__ __forceinline__ void mbar_wait_cluster(uint32_t b, int ph) {
  asm volatile("{\n.reg .pred p;\n.reg .u32 c;\nmov.u32 c, 0;\nL_WAIT:\nmbarrier.try_wait.parity.acquire.cluster.shared::cta.b64 p, [%0], %1;\n@p bra.uni L_DONE;\n"
               "add.u32 c, c, 1;\nsetp.lt.u32 p, c, 4194304;\n@p bra.uni L_WAIT;\ntrap;\nL_DONE:\n}" :: "r"(b), "r"(ph) : "memory");
}
__device__ __forceinline__ uint32_t ld_acquire(const unsigned int* p) { uint32_t v; asm volatile("ld.acquire.gpu.global.u32 %0, [%1];" : "=r"(v) : "l"(p) : "memory"); return v; }
__device__ __forceinline__ uint32_t ld_relaxed(const unsigned int* p) { uint32_t v; asm volatile("ld.relaxed.gpu.global.u32 %0, [%1];" : "=r"(v) : "l"(p) : "memory"); return v; }
__device__ __forceinline__ void wait_ge(const unsigned int* p, uint32_t target) {
#pragma unroll 1
  for (int i = 0; i < (1 << 22); i++) { if ((int)(ld_acquire(p) - target) >= 0) return; }
  __trap();
}
__device__ __forceinline__ void red_relaxed(unsigned int* p) { asm volatile("red.relaxed.gpu.global.add.u32 [%0], 1;" :: "l"(p) : "memory"); }
__device__ __forceinline__ bool elect() { uint32_t p; asm volatile("{\n.reg .pred p;\nelect.sync _|p, 0xffffffff;\nselp.u32 %0, 1, 0, p;\n}" : "=r"(p)); return p; }
__device__ __forceinline__ void fence_async_smem() { asm volatile("fence.proxy.async.shared::cta;" ::: "memory"); }
__device__ __forceinline__ void fence_async_global() { asm volatile("fence.proxy.async.global;" ::: "memory"); }
template <int ID, int N> __device__ __forceinline__ void bar_sync() { asm volatile("bar.sync %0, %1;" :: "n"(ID), "n"(N) : "memory"); }
template <int ID, int N> __device__ __forceinline__ void bar_arrive() { asm volatile("bar.arrive %0, %1;" :: "n"(ID), "n"(N) : "memory"); }
__device__ __forceinline__ void tma2d(uint32_t dst, const CUtensorMap* tm, int c0, int c1, uint32_t bar) {
  asm volatile("cp.async.bulk.tensor.2d.shared::cluster.global.mbarrier::complete_tx::bytes [%0], [%1, {%3, %4}], [%2];"
               :: "r"(dst), "l"(tm), "r"(bar), "r"(c0), "r"(c1) : "memory");
}
__device__ __forceinline__ void tma3d(uint32_t dst, const CUtensorMap* tm, int c0, int c1, int c2, uint32_t bar) {
  asm volatile("cp.async.bulk.tensor.3d.shared::cluster.global.mbarrier::complete_tx::bytes [%0], [%1, {%3, %4, %5}], [%2];"
               :: "r"(dst), "l"(tm), "r"(bar), "r"(c0), "r"(c1), "r"(c2) : "memory");
}
__device__ __forceinline__ void bulk_g2s(uint32_t dst, const void* src, int bytes, uint32_t bar) {
  asm volatile("cp.async.bulk.shared::cluster.global.mbarrier::complete_tx::bytes [%0], [%1], %2, [%3];"
               :: "r"(dst), "l"(src), "r"(bytes), "r"(bar) : "memory");
}
__device__ __forceinline__ void tma_store(const CUtensorMap* tm, int c0, int c1, uint32_t src) {
  asm volatile("cp.async.bulk.tensor.2d.global.shared::cta.bulk_group [%0, {%1, %2}], [%3];" :: "l"(tm), "r"(c0), "r"(c1), "r"(src) : "memory");
}
__device__ __forceinline__ void bulk_done() { asm volatile("cp.async.bulk.commit_group;\ncp.async.bulk.wait_group 0;\nfence.proxy.async.global;" ::: "memory"); }
__device__ __forceinline__ void sts32(uint32_t a, uint32_t x) { asm volatile("st.shared.b32 [%0], %1;" :: "r"(a), "r"(x) : "memory"); }
__device__ __forceinline__ void prefetch_l2(const void* src, int bytes) {
  asm volatile("cp.async.bulk.prefetch.L2.global [%0], %1;" :: "l"(src), "r"(bytes) : "memory");
}
__device__ __forceinline__ void prefetch_tma2d(const CUtensorMap* tm, int c0, int c1) {
  asm volatile("cp.async.bulk.prefetch.tensor.2d.L2.global [%0, {%1, %2}];" :: "l"(tm), "r"(c0), "r"(c1) : "memory");
}
__device__ __forceinline__ uint64_t mkdesc(uint32_t addr, uint32_t lbo, uint32_t sbo, uint32_t mode) {
  return (uint64_t)((addr & 0x3FFFF) >> 4) | ((uint64_t)(lbo >> 4) << 16) | ((uint64_t)(sbo >> 4) << 32) | ((uint64_t)mode << 62);
}
__device__ __forceinline__ void wg_fence() { asm volatile("wgmma.fence.sync.aligned;" ::: "memory"); }
__device__ __forceinline__ void wg_commit() { asm volatile("wgmma.commit_group.sync.aligned;" ::: "memory"); }
template <int N> __device__ __forceinline__ void wg_wait() { asm volatile("wgmma.wait_group.sync.aligned %0;" :: "n"(N) : "memory"); }
template <int N> __device__ __forceinline__ void keep(float (&d)[N]) {
#pragma unroll
  for (int i = 0; i < N; i++) asm volatile("" : "+f"(d[i]) :: "memory");
}
__device__ __forceinline__ uint32_t pack_bf16(float lo, float hi) { uint32_t r; asm("cvt.rn.bf16x2.f32 %0, %1, %2;" : "=r"(r) : "f"(hi), "f"(lo)); return r; }
__device__ __forceinline__ float bf16_round(float v) { return __bfloat162float(__float2bfloat16_rn(v)); }
__device__ __forceinline__ void sts128(uint32_t a, uint32_t x, uint32_t y, uint32_t z, uint32_t w) { asm volatile("st.shared.v4.b32 [%0], {%1,%2,%3,%4};" :: "r"(a), "r"(x), "r"(y), "r"(z), "r"(w) : "memory"); }
__device__ __forceinline__ float4 lds128f(uint32_t a) { float4 v; asm volatile("ld.shared.v4.f32 {%0,%1,%2,%3}, [%4];" : "=f"(v.x), "=f"(v.y), "=f"(v.z), "=f"(v.w) : "r"(a) : "memory"); return v; }

__device__ __forceinline__ uint2 lds64(uint32_t a) { uint2 v; asm volatile("ld.shared.v2.b32 {%0,%1}, [%2];" : "=r"(v.x), "=r"(v.y) : "r"(a) : "memory"); return v; }
__device__ __forceinline__ float bf_lo(uint32_t w) { return __uint_as_float(w << 16); }
__device__ __forceinline__ float bf_hi(uint32_t w) { return __uint_as_float(w & 0xffff0000u); }
__device__ __forceinline__ uint32_t opaque(uint32_t v) { asm volatile("" : "+r"(v)); return v; }
__device__ __forceinline__ uint4 ldg128(const void* p) { uint4 v; asm volatile("ld.global.nc.v4.b32 {%0,%1,%2,%3}, [%4];" : "=r"(v.x), "=r"(v.y), "=r"(v.z), "=r"(v.w) : "l"(p)); return v; }
__device__ __forceinline__ void stg128(void* p, uint32_t x, uint32_t y, uint32_t z, uint32_t w) { asm volatile("st.global.v4.b32 [%0], {%1,%2,%3,%4};" :: "l"(p), "r"(x), "r"(y), "r"(z), "r"(w) : "memory"); }
__device__ __forceinline__ void stg128_l2(void* p, uint32_t x, uint32_t y, uint32_t z, uint32_t w) { asm volatile("st.relaxed.gpu.global.v4.b32 [%0], {%1,%2,%3,%4};" :: "l"(p), "r"(x), "r"(y), "r"(z), "r"(w) : "memory"); }
__device__ __forceinline__ uint2 ldg64_l2(const void* p) { uint2 v; asm volatile("ld.relaxed.gpu.global.v2.b32 {%0,%1}, [%2];" : "=r"(v.x), "=r"(v.y) : "l"(p) : "memory"); return v; }
__device__ __forceinline__ void ldg128_l2(uint32_t (&v)[4], const void* p) { asm volatile("ld.relaxed.gpu.global.v4.b32 {%0,%1,%2,%3}, [%4];" : "=r"(v[0]), "=r"(v[1]), "=r"(v[2]), "=r"(v[3]) : "l"(p) : "memory"); }
__device__ __forceinline__ uint4 lds128(uint32_t a) { uint4 v; asm volatile("ld.shared.v4.b32 {%0,%1,%2,%3}, [%4];" : "=r"(v.x), "=r"(v.y), "=r"(v.z), "=r"(v.w) : "r"(a) : "memory"); return v; }
__device__ __forceinline__ uint32_t lds16(uint32_t a) { uint32_t v; asm volatile("ld.shared.u16 %0, [%1];" : "=r"(v) : "r"(a) : "memory"); return v; }
__device__ __forceinline__ void sts64(uint32_t a, uint32_t x, uint32_t y) { asm volatile("st.shared.v2.b32 [%0], {%1,%2};" :: "r"(a), "r"(x), "r"(y) : "memory"); }
template <int TB> __device__ __forceinline__ void wgmma_rs_128(float (&d)[64], const uint32_t (&a)[4], uint64_t db, int sc) {
  asm volatile("{\n.reg .pred p;\nsetp.ne.b32 p, %69, 0;\n"
    "wgmma.mma_async.sync.aligned.m64n128k16.f32.bf16.bf16 {%0, %1, %2, %3, %4, %5, %6, %7, %8, %9, %10, %11, %12, %13, %14, %15, %16, %17, %18, %19, %20, %21, %22, %23, %24, %25, %26, %27, %28, %29, %30, %31, %32, %33, %34, %35, %36, %37, %38, %39, %40, %41, %42, %43, %44, %45, %46, %47, %48, %49, %50, %51, %52, %53, %54, %55, %56, %57, %58, %59, %60, %61, %62, %63}, {%64, %65, %66, %67}, %68, p, 1, 1, %70;\n}\n"
    : "+f"(d[0]), "+f"(d[1]), "+f"(d[2]), "+f"(d[3]), "+f"(d[4]), "+f"(d[5]), "+f"(d[6]), "+f"(d[7]), "+f"(d[8]), "+f"(d[9]), "+f"(d[10]), "+f"(d[11]), "+f"(d[12]), "+f"(d[13]), "+f"(d[14]), "+f"(d[15]), "+f"(d[16]), "+f"(d[17]), "+f"(d[18]), "+f"(d[19]), "+f"(d[20]), "+f"(d[21]), "+f"(d[22]), "+f"(d[23]), "+f"(d[24]), "+f"(d[25]), "+f"(d[26]), "+f"(d[27]), "+f"(d[28]), "+f"(d[29]), "+f"(d[30]), "+f"(d[31]), "+f"(d[32]), "+f"(d[33]), "+f"(d[34]), "+f"(d[35]), "+f"(d[36]), "+f"(d[37]), "+f"(d[38]), "+f"(d[39]), "+f"(d[40]), "+f"(d[41]), "+f"(d[42]), "+f"(d[43]), "+f"(d[44]), "+f"(d[45]), "+f"(d[46]), "+f"(d[47]), "+f"(d[48]), "+f"(d[49]), "+f"(d[50]), "+f"(d[51]), "+f"(d[52]), "+f"(d[53]), "+f"(d[54]), "+f"(d[55]), "+f"(d[56]), "+f"(d[57]), "+f"(d[58]), "+f"(d[59]), "+f"(d[60]), "+f"(d[61]), "+f"(d[62]), "+f"(d[63])
    : "r"(a[0]), "r"(a[1]), "r"(a[2]), "r"(a[3]), "l"(db), "r"(sc), "n"(TB));
}
template <int TB> __device__ __forceinline__ void wgmma_rs_64(float (&d)[32], const uint32_t (&a)[4], uint64_t db, int sc) {
  asm volatile("{\n.reg .pred p;\nsetp.ne.b32 p, %37, 0;\n"
    "wgmma.mma_async.sync.aligned.m64n64k16.f32.bf16.bf16 {%0, %1, %2, %3, %4, %5, %6, %7, %8, %9, %10, %11, %12, %13, %14, %15, %16, %17, %18, %19, %20, %21, %22, %23, %24, %25, %26, %27, %28, %29, %30, %31}, {%32, %33, %34, %35}, %36, p, 1, 1, %38;\n}\n"
    : "+f"(d[0]), "+f"(d[1]), "+f"(d[2]), "+f"(d[3]), "+f"(d[4]), "+f"(d[5]), "+f"(d[6]), "+f"(d[7]), "+f"(d[8]), "+f"(d[9]), "+f"(d[10]), "+f"(d[11]), "+f"(d[12]), "+f"(d[13]), "+f"(d[14]), "+f"(d[15]), "+f"(d[16]), "+f"(d[17]), "+f"(d[18]), "+f"(d[19]), "+f"(d[20]), "+f"(d[21]), "+f"(d[22]), "+f"(d[23]), "+f"(d[24]), "+f"(d[25]), "+f"(d[26]), "+f"(d[27]), "+f"(d[28]), "+f"(d[29]), "+f"(d[30]), "+f"(d[31])
    : "r"(a[0]), "r"(a[1]), "r"(a[2]), "r"(a[3]), "l"(db), "r"(sc), "n"(TB));
}
template <int TB> __device__ __forceinline__ void wgmma_rs_56(float (&d)[28], const uint32_t (&a)[4], uint64_t db, int sc) {
  asm volatile("{\n.reg .pred p;\nsetp.ne.b32 p, %33, 0;\n"
    "wgmma.mma_async.sync.aligned.m64n56k16.f32.bf16.bf16 {%0, %1, %2, %3, %4, %5, %6, %7, %8, %9, %10, %11, %12, %13, %14, %15, %16, %17, %18, %19, %20, %21, %22, %23, %24, %25, %26, %27}, {%28, %29, %30, %31}, %32, p, 1, 1, %34;\n}\n"
    : "+f"(d[0]), "+f"(d[1]), "+f"(d[2]), "+f"(d[3]), "+f"(d[4]), "+f"(d[5]), "+f"(d[6]), "+f"(d[7]), "+f"(d[8]), "+f"(d[9]), "+f"(d[10]), "+f"(d[11]), "+f"(d[12]), "+f"(d[13]), "+f"(d[14]), "+f"(d[15]), "+f"(d[16]), "+f"(d[17]), "+f"(d[18]), "+f"(d[19]), "+f"(d[20]), "+f"(d[21]), "+f"(d[22]), "+f"(d[23]), "+f"(d[24]), "+f"(d[25]), "+f"(d[26]), "+f"(d[27])
    : "r"(a[0]), "r"(a[1]), "r"(a[2]), "r"(a[3]), "l"(db), "r"(sc), "n"(TB));
}
template <int TB> __device__ __forceinline__ void wgmma_rs_112(float (&d)[56], const uint32_t (&a)[4], uint64_t db, int sc) {
  asm volatile("{\n.reg .pred p;\nsetp.ne.b32 p, %61, 0;\n"
    "wgmma.mma_async.sync.aligned.m64n112k16.f32.bf16.bf16 {%0, %1, %2, %3, %4, %5, %6, %7, %8, %9, %10, %11, %12, %13, %14, %15, %16, %17, %18, %19, %20, %21, %22, %23, %24, %25, %26, %27, %28, %29, %30, %31, %32, %33, %34, %35, %36, %37, %38, %39, %40, %41, %42, %43, %44, %45, %46, %47, %48, %49, %50, %51, %52, %53, %54, %55}, {%56, %57, %58, %59}, %60, p, 1, 1, %62;\n}\n"
    : "+f"(d[0]), "+f"(d[1]), "+f"(d[2]), "+f"(d[3]), "+f"(d[4]), "+f"(d[5]), "+f"(d[6]), "+f"(d[7]), "+f"(d[8]), "+f"(d[9]), "+f"(d[10]), "+f"(d[11]), "+f"(d[12]), "+f"(d[13]), "+f"(d[14]), "+f"(d[15]), "+f"(d[16]), "+f"(d[17]), "+f"(d[18]), "+f"(d[19]), "+f"(d[20]), "+f"(d[21]), "+f"(d[22]), "+f"(d[23]), "+f"(d[24]), "+f"(d[25]), "+f"(d[26]), "+f"(d[27]), "+f"(d[28]), "+f"(d[29]), "+f"(d[30]), "+f"(d[31]), "+f"(d[32]), "+f"(d[33]), "+f"(d[34]), "+f"(d[35]), "+f"(d[36]), "+f"(d[37]), "+f"(d[38]), "+f"(d[39]), "+f"(d[40]), "+f"(d[41]), "+f"(d[42]), "+f"(d[43]), "+f"(d[44]), "+f"(d[45]), "+f"(d[46]), "+f"(d[47]), "+f"(d[48]), "+f"(d[49]), "+f"(d[50]), "+f"(d[51]), "+f"(d[52]), "+f"(d[53]), "+f"(d[54]), "+f"(d[55])
    : "r"(a[0]), "r"(a[1]), "r"(a[2]), "r"(a[3]), "l"(db), "r"(sc), "n"(TB));
}
template <int TA, int TB> __device__ __forceinline__ void wgmma_ss_56(float (&d)[28], uint64_t da, uint64_t db, int sc) {
  asm volatile("{\n.reg .pred p;\nsetp.ne.b32 p, %30, 0;\n"
    "wgmma.mma_async.sync.aligned.m64n56k16.f32.bf16.bf16 {%0, %1, %2, %3, %4, %5, %6, %7, %8, %9, %10, %11, %12, %13, %14, %15, %16, %17, %18, %19, %20, %21, %22, %23, %24, %25, %26, %27}, %28, %29, p, 1, 1, %31, %32;\n}\n"
    : "+f"(d[0]), "+f"(d[1]), "+f"(d[2]), "+f"(d[3]), "+f"(d[4]), "+f"(d[5]), "+f"(d[6]), "+f"(d[7]), "+f"(d[8]), "+f"(d[9]), "+f"(d[10]), "+f"(d[11]), "+f"(d[12]), "+f"(d[13]), "+f"(d[14]), "+f"(d[15]), "+f"(d[16]), "+f"(d[17]), "+f"(d[18]), "+f"(d[19]), "+f"(d[20]), "+f"(d[21]), "+f"(d[22]), "+f"(d[23]), "+f"(d[24]), "+f"(d[25]), "+f"(d[26]), "+f"(d[27])
    : "l"(da), "l"(db), "r"(sc), "n"(TA), "n"(TB));
}

__device__ __forceinline__ uint32_t cis(float a) { return pack_bf16(__cosf(a), __sinf(a)); }

typedef __nv_bfloat162 b2;
struct c2 { b2 x, y; };
__device__ __forceinline__ b2 as_b2(uint32_t u) { return *reinterpret_cast<b2*>(&u); }
__device__ __forceinline__ uint32_t as_u(b2 v) { return *reinterpret_cast<uint32_t*>(&v); }
__device__ __forceinline__ c2 mk(b2 x, b2 y) { c2 r; r.x = x; r.y = y; return r; }
__device__ __forceinline__ c2 cmul(c2 a, b2 wr, b2 wi) { return mk(__hfma2(a.x, wr, __hneg2(__hmul2(a.y, wi))), __hfma2(a.x, wi, __hmul2(a.y, wr))); }
__device__ __forceinline__ void fft4(c2& a0, c2& a1, c2& a2, c2& a3) {
  c2 t0 = mk(__hadd2(a0.x, a2.x), __hadd2(a0.y, a2.y)), t1 = mk(__hsub2(a0.x, a2.x), __hsub2(a0.y, a2.y));
  c2 t2 = mk(__hadd2(a1.x, a3.x), __hadd2(a1.y, a3.y)), t3 = mk(__hsub2(a1.x, a3.x), __hsub2(a1.y, a3.y));
  a0 = mk(__hadd2(t0.x, t2.x), __hadd2(t0.y, t2.y)); a2 = mk(__hsub2(t0.x, t2.x), __hsub2(t0.y, t2.y));
  a1 = mk(__hadd2(t1.x, t3.y), __hsub2(t1.y, t3.x)); a3 = mk(__hsub2(t1.x, t3.y), __hadd2(t1.y, t3.x));
}
__device__ __forceinline__ void fft4_s2(c2& a0, c2& a1, c2& a2, c2& a3, b2 r) {
  const b2 nr = __hneg2(r);
  c2 t0 = mk(__hfma2(a2.x, r, a0.x), __hfma2(a2.y, r, a0.y)), t1 = mk(__hfma2(a2.x, nr, a0.x), __hfma2(a2.y, nr, a0.y));
  c2 t2 = mk(__hadd2(a1.x, a3.x), __hadd2(a1.y, a3.y)), t3 = mk(__hsub2(a1.x, a3.x), __hsub2(a1.y, a3.y));
  a0 = mk(__hadd2(t0.x, t2.x), __hadd2(t0.y, t2.y)); a2 = mk(__hsub2(t0.x, t2.x), __hsub2(t0.y, t2.y));
  a1 = mk(__hadd2(t1.x, t3.y), __hsub2(t1.y, t3.x)); a3 = mk(__hsub2(t1.x, t3.y), __hadd2(t1.y, t3.x));
}
__device__ __forceinline__ void fft4_s13(c2& a0, c2& a1, c2& a2, c2& a3, b2 r) {
  const b2 nr = __hneg2(r);
  c2 t0 = mk(__hadd2(a0.x, a2.x), __hadd2(a0.y, a2.y)), t1 = mk(__hsub2(a0.x, a2.x), __hsub2(a0.y, a2.y));
  c2 t2 = mk(__hadd2(a1.x, a3.x), __hadd2(a1.y, a3.y)), t3 = mk(__hsub2(a1.x, a3.x), __hsub2(a1.y, a3.y));
  a0 = mk(__hfma2(t2.x, r, t0.x), __hfma2(t2.y, r, t0.y)); a2 = mk(__hfma2(t2.x, nr, t0.x), __hfma2(t2.y, nr, t0.y));
  a1 = mk(__hfma2(t3.y, r, t1.x), __hfma2(t3.x, nr, t1.y)); a3 = mk(__hfma2(t3.y, nr, t1.x), __hfma2(t3.x, r, t1.y));
}
__device__ __forceinline__ c2 rot1(c2 a) { return mk(__hadd2(a.x, a.y), __hsub2(a.y, a.x)); }
__device__ __forceinline__ c2 rot3(c2 a) { return mk(__hsub2(a.y, a.x), __hneg2(__hadd2(a.x, a.y))); }
__device__ __forceinline__ c2 mul_mi(c2 a) { return mk(a.y, __hneg2(a.x)); }
template <int O> __device__ __forceinline__ void fft8(c2 (&v)[16]) {
  const b2 r = as_b2(0x3F353F35u), nr = as_b2(0xBF35BF35u);
  fft4(v[O], v[O + 4], v[O + 8], v[O + 12]);
  fft4(v[O + 2], v[O + 6], v[O + 10], v[O + 14]);
  const c2 o0 = v[O + 2], o1 = rot1(v[O + 6]), o2 = v[O + 10], o3 = rot1(v[O + 14]);
  const c2 e0 = v[O], e1 = v[O + 4], e2 = v[O + 8], e3 = v[O + 12];
  v[O] = mk(__hadd2(e0.x, o0.x), __hadd2(e0.y, o0.y));              v[O + 8] = mk(__hsub2(e0.x, o0.x), __hsub2(e0.y, o0.y));
  v[O + 2] = mk(__hfma2(o1.x, r, e1.x), __hfma2(o1.y, r, e1.y));    v[O + 10] = mk(__hfma2(o1.x, nr, e1.x), __hfma2(o1.y, nr, e1.y));
  v[O + 4] = mk(__hadd2(e2.x, o2.y), __hsub2(e2.y, o2.x));          v[O + 12] = mk(__hsub2(e2.x, o2.y), __hadd2(e2.y, o2.x));
  v[O + 6] = mk(__hfma2(o3.y, r, e3.x), __hfma2(o3.x, nr, e3.y));   v[O + 14] = mk(__hfma2(o3.y, nr, e3.x), __hfma2(o3.x, r, e3.y));
}
__device__ __forceinline__ void fft16(c2 (&v)[16]) {
  const b2 r = as_b2(0x3F353F35u), c1 = as_b2(0x3F6D3F6Du), s1 = as_b2(0x3EC43EC4u), nc1 = as_b2(0xBF6DBF6Du), ns1 = as_b2(0xBEC4BEC4u);
#pragma unroll
  for (int a = 0; a < 4; a++) fft4(v[a], v[a + 4], v[a + 8], v[a + 12]);
  v[5] = cmul(v[5], c1, ns1); v[6] = rot1(v[6]); v[7] = cmul(v[7], s1, nc1);
  v[9] = rot1(v[9]); v[10] = mul_mi(v[10]); v[11] = rot3(v[11]);
  v[13] = cmul(v[13], s1, nc1); v[14] = rot3(v[14]); v[15] = cmul(v[15], nc1, s1);
  fft4(v[0], v[1], v[2], v[3]); fft4_s2(v[4], v[5], v[6], v[7], r); fft4_s13(v[8], v[9], v[10], v[11], r); fft4_s2(v[12], v[13], v[14], v[15], r);
  c2 t;
  t = v[1]; v[1] = v[4]; v[4] = t;  t = v[2]; v[2] = v[8]; v[8] = t;  t = v[3]; v[3] = v[12]; v[12] = t;
  t = v[6]; v[6] = v[9]; v[9] = t;  t = v[7]; v[7] = v[13]; v[13] = t; t = v[11]; v[11] = v[14]; v[14] = t;
}

__device__ __forceinline__ void columns(c2 (&v)[16], uint32_t sb, int t) {
  const int l16 = t & 15;
  const uint32_t row = sb + OFF_EXCH + (t >> 4) * 2304;
  const uint32_t pos = sb + OFF_EXCH + (t >> 3) * 144 + (t & 7) * 16;
#pragma unroll 1
  for (int ps = 0; ps < 6; ps++) {
    if (ps == 0 || ps == 5) { fft8<0>(v); fft8<1>(v); } else fft16(v);
    if (ps == 5) break;
    if (ps == 2) {
      const uint32_t ws = sb + OFF_WS + (l16 >> 1) * 128 + ((((t >> 4) + (l16 >> 1)) & 7) * 2 + (l16 & 1)) * 8;
      mbar_wait(sb + OFF_BAR + B_WFULL * 8, 0);
#pragma unroll
      for (int q = 0; q < 16; q++) {
        const uint2 w = lds64(ws + q * 1024);
        const c2 z = cmul(v[q], as_b2(w.x), as_b2(w.y));
        v[q] = mk(z.y, z.x);
      }
      continue;
    }
    {
      const bool full = ps == 0 || ps == 4;
      const uint32_t tw = sb + OFF_TW + (full ? ps * 2048 + t * 16 : 16384 + l16 * 16);
      const uint32_t st = full ? 2048 : 256;
#pragma unroll
      for (int i = 0; i < 4; i++) {
        const uint4 w4 = lds128(tw + i * st);
        const uint32_t w[4] = {w4.x, w4.y, w4.z, w4.w};
#pragma unroll
        for (int e = 0; e < 4; e++) v[4 * i + e] = cmul(v[4 * i + e], __low2bfloat162(as_b2(w[e])), __high2bfloat162(as_b2(w[e])));
      }
    }
    if (ps == 0) {
#pragma unroll
      for (int q = 0; q < 8; q++) sts128(pos + q * 2304, as_u(v[2 * q].x), as_u(v[2 * q].y), as_u(v[2 * q + 1].x), as_u(v[2 * q + 1].y));
      bar_sync<3, 128>();
#pragma unroll
      for (int q = 0; q < 16; q++) { const uint2 a = lds64(row + q * 144 + l16 * 8); v[q] = mk(as_b2(a.x), as_b2(a.y)); }
    } else {
      __syncwarp();
#pragma unroll
      for (int q = 0; q < 16; q++) sts64(row + q * 144 + l16 * 8, as_u(v[q].x), as_u(v[q].y));
      if (ps == 4) bar_sync<3, 128>(); else __syncwarp();
      const uint32_t src = ps == 4 ? pos : row + l16 * 144, st = ps == 4 ? 2304 : 16;
#pragma unroll
      for (int q = 0; q < 8; q++) { const uint4 a = lds128(src + q * st); v[2 * q] = mk(as_b2(a.x), as_b2(a.y)); v[2 * q + 1] = mk(as_b2(a.z), as_b2(a.w)); }
    }
  }
}

template <int NH> __device__ __forceinline__ void h_epilogue(float (&acc)[NH * 8], unsigned char* gdst, uint32_t tag) {
#pragma unroll
  for (int c = 0; c < NH / 2; c++) {
    uint32_t pk[4];
#pragma unroll
    for (int i = 0; i < 4; i++) {
      float hv[2];
#pragma unroll
      for (int e = 0; e < 2; e++) {
        float hg = 0.5f * acc[c * 8 + i * 2 + e], up = acc[NH * 4 + c * 8 + i * 2 + e];
        float th; asm("tanh.approx.f32 %0, %1;" : "=f"(th) : "f"(hg));
        hv[e] = fmaf(hg, th, hg) * up;
      }
      pk[i] = pack_bf16(hv[0], hv[1]);
    }
    stg128_l2(gdst + c * 4096, (pk[0] & ~1u) | tag, pk[1], pk[2], pk[3]);
  }
}

__device__ __forceinline__ void frag_ready(uint32_t (&a)[4], uint32_t (&b)[4], uint32_t (&c)[4], uint32_t (&d)[4], const unsigned char* p, uint32_t tag) {
  asm volatile("{\n.reg .pred p;\n.reg .u32 c, m, q;\nmov.u32 c, 0;\nL_TRY:\n"
               "lop3.b32 m, %0, %4, %17, 0x7E;\nlop3.b32 q, %8, %12, %17, 0x7E;\nlop3.b32 m, m, q, 1, 0xA8;\nsetp.ne.u32 p, m, 0;\n"
               "vote.sync.any.pred p, p, 0xffffffff;\n@!p bra.uni L_OK;\n"
               "ld.relaxed.gpu.global.v4.b32 {%0,%1,%2,%3}, [%16];\nld.relaxed.gpu.global.v4.b32 {%4,%5,%6,%7}, [%16+4096];\n"
               "ld.relaxed.gpu.global.v4.b32 {%8,%9,%10,%11}, [%16+8192];\nld.relaxed.gpu.global.v4.b32 {%12,%13,%14,%15}, [%16+12288];\n"
               "add.u32 c, c, 1;\nsetp.lt.u32 p, c, 262144;\n@p bra.uni L_TRY;\ntrap;\nL_OK:\n}"
               : "+r"(a[0]), "+r"(a[1]), "+r"(a[2]), "+r"(a[3]), "+r"(b[0]), "+r"(b[1]), "+r"(b[2]), "+r"(b[3]),
                 "+r"(c[0]), "+r"(c[1]), "+r"(c[2]), "+r"(c[3]), "+r"(d[0]), "+r"(d[1]), "+r"(d[2]), "+r"(d[3])
               : "l"(p), "r"(tag) : "memory");
}

#define MAP 0
#define LEAD2 0
#define LEAD1 3

__global__ void __cluster_dims__(2, 1, 1) __launch_bounds__(NTHREADS, 1)
fused_kernel(const __grid_constant__ CUtensorMap tm_x, const __grid_constant__ CUtensorMap tm_g, const __grid_constant__ CUtensorMap tm_u,
             const __grid_constant__ CUtensorMap tm_g32, const __grid_constant__ CUtensorMap tm_u32, const __grid_constant__ CUtensorMap tm_d,
             const __grid_constant__ CUtensorMap tm_s,
             const __nv_bfloat16* __restrict__ w_r, const __nv_bfloat16* __restrict__ w_i,
             const __nv_bfloat16* __restrict__ w_gate, const __nv_bfloat16* __restrict__ w_up,
             const __nv_bfloat16* __restrict__ w_down, const __nv_bfloat16* __restrict__ gate_w, __nv_bfloat16* __restrict__ out) {
  extern __shared__ __align__(1024) unsigned char smem[];
  const uint32_t sb = s2u(smem);
  const uint32_t bars = sb + OFF_BAR;
  const int tid = threadIdx.x, warp = __shfl_sync(0xffffffffu, tid >> 5, 0), lane = tid & 31;
  const int cl = blockIdx.x >> 1, kh = blockIdx.x & 1;
  const int n0 = cl < 4 ? cl : (cl < 36 ? (cl - 4) >> 3 : (cl - 36) / 7);
  const int m0 = cl < 4 ? 15 : (cl < 36 ? (cl - 4) & 7 : cl - 28 - 7 * n0);
  const int n = MAP == 0 ? n0 : (MAP == 1 ? (m0 & 3) : ((n0 & 1) | ((m0 & 1) << 1)));
  const int m = MAP == 0 ? m0 : (MAP == 1 ? ((m0 & 12) | n0) : ((m0 & 14) | (n0 >> 1)));
  const int j = kh * 4 + n, bid = m * 8 + n * 2 + kh;

  const int c64 = 224 * j + (j & 1) * 32;
  if (warp < 8) {
    asm volatile("setmaxnreg.inc.sync.aligned.u32 208;");
    const int wg = warp >> 2, w4 = warp & 3, g = lane >> 2, t = lane & 3;
    const int rh = wg ^ kh ^ 1;
    const int p = j & 1, r = (j >> 1) & 1, hh = j >> 2;
    const uint32_t epoch = ld_relaxed(&g_ep[bid]);
    if ((tid & 127) == 0) PROF(wg, 30);
#pragma unroll 1
    for (int it = tid; it < 392; it += 256) {
      const int kc = it / 28, sg = it - kc * 28;
      const int k = 2 * (28 * hh + sg) + r;
      const float kf = (float)k * (-6.283185307179586f / 448.0f), a0 = (float)(16 * kc + p) * kf;
      uint32_t c[4], s[4];
#pragma unroll
      for (int q = 0; q < 4; q++) {
        const float a1 = fmaf((float)(2 * q), kf, a0), a2 = fmaf((float)(2 * q + 8), kf, a0);
        c[q] = pack_bf16(__cosf(a1), __cosf(a2)); s[q] = pack_bf16(__sinf(a1), __sinf(a2));
        if (k == 0) s[q] = ((q ^ p) & 1) ? 0xBF80BF80u : 0x3F803F80u;
      }
      const uint32_t a = sb + 6 * SLOT + (kc * 56 + 2 * sg) * 16;
      sts128(a, c[0], c[1], c[2], c[3]);
      sts128(a + 16, s[0], s[1], s[2], s[3]);
    }
    if ((tid & 127) == 0) PROF(wg, 31);
    fence_async_smem();
    bar_sync<0, NTHREADS - 64>();
    asm volatile("barrier.cluster.arrive.relaxed.aligned;" ::: "memory");
    if ((tid & 127) == 0) PROF(wg, 1);

    uint32_t xa[28][4];
    {
      const uint32_t xb = sb + OFF_PQ + wg * HALF_XR + (w4 * 16 + (lane & 15)) * 128;
      mbar_wait(bars + (B_XFULL + wg) * 8, 0);
      if ((tid & 127) == 0) PROF(wg, 2);
#pragma unroll
      for (int kb = 0; kb < 7; kb++) {
#pragma unroll
        for (int kk = 0; kk < 4; kk++) {
          uint32_t a = xb + kb * 8192 + (((2 * kk + (lane >> 4)) ^ (lane & 7)) << 4);
          asm volatile("ldmatrix.sync.aligned.m8n8.x4.shared.b16 {%0,%1,%2,%3}, [%4];"
                       : "=r"(xa[kb * 4 + kk][0]), "=r"(xa[kb * 4 + kk][1]), "=r"(xa[kb * 4 + kk][2]), "=r"(xa[kb * 4 + kk][3]) : "r"(a) : "memory");
        }
      }
    }
    {
      uint32_t ad[7][4];
      const uint32_t sel = p ? 0x7632 : 0x5410;
      const uint32_t sgn = r ? 0xBF80BF80u : 0x3F803F80u;
#pragma unroll
      for (int jj = 0; jj < 7; jj++) {
#pragma unroll
        for (int i = 0; i < 4; i++) {
          int ks = 2 * jj + (i >> 1), rr = i & 1;
          uint32_t lo = __byte_perm(xa[ks][rr], xa[ks][rr + 2], sel);
          uint32_t hi = __byte_perm(xa[ks + 14][rr], xa[ks + 14][rr + 2], sel);
          asm("fma.rn.bf16x2 %0, %1, %2, %3;" : "=r"(ad[jj][i]) : "r"(hi), "r"(sgn), "r"(lo));
        }
      }
      __syncwarp();
      if (lane == 0) mbar_arrive(bars + (B_XFREE + wg) * 8);
      float acc[28];
      wg_fence();
      uint64_t db = mkdesc(sb + 6 * SLOT, 896, 128, 0);
#pragma unroll
      for (int jj = 0; jj < 7; jj++) wgmma_rs_56<0>(acc, ad[jj], db + jj * 112, jj != 0);
      wg_commit();
      wg_wait<0>(); keep(acc);
      if (lane == 0) mbar_arrive(bars + (B_EMPTY + 6) * 8);
      const uint32_t xc = sb + OFF_EXCH + wg * 8192 + t * 256 + w4 * 64 + g * 4;
      mbar_wait(bars + B_XFREE * 8, 0);
#pragma unroll
      for (int i = 0; i < 7; i++) {
        sts32(xc + i * 1024, pack_bf16(acc[4 * i], acc[4 * i + 1]));
        sts32(xc + i * 1024 + 32, pack_bf16(acc[4 * i + 2], acc[4 * i + 3]));
      }
      fence_async_smem();
      __syncwarp();
      if (lane == 0) mbar_arrive(bars + B_PUBX * 8);
    }
    if ((tid & 127) == 0) PROF(wg, 3);
    const uint32_t tag = ~epoch & 1;
    unsigned char* const hbase = g_H + (size_t)(m * 2 + kh) * (56 * 4096) + rh * 2048 + (tid & 127) * 16;
#pragma unroll 1
    for (int u = 0; u < 3; u++) {
      float acc[64];
      if (wg == 1) { if (u & 1) bar_sync<6, 256>(); else bar_sync<2, 256>(); }
      const uint32_t sbu = opaque(sb);
#pragma unroll
      for (int kb = 0; kb < 7; kb++) {
        mbar_wait(sbu + OFF_BAR + (B_FULL + kb) * 8, u & 1);
        wg_fence();
        uint64_t db = mkdesc(sbu + kb * SLOT, 8192, 1024, 1);
#pragma unroll
        for (int kk = 0; kk < 4; kk++) wgmma_rs_128<1>(acc, xa[kb * 4 + kk], db + kk * 128, (kb | kk) != 0);
        wg_commit();
        if (kb == LEAD1 && wg == 0) { if (u & 1) bar_arrive<6, 256>(); else bar_arrive<2, 256>(); }
        if (kb > 0) { wg_wait<1>(); if (lane == 0) mbar_arrive(sbu + OFF_BAR + (B_EMPTY + kb - 1) * 8); }
      }
      wg_wait<0>(); keep(acc);
      if (lane == 0) mbar_arrive(sbu + OFF_BAR + (B_EMPTY + 6) * 8);
      if ((tid & 127) == 0) PROF(wg, 4 + 2 * u);
      h_epilogue<8>(acc, hbase + (u * 16 + n * 4) * 4096, tag);
      if ((tid & 127) == 0) PROF(wg, 5 + 2 * u);
    }
    uint32_t ha[14][4][4];
    auto check = [&](int b0, int b1) {
#pragma unroll
      for (int b = b0; b < b1; b++) frag_ready(ha[b][0], ha[b][1], ha[b][2], ha[b][3], hbase + b * 16384, tag);
    };
    auto load = [&](int b0, int b1) {
#pragma unroll
      for (int i = b0; i < b1; i++) ldg128_l2(ha[i >> 2][i & 3], hbase + i * 4096);
    };
    {
      float acc[32];
      load(0, 3);
      if (wg == 1) bar_sync<6, 256>();
      const uint32_t sbu = opaque(sb);
#pragma unroll
      for (int it = 0; it < 4; it++) {
        mbar_wait(sbu + OFF_BAR + (B_FULL + it) * 8, 1);
        wg_fence();
        uint64_t db = mkdesc(sbu + it * SLOT, 8192, 512, 2);
#pragma unroll
        for (int kk = 0; kk < 8; kk++) if (it * 8 + kk < 28) wgmma_rs_64<1>(acc, xa[it * 8 + kk], db + kk * 64, (it | kk) != 0);
        wg_commit();
        if (it == 2 && wg == 0) bar_arrive<6, 256>();
        if (it > 0) {
          wg_wait<1>();
          if (lane == 0) mbar_arrive(sbu + OFF_BAR + (B_EMPTY + it - 1) * 8);
          if (it == 1) load(3, 11);
          if (it == 2) load(11, 16);
        }
      }
      wg_wait<0>(); keep(acc);
      if (lane == 0) mbar_arrive(sbu + OFF_BAR + (B_EMPTY + 3) * 8);
      if ((tid & 127) == 0) PROF(wg, 10);
      h_epilogue<4>(acc, hbase + (48 + n * 2) * 4096, tag);
    }
    asm volatile("barrier.cluster.wait.aligned;" ::: "memory");
    if ((tid & 127) == 0) PROF(wg, 11);

    float acc[56];
    check(0, 4);
    if (wg == 1) bar_sync<2, 256>();
#pragma unroll
    for (int b = 0; b < 14; b++) {
      if ((tid & 127) == 0) PROF(wg, 16 + b);
      if (b >= 3) mbar_wait(bars + (B_FULL + (b + 1) % 7) * 8, b < 6 || b == 13);
      else if (b == 0) mbar_wait(bars + B_RFULL * 8, 0);
      if (b == 4) check(4, 7);
      if (b == 7) check(7, 11);
      if (b == 11) check(11, 14);
      wg_fence();
      const uint64_t db = mkdesc(b < 3 ? sb + OFF_R + b * SLOT : sb + (b + 1) % 7 * SLOT, 8192, 1024, 1);
#pragma unroll
      for (int kk = 0; kk < 4; kk++) wgmma_rs_112<1>(acc, ha[b][kk], db + kk * 128, (b | kk) != 0);
      wg_commit();
      if (b == LEAD2 && wg == 0) bar_arrive<2, 256>();
      if (b == 0) load(16, 24);
      if (b == 1) load(24, 28);
      if (b == 4 || b == 5) load(8 * b - 4, 8 * b + 4);
      if (b == 7) load(44, 52);
      if (b == 8) load(52, 56);
      if (b > 0) wg_wait<1>();
      if (lane == 0) {
        if (b >= 4 && b <= 9) mbar_arrive(bars + (B_EMPTY + b % 7) * 8);
        if (b == 3) {
          mbar_arrive(bars + B_LFREE * 8);
          asm volatile("{\n.reg .b32 ra;\nmapa.shared::cluster.u32 ra, %0, %1;\nmbarrier.arrive.relaxed.cluster.shared::cluster.b64 _, [ra];\n}"
                       :: "r"(bars + B_RFREE * 8), "r"(kh ^ 1) : "memory");
        }
      }
    }
    const int t128 = tid & 127;
    wg_wait<0>(); keep(acc);
    if (wg == 0) {
      if (t128 == 0) PROF(wg, 12);
      mbar_wait_cluster(bars + B_RFREE * 8, 0);
      uint32_t rdst, rbar;
      asm volatile("mapa.shared::cluster.u32 %0, %1, %2;" : "=r"(rdst) : "r"(sb + OFF_R + t128 * 16), "r"(kh ^ 1));
      asm volatile("mapa.shared::cluster.u32 %0, %1, %2;" : "=r"(rbar) : "r"(bars + B_RECV * 8), "r"(kh ^ 1));
#pragma unroll
      for (int i = 0; i < 14; i++)
        asm volatile("st.async.weak.shared::cluster.mbarrier::complete_tx::bytes.v4.f32 [%0], {%1,%2,%3,%4}, [%5];"
                     :: "r"(rdst + i * 2048), "f"(acc[4 * i]), "f"(acc[4 * i + 1]), "f"(acc[4 * i + 2]), "f"(acc[4 * i + 3]), "r"(rbar) : "memory");
    } else {
      float spec[2][28];
      if (t128 == 0) PROF(wg, 12);
      mbar_wait_cluster(bars + B_RECV * 8, 0);
      if (t128 == 0) PROF(wg, 0);
#pragma unroll
      for (int i = 0; i < 14; i++) {
        const float4 o = lds128f(sb + OFF_R + t128 * 16 + i * 2048);
        acc[4 * i] += o.x; acc[4 * i + 1] += o.y; acc[4 * i + 2] += o.z; acc[4 * i + 3] += o.w;
      }
#pragma unroll
      for (int i = 0; i < 4; i++) {
        if (i == 0) mbar_wait(bars + B_GFULL * 8, 0);
        if (i >= 2) mbar_wait(bars + (B_FULL + i - 1) * 8, 1);
        mbar_wait(bars + (B_PQFULL + i) * 8, 0);
        if (i == 0 && t128 == 0) { PROF(wg, 13); g_ep[bid] = epoch + 1; }
        wg_fence();
        const uint64_t da = mkdesc(sb + OFF_PQ + i * 14336, 1024, 1024, 1);
        const uint64_t db = mkdesc(i < 2 ? sb + OFF_R + 28672 + i * (G_IMG / 2) : sb + (i - 1) * SLOT, 896, 128, 0);
#pragma unroll
        for (int kk = 0; kk < 7; kk++) wgmma_ss_56<1, 0>(spec[i >> 1], da + kk * 128, db + kk * 112, ((i & 1) | kk) != 0);
        wg_commit();
      }
      const float* gs = reinterpret_cast<const float*>(smem + OFF_G) + w4 * 16 + g;
      const float o0 = bf16_round(1.0f - gs[0]), o1 = bf16_round(1.0f - gs[8]);
      const float g0 = gs[0] * (1.0f / (float)(S_ * D_)), g1 = gs[8] * (1.0f / (float)(S_ * D_));
#pragma unroll
      for (int i = 0; i < 56; i++) acc[i] *= (i & 2) ? o1 : o0;
      keep(acc);
      wg_wait<0>(); keep(spec[0]); keep(spec[1]);
      if (t128 == 0) PROF(wg, 14);
      bar_sync<5, 128>();
      const uint32_t st = sb + OFF_PQ + w4 * 3840;
#pragma unroll
      for (int i = 0; i < 7; i++) {
        uint32_t pk[4];
#pragma unroll
        for (int e = 0; e < 2; e++) {
          const int c = 2 * i + e, si = i * 4 + e;
          pk[2 * e] = pack_bf16(fmaf(g0, spec[0][si], acc[4 * c]), fmaf(g0, spec[1][si], acc[4 * c + 1]));
          pk[2 * e + 1] = pack_bf16(fmaf(g1, spec[0][si + 2], acc[4 * c + 2]), fmaf(g1, spec[1][si + 2], acc[4 * c + 3]));
        }
        asm volatile("stmatrix.sync.aligned.m8n8.x4.shared.b16 [%0], {%1,%2,%3,%4};"
                     :: "r"(st + (lane & 15) * 240 + (lane >> 4) * 16 + i * 32), "r"(pk[0]), "r"(pk[1]), "r"(pk[2]), "r"(pk[3]) : "memory");
      }
      __syncwarp();
      if (lane < 28) {
        const int r2 = lane >= 14, cc = lane - r2 * 14;
        unsigned char* ob = reinterpret_cast<unsigned char*>(out) + (size_t)(m * 128 + kh * 64 + w4 * 16 + r2) * (D_ * 2) + n * 224 + cc * 16;
        float4 v[8];
#pragma unroll
        for (int i = 0; i < 8; i++) v[i] = lds128f(st + r2 * 240 + cc * 16 + i * 480);
#pragma unroll
        for (int i = 0; i < 8; i++) stg128(ob + i * (D_ * 4), __float_as_uint(v[i].x), __float_as_uint(v[i].y), __float_as_uint(v[i].z), __float_as_uint(v[i].w));
      }
    }
    if (t128 == 0) { PROF(wg, 15); if (wg) { PROFG(4, 30); PROF(4, 31); } }
  } else if (warp < 12) {
    asm volatile("setmaxnreg.dec.sync.aligned.u32 72;");
    const int t = tid - 256;
    const int k = bid;
    if (t == 0) PROF(2, 0);
    uint4 gv[7];
#pragma unroll
    for (int i = 0; i < 7; i++) gv[i] = ldg128(reinterpret_cast<const uint4*>(gate_w) + i * 8 + (t & 7));
    if (t < 98) {
      int cid = m * 98 + t, kc = cid / 56, nn = cid - kc * 56;
      int d = 112 * n + 8 * (2 * (nn >> 3) + (nn & 1)) + (nn & 6) + kh;
      int dr = d > 224 ? d - 448 : d;
      const float df = (float)dr * (-6.283185307179586f / 448.0f);
      uint32_t pk[4];
#pragma unroll
      for (int e = 0; e < 4; e++) {
        const float a = (float)(4 * kc + e) * df;
        pk[e] = pack_bf16(2.0f * __cosf(a), 2.0f * __sinf(a));
      }
      if (kc == 0) pk[0] = (((d >> 1) ^ kh) & 1) ? 0xBF803F80u : 0x3F803F80u;
      stg128(g_G + (size_t)(n * 2 + kh) * G_IMG + cid * 16, pk[0], pk[1], pk[2], pk[3]);
    }
    bar_sync<0, NTHREADS - 64>();
    asm volatile("barrier.cluster.arrive.relaxed.aligned;" ::: "memory");
    {
      const int row = n * 16 + (t >> 3), l8 = t & 7;
      mbar_wait(bars + (B_XFULL + 1) * 8, 0);
      float sum = 0.f;
#pragma unroll
      for (int i = 0; i < 7; i++) {
        const uint4 a = lds128(sb + OFF_R + i * 8192 + row * 128 + ((l8 ^ (row & 7)) << 4));
        const uint32_t aa[4] = {a.x, a.y, a.z, a.w}, bb[4] = {gv[i].x, gv[i].y, gv[i].z, gv[i].w};
#pragma unroll
        for (int e = 0; e < 4; e++) {
          const uint32_t pr = as_u(__hmul2(as_b2(aa[e]), as_b2(bb[e])));
          sum += bf_lo(pr) + bf_hi(pr);
        }
      }
      sum += __shfl_xor_sync(0xffffffffu, sum, 1); sum += __shfl_xor_sync(0xffffffffu, sum, 2); sum += __shfl_xor_sync(0xffffffffu, sum, 4);
      if (lane == 0) mbar_arrive(bars + (B_XFREE + 1) * 8);
      if (l8 == 0) g_gate[m * 128 + kh * 64 + row] = bf16_round(__fdividef(1.0f, 1.0f + __expf(-bf16_round(sum))));
    }
    __syncwarp();
    if (lane == 0) mbar_arrive(bars + B_PUBW * 8);
    if (t == 0) PROF(2, 11);
    mbar_wait(bars + B_XFREE * 8, 0);
    if (k < 113) {
      const float u = -6.283185307179586f / 2048.0f, t2 = (float)(2 * t) * u, rr = (float)(t >> 4) * u;
#pragma unroll 1
      for (int i = 0; i < 4; i++) {
        const float q = (float)(2 * i), l = (float)((t & 15) + 64 * i);
        sts128(sb + OFF_TW + i * 2048 + t * 16, cis(t2 * q), cis((t2 + u) * q), cis(t2 * (q + 1.0f)), cis((t2 + u) * (q + 1.0f)));
        sts128(sb + OFF_TW + 8192 + i * 2048 + t * 16, cis(rr * l), cis(rr * (l + 16.0f)), cis(rr * (l + 32.0f)), cis(rr * (l + 48.0f)));
      }
      const float l = (float)((t >> 1) & 15) * (8.0f * u), jj = (float)((t >> 5) * 4 + (t & 1) * 2);
      sts64(sb + OFF_TW + 16384 + t * 8, cis(l * jj), cis(l * (jj + 1.0f)));
    }
    if (t == 0) PROF(2, 9);
    mbar_wait(bars + B_PIN * 8, 0);
    mbar_wait(bars + B_XDONE * 8, 0);
    if (t == 0) PROF(2, 4);
    {
      const uint32_t wa = sb + OFF_WS + (((t & 7) - bid) & 7) * 450 + (t >> 3) * 2, wc = wa + 448 - (t >> 3) * 4;
#pragma unroll 1
      for (int h = 0; h < 2; h++) {
        uint32_t w[4][8];
#pragma unroll
        for (int i = 0; i < 4; i++) {
#pragma unroll
          for (int e = 0; e < 4; e++) { w[i][2 * e] = lds16(wa + h * 128 + i * 32 + e * 3600); w[i][2 * e + 1] = lds16(wc - h * 128 - i * 32 + e * 3600); }
        }
#pragma unroll
        for (int i = 0; i < 4; i++)
          sts128(sb + OFF_EXCH + h * 8192 + i * 2048 + t * 16, __byte_perm(w[i][0], w[i][1], 0x5410), __byte_perm(w[i][4], w[i][5], 0x5410), __byte_perm(w[i][2], w[i][3], 0x5410), __byte_perm(w[i][6], w[i][7], 0x5410));
      }
    }
    fence_async_smem();
    __syncwarp();
    if (lane == 0) mbar_arrive(bars + B_PUBW * 8);
    bar_sync<3, 128>();
    if (k < 113) {
      if (t == 0) PROF(2, 2);
      mbar_wait(bars + B_XCFULL * 8, 0);
      if (t == 0) PROF(2, 3);
      c2 v[16];
      uint2 xe[8], xo[8];
      const int sl = k == 112 ? 0 : k, hi = sl >= 56;
      const unsigned char* xs = g_X + (192 + (sl & 1) * 64 + hi * 72 + (sl & ~1) + ((t >> 4) & 1)) * XP + (t >> 5) * 256 + (t & 15) * 8;
#pragma unroll
      for (int jj = 0; jj < 8; jj++) { xe[jj] = ldg64_l2(xs + jj * 1024); xo[jj] = ldg64_l2(xs + jj * 1024 + 128); }
      const uint32_t se = k == 0 ? 0x4410 : (k == 112 ? 0x4432 : 0x3210), so = k == 0 ? 0x4410 : (k == 112 ? 0x3244 : 0x3210);
#pragma unroll
      for (int jj = 0; jj < 8; jj++) {
        const uint2 e2 = xe[jj], o2 = xo[jj];
#pragma unroll
        for (int h = 0; h < 2; h++) {
          const b2 e = as_b2(__byte_perm(h ? e2.y : e2.x, 0, se)), o = as_b2(__byte_perm(h ? o2.y : o2.x, 0, so));
          const uint32_t s = as_u(__hadd2(e, o)), d = as_u(__hsub2(e, o)) ^ 0x80000000u;
          v[2 * jj + h] = mk(as_b2(__byte_perm(s, d, 0x5410)), as_b2(__byte_perm(s, d, 0x7632)));
        }
      }
      mbar_wait(bars + B_XDONE * 8, 1);
      if (t == 0) PROF(2, 12);
      columns(v, sb, t);
      if (t == 0) PROF(2, 14);
      const int pre = (k == 112) ? 1 : 2 * k, pim = (k == 112) ? 1 : 2 * k + 1;
      const uint32_t pr = sb + OFF_EXCH + (t >> 5) * 256 + ((((lane >> 2) ^ pre) & 7) << 4) + (lane & 3) * 4;
      const uint32_t pi = sb + OFF_EXCH + 8192 + (t >> 5) * 256 + ((((lane >> 2) ^ pim) & 7) << 4) + (lane & 3) * 4;
      bar_sync<3, 128>();
#pragma unroll
      for (int jj = 0; jj < 8; jj++) {
        const b2 ar = as_b2(__byte_perm(as_u(v[2 * jj].y), as_u(v[2 * jj + 1].y), 0x5410)), br = as_b2(__byte_perm(as_u(v[2 * jj].y), as_u(v[2 * jj + 1].y), 0x7632));
        const b2 ai = as_b2(__byte_perm(as_u(v[2 * jj].x), as_u(v[2 * jj + 1].x), 0x5410)), bi = as_b2(__byte_perm(as_u(v[2 * jj].x), as_u(v[2 * jj + 1].x), 0x7632));
        sts32(pr + jj * 1024, as_u(__hadd2(ar, br)));
        sts32(pr + jj * 1024 + 128, as_u(k == 112 ? __hadd2(ai, bi) : __hsub2(ar, br)));
        sts32(pi + jj * 1024 + 128, as_u(__hadd2(ai, bi)));
        sts32(pi + jj * 1024, as_u(__hsub2(ai, bi)));
      }
      fence_async_smem();
      bar_sync<3, 128>();
      if (t == 0) {
        PROF(2, 5);
        tma_store(&tm_s, pre * 64, 0, sb + OFF_EXCH);
        if (k != 0 && k != 112) tma_store(&tm_s, pim * 64, 0, sb + OFF_EXCH + 8192);
        bulk_done();
      }
    } else {
      mbar_wait(bars + B_XDONE * 8, 1);
    }
    if (t == 0) { red_relaxed(&g_cnt[5 * 32]); PROF(2, 7); }
    __syncwarp();
    asm volatile("barrier.cluster.wait.aligned;" ::: "memory");
  } else {
    asm volatile("setmaxnreg.dec.sync.aligned.u32 24;");
    auto wd_tile = [&](int b, uint32_t dst, uint32_t fb) {
#pragma unroll
      for (int hf = 0; hf < 2; hf++) {
        const int js = kh * 4 + (b < 12 ? (b & 3) : (b & 1) * 2 + hf);
        const int row = 224 * js + (b < 12 ? (js & 1) * 32 + (b >> 2) * 64 + hf * 32 : 192 - hf * 192);
        tma2d(dst + hf * 4096, &tm_d, 112 * n, row, fb);
        tma2d(dst + 8192 + hf * 4096, &tm_d, 112 * n + 64, row, fb);
      }
    };
    if (warp == 12) {
      if (elect()) {
        mbar_init(bars + B_XFULL * 8, 1); mbar_init(bars + (B_XFULL + 1) * 8, 1);
        fence_async_smem();
#pragma unroll
        for (int w = 0; w < 2; w++) {
          mbar_expect(bars + (B_XFULL + w) * 8, HALF_XR);
          tma3d(sb + OFF_PQ + w * HALF_XR, &tm_x, 0, m * 128 + (w ^ kh ^ 1) * 64, 0, bars + (B_XFULL + w) * 8);
        }
        PROF(3, 3);
#pragma unroll
        for (int i = 0; i < NSLOT; i++) mbar_init(bars + (B_FULL + i) * 8, 1);
        mbar_init(bars + B_PIN * 8, 1);
        fence_async_smem();
      }
      bar_arrive<0, NTHREADS - 64>();
#pragma unroll 1
      for (int i = 0; i < 6; i++) {
        if (elect()) {
          const uint32_t fb = bars + (B_FULL + i) * 8;
          mbar_expect(fb, SLOT);
          tma2d(sb + i * SLOT, &tm_g, c64, i * 64, fb);
          tma2d(sb + i * SLOT + 8192, &tm_u, c64, i * 64, fb);
          PROF(3, 4 + i);
        }
      }
      if (elect()) {
        prefetch_l2(reinterpret_cast<const unsigned char*>(w_r) + bid * 7200, 7200);
        prefetch_l2(reinterpret_cast<const unsigned char*>(w_i) + bid * 7200, 7200);
        prefetch_tma2d(&tm_g, c64, 384); prefetch_tma2d(&tm_u, c64, 384);
      }
    } else if (warp == 14) {
      if (elect()) {
#pragma unroll
        for (int i = B_EMPTY; i < B_END; i++)
          if (i < B_XFULL || i >= B_XFREE) mbar_init(bars + i * 8, i >= B_PQFULL ? 1 : ((i == B_XFREE || i == B_PUBW) ? 4 : 8));
        asm volatile("fence.mbarrier_init.release.cluster;" ::: "memory");
        fence_async_smem();
        mbar_expect(bars + B_RECV * 8, 64 * 112 * 4);
      }
      bar_arrive<0, NTHREADS - 64>();
    }
    const uint32_t epoch = ld_relaxed(&g_ep[bid]);
    if (warp == 13 && lane == 0) { PROFG(4, 0); PROF(4, 1); }
    bar_sync<1, 128>();
    asm volatile("barrier.cluster.arrive.relaxed.aligned;" ::: "memory");
    if (warp == 12) {
      int slot = 6, ph = 1;
      auto wait_slot = [&]() { mbar_wait(bars + (B_EMPTY + slot) * 8, ph ^ (slot == 6)); };
      auto adv = [&]() { if (++slot == NSLOT) { slot = 0; ph ^= 1; } };
      const int c32 = 224 * j + ((j & 1) ? 0 : 192);
#pragma unroll 1
      for (int i = 6; i < 25; i++) {
        wait_slot();
        if (elect()) {
          const uint32_t dst = sb + slot * SLOT, fb = bars + (B_FULL + slot) * 8;
          const bool last = i >= 21;
          const int cc = last ? c32 : c64 + 64 * (i / 7), rr = last ? slot * 128 : slot * 64;
          mbar_expect(fb, SLOT);
          tma2d(dst, last ? &tm_g32 : &tm_g, cc, rr, fb);
          tma2d(dst + 8192, last ? &tm_u32 : &tm_u, cc, rr, fb);
        }
        adv();
      }
      if (lane == 0) PROF(3, 0);
#pragma unroll 1
      for (int i = 3; i < 16; i++) {
        if (lane == 0) PROF(3, 16 + i);
        if (i == 14) mbar_wait(bars + B_PREP * 8, 0);
        wait_slot();
        if (elect()) {
          const uint32_t fb = bars + (B_FULL + slot) * 8;
          mbar_expect(fb, i < 14 ? SLOT : G_IMG / 2);
          if (i < 14) wd_tile(i, sb + slot * SLOT, fb);
          else bulk_g2s(sb + slot * SLOT, g_G + (size_t)(n * 4 + i - 12) * (G_IMG / 2), G_IMG / 2, fb);
        }
        adv();
      }
      if (lane == 0) PROF(3, 2);
    } else if (warp == 13) {
      mbar_wait(bars + B_PUBX * 8, 0);
      if (elect()) {
        PROF(4, 8);
#pragma unroll
        for (int w = 0; w < 2; w++) tma_store(&tm_s, ((m * 2 + (w ^ kh ^ 1)) * 2 + (j & 1)) * 64, 192 + (j >> 1) * 64, sb + OFF_EXCH + w * 8192);
        bulk_done();
        red_relaxed(&g_cnt[(j >> 1) * 32]);
        PROF(4, 12);
      }
      mbar_wait(bars + B_PUBW * 8, 0);
      if (elect()) mbar_arrive(bars + B_XDONE * 8);
      asm volatile("fence.acq_rel.gpu;" ::: "memory");
      mbar_wait(bars + B_PUBW * 8, 1);
      if (elect()) {
        PROF(4, 9);
        tma_store(&tm_s, bid * 64, 64, sb + OFF_EXCH);
        tma_store(&tm_s, bid * 64, 128, sb + OFF_EXCH + 8192);
        bulk_done();
        red_relaxed(&g_cnt[4 * 32]);
        mbar_arrive(bars + B_XDONE * 8);
        PROF(4, 13);
      }
      mbar_wait(bars + B_PREP * 8, 0);
      mbar_wait(bars + B_LFREE * 8, 0);
      if (elect()) {
        mbar_expect(bars + B_GFULL * 8, G_IMG);
        bulk_g2s(sb + OFF_R + 28672, g_G + (size_t)(n * 2) * G_IMG, G_IMG, bars + B_GFULL * 8);
      }
    } else if (warp == 14) {
      wait_ge(&g_cnt[4 * 32], (epoch + 1) * 128);
      fence_async_global();
      if (elect()) {
        mbar_arrive(bars + B_PREP * 8);
        if (bid < 113) {
          mbar_expect(bars + B_WFULL * 8, 16384);
          bulk_g2s(sb + OFF_WS, g_X + (64 + bid) * XP, 16384, bars + B_WFULL * 8);
        }
        PROF(5, 17);
      }
    } else {
      mbar_wait(bars + B_XFREE * 8, 0);
      if (elect()) {
        mbar_expect(bars + B_PIN * 8, 14400);
        bulk_g2s(sb + OFF_WS, reinterpret_cast<const unsigned char*>(w_r) + bid * 7200, 7200, bars + B_PIN * 8);
        bulk_g2s(sb + OFF_WS + 7200, reinterpret_cast<const unsigned char*>(w_i) + bid * 7200, 7200, bars + B_PIN * 8);
        prefetch_l2(reinterpret_cast<const unsigned char*>(w_gate) + bid * 12544, 12544);
        prefetch_l2(reinterpret_cast<const unsigned char*>(w_up) + bid * 12544, 12544);
        prefetch_l2(reinterpret_cast<const unsigned char*>(w_down) + bid * 12544, 12544);
        PROF(5, 2);
      }
      if (bid < 113) {
        const int sl = (bid == 112) ? 0 : bid;
        wait_ge(&g_cnt[((sl & 1) + 2 * ((sl >> 1) / 28)) * 32], (epoch + 1) * 32);
        if (elect()) { PROF(5, 16); mbar_arrive(bars + B_XCFULL * 8); }
      }
      mbar_wait(bars + (B_XFREE + 1) * 8, 0);
      if (elect()) mbar_expect(bars + B_RFULL * 8, 3 * SLOT);
#pragma unroll 1
      for (int i = 0; i < 3; i++) {
        mbar_wait(bars + (B_FULL + 2 * i + 1) * 8, 1);
        if (elect()) wd_tile(i, sb + OFF_R + i * SLOT, bars + B_RFULL * 8);
      }
      if (lane == 0) PROF(5, 19);
      mbar_wait(bars + B_PREP * 8, 0);
      wait_ge(&g_cnt[5 * 32], (epoch + 1) * 128);
      fence_async_global();
      if (elect()) {
        PROF(5, 18);
        const unsigned char* src = g_X + (m * 2 + kh) * HALF_XR;
#pragma unroll
        for (int i = 0; i < 4; i++) {
          mbar_expect(bars + (B_PQFULL + i) * 8, i ? 14336 : 14336 + 256);
          bulk_g2s(sb + OFF_PQ + i * 14336, src + i * 14336, 14336, bars + (B_PQFULL + i) * 8);
        }
        bulk_g2s(sb + OFF_G, g_gate + m * 128 + kh * 64, 256, bars + B_PQFULL * 8);
      }
    }
    __syncwarp();
    asm volatile("barrier.cluster.wait.aligned;" ::: "memory");
  }
}

typedef CUresult (*EncodeFn)(CUtensorMap*, CUtensorMapDataType, cuuint32_t, void*, const cuuint64_t*, const cuuint64_t*, const cuuint32_t*,
                             const cuuint32_t*, CUtensorMapInterleave, CUtensorMapSwizzle, CUtensorMapL2promotion, CUtensorMapFloatOOBfill);

void make_map(EncodeFn enc, CUtensorMap* tm, const void* base, int cols, int rows, int bc, int br, CUtensorMapSwizzle sw) {
  cuuint64_t gd[2] = {(cuuint64_t)cols, (cuuint64_t)rows};
  cuuint64_t gs[1] = {(cuuint64_t)cols * 2};
  cuuint32_t bd[2] = {(cuuint32_t)bc, (cuuint32_t)br};
  cuuint32_t es[2] = {1, 1};
  enc(tm, CU_TENSOR_MAP_DATA_TYPE_BFLOAT16, 2, const_cast<void*>(base), gd, gs, bd, es, CU_TENSOR_MAP_INTERLEAVE_NONE, sw,
      CU_TENSOR_MAP_L2_PROMOTION_L2_128B, CU_TENSOR_MAP_FLOAT_OOB_FILL_NONE);
}

}

extern "C" void kernel_launch(void* const* d_in, const int* in_sizes, int n_in, void* d_out, int out_size) {
  (void)in_sizes; (void)n_in; (void)out_size;
  const __nv_bfloat16* x = (const __nv_bfloat16*)d_in[0];
  const __nv_bfloat16* w_r = (const __nv_bfloat16*)d_in[1];
  const __nv_bfloat16* w_i = (const __nv_bfloat16*)d_in[2];
  const __nv_bfloat16* w_gate = (const __nv_bfloat16*)d_in[4];
  const __nv_bfloat16* w_up = (const __nv_bfloat16*)d_in[5];
  const __nv_bfloat16* w_down = (const __nv_bfloat16*)d_in[6];
  const __nv_bfloat16* gate_w = (const __nv_bfloat16*)d_in[7];
  static EncodeFn enc = nullptr;
  static void* xbuf = nullptr;
  static bool ok = false;
  if (!enc) {
    cudaDriverEntryPointQueryResult qr;
    cudaGetDriverEntryPoint("cuTensorMapEncodeTiled", (void**)&enc, cudaEnableDefault, &qr);
    cudaFuncSetAttribute(fused_kernel, cudaFuncAttributeMaxDynamicSharedMemorySize, SMEM_BYTES);
    cudaGetSymbolAddress(&xbuf, g_X);
    cudaFuncAttributes fa;
    cudaFuncGetAttributes(&fa, fused_kernel);
    ok = (fa.numRegs == 128);
  }
  if (!ok) return;
  CUtensorMap tx, tg, tu, tg32, tu32, td, ts;
  {
    cuuint64_t gd[3] = {64, (cuuint64_t)S_, 7};
    cuuint64_t gs[2] = {(cuuint64_t)D_ * 2, 128};
    cuuint32_t bd[3] = {64, 64, 7};
    cuuint32_t es[3] = {1, 1, 1};
    enc(&tx, CU_TENSOR_MAP_DATA_TYPE_BFLOAT16, 3, const_cast<__nv_bfloat16*>(x), gd, gs, bd, es, CU_TENSOR_MAP_INTERLEAVE_NONE, CU_TENSOR_MAP_SWIZZLE_128B,
        CU_TENSOR_MAP_L2_PROMOTION_L2_128B, CU_TENSOR_MAP_FLOAT_OOB_FILL_NONE);
  }
  make_map(enc, &tg, w_gate, F_, D_, 64, 64, CU_TENSOR_MAP_SWIZZLE_128B);
  make_map(enc, &tu, w_up, F_, D_, 64, 64, CU_TENSOR_MAP_SWIZZLE_128B);
  make_map(enc, &tg32, w_gate, F_, D_, 32, 128, CU_TENSOR_MAP_SWIZZLE_64B);
  make_map(enc, &tu32, w_up, F_, D_, 32, 128, CU_TENSOR_MAP_SWIZZLE_64B);
  make_map(enc, &td, w_down, D_, F_, 64, 32, CU_TENSOR_MAP_SWIZZLE_128B);
  make_map(enc, &ts, (const __nv_bfloat16*)xbuf, XP / 2, 448, 64, 64, CU_TENSOR_MAP_SWIZZLE_NONE);
  fused_kernel<<<128, NTHREADS, SMEM_BYTES>>>(tx, tg, tu, tg32, tu32, td, ts, w_r, w_i, w_gate, w_up, w_down, gate_w, (__nv_bfloat16*)d_out);
}
```

```cpp
#include <cuda_runtime.h>
#include <cuda_bf16.h>
#include <cuda.h>
#include <stdint.h>

namespace {

constexpr int S_ = 2048, D_ = 448, F_ = 1792;
constexpr int NTHREADS = 512;
constexpr int SLOT = 16384, NSLOT = 7;
constexpr int HALF_XR = 57344;
constexpr int OFF_PQ = NSLOT * SLOT;
constexpr int OFF_R = OFF_PQ + HALF_XR;
constexpr int OFF_EXCH = OFF_PQ;
constexpr int OFF_WS = OFF_EXCH + 18432;
constexpr int OFF_TW = OFF_WS + 16384;
constexpr int OFF_MISC = OFF_R + HALF_XR;
constexpr int OFF_G = OFF_MISC;
constexpr int OFF_BAR = OFF_MISC + 512;
constexpr int SMEM_BYTES = OFF_BAR + 512;
constexpr int B_FULL = 0, B_EMPTY = 7, B_XFULL = 14  ;
constexpr int B_XFREE = 16  , B_PUBX = 18, B_RFREE = 19, B_LFREE = 20;
constexpr int B_PUBW = 21;
constexpr int B_PQFULL = 22  , B_RECV = 26, B_WFULL = 27, B_XCFULL = 28, B_PREP = 29, B_RFULL = 30, B_GFULL = 31, B_XDONE = 32, B_END = 33, B_PIN = 33;

constexpr int G_IMG = 224 * 56 * 2;

__device__ __align__(1024) unsigned char g_H[32 * 56 * 4096];
constexpr int XP = 28672;
__device__ __align__(1024) unsigned char g_X[448 * XP];
__device__ __align__(1024) unsigned char g_G[8 * G_IMG];
__device__ __align__(1024) float g_gate[S_];
__device__ __align__(128) unsigned int g_ep[128];
__device__ __align__(128) unsigned int g_cnt[8 * 32];

#define PROF(role, idx) do {} while (0)
#define PROFG(role, idx) do {} while (0)

__device__ __forceinline__ uint32_t s2u(const void* p) { return (uint32_t)__cvta_generic_to_shared(p); }
__device__ __forceinline__ void mbar_init(uint32_t b, int c) { asm volatile("mbarrier.init.shared::cta.b64 [%0], %1;" :: "r"(b), "r"(c) : "memory"); }
__device__ __forceinline__ void mbar_expect(uint32_t b, int bytes) { asm volatile("mbarrier.arrive.expect_tx.shared::cta.b64 _, [%0], %1;" :: "r"(b), "r"(bytes) : "memory"); }
__device__ __forceinline__ void mbar_arrive(uint32_t b) { asm volatile("mbarrier.arrive.shared::cta.b64 _, [%0];" :: "r"(b) : "memory"); }
__device__ __forceinline__ void mbar_wait(uint32_t b, int ph) {
  asm volatile("{\n.reg .pred p;\n.reg .u32 c;\nmov.u32 c, 0;\nL_WAIT:\nmbarrier.try_wait.parity.shared::cta.b64 p, [%0], %1;\n@p bra.uni L_DONE;\n"
               "add.u32 c, c, 1;\nsetp.lt.u32 p, c, 4194304;\n@p bra.uni L_WAIT;\ntrap;\nL_DONE:\n}" :: "r"(b), "r"(ph) : "memory");
}
__device__ __forceinline__ void mbar_wait_cluster(uint32_t b, int ph) {
  asm volatile("{\n.reg .pred p;\n.reg .u32 c;\nmov.u32 c, 0;\nL_WAIT:\nmbarrier.try_wait.parity.acquire.cluster.shared::cta.b64 p, [%0], %1;\n@p bra.uni L_DONE;\n"
               "add.u32 c, c, 1;\nsetp.lt.u32 p, c, 4194304;\n@p bra.uni L_WAIT;\ntrap;\nL_DONE:\n}" :: "r"(b), "r"(ph) : "memory");
}
__device__ __forceinline__ uint32_t ld_acquire(const unsigned int* p) { uint32_t v; asm volatile("ld.acquire.gpu.global.u32 %0, [%1];" : "=r"(v) : "l"(p) : "memory"); return v; }
__device__ __forceinline__ uint32_t ld_relaxed(const unsigned int* p) { uint32_t v; asm volatile("ld.relaxed.gpu.global.u32 %0, [%1];" : "=r"(v) : "l"(p) : "memory"); return v; }
__device__ __forceinline__ void wait_ge(const unsigned int* p, uint32_t target) {
#pragma unroll 1
  for (int i = 0; i < (1 << 22); i++) { if ((int)(ld_acquire(p) - target) >= 0) return; }
  __trap();
}
__device__ __forceinline__ void red_relaxed(unsigned int* p) { asm volatile("red.relaxed.gpu.global.add.u32 [%0], 1;" :: "l"(p) : "memory"); }
__device__ __forceinline__ bool elect() { uint32_t p; asm volatile("{\n.reg .pred p;\nelect.sync _|p, 0xffffffff;\nselp.u32 %0, 1, 0, p;\n}" : "=r"(p)); return p; }
__device__ __forceinline__ void fence_async_smem() { asm volatile("fence.proxy.async.shared::cta;" ::: "memory"); }
__device__ __forceinline__ void fence_async_global() { asm volatile("fence.proxy.async.global;" ::: "memory"); }
template <int ID, int N> __device__ __forceinline__ void bar_sync() { asm volatile("bar.sync %0, %1;" :: "n"(ID), "n"(N) : "memory"); }
template <int ID, int N> __device__ __forceinline__ void bar_arrive() { asm volatile("bar.arrive %0, %1;" :: "n"(ID), "n"(N) : "memory"); }
__device__ __forceinline__ void tma2d(uint32_t dst, const CUtensorMap* tm, int c0, int c1, uint32_t bar) {
  asm volatile("cp.async.bulk.tensor.2d.shared::cluster.global.mbarrier::complete_tx::bytes [%0], [%1, {%3, %4}], [%2];"
               :: "r"(dst), "l"(tm), "r"(bar), "r"(c0), "r"(c1) : "memory");
}
__device__ __forceinline__ void tma3d(uint32_t dst, const CUtensorMap* tm, int c0, int c1, int c2, uint32_t bar) {
  asm volatile("cp.async.bulk.tensor.3d.shared::cluster.global.mbarrier::complete_tx::bytes [%0], [%1, {%3, %4, %5}], [%2];"
               :: "r"(dst), "l"(tm), "r"(bar), "r"(c0), "r"(c1), "r"(c2) : "memory");
}
__device__ __forceinline__ void bulk_g2s(uint32_t dst, const void* src, int bytes, uint32_t bar) {
  asm volatile("cp.async.bulk.shared::cluster.global.mbarrier::complete_tx::bytes [%0], [%1], %2, [%3];"
               :: "r"(dst), "l"(src), "r"(bytes), "r"(bar) : "memory");
}
__device__ __forceinline__ void tma_store(const CUtensorMap* tm, int c0, int c1, uint32_t src) {
  asm volatile("cp.async.bulk.tensor.2d.global.shared::cta.bulk_group [%0, {%1, %2}], [%3];" :: "l"(tm), "r"(c0), "r"(c1), "r"(src) : "memory");
}
__device__ __forceinline__ void bulk_done() { asm volatile("cp.async.bulk.commit_group;\ncp.async.bulk.wait_group 0;\nfence.proxy.async.global;" ::: "memory"); }
__device__ __forceinline__ void sts32(uint32_t a, uint32_t x) { asm volatile("st.shared.b32 [%0], %1;" :: "r"(a), "r"(x) : "memory"); }
__device__ __forceinline__ void prefetch_l2(const void* src, int bytes) {
  asm volatile("cp.async.bulk.prefetch.L2.global [%0], %1;" :: "l"(src), "r"(bytes) : "memory");
}
__device__ __forceinline__ void prefetch_tma2d(const CUtensorMap* tm, int c0, int c1) {
  asm volatile("cp.async.bulk.prefetch.tensor.2d.L2.global [%0, {%1, %2}];" :: "l"(tm), "r"(c0), "r"(c1) : "memory");
}
__device__ __forceinline__ uint64_t mkdesc(uint32_t addr, uint32_t lbo, uint32_t sbo, uint32_t mode) {
  return (uint64_t)((addr & 0x3FFFF) >> 4) | ((uint64_t)(lbo >> 4) << 16) | ((uint64_t)(sbo >> 4) << 32) | ((uint64_t)mode << 62);
}
__device__ __forceinline__ void wg_fence() { asm volatile("wgmma.fence.sync.aligned;" ::: "memory"); }
__device__ __forceinline__ void wg_commit() { asm volatile("wgmma.commit_group.sync.aligned;" ::: "memory"); }
template <int N> __device__ __forceinline__ void wg_wait() { asm volatile("wgmma.wait_group.sync.aligned %0;" :: "n"(N) : "memory"); }
template <int N> __device__ __forceinline__ void keep(float (&d)[N]) {
#pragma unroll
  for (int i = 0; i < N; i++) asm volatile("" : "+f"(d[i]) :: "memory");
}
__device__ __forceinline__ uint32_t pack_bf16(float lo, float hi) { uint32_t r; asm("cvt.rn.bf16x2.f32 %0, %1, %2;" : "=r"(r) : "f"(hi), "f"(lo)); return r; }
__device__ __forceinline__ float bf16_round(float v) { return __bfloat162float(__float2bfloat16_rn(v)); }
__device__ __forceinline__ void sts128(uint32_t a, uint32_t x, uint32_t y, uint32_t z, uint32_t w) { asm volatile("st.shared.v4.b32 [%0], {%1,%2,%3,%4};" :: "r"(a), "r"(x), "r"(y), "r"(z), "r"(w) : "memory"); }
__device__ __forceinline__ float4 lds128f(uint32_t a) { float4 v; asm volatile("ld.shared.v4.f32 {%0,%1,%2,%3}, [%4];" : "=f"(v.x), "=f"(v.y), "=f"(v.z), "=f"(v.w) : "r"(a) : "memory"); return v; }

__device__ __forceinline__ uint2 lds64(uint32_t a) { uint2 v; asm volatile("ld.shared.v2.b32 {%0,%1}, [%2];" : "=r"(v.x), "=r"(v.y) : "r"(a) : "memory"); return v; }
__device__ __forceinline__ float bf_lo(uint32_t w) { return __uint_as_float(w << 16); }
__device__ __forceinline__ float bf_hi(uint32_t w) { return __uint_as_float(w & 0xffff0000u); }
__device__ __forceinline__ uint32_t opaque(uint32_t v) { asm volatile("" : "+r"(v)); return v; }
__device__ __forceinline__ uint4 ldg128(const void* p) { uint4 v; asm volatile("ld.global.nc.v4.b32 {%0,%1,%2,%3}, [%4];" : "=r"(v.x), "=r"(v.y), "=r"(v.z), "=r"(v.w) : "l"(p)); return v; }
__device__ __forceinline__ void stg128(void* p, uint32_t x, uint32_t y, uint32_t z, uint32_t w) { asm volatile("st.global.v4.b32 [%0], {%1,%2,%3,%4};" :: "l"(p), "r"(x), "r"(y), "r"(z), "r"(w) : "memory"); }
__device__ __forceinline__ void stg128_l2(void* p, uint32_t x, uint32_t y, uint32_t z, uint32_t w) { asm volatile("st.relaxed.gpu.global.v4.b32 [%0], {%1,%2,%3,%4};" :: "l"(p), "r"(x), "r"(y), "r"(z), "r"(w) : "memory"); }
__device__ __forceinline__ uint2 ldg64_l2(const void* p) { uint2 v; asm volatile("ld.relaxed.gpu.global.v2.b32 {%0,%1}, [%2];" : "=r"(v.x), "=r"(v.y) : "l"(p) : "memory"); return v; }
__device__ __forceinline__ void ldg128_l2(uint32_t (&v)[4], const void* p) { asm volatile("ld.relaxed.gpu.global.v4.b32 {%0,%1,%2,%3}, [%4];" : "=r"(v[0]), "=r"(v[1]), "=r"(v[2]), "=r"(v[3]) : "l"(p) : "memory"); }
__device__ __forceinline__ uint4 lds128(uint32_t a) { uint4 v; asm volatile("ld.shared.v4.b32 {%0,%1,%2,%3}, [%4];" : "=r"(v.x), "=r"(v.y), "=r"(v.z), "=r"(v.w) : "r"(a) : "memory"); return v; }
__device__ __forceinline__ uint32_t lds16(uint32_t a) { uint32_t v; asm volatile("ld.shared.u16 %0, [%1];" : "=r"(v) : "r"(a) : "memory"); return v; }
__device__ __forceinline__ void sts64(uint32_t a, uint32_t x, uint32_t y) { asm volatile("st.shared.v2.b32 [%0], {%1,%2};" :: "r"(a), "r"(x), "r"(y) : "memory"); }
template <int TB> __device__ __forceinline__ void wgmma_rs_128(float (&d)[64], const uint32_t (&a)[4], uint64_t db, int sc) {
  asm volatile("{\n.reg .pred p;\nsetp.ne.b32 p, %69, 0;\n"
    "wgmma.mma_async.sync.aligned.m64n128k16.f32.bf16.bf16 {%0, %1, %2, %3, %4, %5, %6, %7, %8, %9, %10, %11, %12, %13, %14, %15, %16, %17, %18, %19, %20, %21, %22, %23, %24, %25, %26, %27, %28, %29, %30, %31, %32, %33, %34, %35, %36, %37, %38, %39, %40, %41, %42, %43, %44, %45, %46, %47, %48, %49, %50, %51, %52, %53, %54, %55, %56, %57, %58, %59, %60, %61, %62, %63}, {%64, %65, %66, %67}, %68, p, 1, 1, %70;\n}\n"
    : "+f"(d[0]), "+f"(d[1]), "+f"(d[2]), "+f"(d[3]), "+f"(d[4]), "+f"(d[5]), "+f"(d[6]), "+f"(d[7]), "+f"(d[8]), "+f"(d[9]), "+f"(d[10]), "+f"(d[11]), "+f"(d[12]), "+f"(d[13]), "+f"(d[14]), "+f"(d[15]), "+f"(d[16]), "+f"(d[17]), "+f"(d[18]), "+f"(d[19]), "+f"(d[20]), "+f"(d[21]), "+f"(d[22]), "+f"(d[23]), "+f"(d[24]), "+f"(d[25]), "+f"(d[26]), "+f"(d[27]), "+f"(d[28]), "+f"(d[29]), "+f"(d[30]), "+f"(d[31]), "+f"(d[32]), "+f"(d[33]), "+f"(d[34]), "+f"(d[35]), "+f"(d[36]), "+f"(d[37]), "+f"(d[38]), "+f"(d[39]), "+f"(d[40]), "+f"(d[41]), "+f"(d[42]), "+f"(d[43]), "+f"(d[44]), "+f"(d[45]), "+f"(d[46]), "+f"(d[47]), "+f"(d[48]), "+f"(d[49]), "+f"(d[50]), "+f"(d[51]), "+f"(d[52]), "+f"(d[53]), "+f"(d[54]), "+f"(d[55]), "+f"(d[56]), "+f"(d[57]), "+f"(d[58]), "+f"(d[59]), "+f"(d[60]), "+f"(d[61]), "+f"(d[62]), "+f"(d[63])
    : "r"(a[0]), "r"(a[1]), "r"(a[2]), "r"(a[3]), "l"(db), "r"(sc), "n"(TB));
}
template <int TB> __device__ __forceinline__ void wgmma_rs_64(float (&d)[32], const uint32_t (&a)[4], uint64_t db, int sc) {
  asm volatile("{\n.reg .pred p;\nsetp.ne.b32 p, %37, 0;\n"
    "wgmma.mma_async.sync.aligned.m64n64k16.f32.bf16.bf16 {%0, %1, %2, %3, %4, %5, %6, %7, %8, %9, %10, %11, %12, %13, %14, %15, %16, %17, %18, %19, %20, %21, %22, %23, %24, %25, %26, %27, %28, %29, %30, %31}, {%32, %33, %34, %35}, %36, p, 1, 1, %38;\n}\n"
    : "+f"(d[0]), "+f"(d[1]), "+f"(d[2]), "+f"(d[3]), "+f"(d[4]), "+f"(d[5]), "+f"(d[6]), "+f"(d[7]), "+f"(d[8]), "+f"(d[9]), "+f"(d[10]), "+f"(d[11]), "+f"(d[12]), "+f"(d[13]), "+f"(d[14]), "+f"(d[15]), "+f"(d[16]), "+f"(d[17]), "+f"(d[18]), "+f"(d[19]), "+f"(d[20]), "+f"(d[21]), "+f"(d[22]), "+f"(d[23]), "+f"(d[24]), "+f"(d[25]), "+f"(d[26]), "+f"(d[27]), "+f"(d[28]), "+f"(d[29]), "+f"(d[30]), "+f"(d[31])
    : "r"(a[0]), "r"(a[1]), "r"(a[2]), "r"(a[3]), "l"(db), "r"(sc), "n"(TB));
}
template <int TB> __device__ __forceinline__ void wgmma_rs_56(float (&d)[28], const uint32_t (&a)[4], uint64_t db, int sc) {
  asm volatile("{\n.reg .pred p;\nsetp.ne.b32 p, %33, 0;\n"
    "wgmma.mma_async.sync.aligned.m64n56k16.f32.bf16.bf16 {%0, %1, %2, %3, %4, %5, %6, %7, %8, %9, %10, %11, %12, %13, %14, %15, %16, %17, %18, %19, %20, %21, %22, %23, %24, %25, %26, %27}, {%28, %29, %30, %31}, %32, p, 1, 1, %34;\n}\n"
    : "+f"(d[0]), "+f"(d[1]), "+f"(d[2]), "+f"(d[3]), "+f"(d[4]), "+f"(d[5]), "+f"(d[6]), "+f"(d[7]), "+f"(d[8]), "+f"(d[9]), "+f"(d[10]), "+f"(d[11]), "+f"(d[12]), "+f"(d[13]), "+f"(d[14]), "+f"(d[15]), "+f"(d[16]), "+f"(d[17]), "+f"(d[18]), "+f"(d[19]), "+f"(d[20]), "+f"(d[21]), "+f"(d[22]), "+f"(d[23]), "+f"(d[24]), "+f"(d[25]), "+f"(d[26]), "+f"(d[27])
    : "r"(a[0]), "r"(a[1]), "r"(a[2]), "r"(a[3]), "l"(db), "r"(sc), "n"(TB));
}
template <int TB> __device__ __forceinline__ void wgmma_rs_112(float (&d)[56], const uint32_t (&a)[4], uint64_t db, int sc) {
  asm volatile("{\n.reg .pred p;\nsetp.ne.b32 p, %61, 0;\n"
    "wgmma.mma_async.sync.aligned.m64n112k16.f32.bf16.bf16 {%0, %1, %2, %3, %4, %5, %6, %7, %8, %9, %10, %11, %12, %13, %14, %15, %16, %17, %18, %19, %20, %21, %22, %23, %24, %25, %26, %27, %28, %29, %30, %31, %32, %33, %34, %35, %36, %37, %38, %39, %40, %41, %42, %43, %44, %45, %46, %47, %48, %49, %50, %51, %52, %53, %54, %55}, {%56, %57, %58, %59}, %60, p, 1, 1, %62;\n}\n"
    : "+f"(d[0]), "+f"(d[1]), "+f"(d[2]), "+f"(d[3]), "+f"(d[4]), "+f"(d[5]), "+f"(d[6]), "+f"(d[7]), "+f"(d[8]), "+f"(d[9]), "+f"(d[10]), "+f"(d[11]), "+f"(d[12]), "+f"(d[13]), "+f"(d[14]), "+f"(d[15]), "+f"(d[16]), "+f"(d[17]), "+f"(d[18]), "+f"(d[19]), "+f"(d[20]), "+f"(d[21]), "+f"(d[22]), "+f"(d[23]), "+f"(d[24]), "+f"(d[25]), "+f"(d[26]), "+f"(d[27]), "+f"(d[28]), "+f"(d[29]), "+f"(d[30]), "+f"(d[31]), "+f"(d[32]), "+f"(d[33]), "+f"(d[34]), "+f"(d[35]), "+f"(d[36]), "+f"(d[37]), "+f"(d[38]), "+f"(d[39]), "+f"(d[40]), "+f"(d[41]), "+f"(d[42]), "+f"(d[43]), "+f"(d[44]), "+f"(d[45]), "+f"(d[46]), "+f"(d[47]), "+f"(d[48]), "+f"(d[49]), "+f"(d[50]), "+f"(d[51]), "+f"(d[52]), "+f"(d[53]), "+f"(d[54]), "+f"(d[55])
    : "r"(a[0]), "r"(a[1]), "r"(a[2]), "r"(a[3]), "l"(db), "r"(sc), "n"(TB));
}
template <int TA, int TB> __device__ __forceinline__ void wgmma_ss_56(float (&d)[28], uint64_t da, uint64_t db, int sc) {
  asm volatile("{\n.reg .pred p;\nsetp.ne.b32 p, %30, 0;\n"
    "wgmma.mma_async.sync.aligned.m64n56k16.f32.bf16.bf16 {%0, %1, %2, %3, %4, %5, %6, %7, %8, %9, %10, %11, %12, %13, %14, %15, %16, %17, %18, %19, %20, %21, %22, %23, %24, %25, %26, %27}, %28, %29, p, 1, 1, %31, %32;\n}\n"
    : "+f"(d[0]), "+f"(d[1]), "+f"(d[2]), "+f"(d[3]), "+f"(d[4]), "+f"(d[5]), "+f"(d[6]), "+f"(d[7]), "+f"(d[8]), "+f"(d[9]), "+f"(d[10]), "+f"(d[11]), "+f"(d[12]), "+f"(d[13]), "+f"(d[14]), "+f"(d[15]), "+f"(d[16]), "+f"(d[17]), "+f"(d[18]), "+f"(d[19]), "+f"(d[20]), "+f"(d[21]), "+f"(d[22]), "+f"(d[23]), "+f"(d[24]), "+f"(d[25]), "+f"(d[26]), "+f"(d[27])
    : "l"(da), "l"(db), "r"(sc), "n"(TA), "n"(TB));
}

__device__ __forceinline__ uint32_t cis(float a) { return pack_bf16(__cosf(a), __sinf(a)); }

typedef __nv_bfloat162 b2;
struct c2 { b2 x, y; };
__device__ __forceinline__ b2 as_b2(uint32_t u) { return *reinterpret_cast<b2*>(&u); }
__device__ __forceinline__ uint32_t as_u(b2 v) { return *reinterpret_cast<uint32_t*>(&v); }
__device__ __forceinline__ c2 mk(b2 x, b2 y) { c2 r; r.x = x; r.y = y; return r; }
__device__ __forceinline__ c2 cmul(c2 a, b2 wr, b2 wi) { return mk(__hfma2(a.x, wr, __hneg2(__hmul2(a.y, wi))), __hfma2(a.x, wi, __hmul2(a.y, wr))); }
__device__ __forceinline__ void fft4(c2& a0, c2& a1, c2& a2, c2& a3) {
  c2 t0 = mk(__hadd2(a0.x, a2.x), __hadd2(a0.y, a2.y)), t1 = mk(__hsub2(a0.x, a2.x), __hsub2(a0.y, a2.y));
  c2 t2 = mk(__hadd2(a1.x, a3.x), __hadd2(a1.y, a3.y)), t3 = mk(__hsub2(a1.x, a3.x), __hsub2(a1.y, a3.y));
  a0 = mk(__hadd2(t0.x, t2.x), __hadd2(t0.y, t2.y)); a2 = mk(__hsub2(t0.x, t2.x), __hsub2(t0.y, t2.y));
  a1 = mk(__hadd2(t1.x, t3.y), __hsub2(t1.y, t3.x)); a3 = mk(__hsub2(t1.x, t3.y), __hadd2(t1.y, t3.x));
}
__device__ __forceinline__ void fft4_s2(c2& a0, c2& a1, c2& a2, c2& a3, b2 r) {
  const b2 nr = __hneg2(r);
  c2 t0 = mk(__hfma2(a2.x, r, a0.x), __hfma2(a2.y, r, a0.y)), t1 = mk(__hfma2(a2.x, nr, a0.x), __hfma2(a2.y, nr, a0.y));
  c2 t2 = mk(__hadd2(a1.x, a3.x), __hadd2(a1.y, a3.y)), t3 = mk(__hsub2(a1.x, a3.x), __hsub2(a1.y, a3.y));
  a0 = mk(__hadd2(t0.x, t2.x), __hadd2(t0.y, t2.y)); a2 = mk(__hsub2(t0.x, t2.x), __hsub2(t0.y, t2.y));
  a1 = mk(__hadd2(t1.x, t3.y), __hsub2(t1.y, t3.x)); a3 = mk(__hsub2(t1.x, t3.y), __hadd2(t1.y, t3.x));
}
__device__ __forceinline__ void fft4_s13(c2& a0, c2& a1, c2& a2, c2& a3, b2 r) {
  const b2 nr = __hneg2(r);
  c2 t0 = mk(__hadd2(a0.x, a2.x), __hadd2(a0.y, a2.y)), t1 = mk(__hsub2(a0.x, a2.x), __hsub2(a0.y, a2.y));
  c2 t2 = mk(__hadd2(a1.x, a3.x), __hadd2(a1.y, a3.y)), t3 = mk(__hsub2(a1.x, a3.x), __hsub2(a1.y, a3.y));
  a0 = mk(__hfma2(t2.x, r, t0.x), __hfma2(t2.y, r, t0.y)); a2 = mk(__hfma2(t2.x, nr, t0.x), __hfma2(t2.y, nr, t0.y));
  a1 = mk(__hfma2(t3.y, r, t1.x), __hfma2(t3.x, nr, t1.y)); a3 = mk(__hfma2(t3.y, nr, t1.x), __hfma2(t3.x, r, t1.y));
}
__device__ __forceinline__ c2 rot1(c2 a) { return mk(__hadd2(a.x, a.y), __hsub2(a.y, a.x)); }
__device__ __forceinline__ c2 rot3(c2 a) { return mk(__hsub2(a.y, a.x), __hneg2(__hadd2(a.x, a.y))); }
__device__ __forceinline__ c2 mul_mi(c2 a) { return mk(a.y, __hneg2(a.x)); }
template <int O> __device__ __forceinline__ void fft8(c2 (&v)[16]) {
  const b2 r = as_b2(0x3F353F35u), nr = as_b2(0xBF35BF35u);
  fft4(v[O], v[O + 4], v[O + 8], v[O + 12]);
  fft4(v[O + 2], v[O + 6], v[O + 10], v[O + 14]);
  const c2 o0 = v[O + 2], o1 = rot1(v[O + 6]), o2 = v[O + 10], o3 = rot1(v[O + 14]);
  const c2 e0 = v[O], e1 = v[O + 4], e2 = v[O + 8], e3 = v[O + 12];
  v[O] = mk(__hadd2(e0.x, o0.x), __hadd2(e0.y, o0.y));              v[O + 8] = mk(__hsub2(e0.x, o0.x), __hsub2(e0.y, o0.y));
  v[O + 2] = mk(__hfma2(o1.x, r, e1.x), __hfma2(o1.y, r, e1.y));    v[O + 10] = mk(__hfma2(o1.x, nr, e1.x), __hfma2(o1.y, nr, e1.y));
  v[O + 4] = mk(__hadd2(e2.x, o2.y), __hsub2(e2.y, o2.x));          v[O + 12] = mk(__hsub2(e2.x, o2.y), __hadd2(e2.y, o2.x));
  v[O + 6] = mk(__hfma2(o3.y, r, e3.x), __hfma2(o3.x, nr, e3.y));   v[O + 14] = mk(__hfma2(o3.y, nr, e3.x), __hfma2(o3.x, r, e3.y));
}
__device__ __forceinline__ void fft16(c2 (&v)[16]) {
  const b2 r = as_b2(0x3F353F35u), c1 = as_b2(0x3F6D3F6Du), s1 = as_b2(0x3EC43EC4u), nc1 = as_b2(0xBF6DBF6Du), ns1 = as_b2(0xBEC4BEC4u);
#pragma unroll
  for (int a = 0; a < 4; a++) fft4(v[a], v[a + 4], v[a + 8], v[a + 12]);
  v[5] = cmul(v[5], c1, ns1); v[6] = rot1(v[6]); v[7] = cmul(v[7], s1, nc1);
  v[9] = rot1(v[9]); v[10] = mul_mi(v[10]); v[11] = rot3(v[11]);
  v[13] = cmul(v[13], s1, nc1); v[14] = rot3(v[14]); v[15] = cmul(v[15], nc1, s1);
  fft4(v[0], v[1], v[2], v[3]); fft4_s2(v[4], v[5], v[6], v[7], r); fft4_s13(v[8], v[9], v[10], v[11], r); fft4_s2(v[12], v[13], v[14], v[15], r);
  c2 t;
  t = v[1]; v[1] = v[4]; v[4] = t;  t = v[2]; v[2] = v[8]; v[8] = t;  t = v[3]; v[3] = v[12]; v[12] = t;
  t = v[6]; v[6] = v[9]; v[9] = t;  t = v[7]; v[7] = v[13]; v[13] = t; t = v[11]; v[11] = v[14]; v[14] = t;
}

__device__ __forceinline__ void columns(c2 (&v)[16], uint32_t sb, int t) {
  const int l16 = t & 15;
  const uint32_t row = sb + OFF_EXCH + (t >> 4) * 2304;
  const uint32_t pos = sb + OFF_EXCH + (t >> 3) * 144 + (t & 7) * 16;
#pragma unroll 1
  for (int ps = 0; ps < 6; ps++) {
    if (ps == 0 || ps == 5) { fft8<0>(v); fft8<1>(v); } else fft16(v);
    if (ps == 5) break;
    if (ps == 2) {
      const uint32_t ws = sb + OFF_WS + (l16 >> 1) * 128 + ((((t >> 4) + (l16 >> 1)) & 7) * 2 + (l16 & 1)) * 8;
      mbar_wait(sb + OFF_BAR + B_WFULL * 8, 0);
#pragma unroll
      for (int q = 0; q < 16; q++) {
        const uint2 w = lds64(ws + q * 1024);
        const c2 z = cmul(v[q], as_b2(w.x), as_b2(w.y));
        v[q] = mk(z.y, z.x);
      }
      continue;
    }
    {
      const bool full = ps == 0 || ps == 4;
      const uint32_t tw = sb + OFF_TW + (full ? ps * 2048 + t * 16 : 16384 + l16 * 16);
      const uint32_t st = full ? 2048 : 256;
#pragma unroll
      for (int i = 0; i < 4; i++) {
        const uint4 w4 = lds128(tw + i * st);
        const uint32_t w[4] = {w4.x, w4.y, w4.z, w4.w};
#pragma unroll
        for (int e = 0; e < 4; e++) v[4 * i + e] = cmul(v[4 * i + e], __low2bfloat162(as_b2(w[e])), __high2bfloat162(as_b2(w[e])));
      }
    }
    if (ps == 0) {
      mbar_wait(sb + OFF_BAR + B_XDONE * 8, 1);
#pragma unroll
      for (int q = 0; q < 8; q++) sts128(pos + q * 2304, as_u(v[2 * q].x), as_u(v[2 * q].y), as_u(v[2 * q + 1].x), as_u(v[2 * q + 1].y));
      bar_sync<3, 128>();
#pragma unroll
      for (int q = 0; q < 16; q++) { const uint2 a = lds64(row + q * 144 + l16 * 8); v[q] = mk(as_b2(a.x), as_b2(a.y)); }
    } else {
      __syncwarp();
#pragma unroll
      for (int q = 0; q < 16; q++) sts64(row + q * 144 + l16 * 8, as_u(v[q].x), as_u(v[q].y));
      if (ps == 4) bar_sync<3, 128>(); else __syncwarp();
      const uint32_t src = ps == 4 ? pos : row + l16 * 144, st = ps == 4 ? 2304 : 16;
#pragma unroll
      for (int q = 0; q < 8; q++) { const uint4 a = lds128(src + q * st); v[2 * q] = mk(as_b2(a.x), as_b2(a.y)); v[2 * q + 1] = mk(as_b2(a.z), as_b2(a.w)); }
    }
  }
}

template <int NH> __device__ __forceinline__ void h_epilogue(float (&acc)[NH * 8], unsigned char* gdst, uint32_t tag) {
#pragma unroll
  for (int c = 0; c < NH / 2; c++) {
    uint32_t pk[4];
#pragma unroll
    for (int i = 0; i < 4; i++) {
      float hv[2];
#pragma unroll
      for (int e = 0; e < 2; e++) {
        float hg = 0.5f * acc[c * 8 + i * 2 + e], up = acc[NH * 4 + c * 8 + i * 2 + e];
        float th; asm("tanh.approx.f32 %0, %1;" : "=f"(th) : "f"(hg));
        hv[e] = fmaf(hg, th, hg) * up;
      }
      pk[i] = pack_bf16(hv[0], hv[1]);
    }
    stg128_l2(gdst + c * 4096, (pk[0] & ~1u) | tag, pk[1], pk[2], pk[3]);
  }
}

__device__ __forceinline__ void frag_ready(uint32_t (&a)[4], uint32_t (&b)[4], uint32_t (&c)[4], uint32_t (&d)[4], const unsigned char* p, uint32_t tag) {
  asm volatile("{\n.reg .pred p;\n.reg .u32 c, m, q;\nmov.u32 c, 0;\nL_TRY:\n"
               "lop3.b32 m, %0, %4, %17, 0x7E;\nlop3.b32 q, %8, %12, %17, 0x7E;\nlop3.b32 m, m, q, 1, 0xA8;\nsetp.ne.u32 p, m, 0;\n"
               "vote.sync.any.pred p, p, 0xffffffff;\n@!p bra.uni L_OK;\n"
               "ld.relaxed.gpu.global.v4.b32 {%0,%1,%2,%3}, [%16];\nld.relaxed.gpu.global.v4.b32 {%4,%5,%6,%7}, [%16+4096];\n"
               "ld.relaxed.gpu.global.v4.b32 {%8,%9,%10,%11}, [%16+8192];\nld.relaxed.gpu.global.v4.b32 {%12,%13,%14,%15}, [%16+12288];\n"
               "add.u32 c, c, 1;\nsetp.lt.u32 p, c, 262144;\n@p bra.uni L_TRY;\ntrap;\nL_OK:\n}"
               : "+r"(a[0]), "+r"(a[1]), "+r"(a[2]), "+r"(a[3]), "+r"(b[0]), "+r"(b[1]), "+r"(b[2]), "+r"(b[3]),
                 "+r"(c[0]), "+r"(c[1]), "+r"(c[2]), "+r"(c[3]), "+r"(d[0]), "+r"(d[1]), "+r"(d[2]), "+r"(d[3])
               : "l"(p), "r"(tag) : "memory");
}

#define MAP 0
#define LEAD2 0
#define LEAD1 3

__global__ void __cluster_dims__(2, 1, 1) __launch_bounds__(NTHREADS, 1)
fused_kernel(const __grid_constant__ CUtensorMap tm_x, const __grid_constant__ CUtensorMap tm_g, const __grid_constant__ CUtensorMap tm_u,
             const __grid_constant__ CUtensorMap tm_g32, const __grid_constant__ CUtensorMap tm_u32, const __grid_constant__ CUtensorMap tm_d,
             const __grid_constant__ CUtensorMap tm_s,
             const __nv_bfloat16* __restrict__ w_r, const __nv_bfloat16* __restrict__ w_i,
             const __nv_bfloat16* __restrict__ w_gate, const __nv_bfloat16* __restrict__ w_up,
             const __nv_bfloat16* __restrict__ w_down, const __nv_bfloat16* __restrict__ gate_w, __nv_bfloat16* __restrict__ out) {
  extern __shared__ __align__(1024) unsigned char smem[];
  const uint32_t sb = s2u(smem);
  const uint32_t bars = sb + OFF_BAR;
  const int tid = threadIdx.x, warp = __shfl_sync(0xffffffffu, tid >> 5, 0), lane = tid & 31;
  const int cl = blockIdx.x >> 1, kh = blockIdx.x & 1;
  const int n0 = cl < 4 ? cl : (cl < 36 ? (cl - 4) >> 3 : (cl - 36) / 7);
  const int m0 = cl < 4 ? 15 : (cl < 36 ? (cl - 4) & 7 : cl - 28 - 7 * n0);
  const int n = MAP == 0 ? n0 : (MAP == 1 ? (m0 & 3) : ((n0 & 1) | ((m0 & 1) << 1)));
  const int m = MAP == 0 ? m0 : (MAP == 1 ? ((m0 & 12) | n0) : ((m0 & 14) | (n0 >> 1)));
  const int j = kh * 4 + n, bid = m * 8 + n * 2 + kh;

  const int c64 = 224 * j + (j & 1) * 32;
  if (warp < 8) {
    asm volatile("setmaxnreg.inc.sync.aligned.u32 208;");
    const int wg = warp >> 2, w4 = warp & 3, g = lane >> 2, t = lane & 3;
    const int rh = wg ^ kh ^ 1;
    const int p = j & 1, r = (j >> 1) & 1, hh = j >> 2;
    const uint32_t epoch = ld_relaxed(&g_ep[bid]);
    if ((tid & 127) == 0) PROF(wg, 30);
#pragma unroll 1
    for (int it = tid; it < 392; it += 256) {
      const int kc = it / 28, sg = it - kc * 28;
      const int k = 2 * (28 * hh + sg) + r;
      const float kf = (float)k * (-6.283185307179586f / 448.0f), a0 = (float)(16 * kc + p) * kf;
      uint32_t c[4], s[4];
#pragma unroll
      for (int q = 0; q < 4; q++) {
        const float a1 = fmaf((float)(2 * q), kf, a0), a2 = fmaf((float)(2 * q + 8), kf, a0);
        c[q] = pack_bf16(__cosf(a1), __cosf(a2)); s[q] = pack_bf16(__sinf(a1), __sinf(a2));
        if (k == 0) s[q] = ((q ^ p) & 1) ? 0xBF80BF80u : 0x3F803F80u;
      }
      const uint32_t a = sb + 6 * SLOT + (kc * 56 + 2 * sg) * 16;
      sts128(a, c[0], c[1], c[2], c[3]);
      sts128(a + 16, s[0], s[1], s[2], s[3]);
    }
    if ((tid & 127) == 0) PROF(wg, 31);
    fence_async_smem();
    bar_sync<0, NTHREADS - 64>();
    asm volatile("barrier.cluster.arrive.relaxed.aligned;" ::: "memory");
    if ((tid & 127) == 0) PROF(wg, 1);

    uint32_t xa[28][4];
    {
      const uint32_t xb = sb + OFF_PQ + wg * HALF_XR + (w4 * 16 + (lane & 15)) * 128;
      mbar_wait(bars + (B_XFULL + wg) * 8, 0);
      if ((tid & 127) == 0) PROF(wg, 2);
#pragma unroll
      for (int kb = 0; kb < 7; kb++) {
#pragma unroll
        for (int kk = 0; kk < 4; kk++) {
          uint32_t a = xb + kb * 8192 + (((2 * kk + (lane >> 4)) ^ (lane & 7)) << 4);
          asm volatile("ldmatrix.sync.aligned.m8n8.x4.shared.b16 {%0,%1,%2,%3}, [%4];"
                       : "=r"(xa[kb * 4 + kk][0]), "=r"(xa[kb * 4 + kk][1]), "=r"(xa[kb * 4 + kk][2]), "=r"(xa[kb * 4 + kk][3]) : "r"(a) : "memory");
        }
      }
    }
    {
      uint32_t ad[7][4];
      const uint32_t sel = p ? 0x7632 : 0x5410;
      const uint32_t sgn = r ? 0xBF80BF80u : 0x3F803F80u;
#pragma unroll
      for (int jj = 0; jj < 7; jj++) {
#pragma unroll
        for (int i = 0; i < 4; i++) {
          int ks = 2 * jj + (i >> 1), rr = i & 1;
          uint32_t lo = __byte_perm(xa[ks][rr], xa[ks][rr + 2], sel);
          uint32_t hi = __byte_perm(xa[ks + 14][rr], xa[ks + 14][rr + 2], sel);
          asm("fma.rn.bf16x2 %0, %1, %2, %3;" : "=r"(ad[jj][i]) : "r"(hi), "r"(sgn), "r"(lo));
        }
      }
      __syncwarp();
      if (lane == 0) mbar_arrive(bars + (B_XFREE + wg) * 8);
      float acc[28];
      wg_fence();
      uint64_t db = mkdesc(sb + 6 * SLOT, 896, 128, 0);
#pragma unroll
      for (int jj = 0; jj < 7; jj++) wgmma_rs_56<0>(acc, ad[jj], db + jj * 112, jj != 0);
      wg_commit();
      wg_wait<0>(); keep(acc);
      if (lane == 0) mbar_arrive(bars + (B_EMPTY + 6) * 8);
      const uint32_t xc = sb + OFF_EXCH + wg * 8192 + t * 256 + w4 * 64 + g * 4;
      mbar_wait(bars + B_XFREE * 8, 0);
#pragma unroll
      for (int i = 0; i < 7; i++) {
        sts32(xc + i * 1024, pack_bf16(acc[4 * i], acc[4 * i + 1]));
        sts32(xc + i * 1024 + 32, pack_bf16(acc[4 * i + 2], acc[4 * i + 3]));
      }
      fence_async_smem();
      __syncwarp();
      if (lane == 0) mbar_arrive(bars + B_PUBX * 8);
    }
    if ((tid & 127) == 0) PROF(wg, 3);
    const uint32_t tag = ~epoch & 1;
    unsigned char* const hbase = g_H + (size_t)(m * 2 + kh) * (56 * 4096) + rh * 2048 + (tid & 127) * 16;
#pragma unroll 1
    for (int u = 0; u < 3; u++) {
      float acc[64];
      if (wg == 1) { if (u & 1) bar_sync<6, 256>(); else bar_sync<2, 256>(); }
      const uint32_t sbu = opaque(sb);
#pragma unroll
      for (int kb = 0; kb < 7; kb++) {
        mbar_wait(sbu + OFF_BAR + (B_FULL + kb) * 8, u & 1);
        wg_fence();
        uint64_t db = mkdesc(sbu + kb * SLOT, 8192, 1024, 1);
#pragma unroll
        for (int kk = 0; kk < 4; kk++) wgmma_rs_128<1>(acc, xa[kb * 4 + kk], db + kk * 128, (kb | kk) != 0);
        wg_commit();
        if (kb == LEAD1 && wg == 0) { if (u & 1) bar_arrive<6, 256>(); else bar_arrive<2, 256>(); }
        if (kb > 0) { wg_wait<1>(); if (lane == 0) mbar_arrive(sbu + OFF_BAR + (B_EMPTY + kb - 1) * 8); }
      }
      wg_wait<0>(); keep(acc);
      if (lane == 0) mbar_arrive(sbu + OFF_BAR + (B_EMPTY + 6) * 8);
      if ((tid & 127) == 0) PROF(wg, 4 + 2 * u);
      h_epilogue<8>(acc, hbase + (u * 16 + n * 4) * 4096, tag);
      if ((tid & 127) == 0) PROF(wg, 5 + 2 * u);
    }
    uint32_t ha[14][4][4];
    auto check = [&](int b0, int b1) {
#pragma unroll
      for (int b = b0; b < b1; b++) frag_ready(ha[b][0], ha[b][1], ha[b][2], ha[b][3], hbase + b * 16384, tag);
    };
    auto load = [&](int b0, int b1) {
#pragma unroll
      for (int i = b0; i < b1; i++) ldg128_l2(ha[i >> 2][i & 3], hbase + i * 4096);
    };
    {
      float acc[32];
      load(0, 3);
      if (wg == 1) bar_sync<6, 256>();
      const uint32_t sbu = opaque(sb);
#pragma unroll
      for (int it = 0; it < 4; it++) {
        mbar_wait(sbu + OFF_BAR + (B_FULL + it) * 8, 1);
        wg_fence();
        uint64_t db = mkdesc(sbu + it * SLOT, 8192, 512, 2);
#pragma unroll
        for (int kk = 0; kk < 8; kk++) if (it * 8 + kk < 28) wgmma_rs_64<1>(acc, xa[it * 8 + kk], db + kk * 64, (it | kk) != 0);
        wg_commit();
        if (it == 2 && wg == 0) bar_arrive<6, 256>();
        if (it > 0) {
          wg_wait<1>();
          if (lane == 0) mbar_arrive(sbu + OFF_BAR + (B_EMPTY + it - 1) * 8);
          if (it == 1) load(3, 11);
          if (it == 2) load(11, 16);
        }
      }
      wg_wait<0>(); keep(acc);
      if (lane == 0) mbar_arrive(sbu + OFF_BAR + (B_EMPTY + 3) * 8);
      if ((tid & 127) == 0) PROF(wg, 10);
      h_epilogue<4>(acc, hbase + (48 + n * 2) * 4096, tag);
    }
    asm volatile("barrier.cluster.wait.aligned;" ::: "memory");
    if ((tid & 127) == 0) PROF(wg, 11);

    float acc[56];
    check(0, 4);
    if (wg == 1) bar_sync<2, 256>();
#pragma unroll
    for (int b = 0; b < 14; b++) {
      if ((tid & 127) == 0) PROF(wg, 16 + b);
      if (b >= 3) mbar_wait(bars + (B_FULL + (b + 1) % 7) * 8, b < 6 || b == 13);
      else if (b == 0) mbar_wait(bars + B_RFULL * 8, 0);
      if (b == 4) check(4, 7);
      if (b == 7) check(7, 11);
      if (b == 11) check(11, 14);
      if (b == 4 || b == 7) wg_wait<0>();
      wg_fence();
      const uint64_t db = mkdesc(b < 3 ? sb + OFF_R + b * SLOT : sb + (b + 1) % 7 * SLOT, 8192, 1024, 1);
#pragma unroll
      for (int kk = 0; kk < 4; kk++) wgmma_rs_112<1>(acc, ha[b][kk], db + kk * 128, (b | kk) != 0);
      wg_commit();
      if (b == LEAD2 && wg == 0) bar_arrive<2, 256>();
      if (b == 0) load(16, 28);
      if (b == 4) load(28, 44);
      if (b == 7) load(44, 56);
      if (b > 0) wg_wait<1>();
      if (lane == 0) {
        if (b >= 4 && b <= 9) mbar_arrive(bars + (B_EMPTY + b % 7) * 8);
        if (b == 3) {
          mbar_arrive(bars + B_LFREE * 8);
          asm volatile("{\n.reg .b32 ra;\nmapa.shared::cluster.u32 ra, %0, %1;\nmbarrier.arrive.relaxed.cluster.shared::cluster.b64 _, [ra];\n}"
                       :: "r"(bars + B_RFREE * 8), "r"(kh ^ 1) : "memory");
        }
      }
    }
    const int t128 = tid & 127;
    wg_wait<0>(); keep(acc);
    if (wg == 0) {
      if (t128 == 0) PROF(wg, 12);
      mbar_wait_cluster(bars + B_RFREE * 8, 0);
      uint32_t rdst, rbar;
      asm volatile("mapa.shared::cluster.u32 %0, %1, %2;" : "=r"(rdst) : "r"(sb + OFF_R + t128 * 16), "r"(kh ^ 1));
      asm volatile("mapa.shared::cluster.u32 %0, %1, %2;" : "=r"(rbar) : "r"(bars + B_RECV * 8), "r"(kh ^ 1));
#pragma unroll
      for (int i = 0; i < 14; i++)
        asm volatile("st.async.weak.shared::cluster.mbarrier::complete_tx::bytes.v4.f32 [%0], {%1,%2,%3,%4}, [%5];"
                     :: "r"(rdst + i * 2048), "f"(acc[4 * i]), "f"(acc[4 * i + 1]), "f"(acc[4 * i + 2]), "f"(acc[4 * i + 3]), "r"(rbar) : "memory");
    } else {
      float spec[2][28];
      if (t128 == 0) PROF(wg, 12);
#pragma unroll
      for (int i = 0; i < 4; i++) {
        if (i == 0) mbar_wait(bars + B_GFULL * 8, 0);
        if (i >= 2) mbar_wait(bars + (B_FULL + i - 1) * 8, 1);
        mbar_wait(bars + (B_PQFULL + i) * 8, 0);
        if (i == 0 && t128 == 0) { PROF(wg, 13); g_ep[bid] = epoch + 1; }
        wg_fence();
        const uint64_t da = mkdesc(sb + OFF_PQ + i * 14336, 1024, 1024, 1);
        const uint64_t db = mkdesc(i < 2 ? sb + OFF_R + 28672 + i * (G_IMG / 2) : sb + (i - 1) * SLOT, 896, 128, 0);
#pragma unroll
        for (int kk = 0; kk < 7; kk++) wgmma_ss_56<1, 0>(spec[i >> 1], da + kk * 128, db + kk * 112, ((i & 1) | kk) != 0);
        wg_commit();
      }
      const float* gs = reinterpret_cast<const float*>(smem + OFF_G) + w4 * 16 + g;
      const float o0 = bf16_round(1.0f - gs[0]), o1 = bf16_round(1.0f - gs[8]);
      const float g0 = gs[0] * (1.0f / (float)(S_ * D_)), g1 = gs[8] * (1.0f / (float)(S_ * D_));
      mbar_wait_cluster(bars + B_RECV * 8, 0);
      if (t128 == 0) PROF(wg, 0);
#pragma unroll
      for (int i = 0; i < 14; i++) {
        const float4 o = lds128f(sb + OFF_R + t128 * 16 + i * 2048);
        acc[4 * i] = (acc[4 * i] + o.x) * o0; acc[4 * i + 1] = (acc[4 * i + 1] + o.y) * o0;
        acc[4 * i + 2] = (acc[4 * i + 2] + o.z) * o1; acc[4 * i + 3] = (acc[4 * i + 3] + o.w) * o1;
      }
      keep(acc);
      wg_wait<0>(); keep(spec[0]); keep(spec[1]);
      if (t128 == 0) PROF(wg, 14);
      bar_sync<5, 128>();
      const uint32_t st = sb + OFF_PQ + w4 * 3840;
#pragma unroll
      for (int i = 0; i < 7; i++) {
        uint32_t pk[4];
#pragma unroll
        for (int e = 0; e < 2; e++) {
          const int c = 2 * i + e, si = i * 4 + e;
          pk[2 * e] = pack_bf16(fmaf(g0, spec[0][si], acc[4 * c]), fmaf(g0, spec[1][si], acc[4 * c + 1]));
          pk[2 * e + 1] = pack_bf16(fmaf(g1, spec[0][si + 2], acc[4 * c + 2]), fmaf(g1, spec[1][si + 2], acc[4 * c + 3]));
        }
        asm volatile("stmatrix.sync.aligned.m8n8.x4.shared.b16 [%0], {%1,%2,%3,%4};"
                     :: "r"(st + (lane & 15) * 240 + (lane >> 4) * 16 + i * 32), "r"(pk[0]), "r"(pk[1]), "r"(pk[2]), "r"(pk[3]) : "memory");
      }
      __syncwarp();
      if (lane < 28) {
        const int r2 = lane >= 14, cc = lane - r2 * 14;
        unsigned char* ob = reinterpret_cast<unsigned char*>(out) + (size_t)(m * 128 + kh * 64 + w4 * 16 + r2) * (D_ * 2) + n * 224 + cc * 16;
        float4 v[8];
#pragma unroll
        for (int i = 0; i < 8; i++) v[i] = lds128f(st + r2 * 240 + cc * 16 + i * 480);
#pragma unroll
        for (int i = 0; i < 8; i++) stg128(ob + i * (D_ * 4), __float_as_uint(v[i].x), __float_as_uint(v[i].y), __float_as_uint(v[i].z), __float_as_uint(v[i].w));
      }
    }
    if (t128 == 0) { PROF(wg, 15); if (wg) { PROFG(4, 30); PROF(4, 31); } }
  } else if (warp < 12) {
    asm volatile("setmaxnreg.dec.sync.aligned.u32 72;");
    const int t = tid - 256;
    const int k = bid;
    if (t == 0) PROF(2, 0);
    uint4 gv[7];
#pragma unroll
    for (int i = 0; i < 7; i++) gv[i] = ldg128(reinterpret_cast<const uint4*>(gate_w) + i * 8 + (t & 7));
    if (t < 98) {
      int cid = m * 98 + t, kc = cid / 56, nn = cid - kc * 56;
      int d = 112 * n + 8 * (2 * (nn >> 3) + (nn & 1)) + (nn & 6) + kh;
      int dr = d > 224 ? d - 448 : d;
      const float df = (float)dr * (-6.283185307179586f / 448.0f);
      uint32_t pk[4];
#pragma unroll
      for (int e = 0; e < 4; e++) {
        const float a = (float)(4 * kc + e) * df;
        pk[e] = pack_bf16(2.0f * __cosf(a), 2.0f * __sinf(a));
      }
      if (kc == 0) pk[0] = (((d >> 1) ^ kh) & 1) ? 0xBF803F80u : 0x3F803F80u;
      stg128(g_G + (size_t)(n * 2 + kh) * G_IMG + cid * 16, pk[0], pk[1], pk[2], pk[3]);
    }
    bar_sync<0, NTHREADS - 64>();
    asm volatile("barrier.cluster.arrive.relaxed.aligned;" ::: "memory");
    {
      const int row = n * 16 + (t >> 3), l8 = t & 7;
      mbar_wait(bars + (B_XFULL + 1) * 8, 0);
      float sum = 0.f;
#pragma unroll
      for (int i = 0; i < 7; i++) {
        const uint4 a = lds128(sb + OFF_R + i * 8192 + row * 128 + ((l8 ^ (row & 7)) << 4));
        const uint32_t aa[4] = {a.x, a.y, a.z, a.w}, bb[4] = {gv[i].x, gv[i].y, gv[i].z, gv[i].w};
#pragma unroll
        for (int e = 0; e < 4; e++) {
          const uint32_t pr = as_u(__hmul2(as_b2(aa[e]), as_b2(bb[e])));
          sum += bf_lo(pr) + bf_hi(pr);
        }
      }
      sum += __shfl_xor_sync(0xffffffffu, sum, 1); sum += __shfl_xor_sync(0xffffffffu, sum, 2); sum += __shfl_xor_sync(0xffffffffu, sum, 4);
      if (lane == 0) mbar_arrive(bars + (B_XFREE + 1) * 8);
      if (l8 == 0) g_gate[m * 128 + kh * 64 + row] = bf16_round(__fdividef(1.0f, 1.0f + __expf(-bf16_round(sum))));
    }
    __syncwarp();
    if (lane == 0) mbar_arrive(bars + B_PUBW * 8);
    if (t == 0) PROF(2, 11);
    mbar_wait(bars + B_XFREE * 8, 0);
    if (k < 113) {
      const float u = -6.283185307179586f / 2048.0f, t2 = (float)(2 * t) * u, rr = (float)(t >> 4) * u;
#pragma unroll 1
      for (int i = 0; i < 4; i++) {
        const float q = (float)(2 * i), l = (float)((t & 15) + 64 * i);
        sts128(sb + OFF_TW + i * 2048 + t * 16, cis(t2 * q), cis((t2 + u) * q), cis(t2 * (q + 1.0f)), cis((t2 + u) * (q + 1.0f)));
        sts128(sb + OFF_TW + 8192 + i * 2048 + t * 16, cis(rr * l), cis(rr * (l + 16.0f)), cis(rr * (l + 32.0f)), cis(rr * (l + 48.0f)));
      }
      const float l = (float)((t >> 1) & 15) * (8.0f * u), jj = (float)((t >> 5) * 4 + (t & 1) * 2);
      sts64(sb + OFF_TW + 16384 + t * 8, cis(l * jj), cis(l * (jj + 1.0f)));
    }
    if (t == 0) PROF(2, 9);
    mbar_wait(bars + B_PIN * 8, 0);
    mbar_wait(bars + B_XDONE * 8, 0);
    if (t == 0) PROF(2, 4);
    {
      const uint32_t wa = sb + OFF_WS + (((t & 7) - bid) & 7) * 450 + (t >> 3) * 2, wc = wa + 448 - (t >> 3) * 4;
#pragma unroll 1
      for (int h = 0; h < 2; h++) {
        uint32_t w[4][8];
#pragma unroll
        for (int i = 0; i < 4; i++) {
#pragma unroll
          for (int e = 0; e < 4; e++) { w[i][2 * e] = lds16(wa + h * 128 + i * 32 + e * 3600); w[i][2 * e + 1] = lds16(wc - h * 128 - i * 32 + e * 3600); }
        }
#pragma unroll
        for (int i = 0; i < 4; i++)
          sts128(sb + OFF_EXCH + h * 8192 + i * 2048 + t * 16, __byte_perm(w[i][0], w[i][1], 0x5410), __byte_perm(w[i][4], w[i][5], 0x5410), __byte_perm(w[i][2], w[i][3], 0x5410), __byte_perm(w[i][6], w[i][7], 0x5410));
      }
    }
    fence_async_smem();
    __syncwarp();
    if (lane == 0) mbar_arrive(bars + B_PUBW * 8);
    bar_sync<3, 128>();
    if (k < 113) {
      if (t == 0) PROF(2, 2);
      mbar_wait(bars + B_XCFULL * 8, 0);
      if (t == 0) PROF(2, 3);
      c2 v[16];
      uint2 xe[8], xo[8];
      const int sl = k == 112 ? 0 : k, hi = sl >= 56;
      const unsigned char* xs = g_X + (192 + (sl & 1) * 64 + hi * 72 + (sl & ~1) + ((t >> 4) & 1)) * XP + (t >> 5) * 256 + (t & 15) * 8;
#pragma unroll
      for (int jj = 0; jj < 8; jj++) { xe[jj] = ldg64_l2(xs + jj * 1024); xo[jj] = ldg64_l2(xs + jj * 1024 + 128); }
      const uint32_t se = k == 0 ? 0x4410 : (k == 112 ? 0x4432 : 0x3210), so = k == 0 ? 0x4410 : (k == 112 ? 0x3244 : 0x3210);
#pragma unroll
      for (int jj = 0; jj < 8; jj++) {
        const uint2 e2 = xe[jj], o2 = xo[jj];
#pragma unroll
        for (int h = 0; h < 2; h++) {
          const b2 e = as_b2(__byte_perm(h ? e2.y : e2.x, 0, se)), o = as_b2(__byte_perm(h ? o2.y : o2.x, 0, so));
          const uint32_t s = as_u(__hadd2(e, o)), d = as_u(__hsub2(e, o)) ^ 0x80000000u;
          v[2 * jj + h] = mk(as_b2(__byte_perm(s, d, 0x5410)), as_b2(__byte_perm(s, d, 0x7632)));
        }
      }
      if (t == 0) PROF(2, 12);
      columns(v, sb, t);
      if (t == 0) PROF(2, 14);
      const int pre = (k == 112) ? 1 : 2 * k, pim = (k == 112) ? 1 : 2 * k + 1;
      const uint32_t pr = sb + OFF_EXCH + (t >> 5) * 256 + ((((lane >> 2) ^ pre) & 7) << 4) + (lane & 3) * 4;
      const uint32_t pi = sb + OFF_EXCH + 8192 + (t >> 5) * 256 + ((((lane >> 2) ^ pim) & 7) << 4) + (lane & 3) * 4;
      bar_sync<3, 128>();
#pragma unroll
      for (int jj = 0; jj < 8; jj++) {
        const b2 ar = as_b2(__byte_perm(as_u(v[2 * jj].y), as_u(v[2 * jj + 1].y), 0x5410)), br = as_b2(__byte_perm(as_u(v[2 * jj].y), as_u(v[2 * jj + 1].y), 0x7632));
        const b2 ai = as_b2(__byte_perm(as_u(v[2 * jj].x), as_u(v[2 * jj + 1].x), 0x5410)), bi = as_b2(__byte_perm(as_u(v[2 * jj].x), as_u(v[2 * jj + 1].x), 0x7632));
        sts32(pr + jj * 1024, as_u(__hadd2(ar, br)));
        sts32(pr + jj * 1024 + 128, as_u(k == 112 ? __hadd2(ai, bi) : __hsub2(ar, br)));
        sts32(pi + jj * 1024 + 128, as_u(__hadd2(ai, bi)));
        sts32(pi + jj * 1024, as_u(__hsub2(ai, bi)));
      }
      fence_async_smem();
      bar_sync<3, 128>();
      if (t == 0) {
        PROF(2, 5);
        tma_store(&tm_s, pre * 64, 0, sb + OFF_EXCH);
        if (k != 0 && k != 112) tma_store(&tm_s, pim * 64, 0, sb + OFF_EXCH + 8192);
        bulk_done();
      }
    } else {
      mbar_wait(bars + B_XDONE * 8, 1);
    }
    if (t == 0) { red_relaxed(&g_cnt[5 * 32]); PROF(2, 7); }
    __syncwarp();
    asm volatile("barrier.cluster.wait.aligned;" ::: "memory");
  } else {
    asm volatile("setmaxnreg.dec.sync.aligned.u32 24;");
    auto wd_tile = [&](int b, uint32_t dst, uint32_t fb) {
#pragma unroll
      for (int hf = 0; hf < 2; hf++) {
        const int js = kh * 4 + (b < 12 ? (b & 3) : (b & 1) * 2 + hf);
        const int row = 224 * js + (b < 12 ? (js & 1) * 32 + (b >> 2) * 64 + hf * 32 : 192 - hf * 192);
        tma2d(dst + hf * 4096, &tm_d, 112 * n, row, fb);
        tma2d(dst + 8192 + hf * 4096, &tm_d, 112 * n + 64, row, fb);
      }
    };
    if (warp == 12) {
      if (elect()) {
        mbar_init(bars + B_XFULL * 8, 1); mbar_init(bars + (B_XFULL + 1) * 8, 1);
        fence_async_smem();
#pragma unroll
        for (int w = 0; w < 2; w++) {
          mbar_expect(bars + (B_XFULL + w) * 8, HALF_XR);
          tma3d(sb + OFF_PQ + w * HALF_XR, &tm_x, 0, m * 128 + (w ^ kh ^ 1) * 64, 0, bars + (B_XFULL + w) * 8);
        }
        PROF(3, 3);
#pragma unroll
        for (int i = 0; i < NSLOT; i++) mbar_init(bars + (B_FULL + i) * 8, 1);
        mbar_init(bars + B_PIN * 8, 1);
        fence_async_smem();
      }
      bar_arrive<0, NTHREADS - 64>();
#pragma unroll 1
      for (int i = 0; i < 6; i++) {
        if (elect()) {
          const uint32_t fb = bars + (B_FULL + i) * 8;
          mbar_expect(fb, SLOT);
          tma2d(sb + i * SLOT, &tm_g, c64, i * 64, fb);
          tma2d(sb + i * SLOT + 8192, &tm_u, c64, i * 64, fb);
          PROF(3, 4 + i);
        }
      }
      if (elect()) {
        prefetch_l2(reinterpret_cast<const unsigned char*>(w_r) + bid * 7200, 7200);
        prefetch_l2(reinterpret_cast<const unsigned char*>(w_i) + bid * 7200, 7200);
        prefetch_tma2d(&tm_g, c64, 384); prefetch_tma2d(&tm_u, c64, 384);
      }
    } else if (warp == 14) {
      if (elect()) {
#pragma unroll
        for (int i = B_EMPTY; i < B_END; i++)
          if (i < B_XFULL || i >= B_XFREE) mbar_init(bars + i * 8, i >= B_PQFULL ? 1 : ((i == B_XFREE || i == B_PUBW) ? 4 : 8));
        asm volatile("fence.mbarrier_init.release.cluster;" ::: "memory");
        fence_async_smem();
        mbar_expect(bars + B_RECV * 8, 64 * 112 * 4);
      }
      bar_arrive<0, NTHREADS - 64>();
    }
    const uint32_t epoch = ld_relaxed(&g_ep[bid]);
    if (warp == 13 && lane == 0) { PROFG(4, 0); PROF(4, 1); }
    bar_sync<1, 128>();
    asm volatile("barrier.cluster.arrive.relaxed.aligned;" ::: "memory");
    if (warp == 12) {
      int slot = 6, ph = 1;
      auto wait_slot = [&]() { mbar_wait(bars + (B_EMPTY + slot) * 8, ph ^ (slot == 6)); };
      auto adv = [&]() { if (++slot == NSLOT) { slot = 0; ph ^= 1; } };
      const int c32 = 224 * j + ((j & 1) ? 0 : 192);
#pragma unroll 1
      for (int i = 6; i < 25; i++) {
        wait_slot();
        if (elect()) {
          const uint32_t dst = sb + slot * SLOT, fb = bars + (B_FULL + slot) * 8;
          const bool last = i >= 21;
          const int cc = last ? c32 : c64 + 64 * (i / 7), rr = last ? slot * 128 : slot * 64;
          mbar_expect(fb, SLOT);
          tma2d(dst, last ? &tm_g32 : &tm_g, cc, rr, fb);
          tma2d(dst + 8192, last ? &tm_u32 : &tm_u, cc, rr, fb);
        }
        adv();
      }
      if (lane == 0) PROF(3, 0);
#pragma unroll 1
      for (int i = 3; i < 16; i++) {
        if (lane == 0) PROF(3, 16 + i);
        if (i == 14) mbar_wait(bars + B_PREP * 8, 0);
        wait_slot();
        if (elect()) {
          const uint32_t fb = bars + (B_FULL + slot) * 8;
          mbar_expect(fb, i < 14 ? SLOT : G_IMG / 2);
          if (i < 14) wd_tile(i, sb + slot * SLOT, fb);
          else bulk_g2s(sb + slot * SLOT, g_G + (size_t)(n * 4 + i - 12) * (G_IMG / 2), G_IMG / 2, fb);
        }
        adv();
      }
      if (lane == 0) PROF(3, 2);
    } else if (warp == 13) {
      mbar_wait(bars + B_PUBX * 8, 0);
      if (elect()) {
        PROF(4, 8);
#pragma unroll
        for (int w = 0; w < 2; w++) tma_store(&tm_s, ((m * 2 + (w ^ kh ^ 1)) * 2 + (j & 1)) * 64, 192 + (j >> 1) * 64, sb + OFF_EXCH + w * 8192);
        bulk_done();
        red_relaxed(&g_cnt[(j >> 1) * 32]);
        PROF(4, 12);
      }
      mbar_wait(bars + B_PUBW * 8, 0);
      if (elect()) mbar_arrive(bars + B_XDONE * 8);
      asm volatile("fence.acq_rel.gpu;" ::: "memory");
      mbar_wait(bars + B_PUBW * 8, 1);
      if (elect()) {
        PROF(4, 9);
        tma_store(&tm_s, bid * 64, 64, sb + OFF_EXCH);
        tma_store(&tm_s, bid * 64, 128, sb + OFF_EXCH + 8192);
        bulk_done();
        red_relaxed(&g_cnt[4 * 32]);
        mbar_arrive(bars + B_XDONE * 8);
        PROF(4, 13);
      }
      mbar_wait(bars + B_PREP * 8, 0);
      mbar_wait(bars + B_LFREE * 8, 0);
      if (elect()) {
        mbar_expect(bars + B_GFULL * 8, G_IMG);
        bulk_g2s(sb + OFF_R + 28672, g_G + (size_t)(n * 2) * G_IMG, G_IMG, bars + B_GFULL * 8);
      }
    } else if (warp == 14) {
      wait_ge(&g_cnt[4 * 32], (epoch + 1) * 128);
      fence_async_global();
      if (elect()) {
        mbar_arrive(bars + B_PREP * 8);
        if (bid < 113) {
          mbar_expect(bars + B_WFULL * 8, 16384);
          bulk_g2s(sb + OFF_WS, g_X + (64 + bid) * XP, 16384, bars + B_WFULL * 8);
        }
        PROF(5, 17);
      }
    } else {
      mbar_wait(bars + B_XFREE * 8, 0);
      if (elect()) {
        mbar_expect(bars + B_PIN * 8, 14400);
        bulk_g2s(sb + OFF_WS, reinterpret_cast<const unsigned char*>(w_r) + bid * 7200, 7200, bars + B_PIN * 8);
        bulk_g2s(sb + OFF_WS + 7200, reinterpret_cast<const unsigned char*>(w_i) + bid * 7200, 7200, bars + B_PIN * 8);
        prefetch_l2(reinterpret_cast<const unsigned char*>(w_gate) + bid * 12544, 12544);
        prefetch_l2(reinterpret_cast<const unsigned char*>(w_up) + bid * 12544, 12544);
        prefetch_l2(reinterpret_cast<const unsigned char*>(w_down) + bid * 12544, 12544);
        PROF(5, 2);
      }
      if (bid < 113) {
        const int sl = (bid == 112) ? 0 : bid;
        wait_ge(&g_cnt[((sl & 1) + 2 * ((sl >> 1) / 28)) * 32], (epoch + 1) * 32);
        if (elect()) { PROF(5, 16); mbar_arrive(bars + B_XCFULL * 8); }
      }
      mbar_wait(bars + (B_XFREE + 1) * 8, 0);
      if (elect()) mbar_expect(bars + B_RFULL * 8, 3 * SLOT);
#pragma unroll 1
      for (int i = 0; i < 3; i++) {
        mbar_wait(bars + (B_FULL + 2 * i + 1) * 8, 1);
        if (elect()) wd_tile(i, sb + OFF_R + i * SLOT, bars + B_RFULL * 8);
      }
      if (lane == 0) PROF(5, 19);
      mbar_wait(bars + B_PREP * 8, 0);
      wait_ge(&g_cnt[5 * 32], (epoch + 1) * 128);
      fence_async_global();
      if (elect()) {
        PROF(5, 18);
        const unsigned char* src = g_X + (m * 2 + kh) * HALF_XR;
#pragma unroll
        for (int i = 0; i < 4; i++) {
          mbar_expect(bars + (B_PQFULL + i) * 8, i ? 14336 : 14336 + 256);
          bulk_g2s(sb + OFF_PQ + i * 14336, src + i * 14336, 14336, bars + (B_PQFULL + i) * 8);
        }
        bulk_g2s(sb + OFF_G, g_gate + m * 128 + kh * 64, 256, bars + B_PQFULL * 8);
      }
    }
    __syncwarp();
    asm volatile("barrier.cluster.wait.aligned;" ::: "memory");
  }
}

typedef CUresult (*EncodeFn)(CUtensorMap*, CUtensorMapDataType, cuuint32_t, void*, const cuuint64_t*, const cuuint64_t*, const cuuint32_t*,
                             const cuuint32_t*, CUtensorMapInterleave, CUtensorMapSwizzle, CUtensorMapL2promotion, CUtensorMapFloatOOBfill);

void make_map(EncodeFn enc, CUtensorMap* tm, const void* base, int cols, int rows, int bc, int br, CUtensorMapSwizzle sw) {
  cuuint64_t gd[2] = {(cuuint64_t)cols, (cuuint64_t)rows};
  cuuint64_t gs[1] = {(cuuint64_t)cols * 2};
  cuuint32_t bd[2] = {(cuuint32_t)bc, (cuuint32_t)br};
  cuuint32_t es[2] = {1, 1};
  enc(tm, CU_TENSOR_MAP_DATA_TYPE_BFLOAT16, 2, const_cast<void*>(base), gd, gs, bd, es, CU_TENSOR_MAP_INTERLEAVE_NONE, sw,
      CU_TENSOR_MAP_L2_PROMOTION_L2_128B, CU_TENSOR_MAP_FLOAT_OOB_FILL_NONE);
}

}

extern "C" void kernel_launch(void* const* d_in, const int* in_sizes, int n_in, void* d_out, int out_size) {
  (void)in_sizes; (void)n_in; (void)out_size;
  const __nv_bfloat16* x = (const __nv_bfloat16*)d_in[0];
  const __nv_bfloat16* w_r = (const __nv_bfloat16*)d_in[1];
  const __nv_bfloat16* w_i = (const __nv_bfloat16*)d_in[2];
  const __nv_bfloat16* w_gate = (const __nv_bfloat16*)d_in[4];
  const __nv_bfloat16* w_up = (const __nv_bfloat16*)d_in[5];
  const __nv_bfloat16* w_down = (const __nv_bfloat16*)d_in[6];
  const __nv_bfloat16* gate_w = (const __nv_bfloat16*)d_in[7];
  static EncodeFn enc = nullptr;
  static void* xbuf = nullptr;
  static bool ok = false;
  if (!enc) {
    cudaDriverEntryPointQueryResult qr;
    cudaGetDriverEntryPoint("cuTensorMapEncodeTiled", (void**)&enc, cudaEnableDefault, &qr);
    cudaFuncSetAttribute(fused_kernel, cudaFuncAttributeMaxDynamicSharedMemorySize, SMEM_BYTES);
    cudaGetSymbolAddress(&xbuf, g_X);
    cudaFuncAttributes fa;
    cudaFuncGetAttributes(&fa, fused_kernel);
    ok = (fa.numRegs == 128);
  }
  if (!ok) return;
  CUtensorMap tx, tg, tu, tg32, tu32, td, ts;
  {
    cuuint64_t gd[3] = {64, (cuuint64_t)S_, 7};
    cuuint64_t gs[2] = {(cuuint64_t)D_ * 2, 128};
    cuuint32_t bd[3] = {64, 64, 7};
    cuuint32_t es[3] = {1, 1, 1};
    enc(&tx, CU_TENSOR_MAP_DATA_TYPE_BFLOAT16, 3, const_cast<__nv_bfloat16*>(x), gd, gs, bd, es, CU_TENSOR_MAP_INTERLEAVE_NONE, CU_TENSOR_MAP_SWIZZLE_128B,
        CU_TENSOR_MAP_L2_PROMOTION_L2_128B, CU_TENSOR_MAP_FLOAT_OOB_FILL_NONE);
  }
  make_map(enc, &tg, w_gate, F_, D_, 64, 64, CU_TENSOR_MAP_SWIZZLE_128B);
  make_map(enc, &tu, w_up, F_, D_, 64, 64, CU_TENSOR_MAP_SWIZZLE_128B);
  make_map(enc, &tg32, w_gate, F_, D_, 32, 128, CU_TENSOR_MAP_SWIZZLE_64B);
  make_map(enc, &tu32, w_up, F_, D_, 32, 128, CU_TENSOR_MAP_SWIZZLE_64B);
  make_map(enc, &td, w_down, D_, F_, 64, 32, CU_TENSOR_MAP_SWIZZLE_128B);
  make_map(enc, &ts, (const __nv_bfloat16*)xbuf, XP / 2, 448, 64, 64, CU_TENSOR_MAP_SWIZZLE_NONE);
  fused_kernel<<<128, NTHREADS, SMEM_BYTES>>>(tx, tg, tu, tg32, tu32, td, ts, w_r, w_i, w_gate, w_up, w_down, gate_w, (__nv_bfloat16*)d_out);
}
```

```cpp
#include <cuda_runtime.h>
#include <cuda_bf16.h>
#include <cuda.h>
#include <stdint.h>

namespace {

constexpr int S_ = 2048, D_ = 448, F_ = 1792;
constexpr int NTHREADS = 512;
constexpr int SLOT = 16384, NSLOT = 7;
constexpr int HALF_XR = 57344;
constexpr int OFF_PQ = NSLOT * SLOT;
constexpr int OFF_R = OFF_PQ + HALF_XR;
constexpr int OFF_EXCH = OFF_PQ;
constexpr int OFF_WS = OFF_EXCH + 18432;
constexpr int OFF_TW = OFF_WS + 16384;
constexpr int OFF_MISC = OFF_R + HALF_XR;
constexpr int OFF_G = OFF_MISC;
constexpr int OFF_BAR = OFF_MISC + 512;
constexpr int SMEM_BYTES = OFF_BAR + 512;
constexpr int B_FULL = 0, B_EMPTY = 7, B_XFULL = 14  ;
constexpr int B_XFREE = 16  , B_PUBX = 18, B_RFREE = 19, B_LFREE = 20;
constexpr int B_PUBW = 21;
constexpr int B_PQFULL = 22  , B_RECV = 26, B_WFULL = 27, B_XCFULL = 28, B_PREP = 29, B_RFULL = 30, B_GFULL = 31, B_XDONE = 32, B_WDONE = 33, B_END = 34, B_PIN = 34;

constexpr int G_IMG = 224 * 56 * 2;

__device__ __align__(1024) unsigned char g_H[32 * 56 * 4096];
constexpr int XP = 28672;
__device__ __align__(1024) unsigned char g_X[448 * XP];
__device__ __align__(1024) unsigned char g_G[8 * G_IMG];
__device__ __align__(1024) float g_gate[S_];
__device__ __align__(128) unsigned int g_ep[128];
__device__ __align__(128) unsigned int g_cnt[8 * 32];

#define PROF(role, idx) do {} while (0)
#define PROFG(role, idx) do {} while (0)

__device__ __forceinline__ uint32_t s2u(const void* p) { return (uint32_t)__cvta_generic_to_shared(p); }
__device__ __forceinline__ void mbar_init(uint32_t b, int c) { asm volatile("mbarrier.init.shared::cta.b64 [%0], %1;" :: "r"(b), "r"(c) : "memory"); }
__device__ __forceinline__ void mbar_expect(uint32_t b, int bytes) { asm volatile("mbarrier.arrive.expect_tx.shared::cta.b64 _, [%0], %1;" :: "r"(b), "r"(bytes) : "memory"); }
__device__ __forceinline__ void mbar_arrive(uint32_t b) { asm volatile("mbarrier.arrive.shared::cta.b64 _, [%0];" :: "r"(b) : "memory"); }
__device__ __forceinline__ void mbar_wait(uint32_t b, int ph) {
  asm volatile("{\n.reg .pred p;\n.reg .u32 c;\nmov.u32 c, 0;\nL_WAIT:\nmbarrier.try_wait.parity.shared::cta.b64 p, [%0], %1;\n@p bra.uni L_DONE;\n"
               "add.u32 c, c, 1;\nsetp.lt.u32 p, c, 4194304;\n@p bra.uni L_WAIT;\ntrap;\nL_DONE:\n}" :: "r"(b), "r"(ph) : "memory");
}
__device__ __forceinline__ void mbar_wait_cluster(uint32_t b, int ph) {
  asm volatile("{\n.reg .pred p;\n.reg .u32 c;\nmov.u32 c, 0;\nL_WAIT:\nmbarrier.try_wait.parity.acquire.cluster.shared::cta.b64 p, [%0], %1;\n@p bra.uni L_DONE;\n"
               "add.u32 c, c, 1;\nsetp.lt.u32 p, c, 4194304;\n@p bra.uni L_WAIT;\ntrap;\nL_DONE:\n}" :: "r"(b), "r"(ph) : "memory");
}
__device__ __forceinline__ uint32_t ld_acquire(const unsigned int* p) { uint32_t v; asm volatile("ld.acquire.gpu.global.u32 %0, [%1];" : "=r"(v) : "l"(p) : "memory"); return v; }
__device__ __forceinline__ uint32_t ld_relaxed(const unsigned int* p) { uint32_t v; asm volatile("ld.relaxed.gpu.global.u32 %0, [%1];" : "=r"(v) : "l"(p) : "memory"); return v; }
__device__ __forceinline__ void wait_ge(const unsigned int* p, uint32_t target) {
#pragma unroll 1
  for (int i = 0; i < (1 << 22); i++) { if ((int)(ld_acquire(p) - target) >= 0) return; }
  __trap();
}
__device__ __forceinline__ void red_relaxed(unsigned int* p) { asm volatile("red.relaxed.gpu.global.add.u32 [%0], 1;" :: "l"(p) : "memory"); }
__device__ __forceinline__ bool elect() { uint32_t p; asm volatile("{\n.reg .pred p;\nelect.sync _|p, 0xffffffff;\nselp.u32 %0, 1, 0, p;\n}" : "=r"(p)); return p; }
__device__ __forceinline__ void fence_async_smem() { asm volatile("fence.proxy.async.shared::cta;" ::: "memory"); }
__device__ __forceinline__ void fence_async_global() { asm volatile("fence.proxy.async.global;" ::: "memory"); }
template <int ID, int N> __device__ __forceinline__ void bar_sync() { asm volatile("bar.sync %0, %1;" :: "n"(ID), "n"(N) : "memory"); }
template <int ID, int N> __device__ __forceinline__ void bar_arrive() { asm volatile("bar.arrive %0, %1;" :: "n"(ID), "n"(N) : "memory"); }
__device__ __forceinline__ void tma2d(uint32_t dst, const CUtensorMap* tm, int c0, int c1, uint32_t bar) {
  asm volatile("cp.async.bulk.tensor.2d.shared::cluster.global.mbarrier::complete_tx::bytes [%0], [%1, {%3, %4}], [%2];"
               :: "r"(dst), "l"(tm), "r"(bar), "r"(c0), "r"(c1) : "memory");
}
__device__ __forceinline__ void tma3d(uint32_t dst, const CUtensorMap* tm, int c0, int c1, int c2, uint32_t bar) {
  asm volatile("cp.async.bulk.tensor.3d.shared::cluster.global.mbarrier::complete_tx::bytes [%0], [%1, {%3, %4, %5}], [%2];"
               :: "r"(dst), "l"(tm), "r"(bar), "r"(c0), "r"(c1), "r"(c2) : "memory");
}
__device__ __forceinline__ void bulk_g2s(uint32_t dst, const void* src, int bytes, uint32_t bar) {
  asm volatile("cp.async.bulk.shared::cluster.global.mbarrier::complete_tx::bytes [%0], [%1], %2, [%3];"
               :: "r"(dst), "l"(src), "r"(bytes), "r"(bar) : "memory");
}
__device__ __forceinline__ void tma_store(const CUtensorMap* tm, int c0, int c1, uint32_t src) {
  asm volatile("cp.async.bulk.tensor.2d.global.shared::cta.bulk_group [%0, {%1, %2}], [%3];" :: "l"(tm), "r"(c0), "r"(c1), "r"(src) : "memory");
}
__device__ __forceinline__ void bulk_done() { asm volatile("cp.async.bulk.commit_group;\ncp.async.bulk.wait_group 0;\nfence.proxy.async.global;" ::: "memory"); }
__device__ __forceinline__ void sts32(uint32_t a, uint32_t x) { asm volatile("st.shared.b32 [%0], %1;" :: "r"(a), "r"(x) : "memory"); }
__device__ __forceinline__ void prefetch_l2(const void* src, int bytes) {
  asm volatile("cp.async.bulk.prefetch.L2.global [%0], %1;" :: "l"(src), "r"(bytes) : "memory");
}
__device__ __forceinline__ void prefetch_tma2d(const CUtensorMap* tm, int c0, int c1) {
  asm volatile("cp.async.bulk.prefetch.tensor.2d.L2.global [%0, {%1, %2}];" :: "l"(tm), "r"(c0), "r"(c1) : "memory");
}
__device__ __forceinline__ uint64_t mkdesc(uint32_t addr, uint32_t lbo, uint32_t sbo, uint32_t mode) {
  return (uint64_t)((addr & 0x3FFFF) >> 4) | ((uint64_t)(lbo >> 4) << 16) | ((uint64_t)(sbo >> 4) << 32) | ((uint64_t)mode << 62);
}
__device__ __forceinline__ void wg_fence() { asm volatile("wgmma.fence.sync.aligned;" ::: "memory"); }
__device__ __forceinline__ void wg_commit() { asm volatile("wgmma.commit_group.sync.aligned;" ::: "memory"); }
template <int N> __device__ __forceinline__ void wg_wait() { asm volatile("wgmma.wait_group.sync.aligned %0;" :: "n"(N) : "memory"); }
template <int N> __device__ __forceinline__ void keep(float (&d)[N]) {
#pragma unroll
  for (int i = 0; i < N; i++) asm volatile("" : "+f"(d[i]) :: "memory");
}
__device__ __forceinline__ uint32_t pack_bf16(float lo, float hi) { uint32_t r; asm("cvt.rn.bf16x2.f32 %0, %1, %2;" : "=r"(r) : "f"(hi), "f"(lo)); return r; }
__device__ __forceinline__ float bf16_round(float v) { return __bfloat162float(__float2bfloat16_rn(v)); }
__device__ __forceinline__ void sts128(uint32_t a, uint32_t x, uint32_t y, uint32_t z, uint32_t w) { asm volatile("st.shared.v4.b32 [%0], {%1,%2,%3,%4};" :: "r"(a), "r"(x), "r"(y), "r"(z), "r"(w) : "memory"); }
__device__ __forceinline__ float4 lds128f(uint32_t a) { float4 v; asm volatile("ld.shared.v4.f32 {%0,%1,%2,%3}, [%4];" : "=f"(v.x), "=f"(v.y), "=f"(v.z), "=f"(v.w) : "r"(a) : "memory"); return v; }

__device__ __forceinline__ uint2 lds64(uint32_t a) { uint2 v; asm volatile("ld.shared.v2.b32 {%0,%1}, [%2];" : "=r"(v.x), "=r"(v.y) : "r"(a) : "memory"); return v; }
__device__ __forceinline__ float bf_lo(uint32_t w) { return __uint_as_float(w << 16); }
__device__ __forceinline__ float bf_hi(uint32_t w) { return __uint_as_float(w & 0xffff0000u); }
__device__ __forceinline__ uint32_t opaque(uint32_t v) { asm volatile("" : "+r"(v)); return v; }
__device__ __forceinline__ uint4 ldg128(const void* p) { uint4 v; asm volatile("ld.global.nc.v4.b32 {%0,%1,%2,%3}, [%4];" : "=r"(v.x), "=r"(v.y), "=r"(v.z), "=r"(v.w) : "l"(p)); return v; }
__device__ __forceinline__ void stg128(void* p, uint32_t x, uint32_t y, uint32_t z, uint32_t w) { asm volatile("st.global.v4.b32 [%0], {%1,%2,%3,%4};" :: "l"(p), "r"(x), "r"(y), "r"(z), "r"(w) : "memory"); }
__device__ __forceinline__ void stg128_l2(void* p, uint32_t x, uint32_t y, uint32_t z, uint32_t w) { asm volatile("st.relaxed.gpu.global.v4.b32 [%0], {%1,%2,%3,%4};" :: "l"(p), "r"(x), "r"(y), "r"(z), "r"(w) : "memory"); }
__device__ __forceinline__ uint2 ldg64_l2(const void* p) { uint2 v; asm volatile("ld.relaxed.gpu.global.v2.b32 {%0,%1}, [%2];" : "=r"(v.x), "=r"(v.y) : "l"(p) : "memory"); return v; }
__device__ __forceinline__ void ldg128_l2(uint32_t (&v)[4], const void* p) { asm volatile("ld.relaxed.gpu.global.v4.b32 {%0,%1,%2,%3}, [%4];" : "=r"(v[0]), "=r"(v[1]), "=r"(v[2]), "=r"(v[3]) : "l"(p) : "memory"); }
__device__ __forceinline__ uint4 lds128(uint32_t a) { uint4 v; asm volatile("ld.shared.v4.b32 {%0,%1,%2,%3}, [%4];" : "=r"(v.x), "=r"(v.y), "=r"(v.z), "=r"(v.w) : "r"(a) : "memory"); return v; }
__device__ __forceinline__ uint32_t lds16(uint32_t a) { uint32_t v; asm volatile("ld.shared.u16 %0, [%1];" : "=r"(v) : "r"(a) : "memory"); return v; }
__device__ __forceinline__ void sts64(uint32_t a, uint32_t x, uint32_t y) { asm volatile("st.shared.v2.b32 [%0], {%1,%2};" :: "r"(a), "r"(x), "r"(y) : "memory"); }
template <int TB> __device__ __forceinline__ void wgmma_rs_128(float (&d)[64], const uint32_t (&a)[4], uint64_t db, int sc) {
  asm volatile("{\n.reg .pred p;\nsetp.ne.b32 p, %69, 0;\n"
    "wgmma.mma_async.sync.aligned.m64n128k16.f32.bf16.bf16 {%0, %1, %2, %3, %4, %5, %6, %7, %8, %9, %10, %11, %12, %13, %14, %15, %16, %17, %18, %19, %20, %21, %22, %23, %24, %25, %26, %27, %28, %29, %30, %31, %32, %33, %34, %35, %36, %37, %38, %39, %40, %41, %42, %43, %44, %45, %46, %47, %48, %49, %50, %51, %52, %53, %54, %55, %56, %57, %58, %59, %60, %61, %62, %63}, {%64, %65, %66, %67}, %68, p, 1, 1, %70;\n}\n"
    : "+f"(d[0]), "+f"(d[1]), "+f"(d[2]), "+f"(d[3]), "+f"(d[4]), "+f"(d[5]), "+f"(d[6]), "+f"(d[7]), "+f"(d[8]), "+f"(d[9]), "+f"(d[10]), "+f"(d[11]), "+f"(d[12]), "+f"(d[13]), "+f"(d[14]), "+f"(d[15]), "+f"(d[16]), "+f"(d[17]), "+f"(d[18]), "+f"(d[19]), "+f"(d[20]), "+f"(d[21]), "+f"(d[22]), "+f"(d[23]), "+f"(d[24]), "+f"(d[25]), "+f"(d[26]), "+f"(d[27]), "+f"(d[28]), "+f"(d[29]), "+f"(d[30]), "+f"(d[31]), "+f"(d[32]), "+f"(d[33]), "+f"(d[34]), "+f"(d[35]), "+f"(d[36]), "+f"(d[37]), "+f"(d[38]), "+f"(d[39]), "+f"(d[40]), "+f"(d[41]), "+f"(d[42]), "+f"(d[43]), "+f"(d[44]), "+f"(d[45]), "+f"(d[46]), "+f"(d[47]), "+f"(d[48]), "+f"(d[49]), "+f"(d[50]), "+f"(d[51]), "+f"(d[52]), "+f"(d[53]), "+f"(d[54]), "+f"(d[55]), "+f"(d[56]), "+f"(d[57]), "+f"(d[58]), "+f"(d[59]), "+f"(d[60]), "+f"(d[61]), "+f"(d[62]), "+f"(d[63])
    : "r"(a[0]), "r"(a[1]), "r"(a[2]), "r"(a[3]), "l"(db), "r"(sc), "n"(TB));
}
template <int TB> __device__ __forceinline__ void wgmma_rs_64(float (&d)[32], const uint32_t (&a)[4], uint64_t db, int sc) {
  asm volatile("{\n.reg .pred p;\nsetp.ne.b32 p, %37, 0;\n"
    "wgmma.mma_async.sync.aligned.m64n64k16.f32.bf16.bf16 {%0, %1, %2, %3, %4, %5, %6, %7, %8, %9, %10, %11, %12, %13, %14, %15, %16, %17, %18, %19, %20, %21, %22, %23, %24, %25, %26, %27, %28, %29, %30, %31}, {%32, %33, %34, %35}, %36, p, 1, 1, %38;\n}\n"
    : "+f"(d[0]), "+f"(d[1]), "+f"(d[2]), "+f"(d[3]), "+f"(d[4]), "+f"(d[5]), "+f"(d[6]), "+f"(d[7]), "+f"(d[8]), "+f"(d[9]), "+f"(d[10]), "+f"(d[11]), "+f"(d[12]), "+f"(d[13]), "+f"(d[14]), "+f"(d[15]), "+f"(d[16]), "+f"(d[17]), "+f"(d[18]), "+f"(d[19]), "+f"(d[20]), "+f"(d[21]), "+f"(d[22]), "+f"(d[23]), "+f"(d[24]), "+f"(d[25]), "+f"(d[26]), "+f"(d[27]), "+f"(d[28]), "+f"(d[29]), "+f"(d[30]), "+f"(d[31])
    : "r"(a[0]), "r"(a[1]), "r"(a[2]), "r"(a[3]), "l"(db), "r"(sc), "n"(TB));
}
template <int TB> __device__ __forceinline__ void wgmma_rs_56(float (&d)[28], const uint32_t (&a)[4], uint64_t db, int sc) {
  asm volatile("{\n.reg .pred p;\nsetp.ne.b32 p, %33, 0;\n"
    "wgmma.mma_async.sync.aligned.m64n56k16.f32.bf16.bf16 {%0, %1, %2, %3, %4, %5, %6, %7, %8, %9, %10, %11, %12, %13, %14, %15, %16, %17, %18, %19, %20, %21, %22, %23, %24, %25, %26, %27}, {%28, %29, %30, %31}, %32, p, 1, 1, %34;\n}\n"
    : "+f"(d[0]), "+f"(d[1]), "+f"(d[2]), "+f"(d[3]), "+f"(d[4]), "+f"(d[5]), "+f"(d[6]), "+f"(d[7]), "+f"(d[8]), "+f"(d[9]), "+f"(d[10]), "+f"(d[11]), "+f"(d[12]), "+f"(d[13]), "+f"(d[14]), "+f"(d[15]), "+f"(d[16]), "+f"(d[17]), "+f"(d[18]), "+f"(d[19]), "+f"(d[20]), "+f"(d[21]), "+f"(d[22]), "+f"(d[23]), "+f"(d[24]), "+f"(d[25]), "+f"(d[26]), "+f"(d[27])
    : "r"(a[0]), "r"(a[1]), "r"(a[2]), "r"(a[3]), "l"(db), "r"(sc), "n"(TB));
}
template <int TB> __device__ __forceinline__ void wgmma_rs_112(float (&d)[56], const uint32_t (&a)[4], uint64_t db, int sc) {
  asm volatile("{\n.reg .pred p;\nsetp.ne.b32 p, %61, 0;\n"
    "wgmma.mma_async.sync.aligned.m64n112k16.f32.bf16.bf16 {%0, %1, %2, %3, %4, %5, %6, %7, %8, %9, %10, %11, %12, %13, %14, %15, %16, %17, %18, %19, %20, %21, %22, %23, %24, %25, %26, %27, %28, %29, %30, %31, %32, %33, %34, %35, %36, %37, %38, %39, %40, %41, %42, %43, %44, %45, %46, %47, %48, %49, %50, %51, %52, %53, %54, %55}, {%56, %57, %58, %59}, %60, p, 1, 1, %62;\n}\n"
    : "+f"(d[0]), "+f"(d[1]), "+f"(d[2]), "+f"(d[3]), "+f"(d[4]), "+f"(d[5]), "+f"(d[6]), "+f"(d[7]), "+f"(d[8]), "+f"(d[9]), "+f"(d[10]), "+f"(d[11]), "+f"(d[12]), "+f"(d[13]), "+f"(d[14]), "+f"(d[15]), "+f"(d[16]), "+f"(d[17]), "+f"(d[18]), "+f"(d[19]), "+f"(d[20]), "+f"(d[21]), "+f"(d[22]), "+f"(d[23]), "+f"(d[24]), "+f"(d[25]), "+f"(d[26]), "+f"(d[27]), "+f"(d[28]), "+f"(d[29]), "+f"(d[30]), "+f"(d[31]), "+f"(d[32]), "+f"(d[33]), "+f"(d[34]), "+f"(d[35]), "+f"(d[36]), "+f"(d[37]), "+f"(d[38]), "+f"(d[39]), "+f"(d[40]), "+f"(d[41]), "+f"(d[42]), "+f"(d[43]), "+f"(d[44]), "+f"(d[45]), "+f"(d[46]), "+f"(d[47]), "+f"(d[48]), "+f"(d[49]), "+f"(d[50]), "+f"(d[51]), "+f"(d[52]), "+f"(d[53]), "+f"(d[54]), "+f"(d[55])
    : "r"(a[0]), "r"(a[1]), "r"(a[2]), "r"(a[3]), "l"(db), "r"(sc), "n"(TB));
}
template <int TA, int TB> __device__ __forceinline__ void wgmma_ss_56(float (&d)[28], uint64_t da, uint64_t db, int sc) {
  asm volatile("{\n.reg .pred p;\nsetp.ne.b32 p, %30, 0;\n"
    "wgmma.mma_async.sync.aligned.m64n56k16.f32.bf16.bf16 {%0, %1, %2, %3, %4, %5, %6, %7, %8, %9, %10, %11, %12, %13, %14, %15, %16, %17, %18, %19, %20, %21, %22, %23, %24, %25, %26, %27}, %28, %29, p, 1, 1, %31, %32;\n}\n"
    : "+f"(d[0]), "+f"(d[1]), "+f"(d[2]), "+f"(d[3]), "+f"(d[4]), "+f"(d[5]), "+f"(d[6]), "+f"(d[7]), "+f"(d[8]), "+f"(d[9]), "+f"(d[10]), "+f"(d[11]), "+f"(d[12]), "+f"(d[13]), "+f"(d[14]), "+f"(d[15]), "+f"(d[16]), "+f"(d[17]), "+f"(d[18]), "+f"(d[19]), "+f"(d[20]), "+f"(d[21]), "+f"(d[22]), "+f"(d[23]), "+f"(d[24]), "+f"(d[25]), "+f"(d[26]), "+f"(d[27])
    : "l"(da), "l"(db), "r"(sc), "n"(TA), "n"(TB));
}

__device__ __forceinline__ uint32_t cis(float a) { return pack_bf16(__cosf(a), __sinf(a)); }

typedef __nv_bfloat162 b2;
struct c2 { b2 x, y; };
__device__ __forceinline__ b2 as_b2(uint32_t u) { return *reinterpret_cast<b2*>(&u); }
__device__ __forceinline__ uint32_t as_u(b2 v) { return *reinterpret_cast<uint32_t*>(&v); }
__device__ __forceinline__ c2 mk(b2 x, b2 y) { c2 r; r.x = x; r.y = y; return r; }
__device__ __forceinline__ c2 cmul(c2 a, b2 wr, b2 wi) { return mk(__hfma2(a.x, wr, __hneg2(__hmul2(a.y, wi))), __hfma2(a.x, wi, __hmul2(a.y, wr))); }
__device__ __forceinline__ void fft4(c2& a0, c2& a1, c2& a2, c2& a3) {
  c2 t0 = mk(__hadd2(a0.x, a2.x), __hadd2(a0.y, a2.y)), t1 = mk(__hsub2(a0.x, a2.x), __hsub2(a0.y, a2.y));
  c2 t2 = mk(__hadd2(a1.x, a3.x), __hadd2(a1.y, a3.y)), t3 = mk(__hsub2(a1.x, a3.x), __hsub2(a1.y, a3.y));
  a0 = mk(__hadd2(t0.x, t2.x), __hadd2(t0.y, t2.y)); a2 = mk(__hsub2(t0.x, t2.x), __hsub2(t0.y, t2.y));
  a1 = mk(__hadd2(t1.x, t3.y), __hsub2(t1.y, t3.x)); a3 = mk(__hsub2(t1.x, t3.y), __hadd2(t1.y, t3.x));
}
__device__ __forceinline__ void fft4_s2(c2& a0, c2& a1, c2& a2, c2& a3, b2 r) {
  const b2 nr = __hneg2(r);
  c2 t0 = mk(__hfma2(a2.x, r, a0.x), __hfma2(a2.y, r, a0.y)), t1 = mk(__hfma2(a2.x, nr, a0.x), __hfma2(a2.y, nr, a0.y));
  c2 t2 = mk(__hadd2(a1.x, a3.x), __hadd2(a1.y, a3.y)), t3 = mk(__hsub2(a1.x, a3.x), __hsub2(a1.y, a3.y));
  a0 = mk(__hadd2(t0.x, t2.x), __hadd2(t0.y, t2.y)); a2 = mk(__hsub2(t0.x, t2.x), __hsub2(t0.y, t2.y));
  a1 = mk(__hadd2(t1.x, t3.y), __hsub2(t1.y, t3.x)); a3 = mk(__hsub2(t1.x, t3.y), __hadd2(t1.y, t3.x));
}
__device__ __forceinline__ void fft4_s13(c2& a0, c2& a1, c2& a2, c2& a3, b2 r) {
  const b2 nr = __hneg2(r);
  c2 t0 = mk(__hadd2(a0.x, a2.x), __hadd2(a0.y, a2.y)), t1 = mk(__hsub2(a0.x, a2.x), __hsub2(a0.y, a2.y));
  c2 t2 = mk(__hadd2(a1.x, a3.x), __hadd2(a1.y, a3.y)), t3 = mk(__hsub2(a1.x, a3.x), __hsub2(a1.y, a3.y));
  a0 = mk(__hfma2(t2.x, r, t0.x), __hfma2(t2.y, r, t0.y)); a2 = mk(__hfma2(t2.x, nr, t0.x), __hfma2(t2.y, nr, t0.y));
  a1 = mk(__hfma2(t3.y, r, t1.x), __hfma2(t3.x, nr, t1.y)); a3 = mk(__hfma2(t3.y, nr, t1.x), __hfma2(t3.x, r, t1.y));
}
__device__ __forceinline__ c2 rot1(c2 a) { return mk(__hadd2(a.x, a.y), __hsub2(a.y, a.x)); }
__device__ __forceinline__ c2 rot3(c2 a) { return mk(__hsub2(a.y, a.x), __hneg2(__hadd2(a.x, a.y))); }
__device__ __forceinline__ c2 mul_mi(c2 a) { return mk(a.y, __hneg2(a.x)); }
template <int O> __device__ __forceinline__ void fft8(c2 (&v)[16]) {
  const b2 r = as_b2(0x3F353F35u), nr = as_b2(0xBF35BF35u);
  fft4(v[O], v[O + 4], v[O + 8], v[O + 12]);
  fft4(v[O + 2], v[O + 6], v[O + 10], v[O + 14]);
  const c2 o0 = v[O + 2], o1 = rot1(v[O + 6]), o2 = v[O + 10], o3 = rot1(v[O + 14]);
  const c2 e0 = v[O], e1 = v[O + 4], e2 = v[O + 8], e3 = v[O + 12];
  v[O] = mk(__hadd2(e0.x, o0.x), __hadd2(e0.y, o0.y));              v[O + 8] = mk(__hsub2(e0.x, o0.x), __hsub2(e0.y, o0.y));
  v[O + 2] = mk(__hfma2(o1.x, r, e1.x), __hfma2(o1.y, r, e1.y));    v[O + 10] = mk(__hfma2(o1.x, nr, e1.x), __hfma2(o1.y, nr, e1.y));
  v[O + 4] = mk(__hadd2(e2.x, o2.y), __hsub2(e2.y, o2.x));          v[O + 12] = mk(__hsub2(e2.x, o2.y), __hadd2(e2.y, o2.x));
  v[O + 6] = mk(__hfma2(o3.y, r, e3.x), __hfma2(o3.x, nr, e3.y));   v[O + 14] = mk(__hfma2(o3.y, nr, e3.x), __hfma2(o3.x, r, e3.y));
}
__device__ __forceinline__ void fft16(c2 (&v)[16]) {
  const b2 r = as_b2(0x3F353F35u), c1 = as_b2(0x3F6D3F6Du), s1 = as_b2(0x3EC43EC4u), nc1 = as_b2(0xBF6DBF6Du), ns1 = as_b2(0xBEC4BEC4u);
#pragma unroll
  for (int a = 0; a < 4; a++) fft4(v[a], v[a + 4], v[a + 8], v[a + 12]);
  v[5] = cmul(v[5], c1, ns1); v[6] = rot1(v[6]); v[7] = cmul(v[7], s1, nc1);
  v[9] = rot1(v[9]); v[10] = mul_mi(v[10]); v[11] = rot3(v[11]);
  v[13] = cmul(v[13], s1, nc1); v[14] = rot3(v[14]); v[15] = cmul(v[15], nc1, s1);
  fft4(v[0], v[1], v[2], v[3]); fft4_s2(v[4], v[5], v[6], v[7], r); fft4_s13(v[8], v[9], v[10], v[11], r); fft4_s2(v[12], v[13], v[14], v[15], r);
  c2 t;
  t = v[1]; v[1] = v[4]; v[4] = t;  t = v[2]; v[2] = v[8]; v[8] = t;  t = v[3]; v[3] = v[12]; v[12] = t;
  t = v[6]; v[6] = v[9]; v[9] = t;  t = v[7]; v[7] = v[13]; v[13] = t; t = v[11]; v[11] = v[14]; v[14] = t;
}

__device__ __forceinline__ void columns(c2 (&v)[16], uint32_t sb, int t) {
  const int l16 = t & 15;
  const uint32_t row = sb + OFF_EXCH + (t >> 4) * 2304;
  const uint32_t pos = sb + OFF_EXCH + (t >> 3) * 144 + (t & 7) * 16;
#pragma unroll 1
  for (int ps = 0; ps < 6; ps++) {
    if (ps == 0 || ps == 5) { fft8<0>(v); fft8<1>(v); } else fft16(v);
    if (ps == 5) break;
    if (ps == 2) {
      const uint32_t ws = sb + OFF_WS + (l16 >> 1) * 128 + ((((t >> 4) + (l16 >> 1)) & 7) * 2 + (l16 & 1)) * 8;
      mbar_wait(sb + OFF_BAR + B_WFULL * 8, 0);
#pragma unroll
      for (int q = 0; q < 16; q++) {
        const uint2 w = lds64(ws + q * 1024);
        const c2 z = cmul(v[q], as_b2(w.x), as_b2(w.y));
        v[q] = mk(z.y, z.x);
      }
      continue;
    }
    {
      const bool full = ps == 0 || ps == 4;
      const uint32_t tw = sb + OFF_TW + (full ? ps * 2048 + t * 16 : 16384 + l16 * 16);
      const uint32_t st = full ? 2048 : 256;
#pragma unroll
      for (int i = 0; i < 4; i++) {
        const uint4 w4 = lds128(tw + i * st);
        const uint32_t w[4] = {w4.x, w4.y, w4.z, w4.w};
#pragma unroll
        for (int e = 0; e < 4; e++) v[4 * i + e] = cmul(v[4 * i + e], __low2bfloat162(as_b2(w[e])), __high2bfloat162(as_b2(w[e])));
      }
    }
    if (ps == 0) {
      mbar_wait(sb + OFF_BAR + B_XDONE * 8, 0);
#pragma unroll
      for (int q = 0; q < 8; q++) sts128(pos + q * 2304, as_u(v[2 * q].x), as_u(v[2 * q].y), as_u(v[2 * q + 1].x), as_u(v[2 * q + 1].y));
      bar_sync<3, 128>();
#pragma unroll
      for (int q = 0; q < 16; q++) { const uint2 a = lds64(row + q * 144 + l16 * 8); v[q] = mk(as_b2(a.x), as_b2(a.y)); }
    } else {
      __syncwarp();
#pragma unroll
      for (int q = 0; q < 16; q++) sts64(row + q * 144 + l16 * 8, as_u(v[q].x), as_u(v[q].y));
      if (ps == 4) bar_sync<3, 128>(); else __syncwarp();
      const uint32_t src = ps == 4 ? pos : row + l16 * 144, st = ps == 4 ? 2304 : 16;
#pragma unroll
      for (int q = 0; q < 8; q++) { const uint4 a = lds128(src + q * st); v[2 * q] = mk(as_b2(a.x), as_b2(a.y)); v[2 * q + 1] = mk(as_b2(a.z), as_b2(a.w)); }
    }
  }
}

template <int NH> __device__ __forceinline__ void h_epilogue(float (&acc)[NH * 8], unsigned char* gdst, uint32_t tag) {
#pragma unroll
  for (int c = 0; c < NH / 2; c++) {
    uint32_t pk[4];
#pragma unroll
    for (int i = 0; i < 4; i++) {
      float hv[2];
#pragma unroll
      for (int e = 0; e < 2; e++) {
        float hg = 0.5f * acc[c * 8 + i * 2 + e], up = acc[NH * 4 + c * 8 + i * 2 + e];
        float th; asm("tanh.approx.f32 %0, %1;" : "=f"(th) : "f"(hg));
        hv[e] = fmaf(hg, th, hg) * up;
      }
      pk[i] = pack_bf16(hv[0], hv[1]);
    }
    stg128_l2(gdst + c * 4096, (pk[0] & ~1u) | tag, pk[1], pk[2], pk[3]);
  }
}

__device__ __forceinline__ void frag_ready(uint32_t (&a)[4], uint32_t (&b)[4], uint32_t (&c)[4], uint32_t (&d)[4], const unsigned char* p, uint32_t tag) {
  asm volatile("{\n.reg .pred p;\n.reg .u32 c, m, q;\nmov.u32 c, 0;\nL_TRY:\n"
               "lop3.b32 m, %0, %4, %17, 0x7E;\nlop3.b32 q, %8, %12, %17, 0x7E;\nlop3.b32 m, m, q, 1, 0xA8;\nsetp.ne.u32 p, m, 0;\n"
               "vote.sync.any.pred p, p, 0xffffffff;\n@!p bra.uni L_OK;\n"
               "ld.relaxed.gpu.global.v4.b32 {%0,%1,%2,%3}, [%16];\nld.relaxed.gpu.global.v4.b32 {%4,%5,%6,%7}, [%16+4096];\n"
               "ld.relaxed.gpu.global.v4.b32 {%8,%9,%10,%11}, [%16+8192];\nld.relaxed.gpu.global.v4.b32 {%12,%13,%14,%15}, [%16+12288];\n"
               "add.u32 c, c, 1;\nsetp.lt.u32 p, c, 262144;\n@p bra.uni L_TRY;\ntrap;\nL_OK:\n}"
               : "+r"(a[0]), "+r"(a[1]), "+r"(a[2]), "+r"(a[3]), "+r"(b[0]), "+r"(b[1]), "+r"(b[2]), "+r"(b[3]),
                 "+r"(c[0]), "+r"(c[1]), "+r"(c[2]), "+r"(c[3]), "+r"(d[0]), "+r"(d[1]), "+r"(d[2]), "+r"(d[3])
               : "l"(p), "r"(tag) : "memory");
}

#define MAP 0
#define LEAD2 0
#define LEAD1 3

__global__ void __cluster_dims__(2, 1, 1) __launch_bounds__(NTHREADS, 1)
fused_kernel(const __grid_constant__ CUtensorMap tm_x, const __grid_constant__ CUtensorMap tm_g, const __grid_constant__ CUtensorMap tm_u,
             const __grid_constant__ CUtensorMap tm_g32, const __grid_constant__ CUtensorMap tm_u32, const __grid_constant__ CUtensorMap tm_d,
             const __grid_constant__ CUtensorMap tm_s,
             const __nv_bfloat16* __restrict__ w_r, const __nv_bfloat16* __restrict__ w_i,
             const __nv_bfloat16* __restrict__ w_gate, const __nv_bfloat16* __restrict__ w_up,
             const __nv_bfloat16* __restrict__ w_down, const __nv_bfloat16* __restrict__ gate_w, __nv_bfloat16* __restrict__ out) {
  extern __shared__ __align__(1024) unsigned char smem[];
  const uint32_t sb = s2u(smem);
  const uint32_t bars = sb + OFF_BAR;
  const int tid = threadIdx.x, warp = __shfl_sync(0xffffffffu, tid >> 5, 0), lane = tid & 31;
  const int cl = blockIdx.x >> 1, kh = blockIdx.x & 1;
  const int n0 = cl < 4 ? cl : (cl < 36 ? (cl - 4) >> 3 : (cl - 36) / 7);
  const int m0 = cl < 4 ? 15 : (cl < 36 ? (cl - 4) & 7 : cl - 28 - 7 * n0);
  const int n = MAP == 0 ? n0 : (MAP == 1 ? (m0 & 3) : ((n0 & 1) | ((m0 & 1) << 1)));
  const int m = MAP == 0 ? m0 : (MAP == 1 ? ((m0 & 12) | n0) : ((m0 & 14) | (n0 >> 1)));
  const int j = kh * 4 + n, bid = m * 8 + n * 2 + kh;

  const int c64 = 224 * j + (j & 1) * 32;
  if (warp < 8) {
    asm volatile("setmaxnreg.inc.sync.aligned.u32 208;");
    const int wg = warp >> 2, w4 = warp & 3, g = lane >> 2, t = lane & 3;
    const int rh = wg ^ kh ^ 1;
    const int p = j & 1, r = (j >> 1) & 1, hh = j >> 2;
    const uint32_t epoch = ld_relaxed(&g_ep[bid]);
    if ((tid & 127) == 0) PROF(wg, 30);
#pragma unroll 1
    for (int it = tid; it < 392; it += 256) {
      const int kc = it / 28, sg = it - kc * 28;
      const int k = 2 * (28 * hh + sg) + r;
      const float kf = (float)k * (-6.283185307179586f / 448.0f), a0 = (float)(16 * kc + p) * kf;
      uint32_t c[4], s[4];
#pragma unroll
      for (int q = 0; q < 4; q++) {
        const float a1 = fmaf((float)(2 * q), kf, a0), a2 = fmaf((float)(2 * q + 8), kf, a0);
        c[q] = pack_bf16(__cosf(a1), __cosf(a2)); s[q] = pack_bf16(__sinf(a1), __sinf(a2));
        if (k == 0) s[q] = ((q ^ p) & 1) ? 0xBF80BF80u : 0x3F803F80u;
      }
      const uint32_t a = sb + 6 * SLOT + (kc * 56 + 2 * sg) * 16;
      sts128(a, c[0], c[1], c[2], c[3]);
      sts128(a + 16, s[0], s[1], s[2], s[3]);
    }
    if ((tid & 127) == 0) PROF(wg, 31);
    fence_async_smem();
    bar_sync<0, NTHREADS - 64>();
    asm volatile("barrier.cluster.arrive.relaxed.aligned;" ::: "memory");
    if ((tid & 127) == 0) PROF(wg, 1);

    uint32_t xa[28][4];
    {
      const uint32_t xb = sb + OFF_PQ + wg * HALF_XR + (w4 * 16 + (lane & 15)) * 128;
      mbar_wait(bars + (B_XFULL + wg) * 8, 0);
      if ((tid & 127) == 0) PROF(wg, 2);
#pragma unroll
      for (int kb = 0; kb < 7; kb++) {
#pragma unroll
        for (int kk = 0; kk < 4; kk++) {
          uint32_t a = xb + kb * 8192 + (((2 * kk + (lane >> 4)) ^ (lane & 7)) << 4);
          asm volatile("ldmatrix.sync.aligned.m8n8.x4.shared.b16 {%0,%1,%2,%3}, [%4];"
                       : "=r"(xa[kb * 4 + kk][0]), "=r"(xa[kb * 4 + kk][1]), "=r"(xa[kb * 4 + kk][2]), "=r"(xa[kb * 4 + kk][3]) : "r"(a) : "memory");
        }
      }
    }
    {
      uint32_t ad[7][4];
      const uint32_t sel = p ? 0x7632 : 0x5410;
      const uint32_t sgn = r ? 0xBF80BF80u : 0x3F803F80u;
#pragma unroll
      for (int jj = 0; jj < 7; jj++) {
#pragma unroll
        for (int i = 0; i < 4; i++) {
          int ks = 2 * jj + (i >> 1), rr = i & 1;
          uint32_t lo = __byte_perm(xa[ks][rr], xa[ks][rr + 2], sel);
          uint32_t hi = __byte_perm(xa[ks + 14][rr], xa[ks + 14][rr + 2], sel);
          asm("fma.rn.bf16x2 %0, %1, %2, %3;" : "=r"(ad[jj][i]) : "r"(hi), "r"(sgn), "r"(lo));
        }
      }
      __syncwarp();
      if (lane == 0) mbar_arrive(bars + (B_XFREE + wg) * 8);
      float acc[28];
      wg_fence();
      uint64_t db = mkdesc(sb + 6 * SLOT, 896, 128, 0);
#pragma unroll
      for (int jj = 0; jj < 7; jj++) wgmma_rs_56<0>(acc, ad[jj], db + jj * 112, jj != 0);
      wg_commit();
      wg_wait<0>(); keep(acc);
      if (lane == 0) mbar_arrive(bars + (B_EMPTY + 6) * 8);
      const uint32_t xc = sb + OFF_EXCH + wg * 8192 + t * 256 + w4 * 64 + g * 4;
      mbar_wait(bars + B_XFREE * 8, 0);
#pragma unroll
      for (int i = 0; i < 7; i++) {
        sts32(xc + i * 1024, pack_bf16(acc[4 * i], acc[4 * i + 1]));
        sts32(xc + i * 1024 + 32, pack_bf16(acc[4 * i + 2], acc[4 * i + 3]));
      }
      fence_async_smem();
      __syncwarp();
      if (lane == 0) mbar_arrive(bars + B_PUBX * 8);
    }
    if ((tid & 127) == 0) PROF(wg, 3);
    const uint32_t tag = ~epoch & 1;
    unsigned char* const hbase = g_H + (size_t)(m * 2 + kh) * (56 * 4096) + rh * 2048 + (tid & 127) * 16;
#pragma unroll 1
    for (int u = 0; u < 3; u++) {
      float acc[64];
      if (wg == 1) { if (u & 1) bar_sync<6, 256>(); else bar_sync<2, 256>(); }
      const uint32_t sbu = opaque(sb);
#pragma unroll
      for (int kb = 0; kb < 7; kb++) {
        mbar_wait(sbu + OFF_BAR + (B_FULL + kb) * 8, u & 1);
        wg_fence();
        uint64_t db = mkdesc(sbu + kb * SLOT, 8192, 1024, 1);
#pragma unroll
        for (int kk = 0; kk < 4; kk++) wgmma_rs_128<1>(acc, xa[kb * 4 + kk], db + kk * 128, (kb | kk) != 0);
        wg_commit();
        if (kb == LEAD1 && wg == 0) { if (u & 1) bar_arrive<6, 256>(); else bar_arrive<2, 256>(); }
        if (kb > 0) { wg_wait<1>(); if (lane == 0) mbar_arrive(sbu + OFF_BAR + (B_EMPTY + kb - 1) * 8); }
      }
      wg_wait<0>(); keep(acc);
      if (lane == 0) mbar_arrive(sbu + OFF_BAR + (B_EMPTY + 6) * 8);
      if ((tid & 127) == 0) PROF(wg, 4 + 2 * u);
      h_epilogue<8>(acc, hbase + (u * 16 + n * 4) * 4096, tag);
      if ((tid & 127) == 0) PROF(wg, 5 + 2 * u);
    }
    uint32_t ha[14][4][4];
    auto check = [&](int b0, int b1) {
#pragma unroll
      for (int b = b0; b < b1; b++) frag_ready(ha[b][0], ha[b][1], ha[b][2], ha[b][3], hbase + b * 16384, tag);
    };
    auto load = [&](int b0, int b1) {
#pragma unroll
      for (int i = b0; i < b1; i++) ldg128_l2(ha[i >> 2][i & 3], hbase + i * 4096);
    };
    {
      float acc[32];
      load(0, 3);
      if (wg == 1) bar_sync<6, 256>();
      const uint32_t sbu = opaque(sb);
#pragma unroll
      for (int it = 0; it < 4; it++) {
        mbar_wait(sbu + OFF_BAR + (B_FULL + it) * 8, 1);
        wg_fence();
        uint64_t db = mkdesc(sbu + it * SLOT, 8192, 512, 2);
#pragma unroll
        for (int kk = 0; kk < 8; kk++) if (it * 8 + kk < 28) wgmma_rs_64<1>(acc, xa[it * 8 + kk], db + kk * 64, (it | kk) != 0);
        wg_commit();
        if (it == 2 && wg == 0) bar_arrive<6, 256>();
        if (it > 0) {
          wg_wait<1>();
          if (lane == 0) mbar_arrive(sbu + OFF_BAR + (B_EMPTY + it - 1) * 8);
          if (it == 1) load(3, 11);
          if (it == 2) load(11, 16);
        }
      }
      wg_wait<0>(); keep(acc);
      if (lane == 0) mbar_arrive(sbu + OFF_BAR + (B_EMPTY + 3) * 8);
      if ((tid & 127) == 0) PROF(wg, 10);
      h_epilogue<4>(acc, hbase + (48 + n * 2) * 4096, tag);
    }
    asm volatile("barrier.cluster.wait.aligned;" ::: "memory");
    if ((tid & 127) == 0) PROF(wg, 11);

    float acc[56];
    check(0, 4);
    if (wg == 1) bar_sync<2, 256>();
#pragma unroll
    for (int b = 0; b < 14; b++) {
      if ((tid & 127) == 0) PROF(wg, 16 + b);
      if (b >= 3) mbar_wait(bars + (B_FULL + (b + 1) % 7) * 8, b < 6 || b == 13);
      else if (b == 0) mbar_wait(bars + B_RFULL * 8, 0);
      if (b == 4) check(4, 7);
      if (b == 7) check(7, 11);
      if (b == 11) check(11, 14);
      wg_fence();
      const uint64_t db = mkdesc(b < 3 ? sb + OFF_R + b * SLOT : sb + (b + 1) % 7 * SLOT, 8192, 1024, 1);
#pragma unroll
      for (int kk = 0; kk < 4; kk++) wgmma_rs_112<1>(acc, ha[b][kk], db + kk * 128, (b | kk) != 0);
      wg_commit();
      if (b == LEAD2 && wg == 0) bar_arrive<2, 256>();
      if (b == 0) load(16, 24);
      if (b == 1) load(24, 28);
      if (b == 4 || b == 5) load(8 * b - 4, 8 * b + 4);
      if (b == 7) load(44, 52);
      if (b == 8) load(52, 56);
      if (b > 0) wg_wait<1>();
      if (lane == 0) {
        if (b >= 4 && b <= 9) mbar_arrive(bars + (B_EMPTY + b % 7) * 8);
        if (b == 3) {
          mbar_arrive(bars + B_LFREE * 8);
          asm volatile("{\n.reg .b32 ra;\nmapa.shared::cluster.u32 ra, %0, %1;\nmbarrier.arrive.relaxed.cluster.shared::cluster.b64 _, [ra];\n}"
                       :: "r"(bars + B_RFREE * 8), "r"(kh ^ 1) : "memory");
        }
      }
    }
    const int t128 = tid & 127;
    wg_wait<0>(); keep(acc);
    if (wg == 0) {
      if (t128 == 0) PROF(wg, 12);
      mbar_wait_cluster(bars + B_RFREE * 8, 0);
      uint32_t rdst, rbar;
      asm volatile("mapa.shared::cluster.u32 %0, %1, %2;" : "=r"(rdst) : "r"(sb + OFF_R + t128 * 16), "r"(kh ^ 1));
      asm volatile("mapa.shared::cluster.u32 %0, %1, %2;" : "=r"(rbar) : "r"(bars + B_RECV * 8), "r"(kh ^ 1));
#pragma unroll
      for (int i = 0; i < 14; i++)
        asm volatile("st.async.weak.shared::cluster.mbarrier::complete_tx::bytes.v4.f32 [%0], {%1,%2,%3,%4}, [%5];"
                     :: "r"(rdst + i * 2048), "f"(acc[4 * i]), "f"(acc[4 * i + 1]), "f"(acc[4 * i + 2]), "f"(acc[4 * i + 3]), "r"(rbar) : "memory");
    } else {
      float spec[2][28];
      if (t128 == 0) PROF(wg, 12);
#pragma unroll
      for (int i = 0; i < 4; i++) {
        if (i == 0) mbar_wait(bars + B_GFULL * 8, 0);
        if (i >= 2) mbar_wait(bars + (B_FULL + i - 1) * 8, 1);
        mbar_wait(bars + (B_PQFULL + i) * 8, 0);
        if (i == 0 && t128 == 0) { PROF(wg, 13); g_ep[bid] = epoch + 1; }
        wg_fence();
        const uint64_t da = mkdesc(sb + OFF_PQ + i * 14336, 1024, 1024, 1);
        const uint64_t db = mkdesc(i < 2 ? sb + OFF_R + 28672 + i * (G_IMG / 2) : sb + (i - 1) * SLOT, 896, 128, 0);
#pragma unroll
        for (int kk = 0; kk < 7; kk++) wgmma_ss_56<1, 0>(spec[i >> 1], da + kk * 128, db + kk * 112, ((i & 1) | kk) != 0);
        wg_commit();
      }
      const float* gs = reinterpret_cast<const float*>(smem + OFF_G) + w4 * 16 + g;
      const float o0 = bf16_round(1.0f - gs[0]), o1 = bf16_round(1.0f - gs[8]);
      const float g0 = gs[0] * (1.0f / (float)(S_ * D_)), g1 = gs[8] * (1.0f / (float)(S_ * D_));
      mbar_wait_cluster(bars + B_RECV * 8, 0);
      if (t128 == 0) PROF(wg, 0);
#pragma unroll
      for (int i = 0; i < 14; i++) {
        const float4 o = lds128f(sb + OFF_R + t128 * 16 + i * 2048);
        acc[4 * i] = (acc[4 * i] + o.x) * o0; acc[4 * i + 1] = (acc[4 * i + 1] + o.y) * o0;
        acc[4 * i + 2] = (acc[4 * i + 2] + o.z) * o1; acc[4 * i + 3] = (acc[4 * i + 3] + o.w) * o1;
      }
      keep(acc);
      wg_wait<0>(); keep(spec[0]); keep(spec[1]);
      if (t128 == 0) PROF(wg, 14);
      bar_sync<5, 128>();
      const uint32_t st = sb + OFF_PQ + w4 * 3840;
#pragma unroll
      for (int i = 0; i < 7; i++) {
        uint32_t pk[4];
#pragma unroll
        for (int e = 0; e < 2; e++) {
          const int c = 2 * i + e, si = i * 4 + e;
          pk[2 * e] = pack_bf16(fmaf(g0, spec[0][si], acc[4 * c]), fmaf(g0, spec[1][si], acc[4 * c + 1]));
          pk[2 * e + 1] = pack_bf16(fmaf(g1, spec[0][si + 2], acc[4 * c + 2]), fmaf(g1, spec[1][si + 2], acc[4 * c + 3]));
        }
        asm volatile("stmatrix.sync.aligned.m8n8.x4.shared.b16 [%0], {%1,%2,%3,%4};"
                     :: "r"(st + (lane & 15) * 240 + (lane >> 4) * 16 + i * 32), "r"(pk[0]), "r"(pk[1]), "r"(pk[2]), "r"(pk[3]) : "memory");
      }
      __syncwarp();
      if (lane < 28) {
        const int r2 = lane >= 14, cc = lane - r2 * 14;
        unsigned char* ob = reinterpret_cast<unsigned char*>(out) + (size_t)(m * 128 + kh * 64 + w4 * 16 + r2) * (D_ * 2) + n * 224 + cc * 16;
        float4 v[8];
#pragma unroll
        for (int i = 0; i < 8; i++) v[i] = lds128f(st + r2 * 240 + cc * 16 + i * 480);
#pragma unroll
        for (int i = 0; i < 8; i++) stg128(ob + i * (D_ * 4), __float_as_uint(v[i].x), __float_as_uint(v[i].y), __float_as_uint(v[i].z), __float_as_uint(v[i].w));
      }
    }
    if (t128 == 0) { PROF(wg, 15); if (wg) { PROFG(4, 30); PROF(4, 31); } }
  } else if (warp < 12) {
    asm volatile("setmaxnreg.dec.sync.aligned.u32 72;");
    const int t = tid - 256;
    const int k = bid;
    if (t == 0) PROF(2, 0);
    uint4 gv[7];
#pragma unroll
    for (int i = 0; i < 7; i++) gv[i] = ldg128(reinterpret_cast<const uint4*>(gate_w) + i * 8 + (t & 7));
    if (t < 98) {
      int cid = m * 98 + t, kc = cid / 56, nn = cid - kc * 56;
      int d = 112 * n + 8 * (2 * (nn >> 3) + (nn & 1)) + (nn & 6) + kh;
      int dr = d > 224 ? d - 448 : d;
      const float df = (float)dr * (-6.283185307179586f / 448.0f);
      uint32_t pk[4];
#pragma unroll
      for (int e = 0; e < 4; e++) {
        const float a = (float)(4 * kc + e) * df;
        pk[e] = pack_bf16(2.0f * __cosf(a), 2.0f * __sinf(a));
      }
      if (kc == 0) pk[0] = (((d >> 1) ^ kh) & 1) ? 0xBF803F80u : 0x3F803F80u;
      stg128(g_G + (size_t)(n * 2 + kh) * G_IMG + cid * 16, pk[0], pk[1], pk[2], pk[3]);
    }
    bar_sync<0, NTHREADS - 64>();
    asm volatile("barrier.cluster.arrive.relaxed.aligned;" ::: "memory");
    {
      const int row = n * 16 + (t >> 3), l8 = t & 7;
      mbar_wait(bars + (B_XFULL + 1) * 8, 0);
      float sum = 0.f;
#pragma unroll
      for (int i = 0; i < 7; i++) {
        const uint4 a = lds128(sb + OFF_R + i * 8192 + row * 128 + ((l8 ^ (row & 7)) << 4));
        const uint32_t aa[4] = {a.x, a.y, a.z, a.w}, bb[4] = {gv[i].x, gv[i].y, gv[i].z, gv[i].w};
#pragma unroll
        for (int e = 0; e < 4; e++) {
          const uint32_t pr = as_u(__hmul2(as_b2(aa[e]), as_b2(bb[e])));
          sum += bf_lo(pr) + bf_hi(pr);
        }
      }
      sum += __shfl_xor_sync(0xffffffffu, sum, 1); sum += __shfl_xor_sync(0xffffffffu, sum, 2); sum += __shfl_xor_sync(0xffffffffu, sum, 4);
      if (l8 == 0) g_gate[m * 128 + kh * 64 + row] = bf16_round(__fdividef(1.0f, 1.0f + __expf(-bf16_round(sum))));
    }
    __syncwarp();
    if (lane == 0) mbar_arrive(bars + (B_XFREE + 1) * 8);
    if (t == 0) PROF(2, 11);
    mbar_wait(bars + B_PIN * 8, 0);
    mbar_wait(bars + (B_XFREE + 1) * 8, 0);
    if (t == 0) PROF(2, 4);
    {
      const uint32_t wa = sb + OFF_WS + (((t & 7) - bid) & 7) * 450 + (t >> 3) * 2, wc = wa + 448 - (t >> 3) * 4;
#pragma unroll 1
      for (int h = 0; h < 2; h++) {
        uint32_t w[4][8];
#pragma unroll
        for (int i = 0; i < 4; i++) {
#pragma unroll
          for (int e = 0; e < 4; e++) { w[i][2 * e] = lds16(wa + h * 128 + i * 32 + e * 3600); w[i][2 * e + 1] = lds16(wc - h * 128 - i * 32 + e * 3600); }
        }
#pragma unroll
        for (int i = 0; i < 4; i++)
          sts128(sb + OFF_R + h * 8192 + i * 2048 + t * 16, __byte_perm(w[i][0], w[i][1], 0x5410), __byte_perm(w[i][4], w[i][5], 0x5410), __byte_perm(w[i][2], w[i][3], 0x5410), __byte_perm(w[i][6], w[i][7], 0x5410));
      }
    }
    fence_async_smem();
    __syncwarp();
    if (lane == 0) mbar_arrive(bars + B_PUBW * 8);
    if (k < 113) {
      if (t == 0) PROF(2, 2);
      mbar_wait(bars + B_XCFULL * 8, 0);
      if (t == 0) PROF(2, 3);
      c2 v[16];
      uint2 xe[8], xo[8];
      const int sl = k == 112 ? 0 : k, hi = sl >= 56;
      const unsigned char* xs = g_X + (192 + (sl & 1) * 64 + hi * 72 + (sl & ~1) + ((t >> 4) & 1)) * XP + (t >> 5) * 256 + (t & 15) * 8;
#pragma unroll
      for (int jj = 0; jj < 8; jj++) { xe[jj] = ldg64_l2(xs + jj * 1024); xo[jj] = ldg64_l2(xs + jj * 1024 + 128); }
      {
        const float u = -6.283185307179586f / 2048.0f, t2 = (float)(2 * t) * u, rr = (float)(t >> 4) * u;
#pragma unroll 1
        for (int i = 0; i < 4; i++) {
          const float q = (float)(2 * i), l = (float)((t & 15) + 64 * i);
          sts128(sb + OFF_TW + i * 2048 + t * 16, cis(t2 * q), cis((t2 + u) * q), cis(t2 * (q + 1.0f)), cis((t2 + u) * (q + 1.0f)));
          sts128(sb + OFF_TW + 8192 + i * 2048 + t * 16, cis(rr * l), cis(rr * (l + 16.0f)), cis(rr * (l + 32.0f)), cis(rr * (l + 48.0f)));
        }
        const float l = (float)((t >> 1) & 15) * (8.0f * u), jj = (float)((t >> 5) * 4 + (t & 1) * 2);
        sts64(sb + OFF_TW + 16384 + t * 8, cis(l * jj), cis(l * (jj + 1.0f)));
      }
      if (t == 0) PROF(2, 9);
      const uint32_t se = k == 0 ? 0x4410 : (k == 112 ? 0x4432 : 0x3210), so = k == 0 ? 0x4410 : (k == 112 ? 0x3244 : 0x3210);
#pragma unroll
      for (int jj = 0; jj < 8; jj++) {
        const uint2 e2 = xe[jj], o2 = xo[jj];
#pragma unroll
        for (int h = 0; h < 2; h++) {
          const b2 e = as_b2(__byte_perm(h ? e2.y : e2.x, 0, se)), o = as_b2(__byte_perm(h ? o2.y : o2.x, 0, so));
          const uint32_t s = as_u(__hadd2(e, o)), d = as_u(__hsub2(e, o)) ^ 0x80000000u;
          v[2 * jj + h] = mk(as_b2(__byte_perm(s, d, 0x5410)), as_b2(__byte_perm(s, d, 0x7632)));
        }
      }
      if (t == 0) PROF(2, 12);
      columns(v, sb, t);
      if (t == 0) PROF(2, 14);
      const int pre = (k == 112) ? 1 : 2 * k, pim = (k == 112) ? 1 : 2 * k + 1;
      const uint32_t pr = sb + OFF_EXCH + (t >> 5) * 256 + ((((lane >> 2) ^ pre) & 7) << 4) + (lane & 3) * 4;
      const uint32_t pi = sb + OFF_EXCH + 8192 + (t >> 5) * 256 + ((((lane >> 2) ^ pim) & 7) << 4) + (lane & 3) * 4;
      bar_sync<3, 128>();
#pragma unroll
      for (int jj = 0; jj < 8; jj++) {
        const b2 ar = as_b2(__byte_perm(as_u(v[2 * jj].y), as_u(v[2 * jj + 1].y), 0x5410)), br = as_b2(__byte_perm(as_u(v[2 * jj].y), as_u(v[2 * jj + 1].y), 0x7632));
        const b2 ai = as_b2(__byte_perm(as_u(v[2 * jj].x), as_u(v[2 * jj + 1].x), 0x5410)), bi = as_b2(__byte_perm(as_u(v[2 * jj].x), as_u(v[2 * jj + 1].x), 0x7632));
        sts32(pr + jj * 1024, as_u(__hadd2(ar, br)));
        sts32(pr + jj * 1024 + 128, as_u(k == 112 ? __hadd2(ai, bi) : __hsub2(ar, br)));
        sts32(pi + jj * 1024 + 128, as_u(__hadd2(ai, bi)));
        sts32(pi + jj * 1024, as_u(__hsub2(ai, bi)));
      }
      fence_async_smem();
      bar_sync<3, 128>();
      if (t == 0) {
        PROF(2, 5);
        tma_store(&tm_s, pre * 64, 0, sb + OFF_EXCH);
        if (k != 0 && k != 112) tma_store(&tm_s, pim * 64, 0, sb + OFF_EXCH + 8192);
        bulk_done();
      }
    }
    if (t == 0) { red_relaxed(&g_cnt[5 * 32]); PROF(2, 7); }
    __syncwarp();
    asm volatile("barrier.cluster.wait.aligned;" ::: "memory");
  } else {
    asm volatile("setmaxnreg.dec.sync.aligned.u32 24;");
    auto wd_tile = [&](int b, uint32_t dst, uint32_t fb) {
#pragma unroll
      for (int hf = 0; hf < 2; hf++) {
        const int js = kh * 4 + (b < 12 ? (b & 3) : (b & 1) * 2 + hf);
        const int row = 224 * js + (b < 12 ? (js & 1) * 32 + (b >> 2) * 64 + hf * 32 : 192 - hf * 192);
        tma2d(dst + hf * 4096, &tm_d, 112 * n, row, fb);
        tma2d(dst + 8192 + hf * 4096, &tm_d, 112 * n + 64, row, fb);
      }
    };
    if (warp == 12) {
      if (elect()) {
        mbar_init(bars + B_XFULL * 8, 1); mbar_init(bars + (B_XFULL + 1) * 8, 1);
        fence_async_smem();
#pragma unroll
        for (int w = 0; w < 2; w++) {
          mbar_expect(bars + (B_XFULL + w) * 8, HALF_XR);
          tma3d(sb + OFF_PQ + w * HALF_XR, &tm_x, 0, m * 128 + (w ^ kh ^ 1) * 64, 0, bars + (B_XFULL + w) * 8);
        }
        PROF(3, 3);
#pragma unroll
        for (int i = 0; i < NSLOT; i++) mbar_init(bars + (B_FULL + i) * 8, 1);
        mbar_init(bars + B_PIN * 8, 1);
        fence_async_smem();
      }
      bar_arrive<0, NTHREADS - 64>();
#pragma unroll 1
      for (int i = 0; i < 6; i++) {
        if (elect()) {
          const uint32_t fb = bars + (B_FULL + i) * 8;
          mbar_expect(fb, SLOT);
          tma2d(sb + i * SLOT, &tm_g, c64, i * 64, fb);
          tma2d(sb + i * SLOT + 8192, &tm_u, c64, i * 64, fb);
          PROF(3, 4 + i);
        }
      }
      if (elect()) {
        prefetch_l2(reinterpret_cast<const unsigned char*>(w_r) + bid * 7200, 7200);
        prefetch_l2(reinterpret_cast<const unsigned char*>(w_i) + bid * 7200, 7200);
        prefetch_tma2d(&tm_g, c64, 384); prefetch_tma2d(&tm_u, c64, 384);
      }
    } else if (warp == 14) {
      if (elect()) {
#pragma unroll
        for (int i = B_EMPTY; i < B_END; i++)
          if (i < B_XFULL || i >= B_XFREE) mbar_init(bars + i * 8, i >= B_PQFULL ? 1 : ((i == B_XFREE || i == B_PUBW) ? 4 : 8));
        asm volatile("fence.mbarrier_init.release.cluster;" ::: "memory");
        fence_async_smem();
        mbar_expect(bars + B_RECV * 8, 64 * 112 * 4);
      }
      bar_arrive<0, NTHREADS - 64>();
    }
    const uint32_t epoch = ld_relaxed(&g_ep[bid]);
    if (warp == 13 && lane == 0) { PROFG(4, 0); PROF(4, 1); }
    bar_sync<1, 128>();
    asm volatile("barrier.cluster.arrive.relaxed.aligned;" ::: "memory");
    if (warp == 12) {
      int slot = 6, ph = 1;
      auto wait_slot = [&]() { mbar_wait(bars + (B_EMPTY + slot) * 8, ph ^ (slot == 6)); };
      auto adv = [&]() { if (++slot == NSLOT) { slot = 0; ph ^= 1; } };
      const int c32 = 224 * j + ((j & 1) ? 0 : 192);
#pragma unroll 1
      for (int i = 6; i < 25; i++) {
        wait_slot();
        if (elect()) {
          const uint32_t dst = sb + slot * SLOT, fb = bars + (B_FULL + slot) * 8;
          const bool last = i >= 21;
          const int cc = last ? c32 : c64 + 64 * (i / 7), rr = last ? slot * 128 : slot * 64;
          mbar_expect(fb, SLOT);
          tma2d(dst, last ? &tm_g32 : &tm_g, cc, rr, fb);
          tma2d(dst + 8192, last ? &tm_u32 : &tm_u, cc, rr, fb);
        }
        adv();
      }
      if (lane == 0) PROF(3, 0);
#pragma unroll 1
      for (int i = 3; i < 16; i++) {
        if (lane == 0) PROF(3, 16 + i);
        if (i == 14) mbar_wait(bars + B_PREP * 8, 0);
        wait_slot();
        if (elect()) {
          const uint32_t fb = bars + (B_FULL + slot) * 8;
          mbar_expect(fb, i < 14 ? SLOT : G_IMG / 2);
          if (i < 14) wd_tile(i, sb + slot * SLOT, fb);
          else bulk_g2s(sb + slot * SLOT, g_G + (size_t)(n * 4 + i - 12) * (G_IMG / 2), G_IMG / 2, fb);
        }
        adv();
      }
      if (lane == 0) PROF(3, 2);
    } else if (warp == 13) {
      mbar_wait(bars + B_PUBX * 8, 0);
      if (elect()) {
        PROF(4, 8);
#pragma unroll
        for (int w = 0; w < 2; w++) tma_store(&tm_s, ((m * 2 + (w ^ kh ^ 1)) * 2 + (j & 1)) * 64, 192 + (j >> 1) * 64, sb + OFF_EXCH + w * 8192);
        bulk_done();
        red_relaxed(&g_cnt[(j >> 1) * 32]);
        mbar_arrive(bars + B_XDONE * 8);
        PROF(4, 12);
      }
      mbar_wait(bars + (B_XFREE + 1) * 8, 0);
      asm volatile("fence.acq_rel.gpu;" ::: "memory");
      if (lane == 0) PROF(4, 10);
      mbar_wait(bars + B_PUBW * 8, 0);
      if (elect()) {
        PROF(4, 9);
        tma_store(&tm_s, bid * 64, 64, sb + OFF_R);
        tma_store(&tm_s, bid * 64, 128, sb + OFF_R + 8192);
        bulk_done();
        red_relaxed(&g_cnt[4 * 32]);
        mbar_arrive(bars + B_WDONE * 8);
        PROF(4, 13);
      }
      mbar_wait(bars + B_PREP * 8, 0);
      mbar_wait(bars + B_LFREE * 8, 0);
      if (elect()) {
        mbar_expect(bars + B_GFULL * 8, G_IMG);
        bulk_g2s(sb + OFF_R + 28672, g_G + (size_t)(n * 2) * G_IMG, G_IMG, bars + B_GFULL * 8);
      }
    } else if (warp == 14) {
      wait_ge(&g_cnt[4 * 32], (epoch + 1) * 128);
      fence_async_global();
      if (elect()) {
        mbar_arrive(bars + B_PREP * 8);
        if (bid < 113) {
          mbar_expect(bars + B_WFULL * 8, 16384);
          bulk_g2s(sb + OFF_WS, g_X + (64 + bid) * XP, 16384, bars + B_WFULL * 8);
        }
        PROF(5, 17);
      }
    } else {
      mbar_wait(bars + B_XFREE * 8, 0);
      if (elect()) {
        mbar_expect(bars + B_PIN * 8, 14400);
        bulk_g2s(sb + OFF_WS, reinterpret_cast<const unsigned char*>(w_r) + bid * 7200, 7200, bars + B_PIN * 8);
        bulk_g2s(sb + OFF_WS + 7200, reinterpret_cast<const unsigned char*>(w_i) + bid * 7200, 7200, bars + B_PIN * 8);
        prefetch_l2(reinterpret_cast<const unsigned char*>(w_gate) + bid * 12544, 12544);
        prefetch_l2(reinterpret_cast<const unsigned char*>(w_up) + bid * 12544, 12544);
        prefetch_l2(reinterpret_cast<const unsigned char*>(w_down) + bid * 12544, 12544);
        PROF(5, 2);
      }
      if (bid < 113) {
        const int sl = (bid == 112) ? 0 : bid;
        wait_ge(&g_cnt[((sl & 1) + 2 * ((sl >> 1) / 28)) * 32], (epoch + 1) * 32);
        if (elect()) { PROF(5, 16); mbar_arrive(bars + B_XCFULL * 8); }
      }
      mbar_wait(bars + B_WDONE * 8, 0);
      if (elect()) mbar_expect(bars + B_RFULL * 8, 3 * SLOT);
#pragma unroll 1
      for (int i = 0; i < 3; i++) {
        mbar_wait(bars + (B_FULL + 2 * i + 1) * 8, 1);
        if (elect()) wd_tile(i, sb + OFF_R + i * SLOT, bars + B_RFULL * 8);
      }
      if (lane == 0) PROF(5, 19);
      mbar_wait(bars + B_PREP * 8, 0);
      wait_ge(&g_cnt[5 * 32], (epoch + 1) * 128);
      fence_async_global();
      if (elect()) {
        PROF(5, 18);
        const unsigned char* src = g_X + (m * 2 + kh) * HALF_XR;
#pragma unroll
        for (int i = 0; i < 4; i++) {
          mbar_expect(bars + (B_PQFULL + i) * 8, i ? 14336 : 14336 + 256);
          bulk_g2s(sb + OFF_PQ + i * 14336, src + i * 14336, 14336, bars + (B_PQFULL + i) * 8);
        }
        bulk_g2s(sb + OFF_G, g_gate + m * 128 + kh * 64, 256, bars + B_PQFULL * 8);
      }
    }
    __syncwarp();
    asm volatile("barrier.cluster.wait.aligned;" ::: "memory");
  }
}

typedef CUresult (*EncodeFn)(CUtensorMap*, CUtensorMapDataType, cuuint32_t, void*, const cuuint64_t*, const cuuint64_t*, const cuuint32_t*,
                             const cuuint32_t*, CUtensorMapInterleave, CUtensorMapSwizzle, CUtensorMapL2promotion, CUtensorMapFloatOOBfill);

void make_map(EncodeFn enc, CUtensorMap* tm, const void* base, int cols, int rows, int bc, int br, CUtensorMapSwizzle sw) {
  cuuint64_t gd[2] = {(cuuint64_t)cols, (cuuint64_t)rows};
  cuuint64_t gs[1] = {(cuuint64_t)cols * 2};
  cuuint32_t bd[2] = {(cuuint32_t)bc, (cuuint32_t)br};
  cuuint32_t es[2] = {1, 1};
  enc(tm, CU_TENSOR_MAP_DATA_TYPE_BFLOAT16, 2, const_cast<void*>(base), gd, gs, bd, es, CU_TENSOR_MAP_INTERLEAVE_NONE, sw,
      CU_TENSOR_MAP_L2_PROMOTION_L2_128B, CU_TENSOR_MAP_FLOAT_OOB_FILL_NONE);
}

}

extern "C" void kernel_launch(void* const* d_in, const int* in_sizes, int n_in, void* d_out, int out_size) {
  (void)in_sizes; (void)n_in; (void)out_size;
  const __nv_bfloat16* x = (const __nv_bfloat16*)d_in[0];
  const __nv_bfloat16* w_r = (const __nv_bfloat16*)d_in[1];
  const __nv_bfloat16* w_i = (const __nv_bfloat16*)d_in[2];
  const __nv_bfloat16* w_gate = (const __nv_bfloat16*)d_in[4];
  const __nv_bfloat16* w_up = (const __nv_bfloat16*)d_in[5];
  const __nv_bfloat16* w_down = (const __nv_bfloat16*)d_in[6];
  const __nv_bfloat16* gate_w = (const __nv_bfloat16*)d_in[7];
  static EncodeFn enc = nullptr;
  static void* xbuf = nullptr;
  static bool ok = false;
  if (!enc) {
    cudaDriverEntryPointQueryResult qr;
    cudaGetDriverEntryPoint("cuTensorMapEncodeTiled", (void**)&enc, cudaEnableDefault, &qr);
    cudaFuncSetAttribute(fused_kernel, cudaFuncAttributeMaxDynamicSharedMemorySize, SMEM_BYTES);
    cudaGetSymbolAddress(&xbuf, g_X);
    cudaFuncAttributes fa;
    cudaFuncGetAttributes(&fa, fused_kernel);
    ok = (fa.numRegs == 128);
  }
  if (!ok) return;
  CUtensorMap tx, tg, tu, tg32, tu32, td, ts;
  {
    cuuint64_t gd[3] = {64, (cuuint64_t)S_, 7};
    cuuint64_t gs[2] = {(cuuint64_t)D_ * 2, 128};
    cuuint32_t bd[3] = {64, 64, 7};
    cuuint32_t es[3] = {1, 1, 1};
    enc(&tx, CU_TENSOR_MAP_DATA_TYPE_BFLOAT16, 3, const_cast<__nv_bfloat16*>(x), gd, gs, bd, es, CU_TENSOR_MAP_INTERLEAVE_NONE, CU_TENSOR_MAP_SWIZZLE_128B,
        CU_TENSOR_MAP_L2_PROMOTION_L2_128B, CU_TENSOR_MAP_FLOAT_OOB_FILL_NONE);
  }
  make_map(enc, &tg, w_gate, F_, D_, 64, 64, CU_TENSOR_MAP_SWIZZLE_128B);
  make_map(enc, &tu, w_up, F_, D_, 64, 64, CU_TENSOR_MAP_SWIZZLE_128B);
  make_map(enc, &tg32, w_gate, F_, D_, 32, 128, CU_TENSOR_MAP_SWIZZLE_64B);
  make_map(enc, &tu32, w_up, F_, D_, 32, 128, CU_TENSOR_MAP_SWIZZLE_64B);
  make_map(enc, &td, w_down, D_, F_, 64, 32, CU_TENSOR_MAP_SWIZZLE_128B);
  make_map(enc, &ts, (const __nv_bfloat16*)xbuf, XP / 2, 448, 64, 64, CU_TENSOR_MAP_SWIZZLE_NONE);
  fused_kernel<<<128, NTHREADS, SMEM_BYTES>>>(tx, tg, tu, tg32, tu32, td, ts, w_r, w_i, w_gate, w_up, w_down, gate_w, (__nv_bfloat16*)d_out);
}
```

```cpp
#include <cuda_runtime.h>
#include <cuda_bf16.h>
#include <cuda.h>
#include <stdint.h>

namespace {

constexpr int S_ = 2048, D_ = 448, F_ = 1792;
constexpr int NTHREADS = 512;
constexpr int SLOT = 16384, NSLOT = 7;
constexpr int HALF_XR = 57344;
constexpr int OFF_PQ = NSLOT * SLOT;
constexpr int OFF_R = OFF_PQ + HALF_XR;
constexpr int OFF_EXCH = OFF_PQ;
constexpr int OFF_WS = OFF_EXCH + 18432;
constexpr int OFF_TW = OFF_WS + 16384;
constexpr int OFF_MISC = OFF_R + HALF_XR;
constexpr int OFF_G = OFF_MISC;
constexpr int OFF_BAR = OFF_MISC + 512;
constexpr int SMEM_BYTES = OFF_BAR + 512;
constexpr int B_FULL = 0, B_EMPTY = 7, B_XFULL = 14  ;
constexpr int B_XFREE = 16  , B_PUBX = 18, B_RFREE = 19, B_LFREE = 20;
constexpr int B_PUBW = 21;
constexpr int B_PQFULL = 22  , B_RECV = 26, B_WFULL = 27, B_XCFULL = 28, B_PREP = 29, B_RFULL = 30, B_GFULL = 31, B_XDONE = 32, B_WDONE = 33, B_END = 34, B_PIN = 34;

constexpr int G_IMG = 224 * 56 * 2;

__device__ __align__(1024) unsigned char g_H[32 * 56 * 4096];
constexpr int XP = 28672;
__device__ __align__(1024) unsigned char g_X[448 * XP];
__device__ __align__(1024) unsigned char g_G[8 * G_IMG];
__device__ __align__(1024) float g_gate[S_];
__device__ __align__(128) unsigned int g_ep[128];
__device__ __align__(128) unsigned int g_cnt[8 * 32];

#define POLL ld_relaxed
#define PROF(role, idx) do {} while (0)
#define PROFG(role, idx) do {} while (0)

__device__ __forceinline__ uint32_t s2u(const void* p) { return (uint32_t)__cvta_generic_to_shared(p); }
__device__ __forceinline__ void mbar_init(uint32_t b, int c) { asm volatile("mbarrier.init.shared::cta.b64 [%0], %1;" :: "r"(b), "r"(c) : "memory"); }
__device__ __forceinline__ void mbar_expect(uint32_t b, int bytes) { asm volatile("mbarrier.arrive.expect_tx.shared::cta.b64 _, [%0], %1;" :: "r"(b), "r"(bytes) : "memory"); }
__device__ __forceinline__ void mbar_arrive(uint32_t b) { asm volatile("mbarrier.arrive.shared::cta.b64 _, [%0];" :: "r"(b) : "memory"); }
__device__ __forceinline__ void mbar_wait(uint32_t b, int ph) {
  asm volatile("{\n.reg .pred p;\n.reg .u32 c;\nmov.u32 c, 0;\nL_WAIT:\nmbarrier.try_wait.parity.shared::cta.b64 p, [%0], %1;\n@p bra.uni L_DONE;\n"
               "add.u32 c, c, 1;\nsetp.lt.u32 p, c, 4194304;\n@p bra.uni L_WAIT;\ntrap;\nL_DONE:\n}" :: "r"(b), "r"(ph) : "memory");
}
__device__ __forceinline__ void mbar_wait_cluster(uint32_t b, int ph) {
  asm volatile("{\n.reg .pred p;\n.reg .u32 c;\nmov.u32 c, 0;\nL_WAIT:\nmbarrier.try_wait.parity.acquire.cluster.shared::cta.b64 p, [%0], %1;\n@p bra.uni L_DONE;\n"
               "add.u32 c, c, 1;\nsetp.lt.u32 p, c, 4194304;\n@p bra.uni L_WAIT;\ntrap;\nL_DONE:\n}" :: "r"(b), "r"(ph) : "memory");
}
__device__ __forceinline__ uint32_t ld_acquire(const unsigned int* p) { uint32_t v; asm volatile("ld.acquire.gpu.global.u32 %0, [%1];" : "=r"(v) : "l"(p) : "memory"); return v; }
__device__ __forceinline__ uint32_t ld_relaxed(const unsigned int* p) { uint32_t v; asm volatile("ld.relaxed.gpu.global.u32 %0, [%1];" : "=r"(v) : "l"(p) : "memory"); return v; }
__device__ __forceinline__ void wait_ge(const unsigned int* p, uint32_t target) {
#pragma unroll 1
  for (int i = 0; i < (1 << 22); i++) { if ((int)(POLL(p) - target) >= 0) return; }
  __trap();
}
__device__ __forceinline__ void red_relaxed(unsigned int* p) { asm volatile("red.relaxed.gpu.global.add.u32 [%0], 1;" :: "l"(p) : "memory"); }
__device__ __forceinline__ bool elect() { uint32_t p; asm volatile("{\n.reg .pred p;\nelect.sync _|p, 0xffffffff;\nselp.u32 %0, 1, 0, p;\n}" : "=r"(p)); return p; }
__device__ __forceinline__ void fence_async_smem() { asm volatile("fence.proxy.async.shared::cta;" ::: "memory"); }
__device__ __forceinline__ void fence_async_global() { asm volatile("fence.proxy.async.global;" ::: "memory"); }
template <int ID, int N> __device__ __forceinline__ void bar_sync() { asm volatile("bar.sync %0, %1;" :: "n"(ID), "n"(N) : "memory"); }
template <int ID, int N> __device__ __forceinline__ void bar_arrive() { asm volatile("bar.arrive %0, %1;" :: "n"(ID), "n"(N) : "memory"); }
__device__ __forceinline__ void tma2d(uint32_t dst, const CUtensorMap* tm, int c0, int c1, uint32_t bar) {
  asm volatile("cp.async.bulk.tensor.2d.shared::cluster.global.mbarrier::complete_tx::bytes [%0], [%1, {%3, %4}], [%2];"
               :: "r"(dst), "l"(tm), "r"(bar), "r"(c0), "r"(c1) : "memory");
}
__device__ __forceinline__ void tma3d(uint32_t dst, const CUtensorMap* tm, int c0, int c1, int c2, uint32_t bar) {
  asm volatile("cp.async.bulk.tensor.3d.shared::cluster.global.mbarrier::complete_tx::bytes [%0], [%1, {%3, %4, %5}], [%2];"
               :: "r"(dst), "l"(tm), "r"(bar), "r"(c0), "r"(c1), "r"(c2) : "memory");
}
__device__ __forceinline__ void bulk_g2s(uint32_t dst, const void* src, int bytes, uint32_t bar) {
  asm volatile("cp.async.bulk.shared::cluster.global.mbarrier::complete_tx::bytes [%0], [%1], %2, [%3];"
               :: "r"(dst), "l"(src), "r"(bytes), "r"(bar) : "memory");
}
__device__ __forceinline__ void tma_store(const CUtensorMap* tm, int c0, int c1, uint32_t src) {
  asm volatile("cp.async.bulk.tensor.2d.global.shared::cta.bulk_group [%0, {%1, %2}], [%3];" :: "l"(tm), "r"(c0), "r"(c1), "r"(src) : "memory");
}
__device__ __forceinline__ void bulk_done() { asm volatile("cp.async.bulk.commit_group;\ncp.async.bulk.wait_group 0;\nfence.proxy.async.global;" ::: "memory"); }
__device__ __forceinline__ void sts32(uint32_t a, uint32_t x) { asm volatile("st.shared.b32 [%0], %1;" :: "r"(a), "r"(x) : "memory"); }
__device__ __forceinline__ void prefetch_l2(const void* src, int bytes) {
  asm volatile("cp.async.bulk.prefetch.L2.global [%0], %1;" :: "l"(src), "r"(bytes) : "memory");
}
__device__ __forceinline__ void prefetch_tma2d(const CUtensorMap* tm, int c0, int c1) {
  asm volatile("cp.async.bulk.prefetch.tensor.2d.L2.global [%0, {%1, %2}];" :: "l"(tm), "r"(c0), "r"(c1) : "memory");
}
__device__ __forceinline__ uint64_t mkdesc(uint32_t addr, uint32_t lbo, uint32_t sbo, uint32_t mode) {
  return (uint64_t)((addr & 0x3FFFF) >> 4) | ((uint64_t)(lbo >> 4) << 16) | ((uint64_t)(sbo >> 4) << 32) | ((uint64_t)mode << 62);
}
__device__ __forceinline__ void wg_fence() { asm volatile("wgmma.fence.sync.aligned;" ::: "memory"); }
__device__ __forceinline__ void wg_commit() { asm volatile("wgmma.commit_group.sync.aligned;" ::: "memory"); }
template <int N> __device__ __forceinline__ void wg_wait() { asm volatile("wgmma.wait_group.sync.aligned %0;" :: "n"(N) : "memory"); }
template <int N> __device__ __forceinline__ void keep(float (&d)[N]) {
#pragma unroll
  for (int i = 0; i < N; i++) asm volatile("" : "+f"(d[i]) :: "memory");
}
__device__ __forceinline__ uint32_t pack_bf16(float lo, float hi) { uint32_t r; asm("cvt.rn.bf16x2.f32 %0, %1, %2;" : "=r"(r) : "f"(hi), "f"(lo)); return r; }
__device__ __forceinline__ float bf16_round(float v) { return __bfloat162float(__float2bfloat16_rn(v)); }
__device__ __forceinline__ void sts128(uint32_t a, uint32_t x, uint32_t y, uint32_t z, uint32_t w) { asm volatile("st.shared.v4.b32 [%0], {%1,%2,%3,%4};" :: "r"(a), "r"(x), "r"(y), "r"(z), "r"(w) : "memory"); }
__device__ __forceinline__ float4 lds128f(uint32_t a) { float4 v; asm volatile("ld.shared.v4.f32 {%0,%1,%2,%3}, [%4];" : "=f"(v.x), "=f"(v.y), "=f"(v.z), "=f"(v.w) : "r"(a) : "memory"); return v; }

__device__ __forceinline__ uint2 lds64(uint32_t a) { uint2 v; asm volatile("ld.shared.v2.b32 {%0,%1}, [%2];" : "=r"(v.x), "=r"(v.y) : "r"(a) : "memory"); return v; }
__device__ __forceinline__ float bf_lo(uint32_t w) { return __uint_as_float(w << 16); }
__device__ __forceinline__ float bf_hi(uint32_t w) { return __uint_as_float(w & 0xffff0000u); }
__device__ __forceinline__ uint32_t opaque(uint32_t v) { asm volatile("" : "+r"(v)); return v; }
__device__ __forceinline__ uint4 ldg128(const void* p) { uint4 v; asm volatile("ld.global.nc.v4.b32 {%0,%1,%2,%3}, [%4];" : "=r"(v.x), "=r"(v.y), "=r"(v.z), "=r"(v.w) : "l"(p)); return v; }
__device__ __forceinline__ void stg128(void* p, uint32_t x, uint32_t y, uint32_t z, uint32_t w) { asm volatile("st.global.v4.b32 [%0], {%1,%2,%3,%4};" :: "l"(p), "r"(x), "r"(y), "r"(z), "r"(w) : "memory"); }
__device__ __forceinline__ void stg128_l2(void* p, uint32_t x, uint32_t y, uint32_t z, uint32_t w) { asm volatile("st.relaxed.gpu.global.v4.b32 [%0], {%1,%2,%3,%4};" :: "l"(p), "r"(x), "r"(y), "r"(z), "r"(w) : "memory"); }
__device__ __forceinline__ uint2 ldg64_l2(const void* p) { uint2 v; asm volatile("ld.relaxed.gpu.global.v2.b32 {%0,%1}, [%2];" : "=r"(v.x), "=r"(v.y) : "l"(p) : "memory"); return v; }
__device__ __forceinline__ void ldg128_l2(uint32_t (&v)[4], const void* p) { asm volatile("ld.relaxed.gpu.global.v4.b32 {%0,%1,%2,%3}, [%4];" : "=r"(v[0]), "=r"(v[1]), "=r"(v[2]), "=r"(v[3]) : "l"(p) : "memory"); }
__device__ __forceinline__ uint4 lds128(uint32_t a) { uint4 v; asm volatile("ld.shared.v4.b32 {%0,%1,%2,%3}, [%4];" : "=r"(v.x), "=r"(v.y), "=r"(v.z), "=r"(v.w) : "r"(a) : "memory"); return v; }
__device__ __forceinline__ uint32_t lds16(uint32_t a) { uint32_t v; asm volatile("ld.shared.u16 %0, [%1];" : "=r"(v) : "r"(a) : "memory"); return v; }
__device__ __forceinline__ void sts64(uint32_t a, uint32_t x, uint32_t y) { asm volatile("st.shared.v2.b32 [%0], {%1,%2};" :: "r"(a), "r"(x), "r"(y) : "memory"); }
template <int TB> __device__ __forceinline__ void wgmma_rs_128(float (&d)[64], const uint32_t (&a)[4], uint64_t db, int sc) {
  asm volatile("{\n.reg .pred p;\nsetp.ne.b32 p, %69, 0;\n"
    "wgmma.mma_async.sync.aligned.m64n128k16.f32.bf16.bf16 {%0, %1, %2, %3, %4, %5, %6, %7, %8, %9, %10, %11, %12, %13, %14, %15, %16, %17, %18, %19, %20, %21, %22, %23, %24, %25, %26, %27, %28, %29, %30, %31, %32, %33, %34, %35, %36, %37, %38, %39, %40, %41, %42, %43, %44, %45, %46, %47, %48, %49, %50, %51, %52, %53, %54, %55, %56, %57, %58, %59, %60, %61, %62, %63}, {%64, %65, %66, %67}, %68, p, 1, 1, %70;\n}\n"
    : "+f"(d[0]), "+f"(d[1]), "+f"(d[2]), "+f"(d[3]), "+f"(d[4]), "+f"(d[5]), "+f"(d[6]), "+f"(d[7]), "+f"(d[8]), "+f"(d[9]), "+f"(d[10]), "+f"(d[11]), "+f"(d[12]), "+f"(d[13]), "+f"(d[14]), "+f"(d[15]), "+f"(d[16]), "+f"(d[17]), "+f"(d[18]), "+f"(d[19]), "+f"(d[20]), "+f"(d[21]), "+f"(d[22]), "+f"(d[23]), "+f"(d[24]), "+f"(d[25]), "+f"(d[26]), "+f"(d[27]), "+f"(d[28]), "+f"(d[29]), "+f"(d[30]), "+f"(d[31]), "+f"(d[32]), "+f"(d[33]), "+f"(d[34]), "+f"(d[35]), "+f"(d[36]), "+f"(d[37]), "+f"(d[38]), "+f"(d[39]), "+f"(d[40]), "+f"(d[41]), "+f"(d[42]), "+f"(d[43]), "+f"(d[44]), "+f"(d[45]), "+f"(d[46]), "+f"(d[47]), "+f"(d[48]), "+f"(d[49]), "+f"(d[50]), "+f"(d[51]), "+f"(d[52]), "+f"(d[53]), "+f"(d[54]), "+f"(d[55]), "+f"(d[56]), "+f"(d[57]), "+f"(d[58]), "+f"(d[59]), "+f"(d[60]), "+f"(d[61]), "+f"(d[62]), "+f"(d[63])
    : "r"(a[0]), "r"(a[1]), "r"(a[2]), "r"(a[3]), "l"(db), "r"(sc), "n"(TB));
}
template <int TB> __device__ __forceinline__ void wgmma_rs_64(float (&d)[32], const uint32_t (&a)[4], uint64_t db, int sc) {
  asm volatile("{\n.reg .pred p;\nsetp.ne.b32 p, %37, 0;\n"
    "wgmma.mma_async.sync.aligned.m64n64k16.f32.bf16.bf16 {%0, %1, %2, %3, %4, %5, %6, %7, %8, %9, %10, %11, %12, %13, %14, %15, %16, %17, %18, %19, %20, %21, %22, %23, %24, %25, %26, %27, %28, %29, %30, %31}, {%32, %33, %34, %35}, %36, p, 1, 1, %38;\n}\n"
    : "+f"(d[0]), "+f"(d[1]), "+f"(d[2]), "+f"(d[3]), "+f"(d[4]), "+f"(d[5]), "+f"(d[6]), "+f"(d[7]), "+f"(d[8]), "+f"(d[9]), "+f"(d[10]), "+f"(d[11]), "+f"(d[12]), "+f"(d[13]), "+f"(d[14]), "+f"(d[15]), "+f"(d[16]), "+f"(d[17]), "+f"(d[18]), "+f"(d[19]), "+f"(d[20]), "+f"(d[21]), "+f"(d[22]), "+f"(d[23]), "+f"(d[24]), "+f"(d[25]), "+f"(d[26]), "+f"(d[27]), "+f"(d[28]), "+f"(d[29]), "+f"(d[30]), "+f"(d[31])
    : "r"(a[0]), "r"(a[1]), "r"(a[2]), "r"(a[3]), "l"(db), "r"(sc), "n"(TB));
}
template <int TB> __device__ __forceinline__ void wgmma_rs_56(float (&d)[28], const uint32_t (&a)[4], uint64_t db, int sc) {
  asm volatile("{\n.reg .pred p;\nsetp.ne.b32 p, %33, 0;\n"
    "wgmma.mma_async.sync.aligned.m64n56k16.f32.bf16.bf16 {%0, %1, %2, %3, %4, %5, %6, %7, %8, %9, %10, %11, %12, %13, %14, %15, %16, %17, %18, %19, %20, %21, %22, %23, %24, %25, %26, %27}, {%28, %29, %30, %31}, %32, p, 1, 1, %34;\n}\n"
    : "+f"(d[0]), "+f"(d[1]), "+f"(d[2]), "+f"(d[3]), "+f"(d[4]), "+f"(d[5]), "+f"(d[6]), "+f"(d[7]), "+f"(d[8]), "+f"(d[9]), "+f"(d[10]), "+f"(d[11]), "+f"(d[12]), "+f"(d[13]), "+f"(d[14]), "+f"(d[15]), "+f"(d[16]), "+f"(d[17]), "+f"(d[18]), "+f"(d[19]), "+f"(d[20]), "+f"(d[21]), "+f"(d[22]), "+f"(d[23]), "+f"(d[24]), "+f"(d[25]), "+f"(d[26]), "+f"(d[27])
    : "r"(a[0]), "r"(a[1]), "r"(a[2]), "r"(a[3]), "l"(db), "r"(sc), "n"(TB));
}
template <int TB> __device__ __forceinline__ void wgmma_rs_112(float (&d)[56], const uint32_t (&a)[4], uint64_t db, int sc) {
  asm volatile("{\n.reg .pred p;\nsetp.ne.b32 p, %61, 0;\n"
    "wgmma.mma_async.sync.aligned.m64n112k16.f32.bf16.bf16 {%0, %1, %2, %3, %4, %5, %6, %7, %8, %9, %10, %11, %12, %13, %14, %15, %16, %17, %18, %19, %20, %21, %22, %23, %24, %25, %26, %27, %28, %29, %30, %31, %32, %33, %34, %35, %36, %37, %38, %39, %40, %41, %42, %43, %44, %45, %46, %47, %48, %49, %50, %51, %52, %53, %54, %55}, {%56, %57, %58, %59}, %60, p, 1, 1, %62;\n}\n"
    : "+f"(d[0]), "+f"(d[1]), "+f"(d[2]), "+f"(d[3]), "+f"(d[4]), "+f"(d[5]), "+f"(d[6]), "+f"(d[7]), "+f"(d[8]), "+f"(d[9]), "+f"(d[10]), "+f"(d[11]), "+f"(d[12]), "+f"(d[13]), "+f"(d[14]), "+f"(d[15]), "+f"(d[16]), "+f"(d[17]), "+f"(d[18]), "+f"(d[19]), "+f"(d[20]), "+f"(d[21]), "+f"(d[22]), "+f"(d[23]), "+f"(d[24]), "+f"(d[25]), "+f"(d[26]), "+f"(d[27]), "+f"(d[28]), "+f"(d[29]), "+f"(d[30]), "+f"(d[31]), "+f"(d[32]), "+f"(d[33]), "+f"(d[34]), "+f"(d[35]), "+f"(d[36]), "+f"(d[37]), "+f"(d[38]), "+f"(d[39]), "+f"(d[40]), "+f"(d[41]), "+f"(d[42]), "+f"(d[43]), "+f"(d[44]), "+f"(d[45]), "+f"(d[46]), "+f"(d[47]), "+f"(d[48]), "+f"(d[49]), "+f"(d[50]), "+f"(d[51]), "+f"(d[52]), "+f"(d[53]), "+f"(d[54]), "+f"(d[55])
    : "r"(a[0]), "r"(a[1]), "r"(a[2]), "r"(a[3]), "l"(db), "r"(sc), "n"(TB));
}
template <int TA, int TB> __device__ __forceinline__ void wgmma_ss_56(float (&d)[28], uint64_t da, uint64_t db, int sc) {
  asm volatile("{\n.reg .pred p;\nsetp.ne.b32 p, %30, 0;\n"
    "wgmma.mma_async.sync.aligned.m64n56k16.f32.bf16.bf16 {%0, %1, %2, %3, %4, %5, %6, %7, %8, %9, %10, %11, %12, %13, %14, %15, %16, %17, %18, %19, %20, %21, %22, %23, %24, %25, %26, %27}, %28, %29, p, 1, 1, %31, %32;\n}\n"
    : "+f"(d[0]), "+f"(d[1]), "+f"(d[2]), "+f"(d[3]), "+f"(d[4]), "+f"(d[5]), "+f"(d[6]), "+f"(d[7]), "+f"(d[8]), "+f"(d[9]), "+f"(d[10]), "+f"(d[11]), "+f"(d[12]), "+f"(d[13]), "+f"(d[14]), "+f"(d[15]), "+f"(d[16]), "+f"(d[17]), "+f"(d[18]), "+f"(d[19]), "+f"(d[20]), "+f"(d[21]), "+f"(d[22]), "+f"(d[23]), "+f"(d[24]), "+f"(d[25]), "+f"(d[26]), "+f"(d[27])
    : "l"(da), "l"(db), "r"(sc), "n"(TA), "n"(TB));
}

__device__ __forceinline__ uint32_t cis(float a) { return pack_bf16(__cosf(a), __sinf(a)); }

typedef __nv_bfloat162 b2;
struct c2 { b2 x, y; };
__device__ __forceinline__ b2 as_b2(uint32_t u) { return *reinterpret_cast<b2*>(&u); }
__device__ __forceinline__ uint32_t as_u(b2 v) { return *reinterpret_cast<uint32_t*>(&v); }
__device__ __forceinline__ c2 mk(b2 x, b2 y) { c2 r; r.x = x; r.y = y; return r; }
__device__ __forceinline__ c2 cmul(c2 a, b2 wr, b2 wi) { return mk(__hfma2(a.x, wr, __hneg2(__hmul2(a.y, wi))), __hfma2(a.x, wi, __hmul2(a.y, wr))); }
__device__ __forceinline__ void fft4(c2& a0, c2& a1, c2& a2, c2& a3) {
  c2 t0 = mk(__hadd2(a0.x, a2.x), __hadd2(a0.y, a2.y)), t1 = mk(__hsub2(a0.x, a2.x), __hsub2(a0.y, a2.y));
  c2 t2 = mk(__hadd2(a1.x, a3.x), __hadd2(a1.y, a3.y)), t3 = mk(__hsub2(a1.x, a3.x), __hsub2(a1.y, a3.y));
  a0 = mk(__hadd2(t0.x, t2.x), __hadd2(t0.y, t2.y)); a2 = mk(__hsub2(t0.x, t2.x), __hsub2(t0.y, t2.y));
  a1 = mk(__hadd2(t1.x, t3.y), __hsub2(t1.y, t3.x)); a3 = mk(__hsub2(t1.x, t3.y), __hadd2(t1.y, t3.x));
}
__device__ __forceinline__ void fft4_s2(c2& a0, c2& a1, c2& a2, c2& a3, b2 r) {
  const b2 nr = __hneg2(r);
  c2 t0 = mk(__hfma2(a2.x, r, a0.x), __hfma2(a2.y, r, a0.y)), t1 = mk(__hfma2(a2.x, nr, a0.x), __hfma2(a2.y, nr, a0.y));
  c2 t2 = mk(__hadd2(a1.x, a3.x), __hadd2(a1.y, a3.y)), t3 = mk(__hsub2(a1.x, a3.x), __hsub2(a1.y, a3.y));
  a0 = mk(__hadd2(t0.x, t2.x), __hadd2(t0.y, t2.y)); a2 = mk(__hsub2(t0.x, t2.x), __hsub2(t0.y, t2.y));
  a1 = mk(__hadd2(t1.x, t3.y), __hsub2(t1.y, t3.x)); a3 = mk(__hsub2(t1.x, t3.y), __hadd2(t1.y, t3.x));
}
__device__ __forceinline__ void fft4_s13(c2& a0, c2& a1, c2& a2, c2& a3, b2 r) {
  const b2 nr = __hneg2(r);
  c2 t0 = mk(__hadd2(a0.x, a2.x), __hadd2(a0.y, a2.y)), t1 = mk(__hsub2(a0.x, a2.x), __hsub2(a0.y, a2.y));
  c2 t2 = mk(__hadd2(a1.x, a3.x), __hadd2(a1.y, a3.y)), t3 = mk(__hsub2(a1.x, a3.x), __hsub2(a1.y, a3.y));
  a0 = mk(__hfma2(t2.x, r, t0.x), __hfma2(t2.y, r, t0.y)); a2 = mk(__hfma2(t2.x, nr, t0.x), __hfma2(t2.y, nr, t0.y));
  a1 = mk(__hfma2(t3.y, r, t1.x), __hfma2(t3.x, nr, t1.y)); a3 = mk(__hfma2(t3.y, nr, t1.x), __hfma2(t3.x, r, t1.y));
}
__device__ __forceinline__ c2 rot1(c2 a) { return mk(__hadd2(a.x, a.y), __hsub2(a.y, a.x)); }
__device__ __forceinline__ c2 rot3(c2 a) { return mk(__hsub2(a.y, a.x), __hneg2(__hadd2(a.x, a.y))); }
__device__ __forceinline__ c2 mul_mi(c2 a) { return mk(a.y, __hneg2(a.x)); }
template <int O> __device__ __forceinline__ void fft8(c2 (&v)[16]) {
  const b2 r = as_b2(0x3F353F35u), nr = as_b2(0xBF35BF35u);
  fft4(v[O], v[O + 4], v[O + 8], v[O + 12]);
  fft4(v[O + 2], v[O + 6], v[O + 10], v[O + 14]);
  const c2 o0 = v[O + 2], o1 = rot1(v[O + 6]), o2 = v[O + 10], o3 = rot1(v[O + 14]);
  const c2 e0 = v[O], e1 = v[O + 4], e2 = v[O + 8], e3 = v[O + 12];
  v[O] = mk(__hadd2(e0.x, o0.x), __hadd2(e0.y, o0.y));              v[O + 8] = mk(__hsub2(e0.x, o0.x), __hsub2(e0.y, o0.y));
  v[O + 2] = mk(__hfma2(o1.x, r, e1.x), __hfma2(o1.y, r, e1.y));    v[O + 10] = mk(__hfma2(o1.x, nr, e1.x), __hfma2(o1.y, nr, e1.y));
  v[O + 4] = mk(__hadd2(e2.x, o2.y), __hsub2(e2.y, o2.x));          v[O + 12] = mk(__hsub2(e2.x, o2.y), __hadd2(e2.y, o2.x));
  v[O + 6] = mk(__hfma2(o3.y, r, e3.x), __hfma2(o3.x, nr, e3.y));   v[O + 14] = mk(__hfma2(o3.y, nr, e3.x), __hfma2(o3.x, r, e3.y));
}
__device__ __forceinline__ void fft16(c2 (&v)[16]) {
  const b2 r = as_b2(0x3F353F35u), c1 = as_b2(0x3F6D3F6Du), s1 = as_b2(0x3EC43EC4u), nc1 = as_b2(0xBF6DBF6Du), ns1 = as_b2(0xBEC4BEC4u);
#pragma unroll
  for (int a = 0; a < 4; a++) fft4(v[a], v[a + 4], v[a + 8], v[a + 12]);
  v[5] = cmul(v[5], c1, ns1); v[6] = rot1(v[6]); v[7] = cmul(v[7], s1, nc1);
  v[9] = rot1(v[9]); v[10] = mul_mi(v[10]); v[11] = rot3(v[11]);
  v[13] = cmul(v[13], s1, nc1); v[14] = rot3(v[14]); v[15] = cmul(v[15], nc1, s1);
  fft4(v[0], v[1], v[2], v[3]); fft4_s2(v[4], v[5], v[6], v[7], r); fft4_s13(v[8], v[9], v[10], v[11], r); fft4_s2(v[12], v[13], v[14], v[15], r);
  c2 t;
  t = v[1]; v[1] = v[4]; v[4] = t;  t = v[2]; v[2] = v[8]; v[8] = t;  t = v[3]; v[3] = v[12]; v[12] = t;
  t = v[6]; v[6] = v[9]; v[9] = t;  t = v[7]; v[7] = v[13]; v[13] = t; t = v[11]; v[11] = v[14]; v[14] = t;
}

__device__ __forceinline__ void columns(c2 (&v)[16], uint32_t sb, int t) {
  const int l16 = t & 15;
  const uint32_t row = sb + OFF_EXCH + (t >> 4) * 2304;
  const uint32_t pos = sb + OFF_EXCH + (t >> 3) * 144 + (t & 7) * 16;
#pragma unroll 1
  for (int ps = 0; ps < 6; ps++) {
    if (ps == 0 || ps == 5) { fft8<0>(v); fft8<1>(v); } else fft16(v);
    if (ps == 5) break;
    if (ps == 2) {
      const uint32_t ws = sb + OFF_WS + (l16 >> 1) * 128 + ((((t >> 4) + (l16 >> 1)) & 7) * 2 + (l16 & 1)) * 8;
      mbar_wait(sb + OFF_BAR + B_WFULL * 8, 0);
#pragma unroll
      for (int q = 0; q < 16; q++) {
        const uint2 w = lds64(ws + q * 1024);
        const c2 z = cmul(v[q], as_b2(w.x), as_b2(w.y));
        v[q] = mk(z.y, z.x);
      }
      continue;
    }
    {
      const bool full = ps == 0 || ps == 4;
      const uint32_t tw = sb + OFF_TW + (full ? ps * 2048 + t * 16 : 16384 + l16 * 16);
      const uint32_t st = full ? 2048 : 256;
#pragma unroll
      for (int i = 0; i < 4; i++) {
        const uint4 w4 = lds128(tw + i * st);
        const uint32_t w[4] = {w4.x, w4.y, w4.z, w4.w};
#pragma unroll
        for (int e = 0; e < 4; e++) v[4 * i + e] = cmul(v[4 * i + e], __low2bfloat162(as_b2(w[e])), __high2bfloat162(as_b2(w[e])));
      }
    }
    if (ps == 0) {
      mbar_wait(sb + OFF_BAR + B_XDONE * 8, 0);
#pragma unroll
      for (int q = 0; q < 8; q++) sts128(pos + q * 2304, as_u(v[2 * q].x), as_u(v[2 * q].y), as_u(v[2 * q + 1].x), as_u(v[2 * q + 1].y));
      bar_sync<3, 128>();
#pragma unroll
      for (int q = 0; q < 16; q++) { const uint2 a = lds64(row + q * 144 + l16 * 8); v[q] = mk(as_b2(a.x), as_b2(a.y)); }
    } else {
      __syncwarp();
#pragma unroll
      for (int q = 0; q < 16; q++) sts64(row + q * 144 + l16 * 8, as_u(v[q].x), as_u(v[q].y));
      if (ps == 4) bar_sync<3, 128>(); else __syncwarp();
      const uint32_t src = ps == 4 ? pos : row + l16 * 144, st = ps == 4 ? 2304 : 16;
#pragma unroll
      for (int q = 0; q < 8; q++) { const uint4 a = lds128(src + q * st); v[2 * q] = mk(as_b2(a.x), as_b2(a.y)); v[2 * q + 1] = mk(as_b2(a.z), as_b2(a.w)); }
    }
  }
}

template <int NH> __device__ __forceinline__ void h_epilogue(float (&acc)[NH * 8], unsigned char* gdst, uint32_t tag) {
#pragma unroll
  for (int c = 0; c < NH / 2; c++) {
    uint32_t pk[4];
#pragma unroll
    for (int i = 0; i < 4; i++) {
      float hv[2];
#pragma unroll
      for (int e = 0; e < 2; e++) {
        float hg = 0.5f * acc[c * 8 + i * 2 + e], up = acc[NH * 4 + c * 8 + i * 2 + e];
        float th; asm("tanh.approx.f32 %0, %1;" : "=f"(th) : "f"(hg));
        hv[e] = fmaf(hg, th, hg) * up;
      }
      pk[i] = pack_bf16(hv[0], hv[1]);
    }
    stg128_l2(gdst + c * 4096, (pk[0] & ~1u) | tag, pk[1], pk[2], pk[3]);
  }
}

__device__ __forceinline__ void frag_ready(uint32_t (&a)[4], uint32_t (&b)[4], uint32_t (&c)[4], uint32_t (&d)[4], const unsigned char* p, uint32_t tag) {
  asm volatile("{\n.reg .pred p;\n.reg .u32 c, m, q;\nmov.u32 c, 0;\nL_TRY:\n"
               "lop3.b32 m, %0, %4, %17, 0x7E;\nlop3.b32 q, %8, %12, %17, 0x7E;\nlop3.b32 m, m, q, 1, 0xA8;\nsetp.ne.u32 p, m, 0;\n"
               "vote.sync.any.pred p, p, 0xffffffff;\n@!p bra.uni L_OK;\n"
               "ld.relaxed.gpu.global.v4.b32 {%0,%1,%2,%3}, [%16];\nld.relaxed.gpu.global.v4.b32 {%4,%5,%6,%7}, [%16+4096];\n"
               "ld.relaxed.gpu.global.v4.b32 {%8,%9,%10,%11}, [%16+8192];\nld.relaxed.gpu.global.v4.b32 {%12,%13,%14,%15}, [%16+12288];\n"
               "add.u32 c, c, 1;\nsetp.lt.u32 p, c, 262144;\n@p bra.uni L_TRY;\ntrap;\nL_OK:\n}"
               : "+r"(a[0]), "+r"(a[1]), "+r"(a[2]), "+r"(a[3]), "+r"(b[0]), "+r"(b[1]), "+r"(b[2]), "+r"(b[3]),
                 "+r"(c[0]), "+r"(c[1]), "+r"(c[2]), "+r"(c[3]), "+r"(d[0]), "+r"(d[1]), "+r"(d[2]), "+r"(d[3])
               : "l"(p), "r"(tag) : "memory");
}

#define MAP 0
#define LEAD2 0
#define LEAD1 3

__global__ void __cluster_dims__(2, 1, 1) __launch_bounds__(NTHREADS, 1)
fused_kernel(const __grid_constant__ CUtensorMap tm_x, const __grid_constant__ CUtensorMap tm_g, const __grid_constant__ CUtensorMap tm_u,
             const __grid_constant__ CUtensorMap tm_g32, const __grid_constant__ CUtensorMap tm_u32, const __grid_constant__ CUtensorMap tm_d,
             const __grid_constant__ CUtensorMap tm_s,
             const __nv_bfloat16* __restrict__ w_r, const __nv_bfloat16* __restrict__ w_i,
             const __nv_bfloat16* __restrict__ w_gate, const __nv_bfloat16* __restrict__ w_up,
             const __nv_bfloat16* __restrict__ w_down, const __nv_bfloat16* __restrict__ gate_w, __nv_bfloat16* __restrict__ out) {
  extern __shared__ __align__(1024) unsigned char smem[];
  const uint32_t sb = s2u(smem);
  const uint32_t bars = sb + OFF_BAR;
  const int tid = threadIdx.x, warp = __shfl_sync(0xffffffffu, tid >> 5, 0), lane = tid & 31;
  const int cl = blockIdx.x >> 1, kh = blockIdx.x & 1;
  const int n0 = cl < 4 ? cl : (cl < 36 ? (cl - 4) >> 3 : (cl - 36) / 7);
  const int m0 = cl < 4 ? 15 : (cl < 36 ? (cl - 4) & 7 : cl - 28 - 7 * n0);
  const int n = MAP == 0 ? n0 : (MAP == 1 ? (m0 & 3) : ((n0 & 1) | ((m0 & 1) << 1)));
  const int m = MAP == 0 ? m0 : (MAP == 1 ? ((m0 & 12) | n0) : ((m0 & 14) | (n0 >> 1)));
  const int j = kh * 4 + n, bid = m * 8 + n * 2 + kh;

  const int c64 = 224 * j + (j & 1) * 32;
  if (warp < 8) {
    asm volatile("setmaxnreg.inc.sync.aligned.u32 208;");
    const int wg = warp >> 2, w4 = warp & 3, g = lane >> 2, t = lane & 3;
    const int rh = wg ^ kh ^ 1;
    const int p = j & 1, r = (j >> 1) & 1, hh = j >> 2;
    const uint32_t epoch = ld_relaxed(&g_ep[bid]);
    if ((tid & 127) == 0) PROF(wg, 30);
#pragma unroll 1
    for (int it = tid; it < 392; it += 256) {
      const int kc = it / 28, sg = it - kc * 28;
      const int k = 2 * (28 * hh + sg) + r;
      const float kf = (float)k * (-6.283185307179586f / 448.0f), a0 = (float)(16 * kc + p) * kf;
      uint32_t c[4], s[4];
#pragma unroll
      for (int q = 0; q < 4; q++) {
        const float a1 = fmaf((float)(2 * q), kf, a0), a2 = fmaf((float)(2 * q + 8), kf, a0);
        c[q] = pack_bf16(__cosf(a1), __cosf(a2)); s[q] = pack_bf16(__sinf(a1), __sinf(a2));
        if (k == 0) s[q] = ((q ^ p) & 1) ? 0xBF80BF80u : 0x3F803F80u;
      }
      const uint32_t a = sb + 6 * SLOT + (kc * 56 + 2 * sg) * 16;
      sts128(a, c[0], c[1], c[2], c[3]);
      sts128(a + 16, s[0], s[1], s[2], s[3]);
    }
    if ((tid & 127) == 0) PROF(wg, 31);
    fence_async_smem();
    bar_sync<0, NTHREADS - 64>();
    asm volatile("barrier.cluster.arrive.relaxed.aligned;" ::: "memory");
    if ((tid & 127) == 0) PROF(wg, 1);

    uint32_t xa[28][4];
    {
      const uint32_t xb = sb + OFF_PQ + wg * HALF_XR + (w4 * 16 + (lane & 15)) * 128;
      mbar_wait(bars + (B_XFULL + wg) * 8, 0);
      if ((tid & 127) == 0) PROF(wg, 2);
#pragma unroll
      for (int kb = 0; kb < 7; kb++) {
#pragma unroll
        for (int kk = 0; kk < 4; kk++) {
          uint32_t a = xb + kb * 8192 + (((2 * kk + (lane >> 4)) ^ (lane & 7)) << 4);
          asm volatile("ldmatrix.sync.aligned.m8n8.x4.shared.b16 {%0,%1,%2,%3}, [%4];"
                       : "=r"(xa[kb * 4 + kk][0]), "=r"(xa[kb * 4 + kk][1]), "=r"(xa[kb * 4 + kk][2]), "=r"(xa[kb * 4 + kk][3]) : "r"(a) : "memory");
        }
      }
    }
    {
      uint32_t ad[7][4];
      const uint32_t sel = p ? 0x7632 : 0x5410;
      const uint32_t sgn = r ? 0xBF80BF80u : 0x3F803F80u;
#pragma unroll
      for (int jj = 0; jj < 7; jj++) {
#pragma unroll
        for (int i = 0; i < 4; i++) {
          int ks = 2 * jj + (i >> 1), rr = i & 1;
          uint32_t lo = __byte_perm(xa[ks][rr], xa[ks][rr + 2], sel);
          uint32_t hi = __byte_perm(xa[ks + 14][rr], xa[ks + 14][rr + 2], sel);
          asm("fma.rn.bf16x2 %0, %1, %2, %3;" : "=r"(ad[jj][i]) : "r"(hi), "r"(sgn), "r"(lo));
        }
      }
      __syncwarp();
      if (lane == 0) mbar_arrive(bars + (B_XFREE + wg) * 8);
      float acc[28];
      wg_fence();
      uint64_t db = mkdesc(sb + 6 * SLOT, 896, 128, 0);
#pragma unroll
      for (int jj = 0; jj < 7; jj++) wgmma_rs_56<0>(acc, ad[jj], db + jj * 112, jj != 0);
      wg_commit();
      wg_wait<0>(); keep(acc);
      if (lane == 0) mbar_arrive(bars + (B_EMPTY + 6) * 8);
      const uint32_t xc = sb + OFF_EXCH + wg * 8192 + t * 256 + w4 * 64 + g * 4;
      mbar_wait(bars + B_XFREE * 8, 0);
#pragma unroll
      for (int i = 0; i < 7; i++) {
        sts32(xc + i * 1024, pack_bf16(acc[4 * i], acc[4 * i + 1]));
        sts32(xc + i * 1024 + 32, pack_bf16(acc[4 * i + 2], acc[4 * i + 3]));
      }
      fence_async_smem();
      __syncwarp();
      if (lane == 0) mbar_arrive(bars + B_PUBX * 8);
    }
    if ((tid & 127) == 0) PROF(wg, 3);
    const uint32_t tag = ~epoch & 1;
    unsigned char* const hbase = g_H + (size_t)(m * 2 + kh) * (56 * 4096) + rh * 2048 + (tid & 127) * 16;
#pragma unroll 1
    for (int u = 0; u < 3; u++) {
      float acc[64];
      if (wg == 1) { if (u & 1) bar_sync<6, 256>(); else bar_sync<2, 256>(); }
      const uint32_t sbu = opaque(sb);
#pragma unroll
      for (int kb = 0; kb < 7; kb++) {
        mbar_wait(sbu + OFF_BAR + (B_FULL + kb) * 8, u & 1);
        wg_fence();
        uint64_t db = mkdesc(sbu + kb * SLOT, 8192, 1024, 1);
#pragma unroll
        for (int kk = 0; kk < 4; kk++) wgmma_rs_128<1>(acc, xa[kb * 4 + kk], db + kk * 128, (kb | kk) != 0);
        wg_commit();
        if (kb == LEAD1 && wg == 0) { if (u & 1) bar_arrive<6, 256>(); else bar_arrive<2, 256>(); }
        if (kb > 0) { wg_wait<1>(); if (lane == 0) mbar_arrive(sbu + OFF_BAR + (B_EMPTY + kb - 1) * 8); }
      }
      wg_wait<0>(); keep(acc);
      if (lane == 0) mbar_arrive(sbu + OFF_BAR + (B_EMPTY + 6) * 8);
      if ((tid & 127) == 0) PROF(wg, 4 + 2 * u);
      h_epilogue<8>(acc, hbase + (u * 16 + n * 4) * 4096, tag);
      if ((tid & 127) == 0) PROF(wg, 5 + 2 * u);
    }
    uint32_t ha[14][4][4];
    auto check = [&](int b0, int b1) {
#pragma unroll
      for (int b = b0; b < b1; b++) frag_ready(ha[b][0], ha[b][1], ha[b][2], ha[b][3], hbase + b * 16384, tag);
    };
    auto load = [&](int b0, int b1) {
#pragma unroll
      for (int i = b0; i < b1; i++) ldg128_l2(ha[i >> 2][i & 3], hbase + i * 4096);
    };
    {
      float acc[32];
      load(0, 3);
      if (wg == 1) bar_sync<6, 256>();
      const uint32_t sbu = opaque(sb);
#pragma unroll
      for (int it = 0; it < 4; it++) {
        mbar_wait(sbu + OFF_BAR + (B_FULL + it) * 8, 1);
        wg_fence();
        uint64_t db = mkdesc(sbu + it * SLOT, 8192, 512, 2);
#pragma unroll
        for (int kk = 0; kk < 8; kk++) if (it * 8 + kk < 28) wgmma_rs_64<1>(acc, xa[it * 8 + kk], db + kk * 64, (it | kk) != 0);
        wg_commit();
        if (it == 2 && wg == 0) bar_arrive<6, 256>();
        if (it > 0) {
          wg_wait<1>();
          if (lane == 0) mbar_arrive(sbu + OFF_BAR + (B_EMPTY + it - 1) * 8);
          if (it == 1) load(3, 11);
          if (it == 2) load(11, 16);
        }
      }
      wg_wait<0>(); keep(acc);
      if (lane == 0) mbar_arrive(sbu + OFF_BAR + (B_EMPTY + 3) * 8);
      if ((tid & 127) == 0) PROF(wg, 10);
      h_epilogue<4>(acc, hbase + (48 + n * 2) * 4096, tag);
    }
    asm volatile("barrier.cluster.wait.aligned;" ::: "memory");
    if ((tid & 127) == 0) PROF(wg, 11);

    float acc[56];
    check(0, 4);
    if (wg == 1) bar_sync<2, 256>();
#pragma unroll
    for (int b = 0; b < 14; b++) {
      if ((tid & 127) == 0) PROF(wg, 16 + b);
      if (b >= 3) mbar_wait(bars + (B_FULL + (b + 1) % 7) * 8, b < 6 || b == 13);
      else if (b == 0) mbar_wait(bars + B_RFULL * 8, 0);
      if (b == 4) check(4, 7);
      if (b == 7) check(7, 11);
      if (b == 11) check(11, 14);
      wg_fence();
      const uint64_t db = mkdesc(b < 3 ? sb + OFF_R + b * SLOT : sb + (b + 1) % 7 * SLOT, 8192, 1024, 1);
#pragma unroll
      for (int kk = 0; kk < 4; kk++) wgmma_rs_112<1>(acc, ha[b][kk], db + kk * 128, (b | kk) != 0);
      wg_commit();
      if (b == LEAD2 && wg == 0) bar_arrive<2, 256>();
      if (b == 0) load(16, 24);
      if (b == 1) load(24, 28);
      if (b == 4 || b == 5) load(8 * b - 4, 8 * b + 4);
      if (b == 7) load(44, 52);
      if (b == 8) load(52, 56);
      if (b > 0) wg_wait<1>();
      if (lane == 0) {
        if (b >= 4 && b <= 9) mbar_arrive(bars + (B_EMPTY + b % 7) * 8);
        if (b == 3) {
          mbar_arrive(bars + B_LFREE * 8);
          asm volatile("{\n.reg .b32 ra;\nmapa.shared::cluster.u32 ra, %0, %1;\nmbarrier.arrive.relaxed.cluster.shared::cluster.b64 _, [ra];\n}"
                       :: "r"(bars + B_RFREE * 8), "r"(kh ^ 1) : "memory");
        }
      }
    }
    const int t128 = tid & 127;
    wg_wait<0>(); keep(acc);
    if (wg == 0) {
      if (t128 == 0) PROF(wg, 12);
      mbar_wait_cluster(bars + B_RFREE * 8, 0);
      uint32_t rdst, rbar;
      asm volatile("mapa.shared::cluster.u32 %0, %1, %2;" : "=r"(rdst) : "r"(sb + OFF_R + t128 * 16), "r"(kh ^ 1));
      asm volatile("mapa.shared::cluster.u32 %0, %1, %2;" : "=r"(rbar) : "r"(bars + B_RECV * 8), "r"(kh ^ 1));
#pragma unroll
      for (int i = 0; i < 14; i++)
        asm volatile("st.async.weak.shared::cluster.mbarrier::complete_tx::bytes.v4.f32 [%0], {%1,%2,%3,%4}, [%5];"
                     :: "r"(rdst + i * 2048), "f"(acc[4 * i]), "f"(acc[4 * i + 1]), "f"(acc[4 * i + 2]), "f"(acc[4 * i + 3]), "r"(rbar) : "memory");
    } else {
      float spec[2][28];
      if (t128 == 0) PROF(wg, 12);
#pragma unroll
      for (int i = 0; i < 4; i++) {
        if (i == 0) mbar_wait(bars + B_GFULL * 8, 0);
        if (i >= 2) mbar_wait(bars + (B_FULL + i - 1) * 8, 1);
        mbar_wait(bars + (B_PQFULL + i) * 8, 0);
        if (i == 0 && t128 == 0) { PROF(wg, 13); g_ep[bid] = epoch + 1; }
        wg_fence();
        const uint64_t da = mkdesc(sb + OFF_PQ + i * 14336, 1024, 1024, 1);
        const uint64_t db = mkdesc(i < 2 ? sb + OFF_R + 28672 + i * (G_IMG / 2) : sb + (i - 1) * SLOT, 896, 128, 0);
#pragma unroll
        for (int kk = 0; kk < 7; kk++) wgmma_ss_56<1, 0>(spec[i >> 1], da + kk * 128, db + kk * 112, ((i & 1) | kk) != 0);
        wg_commit();
      }
      const float* gs = reinterpret_cast<const float*>(smem + OFF_G) + w4 * 16 + g;
      const float o0 = bf16_round(1.0f - gs[0]), o1 = bf16_round(1.0f - gs[8]);
      const float g0 = gs[0] * (1.0f / (float)(S_ * D_)), g1 = gs[8] * (1.0f / (float)(S_ * D_));
      mbar_wait_cluster(bars + B_RECV * 8, 0);
      if (t128 == 0) PROF(wg, 0);
#pragma unroll
      for (int i = 0; i < 14; i++) {
        const float4 o = lds128f(sb + OFF_R + t128 * 16 + i * 2048);
        acc[4 * i] = (acc[4 * i] + o.x) * o0; acc[4 * i + 1] = (acc[4 * i + 1] + o.y) * o0;
        acc[4 * i + 2] = (acc[4 * i + 2] + o.z) * o1; acc[4 * i + 3] = (acc[4 * i + 3] + o.w) * o1;
      }
      keep(acc);
      wg_wait<0>(); keep(spec[0]); keep(spec[1]);
      if (t128 == 0) PROF(wg, 14);
      bar_sync<5, 128>();
      const uint32_t st = sb + OFF_PQ + w4 * 3840;
#pragma unroll
      for (int i = 0; i < 7; i++) {
        uint32_t pk[4];
#pragma unroll
        for (int e = 0; e < 2; e++) {
          const int c = 2 * i + e, si = i * 4 + e;
          pk[2 * e] = pack_bf16(fmaf(g0, spec[0][si], acc[4 * c]), fmaf(g0, spec[1][si], acc[4 * c + 1]));
          pk[2 * e + 1] = pack_bf16(fmaf(g1, spec[0][si + 2], acc[4 * c + 2]), fmaf(g1, spec[1][si + 2], acc[4 * c + 3]));
        }
        asm volatile("stmatrix.sync.aligned.m8n8.x4.shared.b16 [%0], {%1,%2,%3,%4};"
                     :: "r"(st + (lane & 15) * 240 + (lane >> 4) * 16 + i * 32), "r"(pk[0]), "r"(pk[1]), "r"(pk[2]), "r"(pk[3]) : "memory");
      }
      __syncwarp();
      if (lane < 28) {
        const int r2 = lane >= 14, cc = lane - r2 * 14;
        unsigned char* ob = reinterpret_cast<unsigned char*>(out) + (size_t)(m * 128 + kh * 64 + w4 * 16 + r2) * (D_ * 2) + n * 224 + cc * 16;
        float4 v[8];
#pragma unroll
        for (int i = 0; i < 8; i++) v[i] = lds128f(st + r2 * 240 + cc * 16 + i * 480);
#pragma unroll
        for (int i = 0; i < 8; i++) stg128(ob + i * (D_ * 4), __float_as_uint(v[i].x), __float_as_uint(v[i].y), __float_as_uint(v[i].z), __float_as_uint(v[i].w));
      }
    }
    if (t128 == 0) { PROF(wg, 15); if (wg) { PROFG(4, 30); PROF(4, 31); } }
  } else if (warp < 12) {
    asm volatile("setmaxnreg.dec.sync.aligned.u32 72;");
    const int t = tid - 256;
    const int k = bid;
    if (t == 0) PROF(2, 0);
    uint4 gv[7];
#pragma unroll
    for (int i = 0; i < 7; i++) gv[i] = ldg128(reinterpret_cast<const uint4*>(gate_w) + i * 8 + (t & 7));
    if (t < 98) {
      int cid = m * 98 + t, kc = cid / 56, nn = cid - kc * 56;
      int d = 112 * n + 8 * (2 * (nn >> 3) + (nn & 1)) + (nn & 6) + kh;
      int dr = d > 224 ? d - 448 : d;
      const float df = (float)dr * (-6.283185307179586f / 448.0f);
      uint32_t pk[4];
#pragma unroll
      for (int e = 0; e < 4; e++) {
        const float a = (float)(4 * kc + e) * df;
        pk[e] = pack_bf16(2.0f * __cosf(a), 2.0f * __sinf(a));
      }
      if (kc == 0) pk[0] = (((d >> 1) ^ kh) & 1) ? 0xBF803F80u : 0x3F803F80u;
      stg128(g_G + (size_t)(n * 2 + kh) * G_IMG + cid * 16, pk[0], pk[1], pk[2], pk[3]);
    }
    bar_sync<0, NTHREADS - 64>();
    asm volatile("barrier.cluster.arrive.relaxed.aligned;" ::: "memory");
    {
      const int row = n * 16 + (t >> 3), l8 = t & 7;
      mbar_wait(bars + (B_XFULL + 1) * 8, 0);
      float sum = 0.f;
#pragma unroll
      for (int i = 0; i < 7; i++) {
        const uint4 a = lds128(sb + OFF_R + i * 8192 + row * 128 + ((l8 ^ (row & 7)) << 4));
        const uint32_t aa[4] = {a.x, a.y, a.z, a.w}, bb[4] = {gv[i].x, gv[i].y, gv[i].z, gv[i].w};
#pragma unroll
        for (int e = 0; e < 4; e++) {
          const uint32_t pr = as_u(__hmul2(as_b2(aa[e]), as_b2(bb[e])));
          sum += bf_lo(pr) + bf_hi(pr);
        }
      }
      sum += __shfl_xor_sync(0xffffffffu, sum, 1); sum += __shfl_xor_sync(0xffffffffu, sum, 2); sum += __shfl_xor_sync(0xffffffffu, sum, 4);
      if (l8 == 0) g_gate[m * 128 + kh * 64 + row] = bf16_round(__fdividef(1.0f, 1.0f + __expf(-bf16_round(sum))));
    }
    __syncwarp();
    if (lane == 0) mbar_arrive(bars + (B_XFREE + 1) * 8);
    if (t == 0) PROF(2, 11);
    mbar_wait(bars + B_PIN * 8, 0);
    mbar_wait(bars + (B_XFREE + 1) * 8, 0);
    if (t == 0) PROF(2, 4);
    {
      const uint32_t wa = sb + OFF_WS + (((t & 7) - bid) & 7) * 450 + (t >> 3) * 2, wc = wa + 448 - (t >> 3) * 4;
#pragma unroll 1
      for (int h = 0; h < 2; h++) {
        uint32_t w[4][8];
#pragma unroll
        for (int i = 0; i < 4; i++) {
#pragma unroll
          for (int e = 0; e < 4; e++) { w[i][2 * e] = lds16(wa + h * 128 + i * 32 + e * 3600); w[i][2 * e + 1] = lds16(wc - h * 128 - i * 32 + e * 3600); }
        }
#pragma unroll
        for (int i = 0; i < 4; i++)
          sts128(sb + OFF_R + h * 8192 + i * 2048 + t * 16, __byte_perm(w[i][0], w[i][1], 0x5410), __byte_perm(w[i][4], w[i][5], 0x5410), __byte_perm(w[i][2], w[i][3], 0x5410), __byte_perm(w[i][6], w[i][7], 0x5410));
      }
    }
    fence_async_smem();
    __syncwarp();
    if (lane == 0) mbar_arrive(bars + B_PUBW * 8);
    if (k < 113) {
      if (t == 0) PROF(2, 2);
      mbar_wait(bars + B_XCFULL * 8, 0);
      if (t == 0) PROF(2, 3);
      c2 v[16];
      uint2 xe[8], xo[8];
      const int sl = k == 112 ? 0 : k, hi = sl >= 56;
      const unsigned char* xs = g_X + (192 + (sl & 1) * 64 + hi * 72 + (sl & ~1) + ((t >> 4) & 1)) * XP + (t >> 5) * 256 + (t & 15) * 8;
#pragma unroll
      for (int jj = 0; jj < 8; jj++) { xe[jj] = ldg64_l2(xs + jj * 1024); xo[jj] = ldg64_l2(xs + jj * 1024 + 128); }
      {
        const float u = -6.283185307179586f / 2048.0f, t2 = (float)(2 * t) * u, rr = (float)(t >> 4) * u;
#pragma unroll 1
        for (int i = 0; i < 4; i++) {
          const float q = (float)(2 * i), l = (float)((t & 15) + 64 * i);
          sts128(sb + OFF_TW + i * 2048 + t * 16, cis(t2 * q), cis((t2 + u) * q), cis(t2 * (q + 1.0f)), cis((t2 + u) * (q + 1.0f)));
          sts128(sb + OFF_TW + 8192 + i * 2048 + t * 16, cis(rr * l), cis(rr * (l + 16.0f)), cis(rr * (l + 32.0f)), cis(rr * (l + 48.0f)));
        }
        const float l = (float)((t >> 1) & 15) * (8.0f * u), jj = (float)((t >> 5) * 4 + (t & 1) * 2);
        sts64(sb + OFF_TW + 16384 + t * 8, cis(l * jj), cis(l * (jj + 1.0f)));
      }
      if (t == 0) PROF(2, 9);
      const uint32_t se = k == 0 ? 0x4410 : (k == 112 ? 0x4432 : 0x3210), so = k == 0 ? 0x4410 : (k == 112 ? 0x3244 : 0x3210);
#pragma unroll
      for (int jj = 0; jj < 8; jj++) {
        const uint2 e2 = xe[jj], o2 = xo[jj];
#pragma unroll
        for (int h = 0; h < 2; h++) {
          const b2 e = as_b2(__byte_perm(h ? e2.y : e2.x, 0, se)), o = as_b2(__byte_perm(h ? o2.y : o2.x, 0, so));
          const uint32_t s = as_u(__hadd2(e, o)), d = as_u(__hsub2(e, o)) ^ 0x80000000u;
          v[2 * jj + h] = mk(as_b2(__byte_perm(s, d, 0x5410)), as_b2(__byte_perm(s, d, 0x7632)));
        }
      }
      if (t == 0) PROF(2, 12);
      columns(v, sb, t);
      if (t == 0) PROF(2, 14);
      const int pre = (k == 112) ? 1 : 2 * k, pim = (k == 112) ? 1 : 2 * k + 1;
      const uint32_t pr = sb + OFF_EXCH + (t >> 5) * 256 + ((((lane >> 2) ^ pre) & 7) << 4) + (lane & 3) * 4;
      const uint32_t pi = sb + OFF_EXCH + 8192 + (t >> 5) * 256 + ((((lane >> 2) ^ pim) & 7) << 4) + (lane & 3) * 4;
      bar_sync<3, 128>();
#pragma unroll
      for (int jj = 0; jj < 8; jj++) {
        const b2 ar = as_b2(__byte_perm(as_u(v[2 * jj].y), as_u(v[2 * jj + 1].y), 0x5410)), br = as_b2(__byte_perm(as_u(v[2 * jj].y), as_u(v[2 * jj + 1].y), 0x7632));
        const b2 ai = as_b2(__byte_perm(as_u(v[2 * jj].x), as_u(v[2 * jj + 1].x), 0x5410)), bi = as_b2(__byte_perm(as_u(v[2 * jj].x), as_u(v[2 * jj + 1].x), 0x7632));
        sts32(pr + jj * 1024, as_u(__hadd2(ar, br)));
        sts32(pr + jj * 1024 + 128, as_u(k == 112 ? __hadd2(ai, bi) : __hsub2(ar, br)));
        sts32(pi + jj * 1024 + 128, as_u(__hadd2(ai, bi)));
        sts32(pi + jj * 1024, as_u(__hsub2(ai, bi)));
      }
      fence_async_smem();
      bar_sync<3, 128>();
      if (t == 0) {
        PROF(2, 5);
        tma_store(&tm_s, pre * 64, 0, sb + OFF_EXCH);
        if (k != 0 && k != 112) tma_store(&tm_s, pim * 64, 0, sb + OFF_EXCH + 8192);
        bulk_done();
      }
    }
    if (t == 0) { red_relaxed(&g_cnt[5 * 32]); PROF(2, 7); }
    __syncwarp();
    asm volatile("barrier.cluster.wait.aligned;" ::: "memory");
  } else {
    asm volatile("setmaxnreg.dec.sync.aligned.u32 24;");
    auto wd_tile = [&](int b, uint32_t dst, uint32_t fb) {
#pragma unroll
      for (int hf = 0; hf < 2; hf++) {
        const int js = kh * 4 + (b < 12 ? (b & 3) : (b & 1) * 2 + hf);
        const int row = 224 * js + (b < 12 ? (js & 1) * 32 + (b >> 2) * 64 + hf * 32 : 192 - hf * 192);
        tma2d(dst + hf * 4096, &tm_d, 112 * n, row, fb);
        tma2d(dst + 8192 + hf * 4096, &tm_d, 112 * n + 64, row, fb);
      }
    };
    if (warp == 12) {
      if (elect()) {
        mbar_init(bars + B_XFULL * 8, 1); mbar_init(bars + (B_XFULL + 1) * 8, 1);
        fence_async_smem();
#pragma unroll
        for (int w = 0; w < 2; w++) {
          mbar_expect(bars + (B_XFULL + w) * 8, HALF_XR);
          tma3d(sb + OFF_PQ + w * HALF_XR, &tm_x, 0, m * 128 + (w ^ kh ^ 1) * 64, 0, bars + (B_XFULL + w) * 8);
        }
        PROF(3, 3);
#pragma unroll
        for (int i = 0; i < NSLOT; i++) mbar_init(bars + (B_FULL + i) * 8, 1);
        mbar_init(bars + B_PIN * 8, 1);
        fence_async_smem();
      }
      bar_arrive<0, NTHREADS - 64>();
#pragma unroll 1
      for (int i = 0; i < 6; i++) {
        if (elect()) {
          const uint32_t fb = bars + (B_FULL + i) * 8;
          mbar_expect(fb, SLOT);
          tma2d(sb + i * SLOT, &tm_g, c64, i * 64, fb);
          tma2d(sb + i * SLOT + 8192, &tm_u, c64, i * 64, fb);
          PROF(3, 4 + i);
        }
      }
      if (elect()) {
        prefetch_l2(reinterpret_cast<const unsigned char*>(w_r) + bid * 7200, 7200);
        prefetch_l2(reinterpret_cast<const unsigned char*>(w_i) + bid * 7200, 7200);
        prefetch_tma2d(&tm_g, c64, 384); prefetch_tma2d(&tm_u, c64, 384);
      }
    } else if (warp == 14) {
      if (elect()) {
#pragma unroll
        for (int i = B_EMPTY; i < B_END; i++)
          if (i < B_XFULL || i >= B_XFREE) mbar_init(bars + i * 8, i >= B_PQFULL ? 1 : ((i == B_XFREE || i == B_PUBW) ? 4 : 8));
        asm volatile("fence.mbarrier_init.release.cluster;" ::: "memory");
        fence_async_smem();
        mbar_expect(bars + B_RECV * 8, 64 * 112 * 4);
      }
      bar_arrive<0, NTHREADS - 64>();
    }
    const uint32_t epoch = ld_relaxed(&g_ep[bid]);
    if (warp == 13 && lane == 0) { PROFG(4, 0); PROF(4, 1); }
    bar_sync<1, 128>();
    asm volatile("barrier.cluster.arrive.relaxed.aligned;" ::: "memory");
    if (warp == 12) {
      int slot = 6, ph = 1;
      auto wait_slot = [&]() { mbar_wait(bars + (B_EMPTY + slot) * 8, ph ^ (slot == 6)); };
      auto adv = [&]() { if (++slot == NSLOT) { slot = 0; ph ^= 1; } };
      const int c32 = 224 * j + ((j & 1) ? 0 : 192);
#pragma unroll 1
      for (int i = 6; i < 25; i++) {
        wait_slot();
        if (elect()) {
          const uint32_t dst = sb + slot * SLOT, fb = bars + (B_FULL + slot) * 8;
          const bool last = i >= 21;
          const int cc = last ? c32 : c64 + 64 * (i / 7), rr = last ? slot * 128 : slot * 64;
          mbar_expect(fb, SLOT);
          tma2d(dst, last ? &tm_g32 : &tm_g, cc, rr, fb);
          tma2d(dst + 8192, last ? &tm_u32 : &tm_u, cc, rr, fb);
        }
        adv();
      }
      if (lane == 0) PROF(3, 0);
#pragma unroll 1
      for (int i = 3; i < 16; i++) {
        if (lane == 0) PROF(3, 16 + i);
        if (i == 14) mbar_wait(bars + B_PREP * 8, 0);
        wait_slot();
        if (elect()) {
          const uint32_t fb = bars + (B_FULL + slot) * 8;
          mbar_expect(fb, i < 14 ? SLOT : G_IMG / 2);
          if (i < 14) wd_tile(i, sb + slot * SLOT, fb);
          else bulk_g2s(sb + slot * SLOT, g_G + (size_t)(n * 4 + i - 12) * (G_IMG / 2), G_IMG / 2, fb);
        }
        adv();
      }
      if (lane == 0) PROF(3, 2);
    } else if (warp == 13) {
      mbar_wait(bars + B_PUBX * 8, 0);
      if (elect()) {
        PROF(4, 8);
#pragma unroll
        for (int w = 0; w < 2; w++) tma_store(&tm_s, ((m * 2 + (w ^ kh ^ 1)) * 2 + (j & 1)) * 64, 192 + (j >> 1) * 64, sb + OFF_EXCH + w * 8192);
        bulk_done();
        red_relaxed(&g_cnt[(j >> 1) * 32]);
        mbar_arrive(bars + B_XDONE * 8);
        PROF(4, 12);
      }
      mbar_wait(bars + (B_XFREE + 1) * 8, 0);
      asm volatile("fence.acq_rel.gpu;" ::: "memory");
      if (lane == 0) PROF(4, 10);
      mbar_wait(bars + B_PUBW * 8, 0);
      if (elect()) {
        PROF(4, 9);
        tma_store(&tm_s, bid * 64, 64, sb + OFF_R);
        tma_store(&tm_s, bid * 64, 128, sb + OFF_R + 8192);
        bulk_done();
        red_relaxed(&g_cnt[4 * 32]);
        mbar_arrive(bars + B_WDONE * 8);
        PROF(4, 13);
      }
      mbar_wait(bars + B_PREP * 8, 0);
      mbar_wait(bars + B_LFREE * 8, 0);
      if (elect()) {
        mbar_expect(bars + B_GFULL * 8, G_IMG);
        bulk_g2s(sb + OFF_R + 28672, g_G + (size_t)(n * 2) * G_IMG, G_IMG, bars + B_GFULL * 8);
      }
    } else if (warp == 14) {
      wait_ge(&g_cnt[4 * 32], (epoch + 1) * 128);
      fence_async_global();
      if (elect()) {
        mbar_arrive(bars + B_PREP * 8);
        if (bid < 113) {
          mbar_expect(bars + B_WFULL * 8, 16384);
          bulk_g2s(sb + OFF_WS, g_X + (64 + bid) * XP, 16384, bars + B_WFULL * 8);
        }
        PROF(5, 17);
      }
    } else {
      mbar_wait(bars + B_XFREE * 8, 0);
      if (elect()) {
        mbar_expect(bars + B_PIN * 8, 14400);
        bulk_g2s(sb + OFF_WS, reinterpret_cast<const unsigned char*>(w_r) + bid * 7200, 7200, bars + B_PIN * 8);
        bulk_g2s(sb + OFF_WS + 7200, reinterpret_cast<const unsigned char*>(w_i) + bid * 7200, 7200, bars + B_PIN * 8);
        prefetch_l2(reinterpret_cast<const unsigned char*>(w_gate) + bid * 12544, 12544);
        prefetch_l2(reinterpret_cast<const unsigned char*>(w_up) + bid * 12544, 12544);
        PROF(5, 2);
      }
      if (bid < 113) {
        const int sl = (bid == 112) ? 0 : bid;
        wait_ge(&g_cnt[((sl & 1) + 2 * ((sl >> 1) / 28)) * 32], (epoch + 1) * 32);
        if (elect()) { PROF(5, 16); mbar_arrive(bars + B_XCFULL * 8); }
      }
      mbar_wait(bars + B_PUBW * 8, 0);
      if (elect()) prefetch_l2(reinterpret_cast<const unsigned char*>(w_down) + bid * 12544, 12544);
      mbar_wait(bars + B_WDONE * 8, 0);
      if (elect()) mbar_expect(bars + B_RFULL * 8, 3 * SLOT);
#pragma unroll 1
      for (int i = 0; i < 3; i++) {
        mbar_wait(bars + (B_FULL + (i == 1 ? 0 : 3)) * 8, i == 0);
        if (elect()) wd_tile(i, sb + OFF_R + i * SLOT, bars + B_RFULL * 8);
      }
      if (lane == 0) PROF(5, 19);
      mbar_wait(bars + B_PREP * 8, 0);
      wait_ge(&g_cnt[5 * 32], (epoch + 1) * 128);
      fence_async_global();
      if (elect()) {
        PROF(5, 18);
        const unsigned char* src = g_X + (m * 2 + kh) * HALF_XR;
#pragma unroll
        for (int i = 0; i < 4; i++) {
          mbar_expect(bars + (B_PQFULL + i) * 8, i ? 14336 : 14336 + 256);
          bulk_g2s(sb + OFF_PQ + i * 14336, src + i * 14336, 14336, bars + (B_PQFULL + i) * 8);
        }
        bulk_g2s(sb + OFF_G, g_gate + m * 128 + kh * 64, 256, bars + B_PQFULL * 8);
      }
    }
    __syncwarp();
    asm volatile("barrier.cluster.wait.aligned;" ::: "memory");
  }
}

typedef CUresult (*EncodeFn)(CUtensorMap*, CUtensorMapDataType, cuuint32_t, void*, const cuuint64_t*, const cuuint64_t*, const cuuint32_t*,
                             const cuuint32_t*, CUtensorMapInterleave, CUtensorMapSwizzle, CUtensorMapL2promotion, CUtensorMapFloatOOBfill);

void make_map(EncodeFn enc, CUtensorMap* tm, const void* base, int cols, int rows, int bc, int br, CUtensorMapSwizzle sw) {
  cuuint64_t gd[2] = {(cuuint64_t)cols, (cuuint64_t)rows};
  cuuint64_t gs[1] = {(cuuint64_t)cols * 2};
  cuuint32_t bd[2] = {(cuuint32_t)bc, (cuuint32_t)br};
  cuuint32_t es[2] = {1, 1};
  enc(tm, CU_TENSOR_MAP_DATA_TYPE_BFLOAT16, 2, const_cast<void*>(base), gd, gs, bd, es, CU_TENSOR_MAP_INTERLEAVE_NONE, sw,
      CU_TENSOR_MAP_L2_PROMOTION_L2_128B, CU_TENSOR_MAP_FLOAT_OOB_FILL_NONE);
}

}

extern "C" void kernel_launch(void* const* d_in, const int* in_sizes, int n_in, void* d_out, int out_size) {
  (void)in_sizes; (void)n_in; (void)out_size;
  const __nv_bfloat16* x = (const __nv_bfloat16*)d_in[0];
  const __nv_bfloat16* w_r = (const __nv_bfloat16*)d_in[1];
  const __nv_bfloat16* w_i = (const __nv_bfloat16*)d_in[2];
  const __nv_bfloat16* w_gate = (const __nv_bfloat16*)d_in[4];
  const __nv_bfloat16* w_up = (const __nv_bfloat16*)d_in[5];
  const __nv_bfloat16* w_down = (const __nv_bfloat16*)d_in[6];
  const __nv_bfloat16* gate_w = (const __nv_bfloat16*)d_in[7];
  static EncodeFn enc = nullptr;
  static void* xbuf = nullptr;
  static bool ok = false;
  if (!enc) {
    cudaDriverEntryPointQueryResult qr;
    cudaGetDriverEntryPoint("cuTensorMapEncodeTiled", (void**)&enc, cudaEnableDefault, &qr);
    cudaFuncSetAttribute(fused_kernel, cudaFuncAttributeMaxDynamicSharedMemorySize, SMEM_BYTES);
    cudaGetSymbolAddress(&xbuf, g_X);
    cudaFuncAttributes fa;
    cudaFuncGetAttributes(&fa, fused_kernel);
    ok = (fa.numRegs == 128);
  }
  if (!ok) return;
  CUtensorMap tx, tg, tu, tg32, tu32, td, ts;
  {
    cuuint64_t gd[3] = {64, (cuuint64_t)S_, 7};
    cuuint64_t gs[2] = {(cuuint64_t)D_ * 2, 128};
    cuuint32_t bd[3] = {64, 64, 7};
    cuuint32_t es[3] = {1, 1, 1};
    enc(&tx, CU_TENSOR_MAP_DATA_TYPE_BFLOAT16, 3, const_cast<__nv_bfloat16*>(x), gd, gs, bd, es, CU_TENSOR_MAP_INTERLEAVE_NONE, CU_TENSOR_MAP_SWIZZLE_128B,
        CU_TENSOR_MAP_L2_PROMOTION_L2_128B, CU_TENSOR_MAP_FLOAT_OOB_FILL_NONE);
  }
  make_map(enc, &tg, w_gate, F_, D_, 64, 64, CU_TENSOR_MAP_SWIZZLE_128B);
  make_map(enc, &tu, w_up, F_, D_, 64, 64, CU_TENSOR_MAP_SWIZZLE_128B);
  make_map(enc, &tg32, w_gate, F_, D_, 32, 128, CU_TENSOR_MAP_SWIZZLE_64B);
  make_map(enc, &tu32, w_up, F_, D_, 32, 128, CU_TENSOR_MAP_SWIZZLE_64B);
  make_map(enc, &td, w_down, D_, F_, 64, 32, CU_TENSOR_MAP_SWIZZLE_128B);
  make_map(enc, &ts, (const __nv_bfloat16*)xbuf, XP / 2, 448, 64, 64, CU_TENSOR_MAP_SWIZZLE_NONE);
  fused_kernel<<<128, NTHREADS, SMEM_BYTES>>>(tx, tg, tu, tg32, tu32, td, ts, w_r, w_i, w_gate, w_up, w_down, gate_w, (__nv_bfloat16*)d_out);
}
```

```cpp
#include <cuda_runtime.h>
#include <cuda_bf16.h>
#include <cuda.h>
#include <stdint.h>

namespace {

constexpr int S_ = 2048, D_ = 448, F_ = 1792;
constexpr int NTHREADS = 512;
constexpr int SLOT = 16384, NSLOT = 7;
constexpr int HALF_XR = 57344;
constexpr int OFF_PQ = NSLOT * SLOT;
constexpr int OFF_R = OFF_PQ + HALF_XR;
constexpr int OFF_EXCH = OFF_PQ;
constexpr int OFF_WS = OFF_EXCH + 18432;
constexpr int OFF_TW = OFF_WS + 16384;
constexpr int OFF_MISC = OFF_R + HALF_XR;
constexpr int OFF_G = OFF_MISC;
constexpr int OFF_BAR = OFF_MISC + 512;
constexpr int SMEM_BYTES = OFF_BAR + 512;
constexpr int B_FULL = 0, B_EMPTY = 7, B_XFULL = 14  ;
constexpr int B_XFREE = 16  , B_PUBX = 18, B_RFREE = 19, B_LFREE = 20;
constexpr int B_PUBW = 21;
constexpr int B_PQFULL = 22  , B_RECV = 26, B_WFULL = 27, B_XCFULL = 28, B_PREP = 29, B_RFULL = 30, B_GFULL = 31, B_XDONE = 32, B_WDONE = 33, B_END = 34, B_PIN = 34;

constexpr int G_IMG = 224 * 56 * 2;

__device__ __align__(1024) unsigned char g_H[32 * 56 * 4096];
constexpr int XP = 28672;
__device__ __align__(1024) unsigned char g_X[448 * XP];
__device__ __align__(1024) unsigned char g_G[8 * G_IMG];
__device__ __align__(1024) float g_gate[S_];
__device__ __align__(128) unsigned int g_ep[128];
__device__ __align__(128) unsigned int g_cnt[8 * 32];

#define POLL ld_relaxed
#define PROF(role, idx) do {} while (0)
#define PROFG(role, idx) do {} while (0)

__device__ __forceinline__ uint32_t s2u(const void* p) { return (uint32_t)__cvta_generic_to_shared(p); }
__device__ __forceinline__ void mbar_init(uint32_t b, int c) { asm volatile("mbarrier.init.shared::cta.b64 [%0], %1;" :: "r"(b), "r"(c) : "memory"); }
__device__ __forceinline__ void mbar_expect(uint32_t b, int bytes) { asm volatile("mbarrier.arrive.expect_tx.shared::cta.b64 _, [%0], %1;" :: "r"(b), "r"(bytes) : "memory"); }
__device__ __forceinline__ void mbar_arrive(uint32_t b) { asm volatile("mbarrier.arrive.shared::cta.b64 _, [%0];" :: "r"(b) : "memory"); }
__device__ __forceinline__ void mbar_wait(uint32_t b, int ph) {
  asm volatile("{\n.reg .pred p;\n.reg .u32 c;\nmov.u32 c, 0;\nL_WAIT:\nmbarrier.try_wait.parity.shared::cta.b64 p, [%0], %1;\n@p bra.uni L_DONE;\n"
               "add.u32 c, c, 1;\nsetp.lt.u32 p, c, 4194304;\n@p bra.uni L_WAIT;\ntrap;\nL_DONE:\n}" :: "r"(b), "r"(ph) : "memory");
}
__device__ __forceinline__ void mbar_wait_cluster(uint32_t b, int ph) {
  asm volatile("{\n.reg .pred p;\n.reg .u32 c;\nmov.u32 c, 0;\nL_WAIT:\nmbarrier.try_wait.parity.acquire.cluster.shared::cta.b64 p, [%0], %1;\n@p bra.uni L_DONE;\n"
               "add.u32 c, c, 1;\nsetp.lt.u32 p, c, 4194304;\n@p bra.uni L_WAIT;\ntrap;\nL_DONE:\n}" :: "r"(b), "r"(ph) : "memory");
}
__device__ __forceinline__ uint32_t ld_acquire(const unsigned int* p) { uint32_t v; asm volatile("ld.acquire.gpu.global.u32 %0, [%1];" : "=r"(v) : "l"(p) : "memory"); return v; }
__device__ __forceinline__ uint32_t ld_relaxed(const unsigned int* p) { uint32_t v; asm volatile("ld.relaxed.gpu.global.u32 %0, [%1];" : "=r"(v) : "l"(p) : "memory"); return v; }
__device__ __forceinline__ void wait_ge(const unsigned int* p, uint32_t target) {
#pragma unroll 1
  for (int i = 0; i < (1 << 22); i++) { if ((int)(POLL(p) - target) >= 0) return; }
  __trap();
}
__device__ __forceinline__ void red_relaxed(unsigned int* p) { asm volatile("red.relaxed.gpu.global.add.u32 [%0], 1;" :: "l"(p) : "memory"); }
__device__ __forceinline__ bool elect() { uint32_t p; asm volatile("{\n.reg .pred p;\nelect.sync _|p, 0xffffffff;\nselp.u32 %0, 1, 0, p;\n}" : "=r"(p)); return p; }
__device__ __forceinline__ void fence_async_smem() { asm volatile("fence.proxy.async.shared::cta;" ::: "memory"); }
__device__ __forceinline__ void fence_async_global() { asm volatile("fence.proxy.async.global;" ::: "memory"); }
template <int ID, int N> __device__ __forceinline__ void bar_sync() { asm volatile("bar.sync %0, %1;" :: "n"(ID), "n"(N) : "memory"); }
template <int ID, int N> __device__ __forceinline__ void bar_arrive() { asm volatile("bar.arrive %0, %1;" :: "n"(ID), "n"(N) : "memory"); }
__device__ __forceinline__ void tma2d(uint32_t dst, const CUtensorMap* tm, int c0, int c1, uint32_t bar) {
  asm volatile("cp.async.bulk.tensor.2d.shared::cluster.global.mbarrier::complete_tx::bytes [%0], [%1, {%3, %4}], [%2];"
               :: "r"(dst), "l"(tm), "r"(bar), "r"(c0), "r"(c1) : "memory");
}
__device__ __forceinline__ void tma3d(uint32_t dst, const CUtensorMap* tm, int c0, int c1, int c2, uint32_t bar) {
  asm volatile("cp.async.bulk.tensor.3d.shared::cluster.global.mbarrier::complete_tx::bytes [%0], [%1, {%3, %4, %5}], [%2];"
               :: "r"(dst), "l"(tm), "r"(bar), "r"(c0), "r"(c1), "r"(c2) : "memory");
}
__device__ __forceinline__ void bulk_g2s(uint32_t dst, const void* src, int bytes, uint32_t bar) {
  asm volatile("cp.async.bulk.shared::cluster.global.mbarrier::complete_tx::bytes [%0], [%1], %2, [%3];"
               :: "r"(dst), "l"(src), "r"(bytes), "r"(bar) : "memory");
}
__device__ __forceinline__ void tma_store(const CUtensorMap* tm, int c0, int c1, uint32_t src) {
  asm volatile("cp.async.bulk.tensor.2d.global.shared::cta.bulk_group [%0, {%1, %2}], [%3];" :: "l"(tm), "r"(c0), "r"(c1), "r"(src) : "memory");
}
__device__ __forceinline__ void bulk_done() { asm volatile("cp.async.bulk.commit_group;\ncp.async.bulk.wait_group 0;\nfence.proxy.async.global;" ::: "memory"); }
__device__ __forceinline__ void sts32(uint32_t a, uint32_t x) { asm volatile("st.shared.b32 [%0], %1;" :: "r"(a), "r"(x) : "memory"); }
__device__ __forceinline__ void prefetch_l2(const void* src, int bytes) {
  asm volatile("cp.async.bulk.prefetch.L2.global [%0], %1;" :: "l"(src), "r"(bytes) : "memory");
}
__device__ __forceinline__ void prefetch_tma2d(const CUtensorMap* tm, int c0, int c1) {
  asm volatile("cp.async.bulk.prefetch.tensor.2d.L2.global [%0, {%1, %2}];" :: "l"(tm), "r"(c0), "r"(c1) : "memory");
}
__device__ __forceinline__ uint64_t mkdesc(uint32_t addr, uint32_t lbo, uint32_t sbo, uint32_t mode) {
  return (uint64_t)((addr & 0x3FFFF) >> 4) | ((uint64_t)(lbo >> 4) << 16) | ((uint64_t)(sbo >> 4) << 32) | ((uint64_t)mode << 62);
}
__device__ __forceinline__ void wg_fence() { asm volatile("wgmma.fence.sync.aligned;" ::: "memory"); }
__device__ __forceinline__ void wg_commit() { asm volatile("wgmma.commit_group.sync.aligned;" ::: "memory"); }
template <int N> __device__ __forceinline__ void wg_wait() { asm volatile("wgmma.wait_group.sync.aligned %0;" :: "n"(N) : "memory"); }
template <int N> __device__ __forceinline__ void keep(float (&d)[N]) {
#pragma unroll
  for (int i = 0; i < N; i++) asm volatile("" : "+f"(d[i]) :: "memory");
}
__device__ __forceinline__ uint32_t pack_bf16(float lo, float hi) { uint32_t r; asm("cvt.rn.bf16x2.f32 %0, %1, %2;" : "=r"(r) : "f"(hi), "f"(lo)); return r; }
__device__ __forceinline__ float bf16_round(float v) { return __bfloat162float(__float2bfloat16_rn(v)); }
__device__ __forceinline__ void sts128(uint32_t a, uint32_t x, uint32_t y, uint32_t z, uint32_t w) { asm volatile("st.shared.v4.b32 [%0], {%1,%2,%3,%4};" :: "r"(a), "r"(x), "r"(y), "r"(z), "r"(w) : "memory"); }
__device__ __forceinline__ float4 lds128f(uint32_t a) { float4 v; asm volatile("ld.shared.v4.f32 {%0,%1,%2,%3}, [%4];" : "=f"(v.x), "=f"(v.y), "=f"(v.z), "=f"(v.w) : "r"(a) : "memory"); return v; }

__device__ __forceinline__ uint2 lds64(uint32_t a) { uint2 v; asm volatile("ld.shared.v2.b32 {%0,%1}, [%2];" : "=r"(v.x), "=r"(v.y) : "r"(a) : "memory"); return v; }
__device__ __forceinline__ float bf_lo(uint32_t w) { return __uint_as_float(w << 16); }
__device__ __forceinline__ float bf_hi(uint32_t w) { return __uint_as_float(w & 0xffff0000u); }
__device__ __forceinline__ uint32_t opaque(uint32_t v) { asm volatile("" : "+r"(v)); return v; }
__device__ __forceinline__ uint4 ldg128(const void* p) { uint4 v; asm volatile("ld.global.nc.v4.b32 {%0,%1,%2,%3}, [%4];" : "=r"(v.x), "=r"(v.y), "=r"(v.z), "=r"(v.w) : "l"(p)); return v; }
__device__ __forceinline__ void stg128(void* p, uint32_t x, uint32_t y, uint32_t z, uint32_t w) { asm volatile("st.global.v4.b32 [%0], {%1,%2,%3,%4};" :: "l"(p), "r"(x), "r"(y), "r"(z), "r"(w) : "memory"); }
__device__ __forceinline__ void stg128_l2(void* p, uint32_t x, uint32_t y, uint32_t z, uint32_t w) { asm volatile("st.relaxed.gpu.global.v4.b32 [%0], {%1,%2,%3,%4};" :: "l"(p), "r"(x), "r"(y), "r"(z), "r"(w) : "memory"); }
__device__ __forceinline__ uint2 ldg64_l2(const void* p) { uint2 v; asm volatile("ld.relaxed.gpu.global.v2.b32 {%0,%1}, [%2];" : "=r"(v.x), "=r"(v.y) : "l"(p) : "memory"); return v; }
__device__ __forceinline__ void ldg128_l2(uint32_t (&v)[4], const void* p) { asm volatile("ld.relaxed.gpu.global.v4.b32 {%0,%1,%2,%3}, [%4];" : "=r"(v[0]), "=r"(v[1]), "=r"(v[2]), "=r"(v[3]) : "l"(p) : "memory"); }
__device__ __forceinline__ uint4 lds128(uint32_t a) { uint4 v; asm volatile("ld.shared.v4.b32 {%0,%1,%2,%3}, [%4];" : "=r"(v.x), "=r"(v.y), "=r"(v.z), "=r"(v.w) : "r"(a) : "memory"); return v; }
__device__ __forceinline__ uint32_t lds16(uint32_t a) { uint32_t v; asm volatile("ld.shared.u16 %0, [%1];" : "=r"(v) : "r"(a) : "memory"); return v; }
__device__ __forceinline__ void sts64(uint32_t a, uint32_t x, uint32_t y) { asm volatile("st.shared.v2.b32 [%0], {%1,%2};" :: "r"(a), "r"(x), "r"(y) : "memory"); }
template <int TB> __device__ __forceinline__ void wgmma_rs_128(float (&d)[64], const uint32_t (&a)[4], uint64_t db, int sc) {
  asm volatile("{\n.reg .pred p;\nsetp.ne.b32 p, %69, 0;\n"
    "wgmma.mma_async.sync.aligned.m64n128k16.f32.bf16.bf16 {%0, %1, %2, %3, %4, %5, %6, %7, %8, %9, %10, %11, %12, %13, %14, %15, %16, %17, %18, %19, %20, %21, %22, %23, %24, %25, %26, %27, %28, %29, %30, %31, %32, %33, %34, %35, %36, %37, %38, %39, %40, %41, %42, %43, %44, %45, %46, %47, %48, %49, %50, %51, %52, %53, %54, %55, %56, %57, %58, %59, %60, %61, %62, %63}, {%64, %65, %66, %67}, %68, p, 1, 1, %70;\n}\n"
    : "+f"(d[0]), "+f"(d[1]), "+f"(d[2]), "+f"(d[3]), "+f"(d[4]), "+f"(d[5]), "+f"(d[6]), "+f"(d[7]), "+f"(d[8]), "+f"(d[9]), "+f"(d[10]), "+f"(d[11]), "+f"(d[12]), "+f"(d[13]), "+f"(d[14]), "+f"(d[15]), "+f"(d[16]), "+f"(d[17]), "+f"(d[18]), "+f"(d[19]), "+f"(d[20]), "+f"(d[21]), "+f"(d[22]), "+f"(d[23]), "+f"(d[24]), "+f"(d[25]), "+f"(d[26]), "+f"(d[27]), "+f"(d[28]), "+f"(d[29]), "+f"(d[30]), "+f"(d[31]), "+f"(d[32]), "+f"(d[33]), "+f"(d[34]), "+f"(d[35]), "+f"(d[36]), "+f"(d[37]), "+f"(d[38]), "+f"(d[39]), "+f"(d[40]), "+f"(d[41]), "+f"(d[42]), "+f"(d[43]), "+f"(d[44]), "+f"(d[45]), "+f"(d[46]), "+f"(d[47]), "+f"(d[48]), "+f"(d[49]), "+f"(d[50]), "+f"(d[51]), "+f"(d[52]), "+f"(d[53]), "+f"(d[54]), "+f"(d[55]), "+f"(d[56]), "+f"(d[57]), "+f"(d[58]), "+f"(d[59]), "+f"(d[60]), "+f"(d[61]), "+f"(d[62]), "+f"(d[63])
    : "r"(a[0]), "r"(a[1]), "r"(a[2]), "r"(a[3]), "l"(db), "r"(sc), "n"(TB));
}
template <int TB> __device__ __forceinline__ void wgmma_rs_64(float (&d)[32], const uint32_t (&a)[4], uint64_t db, int sc) {
  asm volatile("{\n.reg .pred p;\nsetp.ne.b32 p, %37, 0;\n"
    "wgmma.mma_async.sync.aligned.m64n64k16.f32.bf16.bf16 {%0, %1, %2, %3, %4, %5, %6, %7, %8, %9, %10, %11, %12, %13, %14, %15, %16, %17, %18, %19, %20, %21, %22, %23, %24, %25, %26, %27, %28, %29, %30, %31}, {%32, %33, %34, %35}, %36, p, 1, 1, %38;\n}\n"
    : "+f"(d[0]), "+f"(d[1]), "+f"(d[2]), "+f"(d[3]), "+f"(d[4]), "+f"(d[5]), "+f"(d[6]), "+f"(d[7]), "+f"(d[8]), "+f"(d[9]), "+f"(d[10]), "+f"(d[11]), "+f"(d[12]), "+f"(d[13]), "+f"(d[14]), "+f"(d[15]), "+f"(d[16]), "+f"(d[17]), "+f"(d[18]), "+f"(d[19]), "+f"(d[20]), "+f"(d[21]), "+f"(d[22]), "+f"(d[23]), "+f"(d[24]), "+f"(d[25]), "+f"(d[26]), "+f"(d[27]), "+f"(d[28]), "+f"(d[29]), "+f"(d[30]), "+f"(d[31])
    : "r"(a[0]), "r"(a[1]), "r"(a[2]), "r"(a[3]), "l"(db), "r"(sc), "n"(TB));
}
template <int TB> __device__ __forceinline__ void wgmma_rs_56(float (&d)[28], const uint32_t (&a)[4], uint64_t db, int sc) {
  asm volatile("{\n.reg .pred p;\nsetp.ne.b32 p, %33, 0;\n"
    "wgmma.mma_async.sync.aligned.m64n56k16.f32.bf16.bf16 {%0, %1, %2, %3, %4, %5, %6, %7, %8, %9, %10, %11, %12, %13, %14, %15, %16, %17, %18, %19, %20, %21, %22, %23, %24, %25, %26, %27}, {%28, %29, %30, %31}, %32, p, 1, 1, %34;\n}\n"
    : "+f"(d[0]), "+f"(d[1]), "+f"(d[2]), "+f"(d[3]), "+f"(d[4]), "+f"(d[5]), "+f"(d[6]), "+f"(d[7]), "+f"(d[8]), "+f"(d[9]), "+f"(d[10]), "+f"(d[11]), "+f"(d[12]), "+f"(d[13]), "+f"(d[14]), "+f"(d[15]), "+f"(d[16]), "+f"(d[17]), "+f"(d[18]), "+f"(d[19]), "+f"(d[20]), "+f"(d[21]), "+f"(d[22]), "+f"(d[23]), "+f"(d[24]), "+f"(d[25]), "+f"(d[26]), "+f"(d[27])
    : "r"(a[0]), "r"(a[1]), "r"(a[2]), "r"(a[3]), "l"(db), "r"(sc), "n"(TB));
}
template <int TB> __device__ __forceinline__ void wgmma_rs_112(float (&d)[56], const uint32_t (&a)[4], uint64_t db, int sc) {
  asm volatile("{\n.reg .pred p;\nsetp.ne.b32 p, %61, 0;\n"
    "wgmma.mma_async.sync.aligned.m64n112k16.f32.bf16.bf16 {%0, %1, %2, %3, %4, %5, %6, %7, %8, %9, %10, %11, %12, %13, %14, %15, %16, %17, %18, %19, %20, %21, %22, %23, %24, %25, %26, %27, %28, %29, %30, %31, %32, %33, %34, %35, %36, %37, %38, %39, %40, %41, %42, %43, %44, %45, %46, %47, %48, %49, %50, %51, %52, %53, %54, %55}, {%56, %57, %58, %59}, %60, p, 1, 1, %62;\n}\n"
    : "+f"(d[0]), "+f"(d[1]), "+f"(d[2]), "+f"(d[3]), "+f"(d[4]), "+f"(d[5]), "+f"(d[6]), "+f"(d[7]), "+f"(d[8]), "+f"(d[9]), "+f"(d[10]), "+f"(d[11]), "+f"(d[12]), "+f"(d[13]), "+f"(d[14]), "+f"(d[15]), "+f"(d[16]), "+f"(d[17]), "+f"(d[18]), "+f"(d[19]), "+f"(d[20]), "+f"(d[21]), "+f"(d[22]), "+f"(d[23]), "+f"(d[24]), "+f"(d[25]), "+f"(d[26]), "+f"(d[27]), "+f"(d[28]), "+f"(d[29]), "+f"(d[30]), "+f"(d[31]), "+f"(d[32]), "+f"(d[33]), "+f"(d[34]), "+f"(d[35]), "+f"(d[36]), "+f"(d[37]), "+f"(d[38]), "+f"(d[39]), "+f"(d[40]), "+f"(d[41]), "+f"(d[42]), "+f"(d[43]), "+f"(d[44]), "+f"(d[45]), "+f"(d[46]), "+f"(d[47]), "+f"(d[48]), "+f"(d[49]), "+f"(d[50]), "+f"(d[51]), "+f"(d[52]), "+f"(d[53]), "+f"(d[54]), "+f"(d[55])
    : "r"(a[0]), "r"(a[1]), "r"(a[2]), "r"(a[3]), "l"(db), "r"(sc), "n"(TB));
}
template <int TA, int TB> __device__ __forceinline__ void wgmma_ss_56(float (&d)[28], uint64_t da, uint64_t db, int sc) {
  asm volatile("{\n.reg .pred p;\nsetp.ne.b32 p, %30, 0;\n"
    "wgmma.mma_async.sync.aligned.m64n56k16.f32.bf16.bf16 {%0, %1, %2, %3, %4, %5, %6, %7, %8, %9, %10, %11, %12, %13, %14, %15, %16, %17, %18, %19, %20, %21, %22, %23, %24, %25, %26, %27}, %28, %29, p, 1, 1, %31, %32;\n}\n"
    : "+f"(d[0]), "+f"(d[1]), "+f"(d[2]), "+f"(d[3]), "+f"(d[4]), "+f"(d[5]), "+f"(d[6]), "+f"(d[7]), "+f"(d[8]), "+f"(d[9]), "+f"(d[10]), "+f"(d[11]), "+f"(d[12]), "+f"(d[13]), "+f"(d[14]), "+f"(d[15]), "+f"(d[16]), "+f"(d[17]), "+f"(d[18]), "+f"(d[19]), "+f"(d[20]), "+f"(d[21]), "+f"(d[22]), "+f"(d[23]), "+f"(d[24]), "+f"(d[25]), "+f"(d[26]), "+f"(d[27])
    : "l"(da), "l"(db), "r"(sc), "n"(TA), "n"(TB));
}

__device__ __forceinline__ uint32_t cis(float a) { return pack_bf16(__cosf(a), __sinf(a)); }

typedef __nv_bfloat162 b2;
struct c2 { b2 x, y; };
__device__ __forceinline__ b2 as_b2(uint32_t u) { return *reinterpret_cast<b2*>(&u); }
__device__ __forceinline__ uint32_t as_u(b2 v) { return *reinterpret_cast<uint32_t*>(&v); }
__device__ __forceinline__ c2 mk(b2 x, b2 y) { c2 r; r.x = x; r.y = y; return r; }
__device__ __forceinline__ c2 cmul(c2 a, b2 wr, b2 wi) { return mk(__hfma2(a.x, wr, __hneg2(__hmul2(a.y, wi))), __hfma2(a.x, wi, __hmul2(a.y, wr))); }
__device__ __forceinline__ void fft4(c2& a0, c2& a1, c2& a2, c2& a3) {
  c2 t0 = mk(__hadd2(a0.x, a2.x), __hadd2(a0.y, a2.y)), t1 = mk(__hsub2(a0.x, a2.x), __hsub2(a0.y, a2.y));
  c2 t2 = mk(__hadd2(a1.x, a3.x), __hadd2(a1.y, a3.y)), t3 = mk(__hsub2(a1.x, a3.x), __hsub2(a1.y, a3.y));
  a0 = mk(__hadd2(t0.x, t2.x), __hadd2(t0.y, t2.y)); a2 = mk(__hsub2(t0.x, t2.x), __hsub2(t0.y, t2.y));
  a1 = mk(__hadd2(t1.x, t3.y), __hsub2(t1.y, t3.x)); a3 = mk(__hsub2(t1.x, t3.y), __hadd2(t1.y, t3.x));
}
__device__ __forceinline__ void fft4_s2(c2& a0, c2& a1, c2& a2, c2& a3, b2 r) {
  const b2 nr = __hneg2(r);
  c2 t0 = mk(__hfma2(a2.x, r, a0.x), __hfma2(a2.y, r, a0.y)), t1 = mk(__hfma2(a2.x, nr, a0.x), __hfma2(a2.y, nr, a0.y));
  c2 t2 = mk(__hadd2(a1.x, a3.x), __hadd2(a1.y, a3.y)), t3 = mk(__hsub2(a1.x, a3.x), __hsub2(a1.y, a3.y));
  a0 = mk(__hadd2(t0.x, t2.x), __hadd2(t0.y, t2.y)); a2 = mk(__hsub2(t0.x, t2.x), __hsub2(t0.y, t2.y));
  a1 = mk(__hadd2(t1.x, t3.y), __hsub2(t1.y, t3.x)); a3 = mk(__hsub2(t1.x, t3.y), __hadd2(t1.y, t3.x));
}
__device__ __forceinline__ void fft4_s13(c2& a0, c2& a1, c2& a2, c2& a3, b2 r) {
  const b2 nr = __hneg2(r);
  c2 t0 = mk(__hadd2(a0.x, a2.x), __hadd2(a0.y, a2.y)), t1 = mk(__hsub2(a0.x, a2.x), __hsub2(a0.y, a2.y));
  c2 t2 = mk(__hadd2(a1.x, a3.x), __hadd2(a1.y, a3.y)), t3 = mk(__hsub2(a1.x, a3.x), __hsub2(a1.y, a3.y));
  a0 = mk(__hfma2(t2.x, r, t0.x), __hfma2(t2.y, r, t0.y)); a2 = mk(__hfma2(t2.x, nr, t0.x), __hfma2(t2.y, nr, t0.y));
  a1 = mk(__hfma2(t3.y, r, t1.x), __hfma2(t3.x, nr, t1.y)); a3 = mk(__hfma2(t3.y, nr, t1.x), __hfma2(t3.x, r, t1.y));
}
__device__ __forceinline__ c2 rot1(c2 a) { return mk(__hadd2(a.x, a.y), __hsub2(a.y, a.x)); }
__device__ __forceinline__ c2 rot3(c2 a) { return mk(__hsub2(a.y, a.x), __hneg2(__hadd2(a.x, a.y))); }
__device__ __forceinline__ c2 mul_mi(c2 a) { return mk(a.y, __hneg2(a.x)); }
template <int O> __device__ __forceinline__ void fft8(c2 (&v)[16]) {
  const b2 r = as_b2(0x3F353F35u), nr = as_b2(0xBF35BF35u);
  fft4(v[O], v[O + 4], v[O + 8], v[O + 12]);
  fft4(v[O + 2], v[O + 6], v[O + 10], v[O + 14]);
  const c2 o0 = v[O + 2], o1 = rot1(v[O + 6]), o2 = v[O + 10], o3 = rot1(v[O + 14]);
  const c2 e0 = v[O], e1 = v[O + 4], e2 = v[O + 8], e3 = v[O + 12];
  v[O] = mk(__hadd2(e0.x, o0.x), __hadd2(e0.y, o0.y));              v[O + 8] = mk(__hsub2(e0.x, o0.x), __hsub2(e0.y, o0.y));
  v[O + 2] = mk(__hfma2(o1.x, r, e1.x), __hfma2(o1.y, r, e1.y));    v[O + 10] = mk(__hfma2(o1.x, nr, e1.x), __hfma2(o1.y, nr, e1.y));
  v[O + 4] = mk(__hadd2(e2.x, o2.y), __hsub2(e2.y, o2.x));          v[O + 12] = mk(__hsub2(e2.x, o2.y), __hadd2(e2.y, o2.x));
  v[O + 6] = mk(__hfma2(o3.y, r, e3.x), __hfma2(o3.x, nr, e3.y));   v[O + 14] = mk(__hfma2(o3.y, nr, e3.x), __hfma2(o3.x, r, e3.y));
}
__device__ __forceinline__ void fft16(c2 (&v)[16]) {
  const b2 r = as_b2(0x3F353F35u), c1 = as_b2(0x3F6D3F6Du), s1 = as_b2(0x3EC43EC4u), nc1 = as_b2(0xBF6DBF6Du), ns1 = as_b2(0xBEC4BEC4u);
#pragma unroll
  for (int a = 0; a < 4; a++) fft4(v[a], v[a + 4], v[a + 8], v[a + 12]);
  v[5] = cmul(v[5], c1, ns1); v[6] = rot1(v[6]); v[7] = cmul(v[7], s1, nc1);
  v[9] = rot1(v[9]); v[10] = mul_mi(v[10]); v[11] = rot3(v[11]);
  v[13] = cmul(v[13], s1, nc1); v[14] = rot3(v[14]); v[15] = cmul(v[15], nc1, s1);
  fft4(v[0], v[1], v[2], v[3]); fft4_s2(v[4], v[5], v[6], v[7], r); fft4_s13(v[8], v[9], v[10], v[11], r); fft4_s2(v[12], v[13], v[14], v[15], r);
  c2 t;
  t = v[1]; v[1] = v[4]; v[4] = t;  t = v[2]; v[2] = v[8]; v[8] = t;  t = v[3]; v[3] = v[12]; v[12] = t;
  t = v[6]; v[6] = v[9]; v[9] = t;  t = v[7]; v[7] = v[13]; v[13] = t; t = v[11]; v[11] = v[14]; v[14] = t;
}

__device__ __forceinline__ void columns(c2 (&v)[16], uint32_t sb, int t) {
  const int l16 = t & 15;
  const uint32_t row = sb + OFF_EXCH + (t >> 4) * 2304;
  const uint32_t pos = sb + OFF_EXCH + (t >> 3) * 144 + (t & 7) * 16;
#pragma unroll 1
  for (int ps = 0; ps < 6; ps++) {
    if (ps == 0 || ps == 5) { fft8<0>(v); fft8<1>(v); } else fft16(v);
    if (ps == 5) break;
    if (ps == 2) {
      const uint32_t ws = sb + OFF_WS + (l16 >> 1) * 128 + ((((t >> 4) + (l16 >> 1)) & 7) * 2 + (l16 & 1)) * 8;
      mbar_wait(sb + OFF_BAR + B_WFULL * 8, 0);
#pragma unroll
      for (int q = 0; q < 16; q++) {
        const uint2 w = lds64(ws + q * 1024);
        const c2 z = cmul(v[q], as_b2(w.x), as_b2(w.y));
        v[q] = mk(z.y, z.x);
      }
      continue;
    }
    {
      const bool full = ps == 0 || ps == 4;
      const uint32_t tw = sb + OFF_TW + (full ? ps * 2048 + t * 16 : 16384 + l16 * 16);
      const uint32_t st = full ? 2048 : 256;
#pragma unroll
      for (int i = 0; i < 4; i++) {
        const uint4 w4 = lds128(tw + i * st);
        const uint32_t w[4] = {w4.x, w4.y, w4.z, w4.w};
#pragma unroll
        for (int e = 0; e < 4; e++) v[4 * i + e] = cmul(v[4 * i + e], __low2bfloat162(as_b2(w[e])), __high2bfloat162(as_b2(w[e])));
      }
    }
    if (ps == 0) {
      mbar_wait(sb + OFF_BAR + B_XDONE * 8, 0);
#pragma unroll
      for (int q = 0; q < 8; q++) sts128(pos + q * 2304, as_u(v[2 * q].x), as_u(v[2 * q].y), as_u(v[2 * q + 1].x), as_u(v[2 * q + 1].y));
      bar_sync<3, 128>();
#pragma unroll
      for (int q = 0; q < 16; q++) { const uint2 a = lds64(row + q * 144 + l16 * 8); v[q] = mk(as_b2(a.x), as_b2(a.y)); }
    } else {
      __syncwarp();
#pragma unroll
      for (int q = 0; q < 16; q++) sts64(row + q * 144 + l16 * 8, as_u(v[q].x), as_u(v[q].y));
      if (ps == 4) bar_sync<3, 128>(); else __syncwarp();
      const uint32_t src = ps == 4 ? pos : row + l16 * 144, st = ps == 4 ? 2304 : 16;
#pragma unroll
      for (int q = 0; q < 8; q++) { const uint4 a = lds128(src + q * st); v[2 * q] = mk(as_b2(a.x), as_b2(a.y)); v[2 * q + 1] = mk(as_b2(a.z), as_b2(a.w)); }
    }
  }
}

template <int NH> __device__ __forceinline__ void h_epilogue(float (&acc)[NH * 8], unsigned char* gdst, uint32_t tag) {
#pragma unroll
  for (int c = 0; c < NH / 2; c++) {
    uint32_t pk[4];
#pragma unroll
    for (int i = 0; i < 4; i++) {
      float hv[2];
#pragma unroll
      for (int e = 0; e < 2; e++) {
        float hg = 0.5f * acc[c * 8 + i * 2 + e], up = acc[NH * 4 + c * 8 + i * 2 + e];
        float th; asm("tanh.approx.f32 %0, %1;" : "=f"(th) : "f"(hg));
        hv[e] = fmaf(hg, th, hg) * up;
      }
      pk[i] = pack_bf16(hv[0], hv[1]);
    }
    stg128_l2(gdst + c * 4096, (pk[0] & ~1u) | tag, pk[1], pk[2], pk[3]);
  }
}

__device__ __forceinline__ void frag_ready(uint32_t (&a)[4], uint32_t (&b)[4], uint32_t (&c)[4], uint32_t (&d)[4], const unsigned char* p, uint32_t tag) {
  asm volatile("{\n.reg .pred p;\n.reg .u32 c, m, q;\nmov.u32 c, 0;\nL_TRY:\n"
               "lop3.b32 m, %0, %4, %17, 0x7E;\nlop3.b32 q, %8, %12, %17, 0x7E;\nlop3.b32 m, m, q, 1, 0xA8;\nsetp.ne.u32 p, m, 0;\n"
               "vote.sync.any.pred p, p, 0xffffffff;\n@!p bra.uni L_OK;\n"
               "ld.relaxed.gpu.global.v4.b32 {%0,%1,%2,%3}, [%16];\nld.relaxed.gpu.global.v4.b32 {%4,%5,%6,%7}, [%16+4096];\n"
               "ld.relaxed.gpu.global.v4.b32 {%8,%9,%10,%11}, [%16+8192];\nld.relaxed.gpu.global.v4.b32 {%12,%13,%14,%15}, [%16+12288];\n"
               "add.u32 c, c, 1;\nsetp.lt.u32 p, c, 262144;\n@p bra.uni L_TRY;\ntrap;\nL_OK:\n}"
               : "+r"(a[0]), "+r"(a[1]), "+r"(a[2]), "+r"(a[3]), "+r"(b[0]), "+r"(b[1]), "+r"(b[2]), "+r"(b[3]),
                 "+r"(c[0]), "+r"(c[1]), "+r"(c[2]), "+r"(c[3]), "+r"(d[0]), "+r"(d[1]), "+r"(d[2]), "+r"(d[3])
               : "l"(p), "r"(tag) : "memory");
}

#define MAP 0
#define LEAD2 0
#define LEAD1 2

__global__ void __cluster_dims__(2, 1, 1) __launch_bounds__(NTHREADS, 1)
fused_kernel(const __grid_constant__ CUtensorMap tm_x, const __grid_constant__ CUtensorMap tm_g, const __grid_constant__ CUtensorMap tm_u,
             const __grid_constant__ CUtensorMap tm_g32, const __grid_constant__ CUtensorMap tm_u32, const __grid_constant__ CUtensorMap tm_d,
             const __grid_constant__ CUtensorMap tm_s,
             const __nv_bfloat16* __restrict__ w_r, const __nv_bfloat16* __restrict__ w_i,
             const __nv_bfloat16* __restrict__ w_gate, const __nv_bfloat16* __restrict__ w_up,
             const __nv_bfloat16* __restrict__ w_down, const __nv_bfloat16* __restrict__ gate_w, __nv_bfloat16* __restrict__ out) {
  extern __shared__ __align__(1024) unsigned char smem[];
  const uint32_t sb = s2u(smem);
  const uint32_t bars = sb + OFF_BAR;
  const int tid = threadIdx.x, warp = __shfl_sync(0xffffffffu, tid >> 5, 0), lane = tid & 31;
  const int cl = blockIdx.x >> 1, kh = blockIdx.x & 1;
  const int n0 = cl < 4 ? cl : (cl < 36 ? (cl - 4) >> 3 : (cl - 36) / 7);
  const int m0 = cl < 4 ? 15 : (cl < 36 ? (cl - 4) & 7 : cl - 28 - 7 * n0);
  const int n = MAP == 0 ? n0 : (MAP == 1 ? (m0 & 3) : ((n0 & 1) | ((m0 & 1) << 1)));
  const int m = MAP == 0 ? m0 : (MAP == 1 ? ((m0 & 12) | n0) : ((m0 & 14) | (n0 >> 1)));
  const int j = kh * 4 + n, bid = m * 8 + n * 2 + kh;

  const int c64 = 224 * j + (j & 1) * 32;
  if (warp < 8) {
    asm volatile("setmaxnreg.inc.sync.aligned.u32 208;");
    const int wg = warp >> 2, w4 = warp & 3, g = lane >> 2, t = lane & 3;
    const int rh = wg ^ kh ^ 1;
    const int p = j & 1, r = (j >> 1) & 1, hh = j >> 2;
    const uint32_t epoch = ld_relaxed(&g_ep[bid]);
    if ((tid & 127) == 0) PROF(wg, 30);
#pragma unroll 1
    for (int it = tid; it < 392; it += 256) {
      const int kc = it / 28, sg = it - kc * 28;
      const int k = 2 * (28 * hh + sg) + r;
      const float kf = (float)k * (-6.283185307179586f / 448.0f), a0 = (float)(16 * kc + p) * kf;
      uint32_t c[4], s[4];
#pragma unroll
      for (int q = 0; q < 4; q++) {
        const float a1 = fmaf((float)(2 * q), kf, a0), a2 = fmaf((float)(2 * q + 8), kf, a0);
        c[q] = pack_bf16(__cosf(a1), __cosf(a2)); s[q] = pack_bf16(__sinf(a1), __sinf(a2));
        if (k == 0) s[q] = ((q ^ p) & 1) ? 0xBF80BF80u : 0x3F803F80u;
      }
      const uint32_t a = sb + 6 * SLOT + (kc * 56 + 2 * sg) * 16;
      sts128(a, c[0], c[1], c[2], c[3]);
      sts128(a + 16, s[0], s[1], s[2], s[3]);
    }
    if ((tid & 127) == 0) PROF(wg, 31);
    fence_async_smem();
    bar_sync<0, NTHREADS - 64>();
    asm volatile("barrier.cluster.arrive.relaxed.aligned;" ::: "memory");
    if ((tid & 127) == 0) PROF(wg, 1);

    uint32_t xa[28][4];
    {
      const uint32_t xb = sb + OFF_PQ + wg * HALF_XR + (w4 * 16 + (lane & 15)) * 128;
      mbar_wait(bars + (B_XFULL + wg) * 8, 0);
      if ((tid & 127) == 0) PROF(wg, 2);
#pragma unroll
      for (int kb = 0; kb < 7; kb++) {
#pragma unroll
        for (int kk = 0; kk < 4; kk++) {
          uint32_t a = xb + kb * 8192 + (((2 * kk + (lane >> 4)) ^ (lane & 7)) << 4);
          asm volatile("ldmatrix.sync.aligned.m8n8.x4.shared.b16 {%0,%1,%2,%3}, [%4];"
                       : "=r"(xa[kb * 4 + kk][0]), "=r"(xa[kb * 4 + kk][1]), "=r"(xa[kb * 4 + kk][2]), "=r"(xa[kb * 4 + kk][3]) : "r"(a) : "memory");
        }
      }
    }
    {
      uint32_t ad[7][4];
      const uint32_t sel = p ? 0x7632 : 0x5410;
      const uint32_t sgn = r ? 0xBF80BF80u : 0x3F803F80u;
#pragma unroll
      for (int jj = 0; jj < 7; jj++) {
#pragma unroll
        for (int i = 0; i < 4; i++) {
          int ks = 2 * jj + (i >> 1), rr = i & 1;
          uint32_t lo = __byte_perm(xa[ks][rr], xa[ks][rr + 2], sel);
          uint32_t hi = __byte_perm(xa[ks + 14][rr], xa[ks + 14][rr + 2], sel);
          asm("fma.rn.bf16x2 %0, %1, %2, %3;" : "=r"(ad[jj][i]) : "r"(hi), "r"(sgn), "r"(lo));
        }
      }
      __syncwarp();
      if (lane == 0) mbar_arrive(bars + (B_XFREE + wg) * 8);
      float acc[28];
      wg_fence();
      uint64_t db = mkdesc(sb + 6 * SLOT, 896, 128, 0);
#pragma unroll
      for (int jj = 0; jj < 7; jj++) wgmma_rs_56<0>(acc, ad[jj], db + jj * 112, jj != 0);
      wg_commit();
      wg_wait<0>(); keep(acc);
      if (lane == 0) mbar_arrive(bars + (B_EMPTY + 6) * 8);
      const uint32_t xc = sb + OFF_EXCH + wg * 8192 + t * 256 + w4 * 64 + g * 4;
      mbar_wait(bars + B_XFREE * 8, 0);
#pragma unroll
      for (int i = 0; i < 7; i++) {
        sts32(xc + i * 1024, pack_bf16(acc[4 * i], acc[4 * i + 1]));
        sts32(xc + i * 1024 + 32, pack_bf16(acc[4 * i + 2], acc[4 * i + 3]));
      }
      fence_async_smem();
      __syncwarp();
      if (lane == 0) mbar_arrive(bars + B_PUBX * 8);
    }
    if ((tid & 127) == 0) PROF(wg, 3);
    const uint32_t tag = ~epoch & 1;
    unsigned char* const hbase = g_H + (size_t)(m * 2 + kh) * (56 * 4096) + rh * 2048 + (tid & 127) * 16;
#pragma unroll 1
    for (int u = 0; u < 3; u++) {
      float acc[64];
      if (wg == 1) { if (u & 1) bar_sync<6, 256>(); else bar_sync<2, 256>(); }
      const uint32_t sbu = opaque(sb);
#pragma unroll
      for (int kb = 0; kb < 7; kb++) {
        mbar_wait(sbu + OFF_BAR + (B_FULL + kb) * 8, u & 1);
        wg_fence();
        uint64_t db = mkdesc(sbu + kb * SLOT, 8192, 1024, 1);
#pragma unroll
        for (int kk = 0; kk < 4; kk++) wgmma_rs_128<1>(acc, xa[kb * 4 + kk], db + kk * 128, (kb | kk) != 0);
        wg_commit();
        if (kb == LEAD1 && wg == 0) { if (u & 1) bar_arrive<6, 256>(); else bar_arrive<2, 256>(); }
        if (kb > 0) { wg_wait<1>(); if (lane == 0) mbar_arrive(sbu + OFF_BAR + (B_EMPTY + kb - 1) * 8); }
      }
      wg_wait<0>(); keep(acc);
      if (lane == 0) mbar_arrive(sbu + OFF_BAR + (B_EMPTY + 6) * 8);
      if ((tid & 127) == 0) PROF(wg, 4 + 2 * u);
      h_epilogue<8>(acc, hbase + (u * 16 + n * 4) * 4096, tag);
      if ((tid & 127) == 0) PROF(wg, 5 + 2 * u);
    }
    uint32_t ha[14][4][4];
    auto check = [&](int b0, int b1) {
#pragma unroll
      for (int b = b0; b < b1; b++) frag_ready(ha[b][0], ha[b][1], ha[b][2], ha[b][3], hbase + b * 16384, tag);
    };
    auto load = [&](int b0, int b1) {
#pragma unroll
      for (int i = b0; i < b1; i++) ldg128_l2(ha[i >> 2][i & 3], hbase + i * 4096);
    };
    {
      float acc[32];
      load(0, 3);
      if (wg == 1) bar_sync<6, 256>();
      const uint32_t sbu = opaque(sb);
#pragma unroll
      for (int it = 0; it < 4; it++) {
        mbar_wait(sbu + OFF_BAR + (B_FULL + it) * 8, 1);
        wg_fence();
        uint64_t db = mkdesc(sbu + it * SLOT, 8192, 512, 2);
#pragma unroll
        for (int kk = 0; kk < 8; kk++) if (it * 8 + kk < 28) wgmma_rs_64<1>(acc, xa[it * 8 + kk], db + kk * 64, (it | kk) != 0);
        wg_commit();
        if (it == 2 && wg == 0) bar_arrive<6, 256>();
        if (it > 0) {
          wg_wait<1>();
          if (lane == 0) mbar_arrive(sbu + OFF_BAR + (B_EMPTY + it - 1) * 8);
          if (it == 1) load(3, 11);
          if (it == 2) load(11, 16);
        }
      }
      wg_wait<0>(); keep(acc);
      if (lane == 0) mbar_arrive(sbu + OFF_BAR + (B_EMPTY + 3) * 8);
      if ((tid & 127) == 0) PROF(wg, 10);
      h_epilogue<4>(acc, hbase + (48 + n * 2) * 4096, tag);
    }
    asm volatile("barrier.cluster.wait.aligned;" ::: "memory");
    if ((tid & 127) == 0) PROF(wg, 11);

    float acc[56];
    check(0, 4);
    if (wg == 1) bar_sync<2, 256>();
#pragma unroll
    for (int b = 0; b < 14; b++) {
      if ((tid & 127) == 0) PROF(wg, 16 + b);
      if (b >= 3) mbar_wait(bars + (B_FULL + (b + 1) % 7) * 8, b < 6 || b == 13);
      else if (b == 0) mbar_wait(bars + B_RFULL * 8, 0);
      if (b == 4) check(4, 7);
      if (b == 7) check(7, 11);
      if (b == 11) check(11, 14);
      wg_fence();
      const uint64_t db = mkdesc(b < 3 ? sb + OFF_R + b * SLOT : sb + (b + 1) % 7 * SLOT, 8192, 1024, 1);
#pragma unroll
      for (int kk = 0; kk < 4; kk++) wgmma_rs_112<1>(acc, ha[b][kk], db + kk * 128, (b | kk) != 0);
      wg_commit();
      if (b == LEAD2 && wg == 0) bar_arrive<2, 256>();
      if (b == 0) load(16, 24);
      if (b == 1) load(24, 28);
      if (b == 4 || b == 5) load(8 * b - 4, 8 * b + 4);
      if (b == 7) load(44, 52);
      if (b == 8) load(52, 56);
      if (b > 0) wg_wait<1>();
      if (lane == 0) {
        if (b >= 4 && b <= 9) mbar_arrive(bars + (B_EMPTY + b % 7) * 8);
        if (b == 3) {
          mbar_arrive(bars + B_LFREE * 8);
          asm volatile("{\n.reg .b32 ra;\nmapa.shared::cluster.u32 ra, %0, %1;\nmbarrier.arrive.relaxed.cluster.shared::cluster.b64 _, [ra];\n}"
                       :: "r"(bars + B_RFREE * 8), "r"(kh ^ 1) : "memory");
        }
      }
    }
    const int t128 = tid & 127;
    wg_wait<0>(); keep(acc);
    if (wg == 0) {
      if (t128 == 0) PROF(wg, 12);
      mbar_wait_cluster(bars + B_RFREE * 8, 0);
      uint32_t rdst, rbar;
      asm volatile("mapa.shared::cluster.u32 %0, %1, %2;" : "=r"(rdst) : "r"(sb + OFF_R + t128 * 16), "r"(kh ^ 1));
      asm volatile("mapa.shared::cluster.u32 %0, %1, %2;" : "=r"(rbar) : "r"(bars + B_RECV * 8), "r"(kh ^ 1));
#pragma unroll
      for (int i = 0; i < 14; i++)
        asm volatile("st.async.weak.shared::cluster.mbarrier::complete_tx::bytes.v4.f32 [%0], {%1,%2,%3,%4}, [%5];"
                     :: "r"(rdst + i * 2048), "f"(acc[4 * i]), "f"(acc[4 * i + 1]), "f"(acc[4 * i + 2]), "f"(acc[4 * i + 3]), "r"(rbar) : "memory");
    } else {
      float spec[2][28];
      if (t128 == 0) PROF(wg, 12);
#pragma unroll
      for (int i = 0; i < 4; i++) {
        if (i == 0) mbar_wait(bars + B_GFULL * 8, 0);
        if (i >= 2) mbar_wait(bars + (B_FULL + i - 1) * 8, 1);
        mbar_wait(bars + (B_PQFULL + i) * 8, 0);
        if (i == 0 && t128 == 0) { PROF(wg, 13); g_ep[bid] = epoch + 1; }
        wg_fence();
        const uint64_t da = mkdesc(sb + OFF_PQ + i * 14336, 1024, 1024, 1);
        const uint64_t db = mkdesc(i < 2 ? sb + OFF_R + 28672 + i * (G_IMG / 2) : sb + (i - 1) * SLOT, 896, 128, 0);
#pragma unroll
        for (int kk = 0; kk < 7; kk++) wgmma_ss_56<1, 0>(spec[i >> 1], da + kk * 128, db + kk * 112, ((i & 1) | kk) != 0);
        wg_commit();
      }
      const float* gs = reinterpret_cast<const float*>(smem + OFF_G) + w4 * 16 + g;
      const float o0 = bf16_round(1.0f - gs[0]), o1 = bf16_round(1.0f - gs[8]);
      const float g0 = gs[0] * (1.0f / (float)(S_ * D_)), g1 = gs[8] * (1.0f / (float)(S_ * D_));
      mbar_wait_cluster(bars + B_RECV * 8, 0);
      if (t128 == 0) PROF(wg, 0);
#pragma unroll
      for (int i = 0; i < 14; i++) {
        const float4 o = lds128f(sb + OFF_R + t128 * 16 + i * 2048);
        acc[4 * i] = (acc[4 * i] + o.x) * o0; acc[4 * i + 1] = (acc[4 * i + 1] + o.y) * o0;
        acc[4 * i + 2] = (acc[4 * i + 2] + o.z) * o1; acc[4 * i + 3] = (acc[4 * i + 3] + o.w) * o1;
      }
      keep(acc);
      wg_wait<0>(); keep(spec[0]); keep(spec[1]);
      if (t128 == 0) PROF(wg, 14);
      bar_sync<5, 128>();
      const uint32_t st = sb + OFF_PQ + w4 * 3840;
#pragma unroll
      for (int i = 0; i < 7; i++) {
        uint32_t pk[4];
#pragma unroll
        for (int e = 0; e < 2; e++) {
          const int c = 2 * i + e, si = i * 4 + e;
          pk[2 * e] = pack_bf16(fmaf(g0, spec[0][si], acc[4 * c]), fmaf(g0, spec[1][si], acc[4 * c + 1]));
          pk[2 * e + 1] = pack_bf16(fmaf(g1, spec[0][si + 2], acc[4 * c + 2]), fmaf(g1, spec[1][si + 2], acc[4 * c + 3]));
        }
        asm volatile("stmatrix.sync.aligned.m8n8.x4.shared.b16 [%0], {%1,%2,%3,%4};"
                     :: "r"(st + (lane & 15) * 240 + (lane >> 4) * 16 + i * 32), "r"(pk[0]), "r"(pk[1]), "r"(pk[2]), "r"(pk[3]) : "memory");
      }
      __syncwarp();
      if (lane < 28) {
        const int r2 = lane >= 14, cc = lane - r2 * 14;
        unsigned char* ob = reinterpret_cast<unsigned char*>(out) + (size_t)(m * 128 + kh * 64 + w4 * 16 + r2) * (D_ * 2) + n * 224 + cc * 16;
        float4 v[8];
#pragma unroll
        for (int i = 0; i < 8; i++) v[i] = lds128f(st + r2 * 240 + cc * 16 + i * 480);
#pragma unroll
        for (int i = 0; i < 8; i++) stg128(ob + i * (D_ * 4), __float_as_uint(v[i].x), __float_as_uint(v[i].y), __float_as_uint(v[i].z), __float_as_uint(v[i].w));
      }
    }
    if (t128 == 0) { PROF(wg, 15); if (wg) { PROFG(4, 30); PROF(4, 31); } }
  } else if (warp < 12) {
    asm volatile("setmaxnreg.dec.sync.aligned.u32 72;");
    const int t = tid - 256;
    const int k = bid;
    if (t == 0) PROF(2, 0);
    uint4 gv[7];
#pragma unroll
    for (int i = 0; i < 7; i++) gv[i] = ldg128(reinterpret_cast<const uint4*>(gate_w) + i * 8 + (t & 7));
    if (t < 98) {
      int cid = m * 98 + t, kc = cid / 56, nn = cid - kc * 56;
      int d = 112 * n + 8 * (2 * (nn >> 3) + (nn & 1)) + (nn & 6) + kh;
      int dr = d > 224 ? d - 448 : d;
      const float df = (float)dr * (-6.283185307179586f / 448.0f);
      uint32_t pk[4];
#pragma unroll
      for (int e = 0; e < 4; e++) {
        const float a = (float)(4 * kc + e) * df;
        pk[e] = pack_bf16(2.0f * __cosf(a), 2.0f * __sinf(a));
      }
      if (kc == 0) pk[0] = (((d >> 1) ^ kh) & 1) ? 0xBF803F80u : 0x3F803F80u;
      stg128(g_G + (size_t)(n * 2 + kh) * G_IMG + cid * 16, pk[0], pk[1], pk[2], pk[3]);
    }
    bar_sync<0, NTHREADS - 64>();
    asm volatile("barrier.cluster.arrive.relaxed.aligned;" ::: "memory");
    {
      const int row = n * 16 + (t >> 3), l8 = t & 7;
      mbar_wait(bars + (B_XFULL + 1) * 8, 0);
      float sum = 0.f;
#pragma unroll
      for (int i = 0; i < 7; i++) {
        const uint4 a = lds128(sb + OFF_R + i * 8192 + row * 128 + ((l8 ^ (row & 7)) << 4));
        const uint32_t aa[4] = {a.x, a.y, a.z, a.w}, bb[4] = {gv[i].x, gv[i].y, gv[i].z, gv[i].w};
#pragma unroll
        for (int e = 0; e < 4; e++) {
          const uint32_t pr = as_u(__hmul2(as_b2(aa[e]), as_b2(bb[e])));
          sum += bf_lo(pr) + bf_hi(pr);
        }
      }
      sum += __shfl_xor_sync(0xffffffffu, sum, 1); sum += __shfl_xor_sync(0xffffffffu, sum, 2); sum += __shfl_xor_sync(0xffffffffu, sum, 4);
      if (l8 == 0) g_gate[m * 128 + kh * 64 + row] = bf16_round(__fdividef(1.0f, 1.0f + __expf(-bf16_round(sum))));
    }
    __syncwarp();
    if (lane == 0) mbar_arrive(bars + (B_XFREE + 1) * 8);
    if (t == 0) PROF(2, 11);
    mbar_wait(bars + B_XFREE * 8, 0);
    {
      const float u = -6.283185307179586f / 2048.0f, t2 = (float)(2 * t) * u;
#pragma unroll 1
      for (int i = 0; i < 4; i++) {
        const float q = (float)(2 * i);
        sts128(sb + OFF_TW + i * 2048 + t * 16, cis(t2 * q), cis((t2 + u) * q), cis(t2 * (q + 1.0f)), cis((t2 + u) * (q + 1.0f)));
      }
      const float l = (float)((t >> 1) & 15) * (8.0f * u), jj = (float)((t >> 5) * 4 + (t & 1) * 2);
      sts64(sb + OFF_TW + 16384 + t * 8, cis(l * jj), cis(l * (jj + 1.0f)));
    }
    mbar_wait(bars + B_PIN * 8, 0);
    mbar_wait(bars + (B_XFREE + 1) * 8, 0);
    if (t == 0) PROF(2, 4);
    {
      const uint32_t wa = sb + OFF_WS + (((t & 7) - bid) & 7) * 450 + (t >> 3) * 2, wc = wa + 448 - (t >> 3) * 4;
#pragma unroll 1
      for (int h = 0; h < 2; h++) {
        uint32_t w[4][8];
#pragma unroll
        for (int i = 0; i < 4; i++) {
#pragma unroll
          for (int e = 0; e < 4; e++) { w[i][2 * e] = lds16(wa + h * 128 + i * 32 + e * 3600); w[i][2 * e + 1] = lds16(wc - h * 128 - i * 32 + e * 3600); }
        }
#pragma unroll
        for (int i = 0; i < 4; i++)
          sts128(sb + OFF_R + h * 8192 + i * 2048 + t * 16, __byte_perm(w[i][0], w[i][1], 0x5410), __byte_perm(w[i][4], w[i][5], 0x5410), __byte_perm(w[i][2], w[i][3], 0x5410), __byte_perm(w[i][6], w[i][7], 0x5410));
      }
    }
    fence_async_smem();
    __syncwarp();
    if (lane == 0) mbar_arrive(bars + B_PUBW * 8);
    if (k < 113) {
      if (t == 0) PROF(2, 2);
      mbar_wait(bars + B_XCFULL * 8, 0);
      if (t == 0) PROF(2, 3);
      c2 v[16];
      uint2 xe[8], xo[8];
      const int sl = k == 112 ? 0 : k, hi = sl >= 56;
      const unsigned char* xs = g_X + (192 + (sl & 1) * 64 + hi * 72 + (sl & ~1) + ((t >> 4) & 1)) * XP + (t >> 5) * 256 + (t & 15) * 8;
#pragma unroll
      for (int jj = 0; jj < 8; jj++) { xe[jj] = ldg64_l2(xs + jj * 1024); xo[jj] = ldg64_l2(xs + jj * 1024 + 128); }
      {
        const float rr = (float)(t >> 4) * (-6.283185307179586f / 2048.0f);
#pragma unroll 1
        for (int i = 0; i < 4; i++) {
          const float l = (float)((t & 15) + 64 * i);
          sts128(sb + OFF_TW + 8192 + i * 2048 + t * 16, cis(rr * l), cis(rr * (l + 16.0f)), cis(rr * (l + 32.0f)), cis(rr * (l + 48.0f)));
        }
      }
      if (t == 0) PROF(2, 9);
      const uint32_t se = k == 0 ? 0x4410 : (k == 112 ? 0x4432 : 0x3210), so = k == 0 ? 0x4410 : (k == 112 ? 0x3244 : 0x3210);
#pragma unroll
      for (int jj = 0; jj < 8; jj++) {
        const uint2 e2 = xe[jj], o2 = xo[jj];
#pragma unroll
        for (int h = 0; h < 2; h++) {
          const b2 e = as_b2(__byte_perm(h ? e2.y : e2.x, 0, se)), o = as_b2(__byte_perm(h ? o2.y : o2.x, 0, so));
          const uint32_t s = as_u(__hadd2(e, o)), d = as_u(__hsub2(e, o)) ^ 0x80000000u;
          v[2 * jj + h] = mk(as_b2(__byte_perm(s, d, 0x5410)), as_b2(__byte_perm(s, d, 0x7632)));
        }
      }
      if (t == 0) PROF(2, 12);
      columns(v, sb, t);
      if (t == 0) PROF(2, 14);
      const int pre = (k == 112) ? 1 : 2 * k, pim = (k == 112) ? 1 : 2 * k + 1;
      const uint32_t pr = sb + OFF_EXCH + (t >> 5) * 256 + ((((lane >> 2) ^ pre) & 7) << 4) + (lane & 3) * 4;
      const uint32_t pi = sb + OFF_EXCH + 8192 + (t >> 5) * 256 + ((((lane >> 2) ^ pim) & 7) << 4) + (lane & 3) * 4;
      bar_sync<3, 128>();
#pragma unroll
      for (int jj = 0; jj < 8; jj++) {
        const b2 ar = as_b2(__byte_perm(as_u(v[2 * jj].y), as_u(v[2 * jj + 1].y), 0x5410)), br = as_b2(__byte_perm(as_u(v[2 * jj].y), as_u(v[2 * jj + 1].y), 0x7632));
        const b2 ai = as_b2(__byte_perm(as_u(v[2 * jj].x), as_u(v[2 * jj + 1].x), 0x5410)), bi = as_b2(__byte_perm(as_u(v[2 * jj].x), as_u(v[2 * jj + 1].x), 0x7632));
        sts32(pr + jj * 1024, as_u(__hadd2(ar, br)));
        sts32(pr + jj * 1024 + 128, as_u(k == 112 ? __hadd2(ai, bi) : __hsub2(ar, br)));
        sts32(pi + jj * 1024 + 128, as_u(__hadd2(ai, bi)));
        sts32(pi + jj * 1024, as_u(__hsub2(ai, bi)));
      }
      fence_async_smem();
      bar_sync<3, 128>();
      if (t == 0) {
        PROF(2, 5);
        tma_store(&tm_s, pre * 64, 0, sb + OFF_EXCH);
        if (k != 0 && k != 112) tma_store(&tm_s, pim * 64, 0, sb + OFF_EXCH + 8192);
        bulk_done();
      }
    }
    if (t == 0) { red_relaxed(&g_cnt[5 * 32]); PROF(2, 7); }
    __syncwarp();
    asm volatile("barrier.cluster.wait.aligned;" ::: "memory");
  } else {
    asm volatile("setmaxnreg.dec.sync.aligned.u32 24;");
    auto wd_tile = [&](int b, uint32_t dst, uint32_t fb) {
#pragma unroll
      for (int hf = 0; hf < 2; hf++) {
        const int js = kh * 4 + (b < 12 ? (b & 3) : (b & 1) * 2 + hf);
        const int row = 224 * js + (b < 12 ? (js & 1) * 32 + (b >> 2) * 64 + hf * 32 : 192 - hf * 192);
        tma3d(dst + hf * 4096, &tm_d, 0, n, row, fb);
        tma3d(dst + 8192 + hf * 4096, &tm_d, 64, n, row, fb);
      }
    };
    if (warp == 12) {
      if (elect()) {
        mbar_init(bars + B_XFULL * 8, 1); mbar_init(bars + (B_XFULL + 1) * 8, 1);
        fence_async_smem();
#pragma unroll
        for (int w = 0; w < 2; w++) {
          mbar_expect(bars + (B_XFULL + w) * 8, HALF_XR);
          tma3d(sb + OFF_PQ + w * HALF_XR, &tm_x, 0, m * 128 + (w ^ kh ^ 1) * 64, 0, bars + (B_XFULL + w) * 8);
        }
        PROF(3, 3);
#pragma unroll
        for (int i = 0; i < NSLOT; i++) mbar_init(bars + (B_FULL + i) * 8, 1);
        mbar_init(bars + B_PIN * 8, 1);
        fence_async_smem();
      }
      bar_arrive<0, NTHREADS - 64>();
#pragma unroll 1
      for (int i = 0; i < 6; i++) {
        if (elect()) {
          const uint32_t fb = bars + (B_FULL + i) * 8;
          mbar_expect(fb, SLOT);
          tma2d(sb + i * SLOT, &tm_g, c64, i * 64, fb);
          tma2d(sb + i * SLOT + 8192, &tm_u, c64, i * 64, fb);
          PROF(3, 4 + i);
        }
      }
      if (elect()) {
        prefetch_l2(reinterpret_cast<const unsigned char*>(w_r) + bid * 7200, 7200);
        prefetch_l2(reinterpret_cast<const unsigned char*>(w_i) + bid * 7200, 7200);
        prefetch_tma2d(&tm_g, c64, 384); prefetch_tma2d(&tm_u, c64, 384);
      }
    } else if (warp == 14) {
      if (elect()) {
#pragma unroll
        for (int i = B_EMPTY; i < B_END; i++)
          if (i < B_XFULL || i >= B_XFREE) mbar_init(bars + i * 8, i >= B_PQFULL ? 1 : (i == B_XFREE ? 4 : (i == B_PUBW ? 5 : 8)));
        asm volatile("fence.mbarrier_init.release.cluster;" ::: "memory");
        fence_async_smem();
        mbar_expect(bars + B_RECV * 8, 64 * 112 * 4);
      }
      bar_arrive<0, NTHREADS - 64>();
    }
    const uint32_t epoch = ld_relaxed(&g_ep[bid]);
    if (warp == 13 && lane == 0) { PROFG(4, 0); PROF(4, 1); }
    bar_sync<1, 128>();
    asm volatile("barrier.cluster.arrive.relaxed.aligned;" ::: "memory");
    if (warp == 12) {
      int slot = 6, ph = 1;
      auto wait_slot = [&]() { mbar_wait(bars + (B_EMPTY + slot) * 8, ph ^ (slot == 6)); };
      auto adv = [&]() { if (++slot == NSLOT) { slot = 0; ph ^= 1; } };
      const int c32 = 224 * j + ((j & 1) ? 0 : 192);
#pragma unroll 1
      for (int i = 6; i < 25; i++) {
        wait_slot();
        if (elect()) {
          const uint32_t dst = sb + slot * SLOT, fb = bars + (B_FULL + slot) * 8;
          const bool last = i >= 21;
          const int cc = last ? c32 : c64 + 64 * (i / 7), rr = last ? slot * 128 : slot * 64;
          mbar_expect(fb, SLOT);
          tma2d(dst, last ? &tm_g32 : &tm_g, cc, rr, fb);
          tma2d(dst + 8192, last ? &tm_u32 : &tm_u, cc, rr, fb);
        }
        adv();
      }
      if (lane == 0) PROF(3, 0);
#pragma unroll 1
      for (int i = 3; i < 16; i++) {
        if (lane == 0) PROF(3, 16 + i);
        if (i == 14) mbar_wait(bars + B_PREP * 8, 0);
        wait_slot();
        if (elect()) {
          const uint32_t fb = bars + (B_FULL + slot) * 8;
          mbar_expect(fb, i < 14 ? SLOT : G_IMG / 2);
          if (i < 14) wd_tile(i, sb + slot * SLOT, fb);
          else bulk_g2s(sb + slot * SLOT, g_G + (size_t)(n * 4 + i - 12) * (G_IMG / 2), G_IMG / 2, fb);
        }
        adv();
      }
      if (lane == 0) PROF(3, 2);
    } else if (warp == 13) {
      mbar_wait(bars + B_PUBX * 8, 0);
      if (elect()) {
        PROF(4, 8);
#pragma unroll
        for (int w = 0; w < 2; w++) tma_store(&tm_s, ((m * 2 + (w ^ kh ^ 1)) * 2 + (j & 1)) * 64, 192 + (j >> 1) * 64, sb + OFF_EXCH + w * 8192);
        bulk_done();
        red_relaxed(&g_cnt[(j >> 1) * 32]);
        mbar_arrive(bars + B_XDONE * 8);
        PROF(4, 12);
      }
      mbar_wait(bars + B_PUBW * 8, 0);
      if (elect()) {
        PROF(4, 9);
        tma_store(&tm_s, bid * 64, 64, sb + OFF_R);
        tma_store(&tm_s, bid * 64, 128, sb + OFF_R + 8192);
        bulk_done();
        red_relaxed(&g_cnt[4 * 32]);
        mbar_arrive(bars + B_WDONE * 8);
        PROF(4, 13);
      }
      mbar_wait(bars + B_PREP * 8, 0);
      mbar_wait(bars + B_LFREE * 8, 0);
      if (elect()) {
        mbar_expect(bars + B_GFULL * 8, G_IMG);
        bulk_g2s(sb + OFF_R + 28672, g_G + (size_t)(n * 2) * G_IMG, G_IMG, bars + B_GFULL * 8);
      }
    } else if (warp == 14) {
      mbar_wait(bars + (B_XFREE + 1) * 8, 0);
      asm volatile("fence.acq_rel.gpu;" ::: "memory");
      if (lane == 0) { mbar_arrive(bars + B_PUBW * 8); PROF(5, 3); }
      mbar_wait(bars + B_WDONE * 8, 0);
      wait_ge(&g_cnt[4 * 32], (epoch + 1) * 128);
      fence_async_global();
      if (elect()) {
        mbar_arrive(bars + B_PREP * 8);
        if (bid < 113) {
          mbar_expect(bars + B_WFULL * 8, 16384);
          bulk_g2s(sb + OFF_WS, g_X + (64 + bid) * XP, 16384, bars + B_WFULL * 8);
        }
        PROF(5, 17);
      }
    } else {
      mbar_wait(bars + B_XFREE * 8, 0);
      if (elect()) {
        mbar_expect(bars + B_PIN * 8, 14400);
        bulk_g2s(sb + OFF_WS, reinterpret_cast<const unsigned char*>(w_r) + bid * 7200, 7200, bars + B_PIN * 8);
        bulk_g2s(sb + OFF_WS + 7200, reinterpret_cast<const unsigned char*>(w_i) + bid * 7200, 7200, bars + B_PIN * 8);
        prefetch_l2(reinterpret_cast<const unsigned char*>(w_gate) + bid * 12544, 12544);
        prefetch_l2(reinterpret_cast<const unsigned char*>(w_up) + bid * 12544, 12544);
        PROF(5, 2);
      }
      if (bid < 113) {
        const int sl = (bid == 112) ? 0 : bid;
        wait_ge(&g_cnt[((sl & 1) + 2 * ((sl >> 1) / 28)) * 32], (epoch + 1) * 32);
        if (elect()) { PROF(5, 16); mbar_arrive(bars + B_XCFULL * 8); }
      }
      mbar_wait(bars + B_PUBW * 8, 0);
      if (elect()) prefetch_l2(reinterpret_cast<const unsigned char*>(w_down) + bid * 12544, 12544);
      mbar_wait(bars + B_WDONE * 8, 0);
      if (elect()) mbar_expect(bars + B_RFULL * 8, 3 * SLOT);
#pragma unroll 1
      for (int i = 0; i < 3; i++) {
        mbar_wait(bars + (B_FULL + (i == 1 ? 0 : 3)) * 8, i == 0);
        if (elect()) wd_tile(i, sb + OFF_R + i * SLOT, bars + B_RFULL * 8);
      }
      if (lane == 0) PROF(5, 19);
      mbar_wait(bars + B_PREP * 8, 0);
      wait_ge(&g_cnt[5 * 32], (epoch + 1) * 128);
      fence_async_global();
      if (elect()) {
        PROF(5, 18);
        const unsigned char* src = g_X + (m * 2 + kh) * HALF_XR;
#pragma unroll
        for (int i = 0; i < 4; i++) {
          mbar_expect(bars + (B_PQFULL + i) * 8, i ? 14336 : 14336 + 256);
          bulk_g2s(sb + OFF_PQ + i * 14336, src + i * 14336, 14336, bars + (B_PQFULL + i) * 8);
        }
        bulk_g2s(sb + OFF_G, g_gate + m * 128 + kh * 64, 256, bars + B_PQFULL * 8);
      }
    }
    __syncwarp();
    asm volatile("barrier.cluster.wait.aligned;" ::: "memory");
  }
}

#define DPROM CU_TENSOR_MAP_L2_PROMOTION_NONE
typedef CUresult (*EncodeFn)(CUtensorMap*, CUtensorMapDataType, cuuint32_t, void*, const cuuint64_t*, const cuuint64_t*, const cuuint32_t*,
                             const cuuint32_t*, CUtensorMapInterleave, CUtensorMapSwizzle, CUtensorMapL2promotion, CUtensorMapFloatOOBfill);

void make_map(EncodeFn enc, CUtensorMap* tm, const void* base, int cols, int rows, int bc, int br, CUtensorMapSwizzle sw) {
  cuuint64_t gd[2] = {(cuuint64_t)cols, (cuuint64_t)rows};
  cuuint64_t gs[1] = {(cuuint64_t)cols * 2};
  cuuint32_t bd[2] = {(cuuint32_t)bc, (cuuint32_t)br};
  cuuint32_t es[2] = {1, 1};
  enc(tm, CU_TENSOR_MAP_DATA_TYPE_BFLOAT16, 2, const_cast<void*>(base), gd, gs, bd, es, CU_TENSOR_MAP_INTERLEAVE_NONE, sw,
      CU_TENSOR_MAP_L2_PROMOTION_L2_128B, CU_TENSOR_MAP_FLOAT_OOB_FILL_NONE);
}

}

extern "C" void kernel_launch(void* const* d_in, const int* in_sizes, int n_in, void* d_out, int out_size) {
  (void)in_sizes; (void)n_in; (void)out_size;
  const __nv_bfloat16* x = (const __nv_bfloat16*)d_in[0];
  const __nv_bfloat16* w_r = (const __nv_bfloat16*)d_in[1];
  const __nv_bfloat16* w_i = (const __nv_bfloat16*)d_in[2];
  const __nv_bfloat16* w_gate = (const __nv_bfloat16*)d_in[4];
  const __nv_bfloat16* w_up = (const __nv_bfloat16*)d_in[5];
  const __nv_bfloat16* w_down = (const __nv_bfloat16*)d_in[6];
  const __nv_bfloat16* gate_w = (const __nv_bfloat16*)d_in[7];
  static EncodeFn enc = nullptr;
  static void* xbuf = nullptr;
  static bool ok = false;
  if (!enc) {
    cudaDriverEntryPointQueryResult qr;
    cudaGetDriverEntryPoint("cuTensorMapEncodeTiled", (void**)&enc, cudaEnableDefault, &qr);
    cudaFuncSetAttribute(fused_kernel, cudaFuncAttributeMaxDynamicSharedMemorySize, SMEM_BYTES);
    cudaGetSymbolAddress(&xbuf, g_X);
    cudaFuncAttributes fa;
    cudaFuncGetAttributes(&fa, fused_kernel);
    ok = (fa.numRegs == 128);
  }
  if (!ok) return;
  CUtensorMap tx, tg, tu, tg32, tu32, td, ts;
  {
    cuuint64_t gd[3] = {64, (cuuint64_t)S_, 7};
    cuuint64_t gs[2] = {(cuuint64_t)D_ * 2, 128};
    cuuint32_t bd[3] = {64, 64, 7};
    cuuint32_t es[3] = {1, 1, 1};
    enc(&tx, CU_TENSOR_MAP_DATA_TYPE_BFLOAT16, 3, const_cast<__nv_bfloat16*>(x), gd, gs, bd, es, CU_TENSOR_MAP_INTERLEAVE_NONE, CU_TENSOR_MAP_SWIZZLE_128B,
        CU_TENSOR_MAP_L2_PROMOTION_L2_128B, CU_TENSOR_MAP_FLOAT_OOB_FILL_NONE);
  }
  make_map(enc, &tg, w_gate, F_, D_, 64, 64, CU_TENSOR_MAP_SWIZZLE_128B);
  make_map(enc, &tu, w_up, F_, D_, 64, 64, CU_TENSOR_MAP_SWIZZLE_128B);
  make_map(enc, &tg32, w_gate, F_, D_, 32, 128, CU_TENSOR_MAP_SWIZZLE_64B);
  make_map(enc, &tu32, w_up, F_, D_, 32, 128, CU_TENSOR_MAP_SWIZZLE_64B);
  {
    cuuint64_t gd[3] = {112, 4, (cuuint64_t)F_};
    cuuint64_t gs[2] = {224, (cuuint64_t)D_ * 2};
    cuuint32_t bd[3] = {64, 1, 32};
    cuuint32_t es[3] = {1, 1, 1};
    enc(&td, CU_TENSOR_MAP_DATA_TYPE_BFLOAT16, 3, const_cast<__nv_bfloat16*>(w_down), gd, gs, bd, es, CU_TENSOR_MAP_INTERLEAVE_NONE, CU_TENSOR_MAP_SWIZZLE_128B,
        DPROM, CU_TENSOR_MAP_FLOAT_OOB_FILL_NONE);
  }
  make_map(enc, &ts, (const __nv_bfloat16*)xbuf, XP / 2, 448, 64, 64, CU_TENSOR_MAP_SWIZZLE_NONE);
  fused_kernel<<<128, NTHREADS, SMEM_BYTES>>>(tx, tg, tu, tg32, tu32, td, ts, w_r, w_i, w_gate, w_up, w_down, gate_w, (__nv_bfloat16*)d_out);
}
```

```cpp
#include <cuda_runtime.h>
#include <cuda_bf16.h>
#include <cuda.h>
#include <stdint.h>

namespace {

constexpr int S_ = 2048, D_ = 448, F_ = 1792;
constexpr int NTHREADS = 512;
constexpr int SLOT = 16384, NSLOT = 7;
constexpr int HALF_XR = 57344;
constexpr int OFF_PQ = NSLOT * SLOT;
constexpr int OFF_R = OFF_PQ + HALF_XR;
constexpr int OFF_EXCH = OFF_PQ;
constexpr int OFF_WS = OFF_EXCH + 18432;
constexpr int OFF_TW = OFF_WS + 16384;
constexpr int OFF_MISC = OFF_R + HALF_XR;
constexpr int OFF_G = OFF_MISC;
constexpr int OFF_BAR = OFF_MISC + 512;
constexpr int SMEM_BYTES = OFF_BAR + 512;
constexpr int B_FULL = 0, B_EMPTY = 7, B_XFULL = 14  ;
constexpr int B_XFREE = 16  , B_PUBX = 18, B_RFREE = 19, B_LFREE = 20;
constexpr int B_PUBW = 21;
constexpr int B_PQFULL = 22  , B_RECV = 26, B_WFULL = 27, B_XCFULL = 28, B_PREP = 29, B_RFULL = 30, B_GFULL = 31, B_XDONE = 32, B_WDONE = 33, B_SEEN = 34, B_END = 35, B_PIN = 35;

constexpr int G_IMG = 224 * 56 * 2;

__device__ __align__(1024) unsigned char g_H[32 * 56 * 4096];
constexpr int XP = 28672;
__device__ __align__(1024) unsigned char g_X[448 * XP];
__device__ __align__(1024) unsigned char g_G[8 * G_IMG];
__device__ __align__(1024) float g_gate[S_];
__device__ __align__(128) unsigned int g_ep[128];
__device__ __align__(128) unsigned int g_cnt[8 * 32];

#define POLL ld_relaxed
#define PROF(role, idx) do {} while (0)
#define PROFG(role, idx) do {} while (0)

__device__ __forceinline__ uint32_t s2u(const void* p) { return (uint32_t)__cvta_generic_to_shared(p); }
__device__ __forceinline__ void mbar_init(uint32_t b, int c) { asm volatile("mbarrier.init.shared::cta.b64 [%0], %1;" :: "r"(b), "r"(c) : "memory"); }
__device__ __forceinline__ void mbar_expect(uint32_t b, int bytes) { asm volatile("mbarrier.arrive.expect_tx.shared::cta.b64 _, [%0], %1;" :: "r"(b), "r"(bytes) : "memory"); }
__device__ __forceinline__ void mbar_arrive(uint32_t b) { asm volatile("mbarrier.arrive.shared::cta.b64 _, [%0];" :: "r"(b) : "memory"); }
__device__ __forceinline__ void mbar_wait(uint32_t b, int ph) {
  asm volatile("{\n.reg .pred p;\n.reg .u32 c;\nmov.u32 c, 0;\nL_WAIT:\nmbarrier.try_wait.parity.shared::cta.b64 p, [%0], %1;\n@p bra.uni L_DONE;\n"
               "add.u32 c, c, 1;\nsetp.lt.u32 p, c, 4194304;\n@p bra.uni L_WAIT;\ntrap;\nL_DONE:\n}" :: "r"(b), "r"(ph) : "memory");
}
__device__ __forceinline__ void mbar_wait_cluster(uint32_t b, int ph) {
  asm volatile("{\n.reg .pred p;\n.reg .u32 c;\nmov.u32 c, 0;\nL_WAIT:\nmbarrier.try_wait.parity.acquire.cluster.shared::cta.b64 p, [%0], %1;\n@p bra.uni L_DONE;\n"
               "add.u32 c, c, 1;\nsetp.lt.u32 p, c, 4194304;\n@p bra.uni L_WAIT;\ntrap;\nL_DONE:\n}" :: "r"(b), "r"(ph) : "memory");
}
__device__ __forceinline__ uint32_t ld_acquire(const unsigned int* p) { uint32_t v; asm volatile("ld.acquire.gpu.global.u32 %0, [%1];" : "=r"(v) : "l"(p) : "memory"); return v; }
__device__ __forceinline__ uint32_t ld_relaxed(const unsigned int* p) { uint32_t v; asm volatile("ld.relaxed.gpu.global.u32 %0, [%1];" : "=r"(v) : "l"(p) : "memory"); return v; }
__device__ __forceinline__ void wait_ge(const unsigned int* p, uint32_t target) {
#pragma unroll 1
  for (int i = 0; i < (1 << 22); i++) { if ((int)(POLL(p) - target) >= 0) return; }
  __trap();
}
__device__ __forceinline__ void red_relaxed(unsigned int* p) { asm volatile("red.relaxed.gpu.global.add.u32 [%0], 1;" :: "l"(p) : "memory"); }
__device__ __forceinline__ bool elect() { uint32_t p; asm volatile("{\n.reg .pred p;\nelect.sync _|p, 0xffffffff;\nselp.u32 %0, 1, 0, p;\n}" : "=r"(p)); return p; }
__device__ __forceinline__ void fence_async_smem() { asm volatile("fence.proxy.async.shared::cta;" ::: "memory"); }
__device__ __forceinline__ void fence_async_global() { asm volatile("fence.proxy.async.global;" ::: "memory"); }
template <int ID, int N> __device__ __forceinline__ void bar_sync() { asm volatile("bar.sync %0, %1;" :: "n"(ID), "n"(N) : "memory"); }
template <int ID, int N> __device__ __forceinline__ void bar_arrive() { asm volatile("bar.arrive %0, %1;" :: "n"(ID), "n"(N) : "memory"); }
__device__ __forceinline__ void tma2d(uint32_t dst, const CUtensorMap* tm, int c0, int c1, uint32_t bar) {
  asm volatile("cp.async.bulk.tensor.2d.shared::cluster.global.mbarrier::complete_tx::bytes [%0], [%1, {%3, %4}], [%2];"
               :: "r"(dst), "l"(tm), "r"(bar), "r"(c0), "r"(c1) : "memory");
}
__device__ __forceinline__ void tma3d(uint32_t dst, const CUtensorMap* tm, int c0, int c1, int c2, uint32_t bar) {
  asm volatile("cp.async.bulk.tensor.3d.shared::cluster.global.mbarrier::complete_tx::bytes [%0], [%1, {%3, %4, %5}], [%2];"
               :: "r"(dst), "l"(tm), "r"(bar), "r"(c0), "r"(c1), "r"(c2) : "memory");
}
__device__ __forceinline__ void bulk_g2s(uint32_t dst, const void* src, int bytes, uint32_t bar) {
  asm volatile("cp.async.bulk.shared::cluster.global.mbarrier::complete_tx::bytes [%0], [%1], %2, [%3];"
               :: "r"(dst), "l"(src), "r"(bytes), "r"(bar) : "memory");
}
__device__ __forceinline__ void tma_store(const CUtensorMap* tm, int c0, int c1, uint32_t src) {
  asm volatile("cp.async.bulk.tensor.2d.global.shared::cta.bulk_group [%0, {%1, %2}], [%3];" :: "l"(tm), "r"(c0), "r"(c1), "r"(src) : "memory");
}
__device__ __forceinline__ void bulk_done() { asm volatile("cp.async.bulk.commit_group;\ncp.async.bulk.wait_group 0;\nfence.proxy.async.global;" ::: "memory"); }
__device__ __forceinline__ void sts32(uint32_t a, uint32_t x) { asm volatile("st.shared.b32 [%0], %1;" :: "r"(a), "r"(x) : "memory"); }
__device__ __forceinline__ void prefetch_l2(const void* src, int bytes) {
  asm volatile("cp.async.bulk.prefetch.L2.global [%0], %1;" :: "l"(src), "r"(bytes) : "memory");
}
__device__ __forceinline__ void prefetch_tma2d(const CUtensorMap* tm, int c0, int c1) {
  asm volatile("cp.async.bulk.prefetch.tensor.2d.L2.global [%0, {%1, %2}];" :: "l"(tm), "r"(c0), "r"(c1) : "memory");
}
__device__ __forceinline__ uint64_t mkdesc(uint32_t addr, uint32_t lbo, uint32_t sbo, uint32_t mode) {
  return (uint64_t)((addr & 0x3FFFF) >> 4) | ((uint64_t)(lbo >> 4) << 16) | ((uint64_t)(sbo >> 4) << 32) | ((uint64_t)mode << 62);
}
__device__ __forceinline__ void wg_fence() { asm volatile("wgmma.fence.sync.aligned;" ::: "memory"); }
__device__ __forceinline__ void wg_commit() { asm volatile("wgmma.commit_group.sync.aligned;" ::: "memory"); }
template <int N> __device__ __forceinline__ void wg_wait() { asm volatile("wgmma.wait_group.sync.aligned %0;" :: "n"(N) : "memory"); }
template <int N> __device__ __forceinline__ void keep(float (&d)[N]) {
#pragma unroll
  for (int i = 0; i < N; i++) asm volatile("" : "+f"(d[i]) :: "memory");
}
__device__ __forceinline__ uint32_t pack_bf16(float lo, float hi) { uint32_t r; asm("cvt.rn.bf16x2.f32 %0, %1, %2;" : "=r"(r) : "f"(hi), "f"(lo)); return r; }
__device__ __forceinline__ float bf16_round(float v) { return __bfloat162float(__float2bfloat16_rn(v)); }
__device__ __forceinline__ void sts128(uint32_t a, uint32_t x, uint32_t y, uint32_t z, uint32_t w) { asm volatile("st.shared.v4.b32 [%0], {%1,%2,%3,%4};" :: "r"(a), "r"(x), "r"(y), "r"(z), "r"(w) : "memory"); }
__device__ __forceinline__ float4 lds128f(uint32_t a) { float4 v; asm volatile("ld.shared.v4.f32 {%0,%1,%2,%3}, [%4];" : "=f"(v.x), "=f"(v.y), "=f"(v.z), "=f"(v.w) : "r"(a) : "memory"); return v; }

__device__ __forceinline__ uint2 lds64(uint32_t a) { uint2 v; asm volatile("ld.shared.v2.b32 {%0,%1}, [%2];" : "=r"(v.x), "=r"(v.y) : "r"(a) : "memory"); return v; }
__device__ __forceinline__ float bf_lo(uint32_t w) { return __uint_as_float(w << 16); }
__device__ __forceinline__ float bf_hi(uint32_t w) { return __uint_as_float(w & 0xffff0000u); }
__device__ __forceinline__ uint32_t opaque(uint32_t v) { asm volatile("" : "+r"(v)); return v; }
__device__ __forceinline__ uint4 ldg128(const void* p) { uint4 v; asm volatile("ld.global.nc.v4.b32 {%0,%1,%2,%3}, [%4];" : "=r"(v.x), "=r"(v.y), "=r"(v.z), "=r"(v.w) : "l"(p)); return v; }
__device__ __forceinline__ void stg128(void* p, uint32_t x, uint32_t y, uint32_t z, uint32_t w) { asm volatile("st.global.v4.b32 [%0], {%1,%2,%3,%4};" :: "l"(p), "r"(x), "r"(y), "r"(z), "r"(w) : "memory"); }
__device__ __forceinline__ void stg128_l2(void* p, uint32_t x, uint32_t y, uint32_t z, uint32_t w) { asm volatile("st.relaxed.gpu.global.v4.b32 [%0], {%1,%2,%3,%4};" :: "l"(p), "r"(x), "r"(y), "r"(z), "r"(w) : "memory"); }
__device__ __forceinline__ uint2 ldg64_l2(const void* p) { uint2 v; asm volatile("ld.relaxed.gpu.global.v2.b32 {%0,%1}, [%2];" : "=r"(v.x), "=r"(v.y) : "l"(p) : "memory"); return v; }
__device__ __forceinline__ void ldg128_l2(uint32_t (&v)[4], const void* p) { asm volatile("ld.relaxed.gpu.global.v4.b32 {%0,%1,%2,%3}, [%4];" : "=r"(v[0]), "=r"(v[1]), "=r"(v[2]), "=r"(v[3]) : "l"(p) : "memory"); }
__device__ __forceinline__ uint4 lds128(uint32_t a) { uint4 v; asm volatile("ld.shared.v4.b32 {%0,%1,%2,%3}, [%4];" : "=r"(v.x), "=r"(v.y), "=r"(v.z), "=r"(v.w) : "r"(a) : "memory"); return v; }
__device__ __forceinline__ uint32_t lds16(uint32_t a) { uint32_t v; asm volatile("ld.shared.u16 %0, [%1];" : "=r"(v) : "r"(a) : "memory"); return v; }
__device__ __forceinline__ void sts64(uint32_t a, uint32_t x, uint32_t y) { asm volatile("st.shared.v2.b32 [%0], {%1,%2};" :: "r"(a), "r"(x), "r"(y) : "memory"); }
template <int TB> __device__ __forceinline__ void wgmma_rs_128(float (&d)[64], const uint32_t (&a)[4], uint64_t db, int sc) {
  asm volatile("{\n.reg .pred p;\nsetp.ne.b32 p, %69, 0;\n"
    "wgmma.mma_async.sync.aligned.m64n128k16.f32.bf16.bf16 {%0, %1, %2, %3, %4, %5, %6, %7, %8, %9, %10, %11, %12, %13, %14, %15, %16, %17, %18, %19, %20, %21, %22, %23, %24, %25, %26, %27, %28, %29, %30, %31, %32, %33, %34, %35, %36, %37, %38, %39, %40, %41, %42, %43, %44, %45, %46, %47, %48, %49, %50, %51, %52, %53, %54, %55, %56, %57, %58, %59, %60, %61, %62, %63}, {%64, %65, %66, %67}, %68, p, 1, 1, %70;\n}\n"
    : "+f"(d[0]), "+f"(d[1]), "+f"(d[2]), "+f"(d[3]), "+f"(d[4]), "+f"(d[5]), "+f"(d[6]), "+f"(d[7]), "+f"(d[8]), "+f"(d[9]), "+f"(d[10]), "+f"(d[11]), "+f"(d[12]), "+f"(d[13]), "+f"(d[14]), "+f"(d[15]), "+f"(d[16]), "+f"(d[17]), "+f"(d[18]), "+f"(d[19]), "+f"(d[20]), "+f"(d[21]), "+f"(d[22]), "+f"(d[23]), "+f"(d[24]), "+f"(d[25]), "+f"(d[26]), "+f"(d[27]), "+f"(d[28]), "+f"(d[29]), "+f"(d[30]), "+f"(d[31]), "+f"(d[32]), "+f"(d[33]), "+f"(d[34]), "+f"(d[35]), "+f"(d[36]), "+f"(d[37]), "+f"(d[38]), "+f"(d[39]), "+f"(d[40]), "+f"(d[41]), "+f"(d[42]), "+f"(d[43]), "+f"(d[44]), "+f"(d[45]), "+f"(d[46]), "+f"(d[47]), "+f"(d[48]), "+f"(d[49]), "+f"(d[50]), "+f"(d[51]), "+f"(d[52]), "+f"(d[53]), "+f"(d[54]), "+f"(d[55]), "+f"(d[56]), "+f"(d[57]), "+f"(d[58]), "+f"(d[59]), "+f"(d[60]), "+f"(d[61]), "+f"(d[62]), "+f"(d[63])
    : "r"(a[0]), "r"(a[1]), "r"(a[2]), "r"(a[3]), "l"(db), "r"(sc), "n"(TB));
}
template <int TB> __device__ __forceinline__ void wgmma_rs_64(float (&d)[32], const uint32_t (&a)[4], uint64_t db, int sc) {
  asm volatile("{\n.reg .pred p;\nsetp.ne.b32 p, %37, 0;\n"
    "wgmma.mma_async.sync.aligned.m64n64k16.f32.bf16.bf16 {%0, %1, %2, %3, %4, %5, %6, %7, %8, %9, %10, %11, %12, %13, %14, %15, %16, %17, %18, %19, %20, %21, %22, %23, %24, %25, %26, %27, %28, %29, %30, %31}, {%32, %33, %34, %35}, %36, p, 1, 1, %38;\n}\n"
    : "+f"(d[0]), "+f"(d[1]), "+f"(d[2]), "+f"(d[3]), "+f"(d[4]), "+f"(d[5]), "+f"(d[6]), "+f"(d[7]), "+f"(d[8]), "+f"(d[9]), "+f"(d[10]), "+f"(d[11]), "+f"(d[12]), "+f"(d[13]), "+f"(d[14]), "+f"(d[15]), "+f"(d[16]), "+f"(d[17]), "+f"(d[18]), "+f"(d[19]), "+f"(d[20]), "+f"(d[21]), "+f"(d[22]), "+f"(d[23]), "+f"(d[24]), "+f"(d[25]), "+f"(d[26]), "+f"(d[27]), "+f"(d[28]), "+f"(d[29]), "+f"(d[30]), "+f"(d[31])
    : "r"(a[0]), "r"(a[1]), "r"(a[2]), "r"(a[3]), "l"(db), "r"(sc), "n"(TB));
}
template <int TB> __device__ __forceinline__ void wgmma_rs_56(float (&d)[28], const uint32_t (&a)[4], uint64_t db, int sc) {
  asm volatile("{\n.reg .pred p;\nsetp.ne.b32 p, %33, 0;\n"
    "wgmma.mma_async.sync.aligned.m64n56k16.f32.bf16.bf16 {%0, %1, %2, %3, %4, %5, %6, %7, %8, %9, %10, %11, %12, %13, %14, %15, %16, %17, %18, %19, %20, %21, %22, %23, %24, %25, %26, %27}, {%28, %29, %30, %31}, %32, p, 1, 1, %34;\n}\n"
    : "+f"(d[0]), "+f"(d[1]), "+f"(d[2]), "+f"(d[3]), "+f"(d[4]), "+f"(d[5]), "+f"(d[6]), "+f"(d[7]), "+f"(d[8]), "+f"(d[9]), "+f"(d[10]), "+f"(d[11]), "+f"(d[12]), "+f"(d[13]), "+f"(d[14]), "+f"(d[15]), "+f"(d[16]), "+f"(d[17]), "+f"(d[18]), "+f"(d[19]), "+f"(d[20]), "+f"(d[21]), "+f"(d[22]), "+f"(d[23]), "+f"(d[24]), "+f"(d[25]), "+f"(d[26]), "+f"(d[27])
    : "r"(a[0]), "r"(a[1]), "r"(a[2]), "r"(a[3]), "l"(db), "r"(sc), "n"(TB));
}
template <int TB> __device__ __forceinline__ void wgmma_rs_112(float (&d)[56], const uint32_t (&a)[4], uint64_t db, int sc) {
  asm volatile("{\n.reg .pred p;\nsetp.ne.b32 p, %61, 0;\n"
    "wgmma.mma_async.sync.aligned.m64n112k16.f32.bf16.bf16 {%0, %1, %2, %3, %4, %5, %6, %7, %8, %9, %10, %11, %12, %13, %14, %15, %16, %17, %18, %19, %20, %21, %22, %23, %24, %25, %26, %27, %28, %29, %30, %31, %32, %33, %34, %35, %36, %37, %38, %39, %40, %41, %42, %43, %44, %45, %46, %47, %48, %49, %50, %51, %52, %53, %54, %55}, {%56, %57, %58, %59}, %60, p, 1, 1, %62;\n}\n"
    : "+f"(d[0]), "+f"(d[1]), "+f"(d[2]), "+f"(d[3]), "+f"(d[4]), "+f"(d[5]), "+f"(d[6]), "+f"(d[7]), "+f"(d[8]), "+f"(d[9]), "+f"(d[10]), "+f"(d[11]), "+f"(d[12]), "+f"(d[13]), "+f"(d[14]), "+f"(d[15]), "+f"(d[16]), "+f"(d[17]), "+f"(d[18]), "+f"(d[19]), "+f"(d[20]), "+f"(d[21]), "+f"(d[22]), "+f"(d[23]), "+f"(d[24]), "+f"(d[25]), "+f"(d[26]), "+f"(d[27]), "+f"(d[28]), "+f"(d[29]), "+f"(d[30]), "+f"(d[31]), "+f"(d[32]), "+f"(d[33]), "+f"(d[34]), "+f"(d[35]), "+f"(d[36]), "+f"(d[37]), "+f"(d[38]), "+f"(d[39]), "+f"(d[40]), "+f"(d[41]), "+f"(d[42]), "+f"(d[43]), "+f"(d[44]), "+f"(d[45]), "+f"(d[46]), "+f"(d[47]), "+f"(d[48]), "+f"(d[49]), "+f"(d[50]), "+f"(d[51]), "+f"(d[52]), "+f"(d[53]), "+f"(d[54]), "+f"(d[55])
    : "r"(a[0]), "r"(a[1]), "r"(a[2]), "r"(a[3]), "l"(db), "r"(sc), "n"(TB));
}
template <int TA, int TB> __device__ __forceinline__ void wgmma_ss_56(float (&d)[28], uint64_t da, uint64_t db, int sc) {
  asm volatile("{\n.reg .pred p;\nsetp.ne.b32 p, %30, 0;\n"
    "wgmma.mma_async.sync.aligned.m64n56k16.f32.bf16.bf16 {%0, %1, %2, %3, %4, %5, %6, %7, %8, %9, %10, %11, %12, %13, %14, %15, %16, %17, %18, %19, %20, %21, %22, %23, %24, %25, %26, %27}, %28, %29, p, 1, 1, %31, %32;\n}\n"
    : "+f"(d[0]), "+f"(d[1]), "+f"(d[2]), "+f"(d[3]), "+f"(d[4]), "+f"(d[5]), "+f"(d[6]), "+f"(d[7]), "+f"(d[8]), "+f"(d[9]), "+f"(d[10]), "+f"(d[11]), "+f"(d[12]), "+f"(d[13]), "+f"(d[14]), "+f"(d[15]), "+f"(d[16]), "+f"(d[17]), "+f"(d[18]), "+f"(d[19]), "+f"(d[20]), "+f"(d[21]), "+f"(d[22]), "+f"(d[23]), "+f"(d[24]), "+f"(d[25]), "+f"(d[26]), "+f"(d[27])
    : "l"(da), "l"(db), "r"(sc), "n"(TA), "n"(TB));
}

__device__ __forceinline__ uint32_t cis(float a) { return pack_bf16(__cosf(a), __sinf(a)); }

typedef __nv_bfloat162 b2;
struct c2 { b2 x, y; };
__device__ __forceinline__ b2 as_b2(uint32_t u) { return *reinterpret_cast<b2*>(&u); }
__device__ __forceinline__ uint32_t as_u(b2 v) { return *reinterpret_cast<uint32_t*>(&v); }
__device__ __forceinline__ c2 mk(b2 x, b2 y) { c2 r; r.x = x; r.y = y; return r; }
__device__ __forceinline__ c2 cmul(c2 a, b2 wr, b2 wi) { return mk(__hfma2(a.x, wr, __hneg2(__hmul2(a.y, wi))), __hfma2(a.x, wi, __hmul2(a.y, wr))); }
__device__ __forceinline__ void fft4(c2& a0, c2& a1, c2& a2, c2& a3) {
  c2 t0 = mk(__hadd2(a0.x, a2.x), __hadd2(a0.y, a2.y)), t1 = mk(__hsub2(a0.x, a2.x), __hsub2(a0.y, a2.y));
  c2 t2 = mk(__hadd2(a1.x, a3.x), __hadd2(a1.y, a3.y)), t3 = mk(__hsub2(a1.x, a3.x), __hsub2(a1.y, a3.y));
  a0 = mk(__hadd2(t0.x, t2.x), __hadd2(t0.y, t2.y)); a2 = mk(__hsub2(t0.x, t2.x), __hsub2(t0.y, t2.y));
  a1 = mk(__hadd2(t1.x, t3.y), __hsub2(t1.y, t3.x)); a3 = mk(__hsub2(t1.x, t3.y), __hadd2(t1.y, t3.x));
}
__device__ __forceinline__ void fft4_s2(c2& a0, c2& a1, c2& a2, c2& a3, b2 r) {
  const b2 nr = __hneg2(r);
  c2 t0 = mk(__hfma2(a2.x, r, a0.x), __hfma2(a2.y, r, a0.y)), t1 = mk(__hfma2(a2.x, nr, a0.x), __hfma2(a2.y, nr, a0.y));
  c2 t2 = mk(__hadd2(a1.x, a3.x), __hadd2(a1.y, a3.y)), t3 = mk(__hsub2(a1.x, a3.x), __hsub2(a1.y, a3.y));
  a0 = mk(__hadd2(t0.x, t2.x), __hadd2(t0.y, t2.y)); a2 = mk(__hsub2(t0.x, t2.x), __hsub2(t0.y, t2.y));
  a1 = mk(__hadd2(t1.x, t3.y), __hsub2(t1.y, t3.x)); a3 = mk(__hsub2(t1.x, t3.y), __hadd2(t1.y, t3.x));
}
__device__ __forceinline__ void fft4_s13(c2& a0, c2& a1, c2& a2, c2& a3, b2 r) {
  const b2 nr = __hneg2(r);
  c2 t0 = mk(__hadd2(a0.x, a2.x), __hadd2(a0.y, a2.y)), t1 = mk(__hsub2(a0.x, a2.x), __hsub2(a0.y, a2.y));
  c2 t2 = mk(__hadd2(a1.x, a3.x), __hadd2(a1.y, a3.y)), t3 = mk(__hsub2(a1.x, a3.x), __hsub2(a1.y, a3.y));
  a0 = mk(__hfma2(t2.x, r, t0.x), __hfma2(t2.y, r, t0.y)); a2 = mk(__hfma2(t2.x, nr, t0.x), __hfma2(t2.y, nr, t0.y));
  a1 = mk(__hfma2(t3.y, r, t1.x), __hfma2(t3.x, nr, t1.y)); a3 = mk(__hfma2(t3.y, nr, t1.x), __hfma2(t3.x, r, t1.y));
}
__device__ __forceinline__ c2 rot1(c2 a) { return mk(__hadd2(a.x, a.y), __hsub2(a.y, a.x)); }
__device__ __forceinline__ c2 rot3(c2 a) { return mk(__hsub2(a.y, a.x), __hneg2(__hadd2(a.x, a.y))); }
__device__ __forceinline__ c2 mul_mi(c2 a) { return mk(a.y, __hneg2(a.x)); }
template <int O> __device__ __forceinline__ void fft8(c2 (&v)[16]) {
  const b2 r = as_b2(0x3F353F35u), nr = as_b2(0xBF35BF35u);
  fft4(v[O], v[O + 4], v[O + 8], v[O + 12]);
  fft4(v[O + 2], v[O + 6], v[O + 10], v[O + 14]);
  const c2 o0 = v[O + 2], o1 = rot1(v[O + 6]), o2 = v[O + 10], o3 = rot1(v[O + 14]);
  const c2 e0 = v[O], e1 = v[O + 4], e2 = v[O + 8], e3 = v[O + 12];
  v[O] = mk(__hadd2(e0.x, o0.x), __hadd2(e0.y, o0.y));              v[O + 8] = mk(__hsub2(e0.x, o0.x), __hsub2(e0.y, o0.y));
  v[O + 2] = mk(__hfma2(o1.x, r, e1.x), __hfma2(o1.y, r, e1.y));    v[O + 10] = mk(__hfma2(o1.x, nr, e1.x), __hfma2(o1.y, nr, e1.y));
  v[O + 4] = mk(__hadd2(e2.x, o2.y), __hsub2(e2.y, o2.x));          v[O + 12] = mk(__hsub2(e2.x, o2.y), __hadd2(e2.y, o2.x));
  v[O + 6] = mk(__hfma2(o3.y, r, e3.x), __hfma2(o3.x, nr, e3.y));   v[O + 14] = mk(__hfma2(o3.y, nr, e3.x), __hfma2(o3.x, r, e3.y));
}
__device__ __forceinline__ void fft16(c2 (&v)[16]) {
  const b2 r = as_b2(0x3F353F35u), c1 = as_b2(0x3F6D3F6Du), s1 = as_b2(0x3EC43EC4u), nc1 = as_b2(0xBF6DBF6Du), ns1 = as_b2(0xBEC4BEC4u);
#pragma unroll
  for (int a = 0; a < 4; a++) fft4(v[a], v[a + 4], v[a + 8], v[a + 12]);
  v[5] = cmul(v[5], c1, ns1); v[6] = rot1(v[6]); v[7] = cmul(v[7], s1, nc1);
  v[9] = rot1(v[9]); v[10] = mul_mi(v[10]); v[11] = rot3(v[11]);
  v[13] = cmul(v[13], s1, nc1); v[14] = rot3(v[14]); v[15] = cmul(v[15], nc1, s1);
  fft4(v[0], v[1], v[2], v[3]); fft4_s2(v[4], v[5], v[6], v[7], r); fft4_s13(v[8], v[9], v[10], v[11], r); fft4_s2(v[12], v[13], v[14], v[15], r);
  c2 t;
  t = v[1]; v[1] = v[4]; v[4] = t;  t = v[2]; v[2] = v[8]; v[8] = t;  t = v[3]; v[3] = v[12]; v[12] = t;
  t = v[6]; v[6] = v[9]; v[9] = t;  t = v[7]; v[7] = v[13]; v[13] = t; t = v[11]; v[11] = v[14]; v[14] = t;
}

__device__ __forceinline__ void columns(c2 (&v)[16], uint32_t sb, int t) {
  const int l16 = t & 15;
  const uint32_t row = sb + OFF_EXCH + (t >> 4) * 2304;
  const uint32_t pos = sb + OFF_EXCH + (t >> 3) * 144 + (t & 7) * 16;
#pragma unroll 1
  for (int ps = 0; ps < 6; ps++) {
    if (ps == 0 || ps == 5) { fft8<0>(v); fft8<1>(v); } else fft16(v);
    if (ps == 5) break;
    if (ps == 2) {
      const uint32_t ws = sb + OFF_WS + (l16 >> 1) * 128 + ((((t >> 4) + (l16 >> 1)) & 7) * 2 + (l16 & 1)) * 8;
      mbar_wait(sb + OFF_BAR + B_WFULL * 8, 0);
#pragma unroll
      for (int q = 0; q < 16; q++) {
        const uint2 w = lds64(ws + q * 1024);
        const c2 z = cmul(v[q], as_b2(w.x), as_b2(w.y));
        v[q] = mk(z.y, z.x);
      }
      continue;
    }
    {
      const bool full = ps == 0 || ps == 4;
      const uint32_t tw = sb + OFF_TW + (full ? ps * 2048 + t * 16 : 16384 + l16 * 16);
      const uint32_t st = full ? 2048 : 256;
#pragma unroll
      for (int i = 0; i < 4; i++) {
        const uint4 w4 = lds128(tw + i * st);
        const uint32_t w[4] = {w4.x, w4.y, w4.z, w4.w};
#pragma unroll
        for (int e = 0; e < 4; e++) v[4 * i + e] = cmul(v[4 * i + e], __low2bfloat162(as_b2(w[e])), __high2bfloat162(as_b2(w[e])));
      }
    }
    if (ps == 0) {
      mbar_wait(sb + OFF_BAR + B_XDONE * 8, 0);
#pragma unroll
      for (int q = 0; q < 8; q++) sts128(pos + q * 2304, as_u(v[2 * q].x), as_u(v[2 * q].y), as_u(v[2 * q + 1].x), as_u(v[2 * q + 1].y));
      bar_sync<3, 128>();
#pragma unroll
      for (int q = 0; q < 16; q++) { const uint2 a = lds64(row + q * 144 + l16 * 8); v[q] = mk(as_b2(a.x), as_b2(a.y)); }
    } else {
      __syncwarp();
#pragma unroll
      for (int q = 0; q < 16; q++) sts64(row + q * 144 + l16 * 8, as_u(v[q].x), as_u(v[q].y));
      if (ps == 4) bar_sync<3, 128>(); else __syncwarp();
      const uint32_t src = ps == 4 ? pos : row + l16 * 144, st = ps == 4 ? 2304 : 16;
#pragma unroll
      for (int q = 0; q < 8; q++) { const uint4 a = lds128(src + q * st); v[2 * q] = mk(as_b2(a.x), as_b2(a.y)); v[2 * q + 1] = mk(as_b2(a.z), as_b2(a.w)); }
    }
  }
}

template <int NH> __device__ __forceinline__ void h_epilogue(float (&acc)[NH * 8], unsigned char* gdst, uint32_t tag) {
#pragma unroll
  for (int c = 0; c < NH / 2; c++) {
    uint32_t pk[4];
#pragma unroll
    for (int i = 0; i < 4; i++) {
      float hv[2];
#pragma unroll
      for (int e = 0; e < 2; e++) {
        float hg = 0.5f * acc[c * 8 + i * 2 + e], up = acc[NH * 4 + c * 8 + i * 2 + e];
        float th; asm("tanh.approx.f32 %0, %1;" : "=f"(th) : "f"(hg));
        hv[e] = fmaf(hg, th, hg) * up;
      }
      pk[i] = pack_bf16(hv[0], hv[1]);
    }
    stg128_l2(gdst + c * 4096, (pk[0] & ~1u) | tag, pk[1], pk[2], pk[3]);
  }
}

__device__ __forceinline__ void frag_ready(uint32_t (&a)[4], uint32_t (&b)[4], uint32_t (&c)[4], uint32_t (&d)[4], const unsigned char* p, uint32_t tag) {
  asm volatile("{\n.reg .pred p;\n.reg .u32 c, m, q;\nmov.u32 c, 0;\nL_TRY:\n"
               "lop3.b32 m, %0, %4, %17, 0x7E;\nlop3.b32 q, %8, %12, %17, 0x7E;\nlop3.b32 m, m, q, 1, 0xA8;\nsetp.ne.u32 p, m, 0;\n"
               "vote.sync.any.pred p, p, 0xffffffff;\n@!p bra.uni L_OK;\n"
               "ld.relaxed.gpu.global.v4.b32 {%0,%1,%2,%3}, [%16];\nld.relaxed.gpu.global.v4.b32 {%4,%5,%6,%7}, [%16+4096];\n"
               "ld.relaxed.gpu.global.v4.b32 {%8,%9,%10,%11}, [%16+8192];\nld.relaxed.gpu.global.v4.b32 {%12,%13,%14,%15}, [%16+12288];\n"
               "add.u32 c, c, 1;\nsetp.lt.u32 p, c, 262144;\n@p bra.uni L_TRY;\ntrap;\nL_OK:\n}"
               : "+r"(a[0]), "+r"(a[1]), "+r"(a[2]), "+r"(a[3]), "+r"(b[0]), "+r"(b[1]), "+r"(b[2]), "+r"(b[3]),
                 "+r"(c[0]), "+r"(c[1]), "+r"(c[2]), "+r"(c[3]), "+r"(d[0]), "+r"(d[1]), "+r"(d[2]), "+r"(d[3])
               : "l"(p), "r"(tag) : "memory");
}

#define MAP 0
#define STAG 150
#define LEAD2 0
#define LEAD1 2

__global__ void __cluster_dims__(2, 1, 1) __launch_bounds__(NTHREADS, 1)
fused_kernel(const __grid_constant__ CUtensorMap tm_x, const __grid_constant__ CUtensorMap tm_g, const __grid_constant__ CUtensorMap tm_u,
             const __grid_constant__ CUtensorMap tm_g32, const __grid_constant__ CUtensorMap tm_u32, const __grid_constant__ CUtensorMap tm_d,
             const __grid_constant__ CUtensorMap tm_s,
             const __nv_bfloat16* __restrict__ w_r, const __nv_bfloat16* __restrict__ w_i,
             const __nv_bfloat16* __restrict__ w_gate, const __nv_bfloat16* __restrict__ w_up,
             const __nv_bfloat16* __restrict__ w_down, const __nv_bfloat16* __restrict__ gate_w, __nv_bfloat16* __restrict__ out) {
  extern __shared__ __align__(1024) unsigned char smem[];
  const uint32_t sb = s2u(smem);
  const uint32_t bars = sb + OFF_BAR;
  const int tid = threadIdx.x, warp = __shfl_sync(0xffffffffu, tid >> 5, 0), lane = tid & 31;
  const int cl = blockIdx.x >> 1, kh = blockIdx.x & 1;
  const int n0 = cl < 4 ? cl : (cl < 36 ? (cl - 4) >> 3 : (cl - 36) / 7);
  const int m0 = cl < 4 ? 15 : (cl < 36 ? (cl - 4) & 7 : cl - 28 - 7 * n0);
  const int n = MAP == 0 ? n0 : (MAP == 1 ? (m0 & 3) : ((n0 & 1) | ((m0 & 1) << 1)));
  const int m = MAP == 0 ? m0 : (MAP == 1 ? ((m0 & 12) | n0) : ((m0 & 14) | (n0 >> 1)));
  const int j = kh * 4 + n, bid = m * 8 + n * 2 + kh;

  const int c64 = 224 * j + (j & 1) * 32;
  if (warp < 8) {
    asm volatile("setmaxnreg.inc.sync.aligned.u32 208;");
    const int wg = warp >> 2, w4 = warp & 3, g = lane >> 2, t = lane & 3;
    const int rh = wg ^ kh ^ 1;
    const int p = j & 1, r = (j >> 1) & 1, hh = j >> 2;
    const uint32_t epoch = ld_relaxed(&g_ep[bid]);
    if ((tid & 127) == 0) PROF(wg, 30);
#pragma unroll 1
    for (int it = tid; it < 392; it += 256) {
      const int kc = it / 28, sg = it - kc * 28;
      const int k = 2 * (28 * hh + sg) + r;
      const float kf = (float)k * (-6.283185307179586f / 448.0f), a0 = (float)(16 * kc + p) * kf;
      uint32_t c[4], s[4];
#pragma unroll
      for (int q = 0; q < 4; q++) {
        const float a1 = fmaf((float)(2 * q), kf, a0), a2 = fmaf((float)(2 * q + 8), kf, a0);
        c[q] = pack_bf16(__cosf(a1), __cosf(a2)); s[q] = pack_bf16(__sinf(a1), __sinf(a2));
        if (k == 0) s[q] = ((q ^ p) & 1) ? 0xBF80BF80u : 0x3F803F80u;
      }
      const uint32_t a = sb + 6 * SLOT + (kc * 56 + 2 * sg) * 16;
      sts128(a, c[0], c[1], c[2], c[3]);
      sts128(a + 16, s[0], s[1], s[2], s[3]);
    }
    if ((tid & 127) == 0) PROF(wg, 31);
    fence_async_smem();
    bar_sync<0, NTHREADS - 64>();
    asm volatile("barrier.cluster.arrive.relaxed.aligned;" ::: "memory");
    if ((tid & 127) == 0) PROF(wg, 1);

    uint32_t xa[28][4];
    {
      const uint32_t xb = sb + OFF_PQ + wg * HALF_XR + (w4 * 16 + (lane & 15)) * 128;
      mbar_wait(bars + (B_XFULL + wg) * 8, 0);
      if ((tid & 127) == 0) PROF(wg, 2);
#pragma unroll
      for (int kb = 0; kb < 7; kb++) {
#pragma unroll
        for (int kk = 0; kk < 4; kk++) {
          uint32_t a = xb + kb * 8192 + (((2 * kk + (lane >> 4)) ^ (lane & 7)) << 4);
          asm volatile("ldmatrix.sync.aligned.m8n8.x4.shared.b16 {%0,%1,%2,%3}, [%4];"
                       : "=r"(xa[kb * 4 + kk][0]), "=r"(xa[kb * 4 + kk][1]), "=r"(xa[kb * 4 + kk][2]), "=r"(xa[kb * 4 + kk][3]) : "r"(a) : "memory");
        }
      }
    }
    {
      uint32_t ad[7][4];
      const uint32_t sel = p ? 0x7632 : 0x5410;
      const uint32_t sgn = r ? 0xBF80BF80u : 0x3F803F80u;
#pragma unroll
      for (int jj = 0; jj < 7; jj++) {
#pragma unroll
        for (int i = 0; i < 4; i++) {
          int ks = 2 * jj + (i >> 1), rr = i & 1;
          uint32_t lo = __byte_perm(xa[ks][rr], xa[ks][rr + 2], sel);
          uint32_t hi = __byte_perm(xa[ks + 14][rr], xa[ks + 14][rr + 2], sel);
          asm("fma.rn.bf16x2 %0, %1, %2, %3;" : "=r"(ad[jj][i]) : "r"(hi), "r"(sgn), "r"(lo));
        }
      }
      __syncwarp();
      if (lane == 0) mbar_arrive(bars + (B_XFREE + wg) * 8);
      float acc[28];
      wg_fence();
      uint64_t db = mkdesc(sb + 6 * SLOT, 896, 128, 0);
#pragma unroll
      for (int jj = 0; jj < 7; jj++) wgmma_rs_56<0>(acc, ad[jj], db + jj * 112, jj != 0);
      wg_commit();
      wg_wait<0>(); keep(acc);
      if (lane == 0) mbar_arrive(bars + (B_EMPTY + 6) * 8);
      const uint32_t xc = sb + OFF_EXCH + wg * 8192 + t * 256 + w4 * 64 + g * 4;
      mbar_wait(bars + B_XFREE * 8, 0);
#pragma unroll
      for (int i = 0; i < 7; i++) {
        sts32(xc + i * 1024, pack_bf16(acc[4 * i], acc[4 * i + 1]));
        sts32(xc + i * 1024 + 32, pack_bf16(acc[4 * i + 2], acc[4 * i + 3]));
      }
      fence_async_smem();
      __syncwarp();
      if (lane == 0) mbar_arrive(bars + B_PUBX * 8);
    }
    if ((tid & 127) == 0) PROF(wg, 3);
    const uint32_t tag = ~epoch & 1;
    unsigned char* const hbase = g_H + (size_t)(m * 2 + kh) * (56 * 4096) + rh * 2048 + (tid & 127) * 16;
#pragma unroll 1
    for (int u = 0; u < 3; u++) {
      float acc[64];
      if (wg == 1) { if (u & 1) bar_sync<6, 256>(); else bar_sync<2, 256>(); }
      const uint32_t sbu = opaque(sb);
#pragma unroll
      for (int kb = 0; kb < 7; kb++) {
        mbar_wait(sbu + OFF_BAR + (B_FULL + kb) * 8, u & 1);
        wg_fence();
        uint64_t db = mkdesc(sbu + kb * SLOT, 8192, 1024, 1);
#pragma unroll
        for (int kk = 0; kk < 4; kk++) wgmma_rs_128<1>(acc, xa[kb * 4 + kk], db + kk * 128, (kb | kk) != 0);
        wg_commit();
        if (kb == LEAD1 && wg == 0) { if (u & 1) bar_arrive<6, 256>(); else bar_arrive<2, 256>(); }
        if (kb > 0) { wg_wait<1>(); if (lane == 0) mbar_arrive(sbu + OFF_BAR + (B_EMPTY + kb - 1) * 8); }
      }
      wg_wait<0>(); keep(acc);
      if (lane == 0) mbar_arrive(sbu + OFF_BAR + (B_EMPTY + 6) * 8);
      if ((tid & 127) == 0) PROF(wg, 4 + 2 * u);
      h_epilogue<8>(acc, hbase + (u * 16 + n * 4) * 4096, tag);
      if ((tid & 127) == 0) PROF(wg, 5 + 2 * u);
    }
    uint32_t ha[14][4][4];
    auto check = [&](int b0, int b1) {
#pragma unroll
      for (int b = b0; b < b1; b++) frag_ready(ha[b][0], ha[b][1], ha[b][2], ha[b][3], hbase + b * 16384, tag);
    };
    auto load = [&](int b0, int b1) {
#pragma unroll
      for (int i = b0; i < b1; i++) ldg128_l2(ha[i >> 2][i & 3], hbase + i * 4096);
    };
    {
      float acc[32];
      load(0, 3);
      if (wg == 1) bar_sync<6, 256>();
      const uint32_t sbu = opaque(sb);
#pragma unroll
      for (int it = 0; it < 4; it++) {
        mbar_wait(sbu + OFF_BAR + (B_FULL + it) * 8, 1);
        wg_fence();
        uint64_t db = mkdesc(sbu + it * SLOT, 8192, 512, 2);
#pragma unroll
        for (int kk = 0; kk < 8; kk++) if (it * 8 + kk < 28) wgmma_rs_64<1>(acc, xa[it * 8 + kk], db + kk * 64, (it | kk) != 0);
        wg_commit();
        if (it == 2 && wg == 0) bar_arrive<6, 256>();
        if (it > 0) {
          wg_wait<1>();
          if (lane == 0) mbar_arrive(sbu + OFF_BAR + (B_EMPTY + it - 1) * 8);
          if (it == 1) load(3, 11);
          if (it == 2) load(11, 16);
        }
      }
      wg_wait<0>(); keep(acc);
      if (lane == 0) mbar_arrive(sbu + OFF_BAR + (B_EMPTY + 3) * 8);
      if ((tid & 127) == 0) PROF(wg, 10);
      h_epilogue<4>(acc, hbase + (48 + n * 2) * 4096, tag);
    }
    asm volatile("barrier.cluster.wait.aligned;" ::: "memory");
    if ((tid & 127) == 0) PROF(wg, 11);

    float acc[56];
    check(0, 4);
    if (wg == 1) bar_sync<2, 256>();
#pragma unroll
    for (int b = 0; b < 14; b++) {
      if ((tid & 127) == 0) PROF(wg, 16 + b);
      if (b >= 3) mbar_wait(bars + (B_FULL + (b + 1) % 7) * 8, b < 6 || b == 13);
      else if (b == 0) mbar_wait(bars + B_RFULL * 8, 0);
      if (b == 4) check(4, 7);
      if (b == 7) check(7, 11);
      if (b == 11) check(11, 14);
      wg_fence();
      const uint64_t db = mkdesc(b < 3 ? sb + OFF_R + b * SLOT : sb + (b + 1) % 7 * SLOT, 8192, 1024, 1);
#pragma unroll
      for (int kk = 0; kk < 4; kk++) wgmma_rs_112<1>(acc, ha[b][kk], db + kk * 128, (b | kk) != 0);
      wg_commit();
      if (b == LEAD2 && wg == 0) bar_arrive<2, 256>();
      if (b == 0) load(16, 24);
      if (b == 1) load(24, 28);
      if (b == 4 || b == 5) load(8 * b - 4, 8 * b + 4);
      if (b == 7) load(44, 52);
      if (b == 8) load(52, 56);
      if (b > 0) wg_wait<1>();
      if (lane == 0) {
        if (b >= 4 && b <= 9) mbar_arrive(bars + (B_EMPTY + b % 7) * 8);
        if (b == 3) {
          mbar_arrive(bars + B_LFREE * 8);
          asm volatile("{\n.reg .b32 ra;\nmapa.shared::cluster.u32 ra, %0, %1;\nmbarrier.arrive.relaxed.cluster.shared::cluster.b64 _, [ra];\n}"
                       :: "r"(bars + B_RFREE * 8), "r"(kh ^ 1) : "memory");
        }
      }
    }
    const int t128 = tid & 127;
    wg_wait<0>(); keep(acc);
    if (wg == 0) {
      if (t128 == 0) PROF(wg, 12);
      mbar_wait_cluster(bars + B_RFREE * 8, 0);
      uint32_t rdst, rbar;
      asm volatile("mapa.shared::cluster.u32 %0, %1, %2;" : "=r"(rdst) : "r"(sb + OFF_R + t128 * 16), "r"(kh ^ 1));
      asm volatile("mapa.shared::cluster.u32 %0, %1, %2;" : "=r"(rbar) : "r"(bars + B_RECV * 8), "r"(kh ^ 1));
#pragma unroll
      for (int i = 0; i < 14; i++)
        asm volatile("st.async.weak.shared::cluster.mbarrier::complete_tx::bytes.v4.f32 [%0], {%1,%2,%3,%4}, [%5];"
                     :: "r"(rdst + i * 2048), "f"(acc[4 * i]), "f"(acc[4 * i + 1]), "f"(acc[4 * i + 2]), "f"(acc[4 * i + 3]), "r"(rbar) : "memory");
    } else {
      float spec[2][28];
      if (t128 == 0) PROF(wg, 12);
#pragma unroll
      for (int i = 0; i < 4; i++) {
        if (i == 0) mbar_wait(bars + B_GFULL * 8, 0);
        if (i >= 2) mbar_wait(bars + (B_FULL + i - 1) * 8, 1);
        mbar_wait(bars + (B_PQFULL + i) * 8, 0);
        if (i == 0 && t128 == 0) { PROF(wg, 13); g_ep[bid] = epoch + 1; }
        wg_fence();
        const uint64_t da = mkdesc(sb + OFF_PQ + i * 14336, 1024, 1024, 1);
        const uint64_t db = mkdesc(i < 2 ? sb + OFF_R + 28672 + i * (G_IMG / 2) : sb + (i - 1) * SLOT, 896, 128, 0);
#pragma unroll
        for (int kk = 0; kk < 7; kk++) wgmma_ss_56<1, 0>(spec[i >> 1], da + kk * 128, db + kk * 112, ((i & 1) | kk) != 0);
        wg_commit();
      }
      const float* gs = reinterpret_cast<const float*>(smem + OFF_G) + w4 * 16 + g;
      const float o0 = bf16_round(1.0f - gs[0]), o1 = bf16_round(1.0f - gs[8]);
      const float g0 = gs[0] * (1.0f / (float)(S_ * D_)), g1 = gs[8] * (1.0f / (float)(S_ * D_));
      mbar_wait_cluster(bars + B_RECV * 8, 0);
      if (t128 == 0) PROF(wg, 0);
#pragma unroll
      for (int i = 0; i < 14; i++) {
        const float4 o = lds128f(sb + OFF_R + t128 * 16 + i * 2048);
        acc[4 * i] = (acc[4 * i] + o.x) * o0; acc[4 * i + 1] = (acc[4 * i + 1] + o.y) * o0;
        acc[4 * i + 2] = (acc[4 * i + 2] + o.z) * o1; acc[4 * i + 3] = (acc[4 * i + 3] + o.w) * o1;
      }
      keep(acc);
      wg_wait<0>(); keep(spec[0]); keep(spec[1]);
      if (t128 == 0) PROF(wg, 14);
      bar_sync<5, 128>();
      const uint32_t st = sb + OFF_PQ + w4 * 3840;
#pragma unroll
      for (int i = 0; i < 7; i++) {
        uint32_t pk[4];
#pragma unroll
        for (int e = 0; e < 2; e++) {
          const int c = 2 * i + e, si = i * 4 + e;
          pk[2 * e] = pack_bf16(fmaf(g0, spec[0][si], acc[4 * c]), fmaf(g0, spec[1][si], acc[4 * c + 1]));
          pk[2 * e + 1] = pack_bf16(fmaf(g1, spec[0][si + 2], acc[4 * c + 2]), fmaf(g1, spec[1][si + 2], acc[4 * c + 3]));
        }
        asm volatile("stmatrix.sync.aligned.m8n8.x4.shared.b16 [%0], {%1,%2,%3,%4};"
                     :: "r"(st + (lane & 15) * 240 + (lane >> 4) * 16 + i * 32), "r"(pk[0]), "r"(pk[1]), "r"(pk[2]), "r"(pk[3]) : "memory");
      }
      __syncwarp();
      if (lane < 28) {
        const int r2 = lane >= 14, cc = lane - r2 * 14;
        unsigned char* ob = reinterpret_cast<unsigned char*>(out) + (size_t)(m * 128 + kh * 64 + w4 * 16 + r2) * (D_ * 2) + n * 224 + cc * 16;
        float4 v[8];
#pragma unroll
        for (int i = 0; i < 8; i++) v[i] = lds128f(st + r2 * 240 + cc * 16 + i * 480);
#pragma unroll
        for (int i = 0; i < 8; i++) stg128(ob + i * (D_ * 4), __float_as_uint(v[i].x), __float_as_uint(v[i].y), __float_as_uint(v[i].z), __float_as_uint(v[i].w));
      }
    }
    if (t128 == 0) { PROF(wg, 15); if (wg) { PROFG(4, 30); PROF(4, 31); } }
  } else if (warp < 12) {
    asm volatile("setmaxnreg.dec.sync.aligned.u32 72;");
    const int t = tid - 256;
    const int k = bid;
    if (t == 0) PROF(2, 0);
    uint4 gv[7];
#pragma unroll
    for (int i = 0; i < 7; i++) gv[i] = ldg128(reinterpret_cast<const uint4*>(gate_w) + i * 8 + (t & 7));
    if (t < 98) {
      int cid = m * 98 + t, kc = cid / 56, nn = cid - kc * 56;
      int d = 112 * n + 8 * (2 * (nn >> 3) + (nn & 1)) + (nn & 6) + kh;
      int dr = d > 224 ? d - 448 : d;
      const float df = (float)dr * (-6.283185307179586f / 448.0f);
      uint32_t pk[4];
#pragma unroll
      for (int e = 0; e < 4; e++) {
        const float a = (float)(4 * kc + e) * df;
        pk[e] = pack_bf16(2.0f * __cosf(a), 2.0f * __sinf(a));
      }
      if (kc == 0) pk[0] = (((d >> 1) ^ kh) & 1) ? 0xBF803F80u : 0x3F803F80u;
      stg128(g_G + (size_t)(n * 2 + kh) * G_IMG + cid * 16, pk[0], pk[1], pk[2], pk[3]);
    }
    bar_sync<0, NTHREADS - 64>();
    asm volatile("barrier.cluster.arrive.relaxed.aligned;" ::: "memory");
    {
      const int row = n * 16 + (t >> 3), l8 = t & 7;
      mbar_wait(bars + (B_XFULL + 1) * 8, 0);
      float sum = 0.f;
#pragma unroll
      for (int i = 0; i < 7; i++) {
        const uint4 a = lds128(sb + OFF_R + i * 8192 + row * 128 + ((l8 ^ (row & 7)) << 4));
        const uint32_t aa[4] = {a.x, a.y, a.z, a.w}, bb[4] = {gv[i].x, gv[i].y, gv[i].z, gv[i].w};
#pragma unroll
        for (int e = 0; e < 4; e++) {
          const uint32_t pr = as_u(__hmul2(as_b2(aa[e]), as_b2(bb[e])));
          sum += bf_lo(pr) + bf_hi(pr);
        }
      }
      sum += __shfl_xor_sync(0xffffffffu, sum, 1); sum += __shfl_xor_sync(0xffffffffu, sum, 2); sum += __shfl_xor_sync(0xffffffffu, sum, 4);
      if (l8 == 0) g_gate[m * 128 + kh * 64 + row] = bf16_round(__fdividef(1.0f, 1.0f + __expf(-bf16_round(sum))));
    }
    __syncwarp();
    if (lane == 0) mbar_arrive(bars + (B_XFREE + 1) * 8);
    if (t == 0) PROF(2, 11);
    mbar_wait(bars + B_XFREE * 8, 0);
    {
      const float u = -6.283185307179586f / 2048.0f, t2 = (float)(2 * t) * u;
#pragma unroll 1
      for (int i = 0; i < 4; i++) {
        const float q = (float)(2 * i);
        sts128(sb + OFF_TW + i * 2048 + t * 16, cis(t2 * q), cis((t2 + u) * q), cis(t2 * (q + 1.0f)), cis((t2 + u) * (q + 1.0f)));
      }
      const float l = (float)((t >> 1) & 15) * (8.0f * u), jj = (float)((t >> 5) * 4 + (t & 1) * 2);
      sts64(sb + OFF_TW + 16384 + t * 8, cis(l * jj), cis(l * (jj + 1.0f)));
    }
    mbar_wait(bars + B_PIN * 8, 0);
    mbar_wait(bars + (B_XFREE + 1) * 8, 0);
    if (t == 0) PROF(2, 4);
    {
      const uint32_t wa = sb + OFF_WS + (((t & 7) - bid) & 7) * 450 + (t >> 3) * 2, wc = wa + 448 - (t >> 3) * 4;
#pragma unroll 1
      for (int h = 0; h < 2; h++) {
        uint32_t w[4][8];
#pragma unroll
        for (int i = 0; i < 4; i++) {
#pragma unroll
          for (int e = 0; e < 4; e++) { w[i][2 * e] = lds16(wa + h * 128 + i * 32 + e * 3600); w[i][2 * e + 1] = lds16(wc - h * 128 - i * 32 + e * 3600); }
        }
#pragma unroll
        for (int i = 0; i < 4; i++)
          sts128(sb + OFF_R + h * 8192 + i * 2048 + t * 16, __byte_perm(w[i][0], w[i][1], 0x5410), __byte_perm(w[i][4], w[i][5], 0x5410), __byte_perm(w[i][2], w[i][3], 0x5410), __byte_perm(w[i][6], w[i][7], 0x5410));
      }
    }
    fence_async_smem();
    __syncwarp();
    if (lane == 0) mbar_arrive(bars + B_PUBW * 8);
    if (k < 113) {
      if (t == 0) PROF(2, 2);
      mbar_wait(bars + B_XCFULL * 8, 0);
      if (t == 0) PROF(2, 3);
      c2 v[16];
      uint2 xe[8], xo[8];
      const int sl = k == 112 ? 0 : k, hi = sl >= 56;
      const unsigned char* xs = g_X + (192 + (sl & 1) * 64 + hi * 72 + (sl & ~1) + ((t >> 4) & 1)) * XP + (t >> 5) * 256 + (t & 15) * 8;
#pragma unroll
      for (int jj = 0; jj < 8; jj++) { xe[jj] = ldg64_l2(xs + jj * 1024); xo[jj] = ldg64_l2(xs + jj * 1024 + 128); }
      {
        const float rr = (float)(t >> 4) * (-6.283185307179586f / 2048.0f);
#pragma unroll 1
        for (int i = 0; i < 4; i++) {
          const float l = (float)((t & 15) + 64 * i);
          sts128(sb + OFF_TW + 8192 + i * 2048 + t * 16, cis(rr * l), cis(rr * (l + 16.0f)), cis(rr * (l + 32.0f)), cis(rr * (l + 48.0f)));
        }
      }
      if (t == 0) PROF(2, 9);
      const uint32_t se = k == 0 ? 0x4410 : (k == 112 ? 0x4432 : 0x3210), so = k == 0 ? 0x4410 : (k == 112 ? 0x3244 : 0x3210);
#pragma unroll
      for (int jj = 0; jj < 8; jj++) {
        const uint2 e2 = xe[jj], o2 = xo[jj];
#pragma unroll
        for (int h = 0; h < 2; h++) {
          const b2 e = as_b2(__byte_perm(h ? e2.y : e2.x, 0, se)), o = as_b2(__byte_perm(h ? o2.y : o2.x, 0, so));
          const uint32_t s = as_u(__hadd2(e, o)), d = as_u(__hsub2(e, o)) ^ 0x80000000u;
          v[2 * jj + h] = mk(as_b2(__byte_perm(s, d, 0x5410)), as_b2(__byte_perm(s, d, 0x7632)));
        }
      }
      if (t == 0) PROF(2, 12);
      columns(v, sb, t);
      if (t == 0) PROF(2, 14);
      const int pre = (k == 112) ? 1 : 2 * k, pim = (k == 112) ? 1 : 2 * k + 1;
      const uint32_t pr = sb + OFF_EXCH + (t >> 5) * 256 + ((((lane >> 2) ^ pre) & 7) << 4) + (lane & 3) * 4;
      const uint32_t pi = sb + OFF_EXCH + 8192 + (t >> 5) * 256 + ((((lane >> 2) ^ pim) & 7) << 4) + (lane & 3) * 4;
      bar_sync<3, 128>();
#pragma unroll
      for (int jj = 0; jj < 8; jj++) {
        const b2 ar = as_b2(__byte_perm(as_u(v[2 * jj].y), as_u(v[2 * jj + 1].y), 0x5410)), br = as_b2(__byte_perm(as_u(v[2 * jj].y), as_u(v[2 * jj + 1].y), 0x7632));
        const b2 ai = as_b2(__byte_perm(as_u(v[2 * jj].x), as_u(v[2 * jj + 1].x), 0x5410)), bi = as_b2(__byte_perm(as_u(v[2 * jj].x), as_u(v[2 * jj + 1].x), 0x7632));
        sts32(pr + jj * 1024, as_u(__hadd2(ar, br)));
        sts32(pr + jj * 1024 + 128, as_u(k == 112 ? __hadd2(ai, bi) : __hsub2(ar, br)));
        sts32(pi + jj * 1024 + 128, as_u(__hadd2(ai, bi)));
        sts32(pi + jj * 1024, as_u(__hsub2(ai, bi)));
      }
      fence_async_smem();
      bar_sync<3, 128>();
      if (t == 0) {
        PROF(2, 5);
        tma_store(&tm_s, pre * 64, 0, sb + OFF_EXCH);
        if (k != 0 && k != 112) tma_store(&tm_s, pim * 64, 0, sb + OFF_EXCH + 8192);
        bulk_done();
      }
    }
    if (t == 0) { red_relaxed(&g_cnt[5 * 32]); PROF(2, 7); }
    if (t >= 32) {
      if (k >= 113) mbar_wait(bars + B_LFREE * 8, 0);
      __nanosleep((t >> 5) * STAG);
      wait_ge(&g_cnt[5 * 32], (lds64(sb + OFF_G + 256).x + 1) * 128);
      if (lane == 0) mbar_arrive(bars + B_SEEN * 8);
    }
    __syncwarp();
    asm volatile("barrier.cluster.wait.aligned;" ::: "memory");
  } else {
    asm volatile("setmaxnreg.dec.sync.aligned.u32 24;");
    auto wd_tile = [&](int b, uint32_t dst, uint32_t fb) {
#pragma unroll
      for (int hf = 0; hf < 2; hf++) {
        const int js = kh * 4 + (b < 12 ? (b & 3) : (b & 1) * 2 + hf);
        const int row = 224 * js + (b < 12 ? (js & 1) * 32 + (b >> 2) * 64 + hf * 32 : 192 - hf * 192);
        tma2d(dst + hf * 4096, &tm_d, 112 * n, row, fb);
        tma2d(dst + 8192 + hf * 4096, &tm_d, 112 * n + 64, row, fb);
      }
    };
    if (warp == 12) {
      if (elect()) {
        mbar_init(bars + B_XFULL * 8, 1); mbar_init(bars + (B_XFULL + 1) * 8, 1);
        fence_async_smem();
#pragma unroll
        for (int w = 0; w < 2; w++) {
          mbar_expect(bars + (B_XFULL + w) * 8, HALF_XR);
          tma3d(sb + OFF_PQ + w * HALF_XR, &tm_x, 0, m * 128 + (w ^ kh ^ 1) * 64, 0, bars + (B_XFULL + w) * 8);
        }
        PROF(3, 3);
#pragma unroll
        for (int i = 0; i < NSLOT; i++) mbar_init(bars + (B_FULL + i) * 8, 1);
        mbar_init(bars + B_PIN * 8, 1);
        fence_async_smem();
      }
      bar_arrive<0, NTHREADS - 64>();
#pragma unroll 1
      for (int i = 0; i < 6; i++) {
        if (elect()) {
          const uint32_t fb = bars + (B_FULL + i) * 8;
          mbar_expect(fb, SLOT);
          tma2d(sb + i * SLOT, &tm_g, c64, i * 64, fb);
          tma2d(sb + i * SLOT + 8192, &tm_u, c64, i * 64, fb);
          PROF(3, 4 + i);
        }
      }
      if (elect()) {
        prefetch_l2(reinterpret_cast<const unsigned char*>(w_r) + bid * 7200, 7200);
        prefetch_l2(reinterpret_cast<const unsigned char*>(w_i) + bid * 7200, 7200);
        prefetch_tma2d(&tm_g, c64, 384); prefetch_tma2d(&tm_u, c64, 384);
      }
    } else if (warp == 14) {
      if (elect()) {
#pragma unroll
        for (int i = B_EMPTY; i < B_END; i++)
          if (i < B_XFULL || i >= B_XFREE) mbar_init(bars + i * 8, i >= B_PQFULL ? 1 : (i == B_XFREE ? 4 : (i == B_PUBW ? 5 : 8)));
        asm volatile("fence.mbarrier_init.release.cluster;" ::: "memory");
        fence_async_smem();
        mbar_expect(bars + B_RECV * 8, 64 * 112 * 4);
      }
      bar_arrive<0, NTHREADS - 64>();
    }
    const uint32_t epoch = ld_relaxed(&g_ep[bid]);
    if (warp == 13 && lane == 0) { PROFG(4, 0); PROF(4, 1); }
    bar_sync<1, 128>();
    asm volatile("barrier.cluster.arrive.relaxed.aligned;" ::: "memory");
    if (warp == 12) {
      int slot = 6, ph = 1;
      auto wait_slot = [&]() { mbar_wait(bars + (B_EMPTY + slot) * 8, ph ^ (slot == 6)); };
      auto adv = [&]() { if (++slot == NSLOT) { slot = 0; ph ^= 1; } };
      const int c32 = 224 * j + ((j & 1) ? 0 : 192);
#pragma unroll 1
      for (int i = 6; i < 25; i++) {
        wait_slot();
        if (elect()) {
          const uint32_t dst = sb + slot * SLOT, fb = bars + (B_FULL + slot) * 8;
          const bool last = i >= 21;
          const int cc = last ? c32 : c64 + 64 * (i / 7), rr = last ? slot * 128 : slot * 64;
          mbar_expect(fb, SLOT);
          tma2d(dst, last ? &tm_g32 : &tm_g, cc, rr, fb);
          tma2d(dst + 8192, last ? &tm_u32 : &tm_u, cc, rr, fb);
        }
        adv();
      }
      if (lane == 0) PROF(3, 0);
#pragma unroll 1
      for (int i = 3; i < 16; i++) {
        if (lane == 0) PROF(3, 16 + i);
        if (i == 14) mbar_wait(bars + B_PREP * 8, 0);
        wait_slot();
        if (elect()) {
          const uint32_t fb = bars + (B_FULL + slot) * 8;
          mbar_expect(fb, i < 14 ? SLOT : G_IMG / 2);
          if (i < 14) wd_tile(i, sb + slot * SLOT, fb);
          else bulk_g2s(sb + slot * SLOT, g_G + (size_t)(n * 4 + i - 12) * (G_IMG / 2), G_IMG / 2, fb);
        }
        adv();
      }
      if (lane == 0) PROF(3, 2);
    } else if (warp == 13) {
      mbar_wait(bars + B_PUBX * 8, 0);
      if (elect()) {
        PROF(4, 8);
#pragma unroll
        for (int w = 0; w < 2; w++) tma_store(&tm_s, ((m * 2 + (w ^ kh ^ 1)) * 2 + (j & 1)) * 64, 192 + (j >> 1) * 64, sb + OFF_EXCH + w * 8192);
        bulk_done();
        red_relaxed(&g_cnt[(j >> 1) * 32]);
        mbar_arrive(bars + B_XDONE * 8);
        PROF(4, 12);
      }
      mbar_wait(bars + B_PUBW * 8, 0);
      if (elect()) {
        PROF(4, 9);
        tma_store(&tm_s, bid * 64, 64, sb + OFF_R);
        tma_store(&tm_s, bid * 64, 128, sb + OFF_R + 8192);
        bulk_done();
        red_relaxed(&g_cnt[4 * 32]);
        mbar_arrive(bars + B_WDONE * 8);
        PROF(4, 13);
      }
      mbar_wait(bars + B_PREP * 8, 0);
      mbar_wait(bars + B_LFREE * 8, 0);
      if (elect()) {
        mbar_expect(bars + B_GFULL * 8, G_IMG);
        bulk_g2s(sb + OFF_R + 28672, g_G + (size_t)(n * 2) * G_IMG, G_IMG, bars + B_GFULL * 8);
      }
    } else if (warp == 14) {
      mbar_wait(bars + (B_XFREE + 1) * 8, 0);
      asm volatile("fence.acq_rel.gpu;" ::: "memory");
      if (lane == 0) { mbar_arrive(bars + B_PUBW * 8); PROF(5, 3); }
      mbar_wait(bars + B_WDONE * 8, 0);
      wait_ge(&g_cnt[4 * 32], (epoch + 1) * 128);
      fence_async_global();
      if (elect()) {
        mbar_arrive(bars + B_PREP * 8);
        if (bid < 113) {
          mbar_expect(bars + B_WFULL * 8, 16384);
          bulk_g2s(sb + OFF_WS, g_X + (64 + bid) * XP, 16384, bars + B_WFULL * 8);
        }
        PROF(5, 17);
      }
    } else {
      mbar_wait(bars + B_XFREE * 8, 0);
      if (elect()) {
        sts32(sb + OFF_G + 256, epoch);
        mbar_expect(bars + B_PIN * 8, 14400);
        bulk_g2s(sb + OFF_WS, reinterpret_cast<const unsigned char*>(w_r) + bid * 7200, 7200, bars + B_PIN * 8);
        bulk_g2s(sb + OFF_WS + 7200, reinterpret_cast<const unsigned char*>(w_i) + bid * 7200, 7200, bars + B_PIN * 8);
        prefetch_l2(reinterpret_cast<const unsigned char*>(w_gate) + bid * 12544, 12544);
        prefetch_l2(reinterpret_cast<const unsigned char*>(w_up) + bid * 12544, 12544);
        PROF(5, 2);
      }
      if (bid < 113) {
        const int sl = (bid == 112) ? 0 : bid;
        wait_ge(&g_cnt[((sl & 1) + 2 * ((sl >> 1) / 28)) * 32], (epoch + 1) * 32);
        if (elect()) { PROF(5, 16); mbar_arrive(bars + B_XCFULL * 8); }
      }
      mbar_wait(bars + B_PUBW * 8, 0);
      if (elect()) prefetch_l2(reinterpret_cast<const unsigned char*>(w_down) + bid * 12544, 12544);
      mbar_wait(bars + B_WDONE * 8, 0);
      if (elect()) mbar_expect(bars + B_RFULL * 8, 3 * SLOT);
#pragma unroll 1
      for (int i = 0; i < 3; i++) {
        mbar_wait(bars + (B_FULL + (i == 1 ? 0 : 3)) * 8, i == 0);
        if (elect()) wd_tile(i, sb + OFF_R + i * SLOT, bars + B_RFULL * 8);
      }
      if (lane == 0) PROF(5, 19);
      mbar_wait(bars + B_PREP * 8, 0);
      mbar_wait(bars + B_SEEN * 8, 0);
      fence_async_global();
      if (elect()) {
        PROF(5, 18);
        const unsigned char* src = g_X + (m * 2 + kh) * HALF_XR;
#pragma unroll
        for (int i = 0; i < 4; i++) {
          mbar_expect(bars + (B_PQFULL + i) * 8, i ? 14336 : 14336 + 256);
          bulk_g2s(sb + OFF_PQ + i * 14336, src + i * 14336, 14336, bars + (B_PQFULL + i) * 8);
        }
        bulk_g2s(sb + OFF_G, g_gate + m * 128 + kh * 64, 256, bars + B_PQFULL * 8);
      }
    }
    __syncwarp();
    asm volatile("barrier.cluster.wait.aligned;" ::: "memory");
  }
}

typedef CUresult (*EncodeFn)(CUtensorMap*, CUtensorMapDataType, cuuint32_t, void*, const cuuint64_t*, const cuuint64_t*, const cuuint32_t*,
                             const cuuint32_t*, CUtensorMapInterleave, CUtensorMapSwizzle, CUtensorMapL2promotion, CUtensorMapFloatOOBfill);

void make_map(EncodeFn enc, CUtensorMap* tm, const void* base, int cols, int rows, int bc, int br, CUtensorMapSwizzle sw) {
  cuuint64_t gd[2] = {(cuuint64_t)cols, (cuuint64_t)rows};
  cuuint64_t gs[1] = {(cuuint64_t)cols * 2};
  cuuint32_t bd[2] = {(cuuint32_t)bc, (cuuint32_t)br};
  cuuint32_t es[2] = {1, 1};
  enc(tm, CU_TENSOR_MAP_DATA_TYPE_BFLOAT16, 2, const_cast<void*>(base), gd, gs, bd, es, CU_TENSOR_MAP_INTERLEAVE_NONE, sw,
      CU_TENSOR_MAP_L2_PROMOTION_L2_128B, CU_TENSOR_MAP_FLOAT_OOB_FILL_NONE);
}

}

extern "C" void kernel_launch(void* const* d_in, const int* in_sizes, int n_in, void* d_out, int out_size) {
  (void)in_sizes; (void)n_in; (void)out_size;
  const __nv_bfloat16* x = (const __nv_bfloat16*)d_in[0];
  const __nv_bfloat16* w_r = (const __nv_bfloat16*)d_in[1];
  const __nv_bfloat16* w_i = (const __nv_bfloat16*)d_in[2];
  const __nv_bfloat16* w_gate = (const __nv_bfloat16*)d_in[4];
  const __nv_bfloat16* w_up = (const __nv_bfloat16*)d_in[5];
  const __nv_bfloat16* w_down = (const __nv_bfloat16*)d_in[6];
  const __nv_bfloat16* gate_w = (const __nv_bfloat16*)d_in[7];
  static EncodeFn enc = nullptr;
  static void* xbuf = nullptr;
  static bool ok = false;
  if (!enc) {
    cudaDriverEntryPointQueryResult qr;
    cudaGetDriverEntryPoint("cuTensorMapEncodeTiled", (void**)&enc, cudaEnableDefault, &qr);
    cudaFuncSetAttribute(fused_kernel, cudaFuncAttributeMaxDynamicSharedMemorySize, SMEM_BYTES);
    cudaGetSymbolAddress(&xbuf, g_X);
    cudaFuncAttributes fa;
    cudaFuncGetAttributes(&fa, fused_kernel);
    ok = (fa.numRegs == 128);
  }
  if (!ok) return;
  CUtensorMap tx, tg, tu, tg32, tu32, td, ts;
  {
    cuuint64_t gd[3] = {64, (cuuint64_t)S_, 7};
    cuuint64_t gs[2] = {(cuuint64_t)D_ * 2, 128};
    cuuint32_t bd[3] = {64, 64, 7};
    cuuint32_t es[3] = {1, 1, 1};
    enc(&tx, CU_TENSOR_MAP_DATA_TYPE_BFLOAT16, 3, const_cast<__nv_bfloat16*>(x), gd, gs, bd, es, CU_TENSOR_MAP_INTERLEAVE_NONE, CU_TENSOR_MAP_SWIZZLE_128B,
        CU_TENSOR_MAP_L2_PROMOTION_L2_128B, CU_TENSOR_MAP_FLOAT_OOB_FILL_NONE);
  }
  make_map(enc, &tg, w_gate, F_, D_, 64, 64, CU_TENSOR_MAP_SWIZZLE_128B);
  make_map(enc, &tu, w_up, F_, D_, 64, 64, CU_TENSOR_MAP_SWIZZLE_128B);
  make_map(enc, &tg32, w_gate, F_, D_, 32, 128, CU_TENSOR_MAP_SWIZZLE_64B);
  make_map(enc, &tu32, w_up, F_, D_, 32, 128, CU_TENSOR_MAP_SWIZZLE_64B);
  make_map(enc, &td, w_down, D_, F_, 64, 32, CU_TENSOR_MAP_SWIZZLE_128B);
  make_map(enc, &ts, (const __nv_bfloat16*)xbuf, XP / 2, 448, 64, 64, CU_TENSOR_MAP_SWIZZLE_NONE);
  fused_kernel<<<128, NTHREADS, SMEM_BYTES>>>(tx, tg, tu, tg32, tu32, td, ts, w_r, w_i, w_gate, w_up, w_down, gate_w, (__nv_bfloat16*)d_out);
}
```

```cpp
#include <cuda_runtime.h>
#include <cuda_bf16.h>
#include <cuda.h>
#include <stdint.h>

namespace {

constexpr int S_ = 2048, D_ = 448, F_ = 1792;
constexpr int NTHREADS = 512;
constexpr int SLOT = 16384, NSLOT = 7;
constexpr int HALF_XR = 57344;
constexpr int OFF_PQ = NSLOT * SLOT;
constexpr int OFF_R = OFF_PQ + HALF_XR;
constexpr int OFF_EXCH = OFF_PQ;
constexpr int OFF_WS = OFF_EXCH + 18432;
constexpr int OFF_TW = OFF_WS + 16384;
constexpr int OFF_MISC = OFF_R + HALF_XR;
constexpr int OFF_G = OFF_MISC;
constexpr int OFF_BAR = OFF_MISC + 512;
constexpr int SMEM_BYTES = OFF_BAR + 512;
constexpr int B_FULL = 0, B_EMPTY = 7, B_XFULL = 14  ;
constexpr int B_XFREE = 16  , B_PUBX = 18, B_RFREE = 19, B_LFREE = 20;
constexpr int B_PUBW = 21;
constexpr int B_PQFULL = 22  , B_RECV = 26, B_WFULL = 27, B_XCFULL = 28, B_PREP = 29, B_RFULL = 30, B_GFULL = 31, B_XDONE = 32, B_WDONE = 33, B_SEEN = 34, B_END = 35, B_PIN = 35;

constexpr int G_IMG = 224 * 56 * 2;

__device__ __align__(1024) unsigned char g_H[32 * 56 * 4096];
constexpr int XP = 28672;
__device__ __align__(1024) unsigned char g_X[448 * XP];
__device__ __align__(1024) unsigned char g_G[8 * G_IMG];
__device__ __align__(1024) float g_gate[S_];
__device__ __align__(128) unsigned int g_ep[128];
__device__ __align__(128) unsigned int g_cnt[8 * 32];

#define POLL ld_relaxed
#define PROF(role, idx) do {} while (0)
#define PROFG(role, idx) do {} while (0)

__device__ __forceinline__ uint32_t s2u(const void* p) { return (uint32_t)__cvta_generic_to_shared(p); }
__device__ __forceinline__ void mbar_init(uint32_t b, int c) { asm volatile("mbarrier.init.shared::cta.b64 [%0], %1;" :: "r"(b), "r"(c) : "memory"); }
__device__ __forceinline__ void mbar_expect(uint32_t b, int bytes) { asm volatile("mbarrier.arrive.expect_tx.shared::cta.b64 _, [%0], %1;" :: "r"(b), "r"(bytes) : "memory"); }
__device__ __forceinline__ void mbar_arrive(uint32_t b) { asm volatile("mbarrier.arrive.shared::cta.b64 _, [%0];" :: "r"(b) : "memory"); }
__device__ __forceinline__ void mbar_wait(uint32_t b, int ph) {
  asm volatile("{\n.reg .pred p;\n.reg .u32 c;\nmov.u32 c, 0;\nL_WAIT:\nmbarrier.try_wait.parity.shared::cta.b64 p, [%0], %1;\n@p bra.uni L_DONE;\n"
               "add.u32 c, c, 1;\nsetp.lt.u32 p, c, 4194304;\n@p bra.uni L_WAIT;\ntrap;\nL_DONE:\n}" :: "r"(b), "r"(ph) : "memory");
}
__device__ __forceinline__ void mbar_wait_cluster(uint32_t b, int ph) {
  asm volatile("{\n.reg .pred p;\n.reg .u32 c;\nmov.u32 c, 0;\nL_WAIT:\nmbarrier.try_wait.parity.acquire.cluster.shared::cta.b64 p, [%0], %1;\n@p bra.uni L_DONE;\n"
               "add.u32 c, c, 1;\nsetp.lt.u32 p, c, 4194304;\n@p bra.uni L_WAIT;\ntrap;\nL_DONE:\n}" :: "r"(b), "r"(ph) : "memory");
}
__device__ __forceinline__ uint32_t ld_acquire(const unsigned int* p) { uint32_t v; asm volatile("ld.acquire.gpu.global.u32 %0, [%1];" : "=r"(v) : "l"(p) : "memory"); return v; }
__device__ __forceinline__ uint32_t ld_relaxed(const unsigned int* p) { uint32_t v; asm volatile("ld.relaxed.gpu.global.u32 %0, [%1];" : "=r"(v) : "l"(p) : "memory"); return v; }
__device__ __forceinline__ void wait_ge(const unsigned int* p, uint32_t target) {
#pragma unroll 1
  for (int i = 0; i < (1 << 22); i++) { if ((int)(POLL(p) - target) >= 0) return; }
  __trap();
}
__device__ __forceinline__ void red_relaxed(unsigned int* p) { asm volatile("red.relaxed.gpu.global.add.u32 [%0], 1;" :: "l"(p) : "memory"); }
__device__ __forceinline__ bool elect() { uint32_t p; asm volatile("{\n.reg .pred p;\nelect.sync _|p, 0xffffffff;\nselp.u32 %0, 1, 0, p;\n}" : "=r"(p)); return p; }
__device__ __forceinline__ void fence_async_smem() { asm volatile("fence.proxy.async.shared::cta;" ::: "memory"); }
__device__ __forceinline__ void fence_async_global() { asm volatile("fence.proxy.async.global;" ::: "memory"); }
template <int ID, int N> __device__ __forceinline__ void bar_sync() { asm volatile("bar.sync %0, %1;" :: "n"(ID), "n"(N) : "memory"); }
template <int ID, int N> __device__ __forceinline__ void bar_arrive() { asm volatile("bar.arrive %0, %1;" :: "n"(ID), "n"(N) : "memory"); }
__device__ __forceinline__ void tma2d(uint32_t dst, const CUtensorMap* tm, int c0, int c1, uint32_t bar) {
  asm volatile("cp.async.bulk.tensor.2d.shared::cluster.global.mbarrier::complete_tx::bytes [%0], [%1, {%3, %4}], [%2];"
               :: "r"(dst), "l"(tm), "r"(bar), "r"(c0), "r"(c1) : "memory");
}
__device__ __forceinline__ void tma3d(uint32_t dst, const CUtensorMap* tm, int c0, int c1, int c2, uint32_t bar) {
  asm volatile("cp.async.bulk.tensor.3d.shared::cluster.global.mbarrier::complete_tx::bytes [%0], [%1, {%3, %4, %5}], [%2];"
               :: "r"(dst), "l"(tm), "r"(bar), "r"(c0), "r"(c1), "r"(c2) : "memory");
}
__device__ __forceinline__ void bulk_g2s(uint32_t dst, const void* src, int bytes, uint32_t bar) {
  asm volatile("cp.async.bulk.shared::cluster.global.mbarrier::complete_tx::bytes [%0], [%1], %2, [%3];"
               :: "r"(dst), "l"(src), "r"(bytes), "r"(bar) : "memory");
}
__device__ __forceinline__ void tma_store(const CUtensorMap* tm, int c0, int c1, uint32_t src) {
  asm volatile("cp.async.bulk.tensor.2d.global.shared::cta.bulk_group [%0, {%1, %2}], [%3];" :: "l"(tm), "r"(c0), "r"(c1), "r"(src) : "memory");
}
__device__ __forceinline__ void bulk_done() { asm volatile("cp.async.bulk.commit_group;\ncp.async.bulk.wait_group 0;\nfence.proxy.async.global;" ::: "memory"); }
__device__ __forceinline__ void sts32(uint32_t a, uint32_t x) { asm volatile("st.shared.b32 [%0], %1;" :: "r"(a), "r"(x) : "memory"); }
__device__ __forceinline__ void prefetch_l2(const void* src, int bytes) {
  asm volatile("cp.async.bulk.prefetch.L2.global [%0], %1;" :: "l"(src), "r"(bytes) : "memory");
}
__device__ __forceinline__ uint64_t mkdesc(uint32_t addr, uint32_t lbo, uint32_t sbo, uint32_t mode) {
  return (uint64_t)((addr & 0x3FFFF) >> 4) | ((uint64_t)(lbo >> 4) << 16) | ((uint64_t)(sbo >> 4) << 32) | ((uint64_t)mode << 62);
}
__device__ __forceinline__ void wg_fence() { asm volatile("wgmma.fence.sync.aligned;" ::: "memory"); }
__device__ __forceinline__ void wg_commit() { asm volatile("wgmma.commit_group.sync.aligned;" ::: "memory"); }
template <int N> __device__ __forceinline__ void wg_wait() { asm volatile("wgmma.wait_group.sync.aligned %0;" :: "n"(N) : "memory"); }
template <int N> __device__ __forceinline__ void keep(float (&d)[N]) {
#pragma unroll
  for (int i = 0; i < N; i++) asm volatile("" : "+f"(d[i]) :: "memory");
}
__device__ __forceinline__ uint32_t pack_bf16(float lo, float hi) { uint32_t r; asm("cvt.rn.bf16x2.f32 %0, %1, %2;" : "=r"(r) : "f"(hi), "f"(lo)); return r; }
__device__ __forceinline__ float bf16_round(float v) { return __bfloat162float(__float2bfloat16_rn(v)); }
__device__ __forceinline__ void sts128(uint32_t a, uint32_t x, uint32_t y, uint32_t z, uint32_t w) { asm volatile("st.shared.v4.b32 [%0], {%1,%2,%3,%4};" :: "r"(a), "r"(x), "r"(y), "r"(z), "r"(w) : "memory"); }
__device__ __forceinline__ float4 lds128f(uint32_t a) { float4 v; asm volatile("ld.shared.v4.f32 {%0,%1,%2,%3}, [%4];" : "=f"(v.x), "=f"(v.y), "=f"(v.z), "=f"(v.w) : "r"(a) : "memory"); return v; }

__device__ __forceinline__ uint2 lds64(uint32_t a) { uint2 v; asm volatile("ld.shared.v2.b32 {%0,%1}, [%2];" : "=r"(v.x), "=r"(v.y) : "r"(a) : "memory"); return v; }
__device__ __forceinline__ float bf_lo(uint32_t w) { return __uint_as_float(w << 16); }
__device__ __forceinline__ float bf_hi(uint32_t w) { return __uint_as_float(w & 0xffff0000u); }
__device__ __forceinline__ uint32_t opaque(uint32_t v) { asm volatile("" : "+r"(v)); return v; }
__device__ __forceinline__ uint4 ldg128(const void* p) { uint4 v; asm volatile("ld.global.nc.v4.b32 {%0,%1,%2,%3}, [%4];" : "=r"(v.x), "=r"(v.y), "=r"(v.z), "=r"(v.w) : "l"(p)); return v; }
__device__ __forceinline__ void stg128(void* p, uint32_t x, uint32_t y, uint32_t z, uint32_t w) { asm volatile("st.global.v4.b32 [%0], {%1,%2,%3,%4};" :: "l"(p), "r"(x), "r"(y), "r"(z), "r"(w) : "memory"); }
__device__ __forceinline__ void stg128_l2(void* p, uint32_t x, uint32_t y, uint32_t z, uint32_t w) { asm volatile("st.relaxed.gpu.global.v4.b32 [%0], {%1,%2,%3,%4};" :: "l"(p), "r"(x), "r"(y), "r"(z), "r"(w) : "memory"); }
__device__ __forceinline__ uint2 ldg64_l2(const void* p) { uint2 v; asm volatile("ld.relaxed.gpu.global.v2.b32 {%0,%1}, [%2];" : "=r"(v.x), "=r"(v.y) : "l"(p) : "memory"); return v; }
__device__ __forceinline__ void ldg128_l2(uint32_t (&v)[4], const void* p) { asm volatile("ld.relaxed.gpu.global.v4.b32 {%0,%1,%2,%3}, [%4];" : "=r"(v[0]), "=r"(v[1]), "=r"(v[2]), "=r"(v[3]) : "l"(p) : "memory"); }
__device__ __forceinline__ uint4 lds128(uint32_t a) { uint4 v; asm volatile("ld.shared.v4.b32 {%0,%1,%2,%3}, [%4];" : "=r"(v.x), "=r"(v.y), "=r"(v.z), "=r"(v.w) : "r"(a) : "memory"); return v; }
__device__ __forceinline__ uint32_t lds16(uint32_t a) { uint32_t v; asm volatile("ld.shared.u16 %0, [%1];" : "=r"(v) : "r"(a) : "memory"); return v; }
__device__ __forceinline__ void sts64(uint32_t a, uint32_t x, uint32_t y) { asm volatile("st.shared.v2.b32 [%0], {%1,%2};" :: "r"(a), "r"(x), "r"(y) : "memory"); }
template <int TB> __device__ __forceinline__ void wgmma_rs_128(float (&d)[64], const uint32_t (&a)[4], uint64_t db, int sc) {
  asm volatile("{\n.reg .pred p;\nsetp.ne.b32 p, %69, 0;\n"
    "wgmma.mma_async.sync.aligned.m64n128k16.f32.bf16.bf16 {%0, %1, %2, %3, %4, %5, %6, %7, %8, %9, %10, %11, %12, %13, %14, %15, %16, %17, %18, %19, %20, %21, %22, %23, %24, %25, %26, %27, %28, %29, %30, %31, %32, %33, %34, %35, %36, %37, %38, %39, %40, %41, %42, %43, %44, %45, %46, %47, %48, %49, %50, %51, %52, %53, %54, %55, %56, %57, %58, %59, %60, %61, %62, %63}, {%64, %65, %66, %67}, %68, p, 1, 1, %70;\n}\n"
    : "+f"(d[0]), "+f"(d[1]), "+f"(d[2]), "+f"(d[3]), "+f"(d[4]), "+f"(d[5]), "+f"(d[6]), "+f"(d[7]), "+f"(d[8]), "+f"(d[9]), "+f"(d[10]), "+f"(d[11]), "+f"(d[12]), "+f"(d[13]), "+f"(d[14]), "+f"(d[15]), "+f"(d[16]), "+f"(d[17]), "+f"(d[18]), "+f"(d[19]), "+f"(d[20]), "+f"(d[21]), "+f"(d[22]), "+f"(d[23]), "+f"(d[24]), "+f"(d[25]), "+f"(d[26]), "+f"(d[27]), "+f"(d[28]), "+f"(d[29]), "+f"(d[30]), "+f"(d[31]), "+f"(d[32]), "+f"(d[33]), "+f"(d[34]), "+f"(d[35]), "+f"(d[36]), "+f"(d[37]), "+f"(d[38]), "+f"(d[39]), "+f"(d[40]), "+f"(d[41]), "+f"(d[42]), "+f"(d[43]), "+f"(d[44]), "+f"(d[45]), "+f"(d[46]), "+f"(d[47]), "+f"(d[48]), "+f"(d[49]), "+f"(d[50]), "+f"(d[51]), "+f"(d[52]), "+f"(d[53]), "+f"(d[54]), "+f"(d[55]), "+f"(d[56]), "+f"(d[57]), "+f"(d[58]), "+f"(d[59]), "+f"(d[60]), "+f"(d[61]), "+f"(d[62]), "+f"(d[63])
    : "r"(a[0]), "r"(a[1]), "r"(a[2]), "r"(a[3]), "l"(db), "r"(sc), "n"(TB));
}
template <int TB> __device__ __forceinline__ void wgmma_rs_64(float (&d)[32], const uint32_t (&a)[4], uint64_t db, int sc) {
  asm volatile("{\n.reg .pred p;\nsetp.ne.b32 p, %37, 0;\n"
    "wgmma.mma_async.sync.aligned.m64n64k16.f32.bf16.bf16 {%0, %1, %2, %3, %4, %5, %6, %7, %8, %9, %10, %11, %12, %13, %14, %15, %16, %17, %18, %19, %20, %21, %22, %23, %24, %25, %26, %27, %28, %29, %30, %31}, {%32, %33, %34, %35}, %36, p, 1, 1, %38;\n}\n"
    : "+f"(d[0]), "+f"(d[1]), "+f"(d[2]), "+f"(d[3]), "+f"(d[4]), "+f"(d[5]), "+f"(d[6]), "+f"(d[7]), "+f"(d[8]), "+f"(d[9]), "+f"(d[10]), "+f"(d[11]), "+f"(d[12]), "+f"(d[13]), "+f"(d[14]), "+f"(d[15]), "+f"(d[16]), "+f"(d[17]), "+f"(d[18]), "+f"(d[19]), "+f"(d[20]), "+f"(d[21]), "+f"(d[22]), "+f"(d[23]), "+f"(d[24]), "+f"(d[25]), "+f"(d[26]), "+f"(d[27]), "+f"(d[28]), "+f"(d[29]), "+f"(d[30]), "+f"(d[31])
    : "r"(a[0]), "r"(a[1]), "r"(a[2]), "r"(a[3]), "l"(db), "r"(sc), "n"(TB));
}
template <int TB> __device__ __forceinline__ void wgmma_rs_56(float (&d)[28], const uint32_t (&a)[4], uint64_t db, int sc) {
  asm volatile("{\n.reg .pred p;\nsetp.ne.b32 p, %33, 0;\n"
    "wgmma.mma_async.sync.aligned.m64n56k16.f32.bf16.bf16 {%0, %1, %2, %3, %4, %5, %6, %7, %8, %9, %10, %11, %12, %13, %14, %15, %16, %17, %18, %19, %20, %21, %22, %23, %24, %25, %26, %27}, {%28, %29, %30, %31}, %32, p, 1, 1, %34;\n}\n"
    : "+f"(d[0]), "+f"(d[1]), "+f"(d[2]), "+f"(d[3]), "+f"(d[4]), "+f"(d[5]), "+f"(d[6]), "+f"(d[7]), "+f"(d[8]), "+f"(d[9]), "+f"(d[10]), "+f"(d[11]), "+f"(d[12]), "+f"(d[13]), "+f"(d[14]), "+f"(d[15]), "+f"(d[16]), "+f"(d[17]), "+f"(d[18]), "+f"(d[19]), "+f"(d[20]), "+f"(d[21]), "+f"(d[22]), "+f"(d[23]), "+f"(d[24]), "+f"(d[25]), "+f"(d[26]), "+f"(d[27])
    : "r"(a[0]), "r"(a[1]), "r"(a[2]), "r"(a[3]), "l"(db), "r"(sc), "n"(TB));
}
template <int TB> __device__ __forceinline__ void wgmma_rs_112(float (&d)[56], const uint32_t (&a)[4], uint64_t db, int sc) {
  asm volatile("{\n.reg .pred p;\nsetp.ne.b32 p, %61, 0;\n"
    "wgmma.mma_async.sync.aligned.m64n112k16.f32.bf16.bf16 {%0, %1, %2, %3, %4, %5, %6, %7, %8, %9, %10, %11, %12, %13, %14, %15, %16, %17, %18, %19, %20, %21, %22, %23, %24, %25, %26, %27, %28, %29, %30, %31, %32, %33, %34, %35, %36, %37, %38, %39, %40, %41, %42, %43, %44, %45, %46, %47, %48, %49, %50, %51, %52, %53, %54, %55}, {%56, %57, %58, %59}, %60, p, 1, 1, %62;\n}\n"
    : "+f"(d[0]), "+f"(d[1]), "+f"(d[2]), "+f"(d[3]), "+f"(d[4]), "+f"(d[5]), "+f"(d[6]), "+f"(d[7]), "+f"(d[8]), "+f"(d[9]), "+f"(d[10]), "+f"(d[11]), "+f"(d[12]), "+f"(d[13]), "+f"(d[14]), "+f"(d[15]), "+f"(d[16]), "+f"(d[17]), "+f"(d[18]), "+f"(d[19]), "+f"(d[20]), "+f"(d[21]), "+f"(d[22]), "+f"(d[23]), "+f"(d[24]), "+f"(d[25]), "+f"(d[26]), "+f"(d[27]), "+f"(d[28]), "+f"(d[29]), "+f"(d[30]), "+f"(d[31]), "+f"(d[32]), "+f"(d[33]), "+f"(d[34]), "+f"(d[35]), "+f"(d[36]), "+f"(d[37]), "+f"(d[38]), "+f"(d[39]), "+f"(d[40]), "+f"(d[41]), "+f"(d[42]), "+f"(d[43]), "+f"(d[44]), "+f"(d[45]), "+f"(d[46]), "+f"(d[47]), "+f"(d[48]), "+f"(d[49]), "+f"(d[50]), "+f"(d[51]), "+f"(d[52]), "+f"(d[53]), "+f"(d[54]), "+f"(d[55])
    : "r"(a[0]), "r"(a[1]), "r"(a[2]), "r"(a[3]), "l"(db), "r"(sc), "n"(TB));
}
template <int TA, int TB> __device__ __forceinline__ void wgmma_ss_56(float (&d)[28], uint64_t da, uint64_t db, int sc) {
  asm volatile("{\n.reg .pred p;\nsetp.ne.b32 p, %30, 0;\n"
    "wgmma.mma_async.sync.aligned.m64n56k16.f32.bf16.bf16 {%0, %1, %2, %3, %4, %5, %6, %7, %8, %9, %10, %11, %12, %13, %14, %15, %16, %17, %18, %19, %20, %21, %22, %23, %24, %25, %26, %27}, %28, %29, p, 1, 1, %31, %32;\n}\n"
    : "+f"(d[0]), "+f"(d[1]), "+f"(d[2]), "+f"(d[3]), "+f"(d[4]), "+f"(d[5]), "+f"(d[6]), "+f"(d[7]), "+f"(d[8]), "+f"(d[9]), "+f"(d[10]), "+f"(d[11]), "+f"(d[12]), "+f"(d[13]), "+f"(d[14]), "+f"(d[15]), "+f"(d[16]), "+f"(d[17]), "+f"(d[18]), "+f"(d[19]), "+f"(d[20]), "+f"(d[21]), "+f"(d[22]), "+f"(d[23]), "+f"(d[24]), "+f"(d[25]), "+f"(d[26]), "+f"(d[27])
    : "l"(da), "l"(db), "r"(sc), "n"(TA), "n"(TB));
}

__device__ __forceinline__ uint32_t cis(float a) { return pack_bf16(__cosf(a), __sinf(a)); }

typedef __nv_bfloat162 b2;
struct c2 { b2 x, y; };
__device__ __forceinline__ b2 as_b2(uint32_t u) { return *reinterpret_cast<b2*>(&u); }
__device__ __forceinline__ uint32_t as_u(b2 v) { return *reinterpret_cast<uint32_t*>(&v); }
__device__ __forceinline__ c2 mk(b2 x, b2 y) { c2 r; r.x = x; r.y = y; return r; }
__device__ __forceinline__ c2 cmul(c2 a, b2 wr, b2 wi) { return mk(__hfma2(a.x, wr, __hneg2(__hmul2(a.y, wi))), __hfma2(a.x, wi, __hmul2(a.y, wr))); }
__device__ __forceinline__ void fft4(c2& a0, c2& a1, c2& a2, c2& a3) {
  c2 t0 = mk(__hadd2(a0.x, a2.x), __hadd2(a0.y, a2.y)), t1 = mk(__hsub2(a0.x, a2.x), __hsub2(a0.y, a2.y));
  c2 t2 = mk(__hadd2(a1.x, a3.x), __hadd2(a1.y, a3.y)), t3 = mk(__hsub2(a1.x, a3.x), __hsub2(a1.y, a3.y));
  a0 = mk(__hadd2(t0.x, t2.x), __hadd2(t0.y, t2.y)); a2 = mk(__hsub2(t0.x, t2.x), __hsub2(t0.y, t2.y));
  a1 = mk(__hadd2(t1.x, t3.y), __hsub2(t1.y, t3.x)); a3 = mk(__hsub2(t1.x, t3.y), __hadd2(t1.y, t3.x));
}
__device__ __forceinline__ void fft4_s2(c2& a0, c2& a1, c2& a2, c2& a3, b2 r) {
  const b2 nr = __hneg2(r);
  c2 t0 = mk(__hfma2(a2.x, r, a0.x), __hfma2(a2.y, r, a0.y)), t1 = mk(__hfma2(a2.x, nr, a0.x), __hfma2(a2.y, nr, a0.y));
  c2 t2 = mk(__hadd2(a1.x, a3.x), __hadd2(a1.y, a3.y)), t3 = mk(__hsub2(a1.x, a3.x), __hsub2(a1.y, a3.y));
  a0 = mk(__hadd2(t0.x, t2.x), __hadd2(t0.y, t2.y)); a2 = mk(__hsub2(t0.x, t2.x), __hsub2(t0.y, t2.y));
  a1 = mk(__hadd2(t1.x, t3.y), __hsub2(t1.y, t3.x)); a3 = mk(__hsub2(t1.x, t3.y), __hadd2(t1.y, t3.x));
}
__device__ __forceinline__ void fft4_s13(c2& a0, c2& a1, c2& a2, c2& a3, b2 r) {
  const b2 nr = __hneg2(r);
  c2 t0 = mk(__hadd2(a0.x, a2.x), __hadd2(a0.y, a2.y)), t1 = mk(__hsub2(a0.x, a2.x), __hsub2(a0.y, a2.y));
  c2 t2 = mk(__hadd2(a1.x, a3.x), __hadd2(a1.y, a3.y)), t3 = mk(__hsub2(a1.x, a3.x), __hsub2(a1.y, a3.y));
  a0 = mk(__hfma2(t2.x, r, t0.x), __hfma2(t2.y, r, t0.y)); a2 = mk(__hfma2(t2.x, nr, t0.x), __hfma2(t2.y, nr, t0.y));
  a1 = mk(__hfma2(t3.y, r, t1.x), __hfma2(t3.x, nr, t1.y)); a3 = mk(__hfma2(t3.y, nr, t1.x), __hfma2(t3.x, r, t1.y));
}
__device__ __forceinline__ c2 rot1(c2 a) { return mk(__hadd2(a.x, a.y), __hsub2(a.y, a.x)); }
__device__ __forceinline__ c2 rot3(c2 a) { return mk(__hsub2(a.y, a.x), __hneg2(__hadd2(a.x, a.y))); }
__device__ __forceinline__ c2 mul_mi(c2 a) { return mk(a.y, __hneg2(a.x)); }
template <int O> __device__ __forceinline__ void fft8(c2 (&v)[16]) {
  const b2 r = as_b2(0x3F353F35u), nr = as_b2(0xBF35BF35u);
  fft4(v[O], v[O + 4], v[O + 8], v[O + 12]);
  fft4(v[O + 2], v[O + 6], v[O + 10], v[O + 14]);
  const c2 o0 = v[O + 2], o1 = rot1(v[O + 6]), o2 = v[O + 10], o3 = rot1(v[O + 14]);
  const c2 e0 = v[O], e1 = v[O + 4], e2 = v[O + 8], e3 = v[O + 12];
  v[O] = mk(__hadd2(e0.x, o0.x), __hadd2(e0.y, o0.y));              v[O + 8] = mk(__hsub2(e0.x, o0.x), __hsub2(e0.y, o0.y));
  v[O + 2] = mk(__hfma2(o1.x, r, e1.x), __hfma2(o1.y, r, e1.y));    v[O + 10] = mk(__hfma2(o1.x, nr, e1.x), __hfma2(o1.y, nr, e1.y));
  v[O + 4] = mk(__hadd2(e2.x, o2.y), __hsub2(e2.y, o2.x));          v[O + 12] = mk(__hsub2(e2.x, o2.y), __hadd2(e2.y, o2.x));
  v[O + 6] = mk(__hfma2(o3.y, r, e3.x), __hfma2(o3.x, nr, e3.y));   v[O + 14] = mk(__hfma2(o3.y, nr, e3.x), __hfma2(o3.x, r, e3.y));
}
__device__ __forceinline__ void fft16(c2 (&v)[16]) {
  const b2 r = as_b2(0x3F353F35u), c1 = as_b2(0x3F6D3F6Du), s1 = as_b2(0x3EC43EC4u), nc1 = as_b2(0xBF6DBF6Du), ns1 = as_b2(0xBEC4BEC4u);
#pragma unroll
  for (int a = 0; a < 4; a++) fft4(v[a], v[a + 4], v[a + 8], v[a + 12]);
  v[5] = cmul(v[5], c1, ns1); v[6] = rot1(v[6]); v[7] = cmul(v[7], s1, nc1);
  v[9] = rot1(v[9]); v[10] = mul_mi(v[10]); v[11] = rot3(v[11]);
  v[13] = cmul(v[13], s1, nc1); v[14] = rot3(v[14]); v[15] = cmul(v[15], nc1, s1);
  fft4(v[0], v[1], v[2], v[3]); fft4_s2(v[4], v[5], v[6], v[7], r); fft4_s13(v[8], v[9], v[10], v[11], r); fft4_s2(v[12], v[13], v[14], v[15], r);
  c2 t;
  t = v[1]; v[1] = v[4]; v[4] = t;  t = v[2]; v[2] = v[8]; v[8] = t;  t = v[3]; v[3] = v[12]; v[12] = t;
  t = v[6]; v[6] = v[9]; v[9] = t;  t = v[7]; v[7] = v[13]; v[13] = t; t = v[11]; v[11] = v[14]; v[14] = t;
}

__device__ __forceinline__ void columns(c2 (&v)[16], uint32_t sb, int t) {
  const int l16 = t & 15;
  const uint32_t row = sb + OFF_EXCH + (t >> 4) * 2304;
  const uint32_t pos = sb + OFF_EXCH + (t >> 3) * 144 + (t & 7) * 16;
#pragma unroll 1
  for (int ps = 0; ps < 6; ps++) {
    if (ps == 0 || ps == 5) { fft8<0>(v); fft8<1>(v); } else fft16(v);
    if (ps == 5) break;
    if (ps == 2) {
      const uint32_t ws = sb + OFF_WS + (l16 >> 1) * 128 + ((((t >> 4) + (l16 >> 1)) & 7) * 2 + (l16 & 1)) * 8;
      mbar_wait(sb + OFF_BAR + B_WFULL * 8, 0);
#pragma unroll
      for (int q = 0; q < 16; q++) {
        const uint2 w = lds64(ws + q * 1024);
        const c2 z = cmul(v[q], as_b2(w.x), as_b2(w.y));
        v[q] = mk(z.y, z.x);
      }
      continue;
    }
    {
      const bool full = ps == 0 || ps == 4;
      const uint32_t tw = sb + OFF_TW + (full ? ps * 2048 + t * 16 : 16384 + l16 * 16);
      const uint32_t st = full ? 2048 : 256;
#pragma unroll
      for (int i = 0; i < 4; i++) {
        const uint4 w4 = lds128(tw + i * st);
        const uint32_t w[4] = {w4.x, w4.y, w4.z, w4.w};
#pragma unroll
        for (int e = 0; e < 4; e++) v[4 * i + e] = cmul(v[4 * i + e], __low2bfloat162(as_b2(w[e])), __high2bfloat162(as_b2(w[e])));
      }
    }
    if (ps == 0) {
      mbar_wait(sb + OFF_BAR + B_XDONE * 8, 0);
#pragma unroll
      for (int q = 0; q < 8; q++) sts128(pos + q * 2304, as_u(v[2 * q].x), as_u(v[2 * q].y), as_u(v[2 * q + 1].x), as_u(v[2 * q + 1].y));
      bar_sync<3, 128>();
#pragma unroll
      for (int q = 0; q < 16; q++) { const uint2 a = lds64(row + q * 144 + l16 * 8); v[q] = mk(as_b2(a.x), as_b2(a.y)); }
    } else {
      __syncwarp();
#pragma unroll
      for (int q = 0; q < 16; q++) sts64(row + q * 144 + l16 * 8, as_u(v[q].x), as_u(v[q].y));
      if (ps == 4) bar_sync<3, 128>(); else __syncwarp();
      const uint32_t src = ps == 4 ? pos : row + l16 * 144, st = ps == 4 ? 2304 : 16;
#pragma unroll
      for (int q = 0; q < 8; q++) { const uint4 a = lds128(src + q * st); v[2 * q] = mk(as_b2(a.x), as_b2(a.y)); v[2 * q + 1] = mk(as_b2(a.z), as_b2(a.w)); }
    }
  }
}

template <int NH> __device__ __forceinline__ void h_epilogue(float (&acc)[NH * 8], unsigned char* gdst, uint32_t tag) {
#pragma unroll
  for (int c = 0; c < NH / 2; c++) {
    uint32_t pk[4];
#pragma unroll
    for (int i = 0; i < 4; i++) {
      float hv[2];
#pragma unroll
      for (int e = 0; e < 2; e++) {
        float hg = 0.5f * acc[c * 8 + i * 2 + e], up = acc[NH * 4 + c * 8 + i * 2 + e];
        float th; asm("tanh.approx.f32 %0, %1;" : "=f"(th) : "f"(hg));
        hv[e] = fmaf(hg, th, hg) * up;
      }
      pk[i] = pack_bf16(hv[0], hv[1]);
    }
    stg128_l2(gdst + c * 4096, (pk[0] & ~1u) | tag, pk[1], pk[2], pk[3]);
  }
}

__device__ __forceinline__ void frag_ready(uint32_t (&a)[4], uint32_t (&b)[4], uint32_t (&c)[4], uint32_t (&d)[4], const unsigned char* p, uint32_t tag) {
  asm volatile("{\n.reg .pred p;\n.reg .u32 c, m, q;\nmov.u32 c, 0;\nL_TRY:\n"
               "lop3.b32 m, %0, %4, %17, 0x7E;\nlop3.b32 q, %8, %12, %17, 0x7E;\nlop3.b32 m, m, q, 1, 0xA8;\nsetp.ne.u32 p, m, 0;\n"
               "vote.sync.any.pred p, p, 0xffffffff;\n@!p bra.uni L_OK;\n"
               "ld.relaxed.gpu.global.v4.b32 {%0,%1,%2,%3}, [%16];\nld.relaxed.gpu.global.v4.b32 {%4,%5,%6,%7}, [%16+4096];\n"
               "ld.relaxed.gpu.global.v4.b32 {%8,%9,%10,%11}, [%16+8192];\nld.relaxed.gpu.global.v4.b32 {%12,%13,%14,%15}, [%16+12288];\n"
               "add.u32 c, c, 1;\nsetp.lt.u32 p, c, 262144;\n@p bra.uni L_TRY;\ntrap;\nL_OK:\n}"
               : "+r"(a[0]), "+r"(a[1]), "+r"(a[2]), "+r"(a[3]), "+r"(b[0]), "+r"(b[1]), "+r"(b[2]), "+r"(b[3]),
                 "+r"(c[0]), "+r"(c[1]), "+r"(c[2]), "+r"(c[3]), "+r"(d[0]), "+r"(d[1]), "+r"(d[2]), "+r"(d[3])
               : "l"(p), "r"(tag) : "memory");
}

#define MAP 0
#define STAG 250
#define EARLYPF 1
#define LEAD2 0
#define LEAD1 2

__global__ void __cluster_dims__(2, 1, 1) __launch_bounds__(NTHREADS, 1)
fused_kernel(const __grid_constant__ CUtensorMap tm_x, const __grid_constant__ CUtensorMap tm_g, const __grid_constant__ CUtensorMap tm_u,
             const __grid_constant__ CUtensorMap tm_g32, const __grid_constant__ CUtensorMap tm_u32, const __grid_constant__ CUtensorMap tm_d,
             const __grid_constant__ CUtensorMap tm_s,
             const __nv_bfloat16* __restrict__ w_r, const __nv_bfloat16* __restrict__ w_i,
             const __nv_bfloat16* __restrict__ w_gate, const __nv_bfloat16* __restrict__ w_up,
             const __nv_bfloat16* __restrict__ w_down, const __nv_bfloat16* __restrict__ gate_w, __nv_bfloat16* __restrict__ out) {
  extern __shared__ __align__(1024) unsigned char smem[];
  const uint32_t sb = s2u(smem);
  const uint32_t bars = sb + OFF_BAR;
  const int tid = threadIdx.x, warp = __shfl_sync(0xffffffffu, tid >> 5, 0), lane = tid & 31;
  const int cl = blockIdx.x >> 1, kh = blockIdx.x & 1;
  const int n0 = cl < 4 ? cl : (cl < 36 ? (cl - 4) >> 3 : (cl - 36) / 7);
  const int m0 = cl < 4 ? 15 : (cl < 36 ? (cl - 4) & 7 : cl - 28 - 7 * n0);
  const int n = MAP == 0 ? n0 : (MAP == 1 ? (m0 & 3) : ((n0 & 1) | ((m0 & 1) << 1)));
  const int m = MAP == 0 ? m0 : (MAP == 1 ? ((m0 & 12) | n0) : ((m0 & 14) | (n0 >> 1)));
  const int j = kh * 4 + n, bid = m * 8 + n * 2 + kh;

  const int c64 = 224 * j + (j & 1) * 32;
  if (warp < 8) {
    asm volatile("setmaxnreg.inc.sync.aligned.u32 208;");
    const int wg = warp >> 2, w4 = warp & 3, g = lane >> 2, t = lane & 3;
    const int rh = wg ^ kh ^ 1;
    const int p = j & 1, r = (j >> 1) & 1, hh = j >> 2;
    const uint32_t epoch = ld_relaxed(&g_ep[bid]);
    if ((tid & 127) == 0) PROF(wg, 30);
#pragma unroll 1
    for (int it = tid; it < 392; it += 256) {
      const int kc = it / 28, sg = it - kc * 28;
      const int k = 2 * (28 * hh + sg) + r;
      const float kf = (float)k * (-6.283185307179586f / 448.0f), a0 = (float)(16 * kc + p) * kf;
      uint32_t c[4], s[4];
#pragma unroll
      for (int q = 0; q < 4; q++) {
        const float a1 = fmaf((float)(2 * q), kf, a0), a2 = fmaf((float)(2 * q + 8), kf, a0);
        c[q] = pack_bf16(__cosf(a1), __cosf(a2)); s[q] = pack_bf16(__sinf(a1), __sinf(a2));
        if (k == 0) s[q] = ((q ^ p) & 1) ? 0xBF80BF80u : 0x3F803F80u;
      }
      const uint32_t a = sb + 6 * SLOT + (kc * 56 + 2 * sg) * 16;
      sts128(a, c[0], c[1], c[2], c[3]);
      sts128(a + 16, s[0], s[1], s[2], s[3]);
    }
    if ((tid & 127) == 0) PROF(wg, 31);
    fence_async_smem();
    bar_sync<0, NTHREADS - 64>();
    asm volatile("barrier.cluster.arrive.relaxed.aligned;" ::: "memory");
    if ((tid & 127) == 0) PROF(wg, 1);

    uint32_t xa[28][4];
    {
      const uint32_t xb = sb + OFF_PQ + wg * HALF_XR + (w4 * 16 + (lane & 15)) * 128;
      mbar_wait(bars + (B_XFULL + wg) * 8, 0);
      if ((tid & 127) == 0) PROF(wg, 2);
#pragma unroll
      for (int kb = 0; kb < 7; kb++) {
#pragma unroll
        for (int kk = 0; kk < 4; kk++) {
          uint32_t a = xb + kb * 8192 + (((2 * kk + (lane >> 4)) ^ (lane & 7)) << 4);
          asm volatile("ldmatrix.sync.aligned.m8n8.x4.shared.b16 {%0,%1,%2,%3}, [%4];"
                       : "=r"(xa[kb * 4 + kk][0]), "=r"(xa[kb * 4 + kk][1]), "=r"(xa[kb * 4 + kk][2]), "=r"(xa[kb * 4 + kk][3]) : "r"(a) : "memory");
        }
      }
    }
    {
      uint32_t ad[7][4];
      const uint32_t sel = p ? 0x7632 : 0x5410;
      const uint32_t sgn = r ? 0xBF80BF80u : 0x3F803F80u;
#pragma unroll
      for (int jj = 0; jj < 7; jj++) {
#pragma unroll
        for (int i = 0; i < 4; i++) {
          int ks = 2 * jj + (i >> 1), rr = i & 1;
          uint32_t lo = __byte_perm(xa[ks][rr], xa[ks][rr + 2], sel);
          uint32_t hi = __byte_perm(xa[ks + 14][rr], xa[ks + 14][rr + 2], sel);
          asm("fma.rn.bf16x2 %0, %1, %2, %3;" : "=r"(ad[jj][i]) : "r"(hi), "r"(sgn), "r"(lo));
        }
      }
      __syncwarp();
      if (lane == 0) mbar_arrive(bars + (B_XFREE + wg) * 8);
      float acc[28];
      wg_fence();
      uint64_t db = mkdesc(sb + 6 * SLOT, 896, 128, 0);
#pragma unroll
      for (int jj = 0; jj < 7; jj++) wgmma_rs_56<0>(acc, ad[jj], db + jj * 112, jj != 0);
      wg_commit();
      wg_wait<0>(); keep(acc);
      if (lane == 0) mbar_arrive(bars + (B_EMPTY + 6) * 8);
      const uint32_t xc = sb + OFF_EXCH + wg * 8192 + t * 256 + w4 * 64 + g * 4;
      mbar_wait(bars + B_XFREE * 8, 0);
#pragma unroll
      for (int i = 0; i < 7; i++) {
        sts32(xc + i * 1024, pack_bf16(acc[4 * i], acc[4 * i + 1]));
        sts32(xc + i * 1024 + 32, pack_bf16(acc[4 * i + 2], acc[4 * i + 3]));
      }
      fence_async_smem();
      __syncwarp();
      if (lane == 0) mbar_arrive(bars + B_PUBX * 8);
    }
    if ((tid & 127) == 0) PROF(wg, 3);
    const uint32_t tag = ~epoch & 1;
    unsigned char* const hbase = g_H + (size_t)(m * 2 + kh) * (56 * 4096) + rh * 2048 + (tid & 127) * 16;
#pragma unroll 1
    for (int u = 0; u < 3; u++) {
      float acc[64];
      if (wg == 1) { if (u & 1) bar_sync<6, 256>(); else bar_sync<2, 256>(); }
      const uint32_t sbu = opaque(sb);
#pragma unroll
      for (int kb = 0; kb < 7; kb++) {
        mbar_wait(sbu + OFF_BAR + (B_FULL + kb) * 8, u & 1);
        wg_fence();
        uint64_t db = mkdesc(sbu + kb * SLOT, 8192, 1024, 1);
#pragma unroll
        for (int kk = 0; kk < 4; kk++) wgmma_rs_128<1>(acc, xa[kb * 4 + kk], db + kk * 128, (kb | kk) != 0);
        wg_commit();
        if (kb == LEAD1 && wg == 0) { if (u & 1) bar_arrive<6, 256>(); else bar_arrive<2, 256>(); }
        if (kb > 0) { wg_wait<1>(); if (lane == 0) mbar_arrive(sbu + OFF_BAR + (B_EMPTY + kb - 1) * 8); }
      }
      wg_wait<0>(); keep(acc);
      if (lane == 0) mbar_arrive(sbu + OFF_BAR + (B_EMPTY + 6) * 8);
      if ((tid & 127) == 0) PROF(wg, 4 + 2 * u);
      h_epilogue<8>(acc, hbase + (u * 16 + n * 4) * 4096, tag);
      if ((tid & 127) == 0) PROF(wg, 5 + 2 * u);
    }
    uint32_t ha[14][4][4];
    auto check = [&](int b0, int b1) {
#pragma unroll
      for (int b = b0; b < b1; b++) frag_ready(ha[b][0], ha[b][1], ha[b][2], ha[b][3], hbase + b * 16384, tag);
    };
    auto load = [&](int b0, int b1) {
#pragma unroll
      for (int i = b0; i < b1; i++) ldg128_l2(ha[i >> 2][i & 3], hbase + i * 4096);
    };
    {
      float acc[32];
      load(0, 3);
      if (wg == 1) bar_sync<6, 256>();
      const uint32_t sbu = opaque(sb);
#pragma unroll
      for (int it = 0; it < 4; it++) {
        mbar_wait(sbu + OFF_BAR + (B_FULL + it) * 8, 1);
        wg_fence();
        uint64_t db = mkdesc(sbu + it * SLOT, 8192, 512, 2);
#pragma unroll
        for (int kk = 0; kk < 8; kk++) if (it * 8 + kk < 28) wgmma_rs_64<1>(acc, xa[it * 8 + kk], db + kk * 64, (it | kk) != 0);
        wg_commit();
        if (it == 2 && wg == 0) bar_arrive<6, 256>();
        if (it > 0) {
          wg_wait<1>();
          if (lane == 0) mbar_arrive(sbu + OFF_BAR + (B_EMPTY + it - 1) * 8);
          if (it == 1) load(3, 11);
          if (it == 2) load(11, 16);
        }
      }
      wg_wait<0>(); keep(acc);
      if (lane == 0) mbar_arrive(sbu + OFF_BAR + (B_EMPTY + 3) * 8);
      if ((tid & 127) == 0) PROF(wg, 10);
      h_epilogue<4>(acc, hbase + (48 + n * 2) * 4096, tag);
    }
    asm volatile("barrier.cluster.wait.aligned;" ::: "memory");
    if ((tid & 127) == 0) PROF(wg, 11);

    float acc[56];
    check(0, 4);
    if (wg == 1) bar_sync<2, 256>();
#pragma unroll
    for (int b = 0; b < 14; b++) {
      if ((tid & 127) == 0) PROF(wg, 16 + b);
      if (b >= 3) mbar_wait(bars + (B_FULL + (b + 1) % 7) * 8, b < 6 || b == 13);
      else if (b == 0) mbar_wait(bars + B_RFULL * 8, 0);
      if (b == 4) check(4, 7);
      if (b == 7) check(7, 11);
      if (b == 11) check(11, 14);
      wg_fence();
      const uint64_t db = mkdesc(b < 3 ? sb + OFF_R + b * SLOT : sb + (b + 1) % 7 * SLOT, 8192, 1024, 1);
#pragma unroll
      for (int kk = 0; kk < 4; kk++) wgmma_rs_112<1>(acc, ha[b][kk], db + kk * 128, (b | kk) != 0);
      wg_commit();
      if (b == LEAD2 && wg == 0) bar_arrive<2, 256>();
      if (b == 0) load(16, 24);
      if (b == 1) load(24, 28);
      if (b == 4 || b == 5) load(8 * b - 4, 8 * b + 4);
      if (b == 7) load(44, 52);
      if (b == 8) load(52, 56);
      if (b > 0) wg_wait<1>();
      if (lane == 0) {
        if (b >= 4 && b <= 9) mbar_arrive(bars + (B_EMPTY + b % 7) * 8);
        if (b == 3) {
          mbar_arrive(bars + B_LFREE * 8);
          asm volatile("{\n.reg .b32 ra;\nmapa.shared::cluster.u32 ra, %0, %1;\nmbarrier.arrive.relaxed.cluster.shared::cluster.b64 _, [ra];\n}"
                       :: "r"(bars + B_RFREE * 8), "r"(kh ^ 1) : "memory");
        }
      }
    }
    const int t128 = tid & 127;
    wg_wait<0>(); keep(acc);
    if (wg == 0) {
      if (t128 == 0) PROF(wg, 12);
      mbar_wait_cluster(bars + B_RFREE * 8, 0);
      uint32_t rdst, rbar;
      asm volatile("mapa.shared::cluster.u32 %0, %1, %2;" : "=r"(rdst) : "r"(sb + OFF_R + t128 * 16), "r"(kh ^ 1));
      asm volatile("mapa.shared::cluster.u32 %0, %1, %2;" : "=r"(rbar) : "r"(bars + B_RECV * 8), "r"(kh ^ 1));
#pragma unroll
      for (int i = 0; i < 14; i++)
        asm volatile("st.async.weak.shared::cluster.mbarrier::complete_tx::bytes.v4.f32 [%0], {%1,%2,%3,%4}, [%5];"
                     :: "r"(rdst + i * 2048), "f"(acc[4 * i]), "f"(acc[4 * i + 1]), "f"(acc[4 * i + 2]), "f"(acc[4 * i + 3]), "r"(rbar) : "memory");
    } else {
      float spec[2][28];
      if (t128 == 0) PROF(wg, 12);
#pragma unroll
      for (int i = 0; i < 4; i++) {
        if (i == 0) mbar_wait(bars + B_GFULL * 8, 0);
        if (i >= 2) mbar_wait(bars + (B_FULL + i - 1) * 8, 1);
        mbar_wait(bars + (B_PQFULL + i) * 8, 0);
        if (i == 0 && t128 == 0) { PROF(wg, 13); g_ep[bid] = epoch + 1; }
        wg_fence();
        const uint64_t da = mkdesc(sb + OFF_PQ + i * 14336, 1024, 1024, 1);
        const uint64_t db = mkdesc(i < 2 ? sb + OFF_R + 28672 + i * (G_IMG / 2) : sb + (i - 1) * SLOT, 896, 128, 0);
#pragma unroll
        for (int kk = 0; kk < 7; kk++) wgmma_ss_56<1, 0>(spec[i >> 1], da + kk * 128, db + kk * 112, ((i & 1) | kk) != 0);
        wg_commit();
      }
      const float* gs = reinterpret_cast<const float*>(smem + OFF_G) + w4 * 16 + g;
      const float o0 = bf16_round(1.0f - gs[0]), o1 = bf16_round(1.0f - gs[8]);
      const float g0 = gs[0] * (1.0f / (float)(S_ * D_)), g1 = gs[8] * (1.0f / (float)(S_ * D_));
      mbar_wait_cluster(bars + B_RECV * 8, 0);
      if (t128 == 0) PROF(wg, 0);
#pragma unroll
      for (int i = 0; i < 14; i++) {
        const float4 o = lds128f(sb + OFF_R + t128 * 16 + i * 2048);
        acc[4 * i] = (acc[4 * i] + o.x) * o0; acc[4 * i + 1] = (acc[4 * i + 1] + o.y) * o0;
        acc[4 * i + 2] = (acc[4 * i + 2] + o.z) * o1; acc[4 * i + 3] = (acc[4 * i + 3] + o.w) * o1;
      }
      keep(acc);
      wg_wait<0>(); keep(spec[0]); keep(spec[1]);
      if (t128 == 0) PROF(wg, 14);
      bar_sync<5, 128>();
      const uint32_t st = sb + OFF_PQ + w4 * 3840;
#pragma unroll
      for (int i = 0; i < 7; i++) {
        uint32_t pk[4];
#pragma unroll
        for (int e = 0; e < 2; e++) {
          const int c = 2 * i + e, si = i * 4 + e;
          pk[2 * e] = pack_bf16(fmaf(g0, spec[0][si], acc[4 * c]), fmaf(g0, spec[1][si], acc[4 * c + 1]));
          pk[2 * e + 1] = pack_bf16(fmaf(g1, spec[0][si + 2], acc[4 * c + 2]), fmaf(g1, spec[1][si + 2], acc[4 * c + 3]));
        }
        asm volatile("stmatrix.sync.aligned.m8n8.x4.shared.b16 [%0], {%1,%2,%3,%4};"
                     :: "r"(st + (lane & 15) * 240 + (lane >> 4) * 16 + i * 32), "r"(pk[0]), "r"(pk[1]), "r"(pk[2]), "r"(pk[3]) : "memory");
      }
      __syncwarp();
      if (lane < 28) {
        const int r2 = lane >= 14, cc = lane - r2 * 14;
        unsigned char* ob = reinterpret_cast<unsigned char*>(out) + (size_t)(m * 128 + kh * 64 + w4 * 16 + r2) * (D_ * 2) + n * 224 + cc * 16;
        float4 v[8];
#pragma unroll
        for (int i = 0; i < 8; i++) v[i] = lds128f(st + r2 * 240 + cc * 16 + i * 480);
#pragma unroll
        for (int i = 0; i < 8; i++) stg128(ob + i * (D_ * 4), __float_as_uint(v[i].x), __float_as_uint(v[i].y), __float_as_uint(v[i].z), __float_as_uint(v[i].w));
      }
    }
    if (t128 == 0) { PROF(wg, 15); if (wg) { PROFG(4, 30); PROF(4, 31); } }
  } else if (warp < 12) {
    asm volatile("setmaxnreg.dec.sync.aligned.u32 72;");
    const int t = tid - 256;
    const int k = bid;
    if (t == 0) PROF(2, 0);
    uint4 gv[7];
#pragma unroll
    for (int i = 0; i < 7; i++) gv[i] = ldg128(reinterpret_cast<const uint4*>(gate_w) + i * 8 + (t & 7));
    if (t < 98) {
      int cid = m * 98 + t, kc = cid / 56, nn = cid - kc * 56;
      int d = 112 * n + 8 * (2 * (nn >> 3) + (nn & 1)) + (nn & 6) + kh;
      int dr = d > 224 ? d - 448 : d;
      const float df = (float)dr * (-6.283185307179586f / 448.0f);
      uint32_t pk[4];
#pragma unroll
      for (int e = 0; e < 4; e++) {
        const float a = (float)(4 * kc + e) * df;
        pk[e] = pack_bf16(2.0f * __cosf(a), 2.0f * __sinf(a));
      }
      if (kc == 0) pk[0] = (((d >> 1) ^ kh) & 1) ? 0xBF803F80u : 0x3F803F80u;
      stg128(g_G + (size_t)(n * 2 + kh) * G_IMG + cid * 16, pk[0], pk[1], pk[2], pk[3]);
    }
    bar_sync<0, NTHREADS - 64>();
    asm volatile("barrier.cluster.arrive.relaxed.aligned;" ::: "memory");
    {
      const int row = n * 16 + (t >> 3), l8 = t & 7;
      mbar_wait(bars + (B_XFULL + 1) * 8, 0);
      float sum = 0.f;
#pragma unroll
      for (int i = 0; i < 7; i++) {
        const uint4 a = lds128(sb + OFF_R + i * 8192 + row * 128 + ((l8 ^ (row & 7)) << 4));
        const uint32_t aa[4] = {a.x, a.y, a.z, a.w}, bb[4] = {gv[i].x, gv[i].y, gv[i].z, gv[i].w};
#pragma unroll
        for (int e = 0; e < 4; e++) {
          const uint32_t pr = as_u(__hmul2(as_b2(aa[e]), as_b2(bb[e])));
          sum += bf_lo(pr) + bf_hi(pr);
        }
      }
      sum += __shfl_xor_sync(0xffffffffu, sum, 1); sum += __shfl_xor_sync(0xffffffffu, sum, 2); sum += __shfl_xor_sync(0xffffffffu, sum, 4);
      if (l8 == 0) g_gate[m * 128 + kh * 64 + row] = bf16_round(__fdividef(1.0f, 1.0f + __expf(-bf16_round(sum))));
    }
    __syncwarp();
    if (lane == 0) mbar_arrive(bars + (B_XFREE + 1) * 8);
    if (t == 0) PROF(2, 11);
    mbar_wait(bars + B_XFREE * 8, 0);
    {
      const float u = -6.283185307179586f / 2048.0f, t2 = (float)(2 * t) * u;
#pragma unroll 1
      for (int i = 0; i < 4; i++) {
        const float q = (float)(2 * i);
        sts128(sb + OFF_TW + i * 2048 + t * 16, cis(t2 * q), cis((t2 + u) * q), cis(t2 * (q + 1.0f)), cis((t2 + u) * (q + 1.0f)));
      }
      const float l = (float)((t >> 1) & 15) * (8.0f * u), jj = (float)((t >> 5) * 4 + (t & 1) * 2);
      sts64(sb + OFF_TW + 16384 + t * 8, cis(l * jj), cis(l * (jj + 1.0f)));
    }
    mbar_wait(bars + B_PIN * 8, 0);
    mbar_wait(bars + (B_XFREE + 1) * 8, 0);
    if (t == 0) PROF(2, 4);
    {
      const uint32_t wa = sb + OFF_WS + (((t & 7) - bid) & 7) * 450 + (t >> 3) * 2, wc = wa + 448 - (t >> 3) * 4;
#pragma unroll 1
      for (int h = 0; h < 2; h++) {
        uint32_t w[4][8];
#pragma unroll
        for (int i = 0; i < 4; i++) {
#pragma unroll
          for (int e = 0; e < 4; e++) { w[i][2 * e] = lds16(wa + h * 128 + i * 32 + e * 3600); w[i][2 * e + 1] = lds16(wc - h * 128 - i * 32 + e * 3600); }
        }
#pragma unroll
        for (int i = 0; i < 4; i++)
          sts128(sb + OFF_R + h * 8192 + i * 2048 + t * 16, __byte_perm(w[i][0], w[i][1], 0x5410), __byte_perm(w[i][4], w[i][5], 0x5410), __byte_perm(w[i][2], w[i][3], 0x5410), __byte_perm(w[i][6], w[i][7], 0x5410));
      }
    }
    fence_async_smem();
    __syncwarp();
    if (lane == 0) mbar_arrive(bars + B_PUBW * 8);
    if (k < 113) {
      if (t == 0) PROF(2, 2);
      mbar_wait(bars + B_XCFULL * 8, 0);
      if (t == 0) PROF(2, 3);
      c2 v[16];
      uint2 xe[8], xo[8];
      const int sl = k == 112 ? 0 : k, hi = sl >= 56;
      const unsigned char* xs = g_X + (192 + (sl & 1) * 64 + hi * 72 + (sl & ~1) + ((t >> 4) & 1)) * XP + (t >> 5) * 256 + (t & 15) * 8;
#pragma unroll
      for (int jj = 0; jj < 8; jj++) { xe[jj] = ldg64_l2(xs + jj * 1024); xo[jj] = ldg64_l2(xs + jj * 1024 + 128); }
      {
        const float rr = (float)(t >> 4) * (-6.283185307179586f / 2048.0f);
#pragma unroll 1
        for (int i = 0; i < 4; i++) {
          const float l = (float)((t & 15) + 64 * i);
          sts128(sb + OFF_TW + 8192 + i * 2048 + t * 16, cis(rr * l), cis(rr * (l + 16.0f)), cis(rr * (l + 32.0f)), cis(rr * (l + 48.0f)));
        }
      }
      if (t == 0) PROF(2, 9);
      const uint32_t se = k == 0 ? 0x4410 : (k == 112 ? 0x4432 : 0x3210), so = k == 0 ? 0x4410 : (k == 112 ? 0x3244 : 0x3210);
#pragma unroll
      for (int jj = 0; jj < 8; jj++) {
        const uint2 e2 = xe[jj], o2 = xo[jj];
#pragma unroll
        for (int h = 0; h < 2; h++) {
          const b2 e = as_b2(__byte_perm(h ? e2.y : e2.x, 0, se)), o = as_b2(__byte_perm(h ? o2.y : o2.x, 0, so));
          const uint32_t s = as_u(__hadd2(e, o)), d = as_u(__hsub2(e, o)) ^ 0x80000000u;
          v[2 * jj + h] = mk(as_b2(__byte_perm(s, d, 0x5410)), as_b2(__byte_perm(s, d, 0x7632)));
        }
      }
      if (t == 0) PROF(2, 12);
      columns(v, sb, t);
      if (t == 0) PROF(2, 14);
      const int pre = (k == 112) ? 1 : 2 * k, pim = (k == 112) ? 1 : 2 * k + 1;
      const uint32_t pr = sb + OFF_EXCH + (t >> 5) * 256 + ((((lane >> 2) ^ pre) & 7) << 4) + (lane & 3) * 4;
      const uint32_t pi = sb + OFF_EXCH + 8192 + (t >> 5) * 256 + ((((lane >> 2) ^ pim) & 7) << 4) + (lane & 3) * 4;
      bar_sync<3, 128>();
#pragma unroll
      for (int jj = 0; jj < 8; jj++) {
        const b2 ar = as_b2(__byte_perm(as_u(v[2 * jj].y), as_u(v[2 * jj + 1].y), 0x5410)), br = as_b2(__byte_perm(as_u(v[2 * jj].y), as_u(v[2 * jj + 1].y), 0x7632));
        const b2 ai = as_b2(__byte_perm(as_u(v[2 * jj].x), as_u(v[2 * jj + 1].x), 0x5410)), bi = as_b2(__byte_perm(as_u(v[2 * jj].x), as_u(v[2 * jj + 1].x), 0x7632));
        sts32(pr + jj * 1024, as_u(__hadd2(ar, br)));
        sts32(pr + jj * 1024 + 128, as_u(k == 112 ? __hadd2(ai, bi) : __hsub2(ar, br)));
        sts32(pi + jj * 1024 + 128, as_u(__hadd2(ai, bi)));
        sts32(pi + jj * 1024, as_u(__hsub2(ai, bi)));
      }
      fence_async_smem();
      bar_sync<3, 128>();
      if (t == 0) {
        PROF(2, 5);
        tma_store(&tm_s, pre * 64, 0, sb + OFF_EXCH);
        if (k != 0 && k != 112) tma_store(&tm_s, pim * 64, 0, sb + OFF_EXCH + 8192);
        bulk_done();
      }
    }
    if (t == 0) { red_relaxed(&g_cnt[5 * 32]); PROF(2, 7); }
    if (t >= 32) {
      if (k >= 113) mbar_wait(bars + B_LFREE * 8, 0);
      __nanosleep((t >> 5) * STAG);
      wait_ge(&g_cnt[5 * 32], (lds64(sb + OFF_G + 256).x + 1) * 128);
      if (lane == 0) mbar_arrive(bars + B_SEEN * 8);
    }
    __syncwarp();
    asm volatile("barrier.cluster.wait.aligned;" ::: "memory");
  } else {
    asm volatile("setmaxnreg.dec.sync.aligned.u32 24;");
    auto wd_tile = [&](int b, uint32_t dst, uint32_t fb) {
#pragma unroll
      for (int hf = 0; hf < 2; hf++) {
        const int js = kh * 4 + (b < 12 ? (b & 3) : (b & 1) * 2 + hf);
        const int row = 224 * js + (b < 12 ? (js & 1) * 32 + (b >> 2) * 64 + hf * 32 : 192 - hf * 192);
        tma2d(dst + hf * 4096, &tm_d, 112 * n, row, fb);
        tma2d(dst + 8192 + hf * 4096, &tm_d, 112 * n + 64, row, fb);
      }
    };
    if (warp == 12) {
      if (elect()) {
        mbar_init(bars + B_XFULL * 8, 1); mbar_init(bars + (B_XFULL + 1) * 8, 1);
        fence_async_smem();
#pragma unroll
        for (int w = 0; w < 2; w++) {
          mbar_expect(bars + (B_XFULL + w) * 8, HALF_XR);
          tma3d(sb + OFF_PQ + w * HALF_XR, &tm_x, 0, m * 128 + (w ^ kh ^ 1) * 64, 0, bars + (B_XFULL + w) * 8);
        }
        PROF(3, 3);
#pragma unroll
        for (int i = 0; i < NSLOT; i++) mbar_init(bars + (B_FULL + i) * 8, 1);
        mbar_init(bars + B_PIN * 8, 1);
        fence_async_smem();
      }
      bar_arrive<0, NTHREADS - 64>();
#pragma unroll 1
      for (int i = 0; i < 6; i++) {
        if (elect()) {
          const uint32_t fb = bars + (B_FULL + i) * 8;
          mbar_expect(fb, SLOT);
          tma2d(sb + i * SLOT, &tm_g, c64, i * 64, fb);
          tma2d(sb + i * SLOT + 8192, &tm_u, c64, i * 64, fb);
          PROF(3, 4 + i);
        }
      }
      if (elect()) {
        prefetch_l2(reinterpret_cast<const unsigned char*>(w_r) + bid * 7200, 7200);
        prefetch_l2(reinterpret_cast<const unsigned char*>(w_i) + bid * 7200, 7200);
        prefetch_l2(reinterpret_cast<const unsigned char*>(w_gate) + bid * 12544, 12544);
        prefetch_l2(reinterpret_cast<const unsigned char*>(w_up) + bid * 12544, 12544);
        if (EARLYPF) prefetch_l2(reinterpret_cast<const unsigned char*>(w_down) + bid * 12544, 12544);
      }
    } else if (warp == 14) {
      if (elect()) {
#pragma unroll
        for (int i = B_EMPTY; i < B_END; i++)
          if (i < B_XFULL || i >= B_XFREE) mbar_init(bars + i * 8, i >= B_PQFULL ? 1 : (i == B_XFREE ? 4 : (i == B_PUBW ? 5 : 8)));
        asm volatile("fence.mbarrier_init.release.cluster;" ::: "memory");
        fence_async_smem();
        mbar_expect(bars + B_RECV * 8, 64 * 112 * 4);
      }
      bar_arrive<0, NTHREADS - 64>();
    }
    const uint32_t epoch = ld_relaxed(&g_ep[bid]);
    if (warp == 13 && lane == 0) { PROFG(4, 0); PROF(4, 1); }
    bar_sync<1, 128>();
    asm volatile("barrier.cluster.arrive.relaxed.aligned;" ::: "memory");
    if (warp == 12) {
      int slot = 6, ph = 1;
      auto wait_slot = [&]() { mbar_wait(bars + (B_EMPTY + slot) * 8, ph ^ (slot == 6)); };
      auto adv = [&]() { if (++slot == NSLOT) { slot = 0; ph ^= 1; } };
      const int c32 = 224 * j + ((j & 1) ? 0 : 192);
#pragma unroll 1
      for (int i = 6; i < 25; i++) {
        wait_slot();
        if (elect()) {
          const uint32_t dst = sb + slot * SLOT, fb = bars + (B_FULL + slot) * 8;
          const bool last = i >= 21;
          const int cc = last ? c32 : c64 + 64 * (i / 7), rr = last ? slot * 128 : slot * 64;
          mbar_expect(fb, SLOT);
          tma2d(dst, last ? &tm_g32 : &tm_g, cc, rr, fb);
          tma2d(dst + 8192, last ? &tm_u32 : &tm_u, cc, rr, fb);
        }
        adv();
      }
      if (lane == 0) PROF(3, 0);
#pragma unroll 1
      for (int i = 3; i < 16; i++) {
        if (lane == 0) PROF(3, 16 + i);
        if (i == 14) mbar_wait(bars + B_PREP * 8, 0);
        wait_slot();
        if (elect()) {
          const uint32_t fb = bars + (B_FULL + slot) * 8;
          mbar_expect(fb, i < 14 ? SLOT : G_IMG / 2);
          if (i < 14) wd_tile(i, sb + slot * SLOT, fb);
          else bulk_g2s(sb + slot * SLOT, g_G + (size_t)(n * 4 + i - 12) * (G_IMG / 2), G_IMG / 2, fb);
        }
        adv();
      }
      if (lane == 0) PROF(3, 2);
    } else if (warp == 13) {
      mbar_wait(bars + B_PUBX * 8, 0);
      if (elect()) {
        PROF(4, 8);
#pragma unroll
        for (int w = 0; w < 2; w++) tma_store(&tm_s, ((m * 2 + (w ^ kh ^ 1)) * 2 + (j & 1)) * 64, 192 + (j >> 1) * 64, sb + OFF_EXCH + w * 8192);
        bulk_done();
        red_relaxed(&g_cnt[(j >> 1) * 32]);
        mbar_arrive(bars + B_XDONE * 8);
        PROF(4, 12);
      }
      mbar_wait(bars + B_PUBW * 8, 0);
      if (elect()) {
        PROF(4, 9);
        tma_store(&tm_s, bid * 64, 64, sb + OFF_R);
        tma_store(&tm_s, bid * 64, 128, sb + OFF_R + 8192);
        bulk_done();
        red_relaxed(&g_cnt[4 * 32]);
        mbar_arrive(bars + B_WDONE * 8);
        PROF(4, 13);
      }
      mbar_wait(bars + B_PREP * 8, 0);
      mbar_wait(bars + B_LFREE * 8, 0);
      if (elect()) {
        mbar_expect(bars + B_GFULL * 8, G_IMG);
        bulk_g2s(sb + OFF_R + 28672, g_G + (size_t)(n * 2) * G_IMG, G_IMG, bars + B_GFULL * 8);
      }
    } else if (warp == 14) {
      mbar_wait(bars + (B_XFREE + 1) * 8, 0);
      asm volatile("fence.acq_rel.gpu;" ::: "memory");
      if (lane == 0) { mbar_arrive(bars + B_PUBW * 8); PROF(5, 3); }
      mbar_wait(bars + B_WDONE * 8, 0);
      wait_ge(&g_cnt[4 * 32], (epoch + 1) * 128);
      fence_async_global();
      if (elect()) {
        mbar_arrive(bars + B_PREP * 8);
        if (bid < 113) {
          mbar_expect(bars + B_WFULL * 8, 16384);
          bulk_g2s(sb + OFF_WS, g_X + (64 + bid) * XP, 16384, bars + B_WFULL * 8);
        }
        PROF(5, 17);
      }
    } else {
      mbar_wait(bars + B_XFREE * 8, 0);
      if (elect()) {
        sts32(sb + OFF_G + 256, epoch);
        mbar_expect(bars + B_PIN * 8, 14400);
        bulk_g2s(sb + OFF_WS, reinterpret_cast<const unsigned char*>(w_r) + bid * 7200, 7200, bars + B_PIN * 8);
        bulk_g2s(sb + OFF_WS + 7200, reinterpret_cast<const unsigned char*>(w_i) + bid * 7200, 7200, bars + B_PIN * 8);
        PROF(5, 2);
      }
      if (bid < 113) {
        const int sl = (bid == 112) ? 0 : bid;
        wait_ge(&g_cnt[((sl & 1) + 2 * ((sl >> 1) / 28)) * 32], (epoch + 1) * 32);
        if (elect()) { PROF(5, 16); mbar_arrive(bars + B_XCFULL * 8); }
      }
      if (!EARLYPF) {
#pragma unroll 1
        for (int i = lane; i < 98; i += 32) asm volatile("prefetch.global.L2 [%0];\nprefetch.global.L2 [%0+64];" :: "l"(reinterpret_cast<const unsigned char*>(w_down) + bid * 12544 + i * 128));
      }
      mbar_wait(bars + B_WDONE * 8, 0);
      if (elect()) mbar_expect(bars + B_RFULL * 8, 3 * SLOT);
#pragma unroll 1
      for (int i = 0; i < 3; i++) {
        mbar_wait(bars + (B_FULL + (i == 1 ? 0 : 3)) * 8, i == 0);
        if (elect()) wd_tile(i, sb + OFF_R + i * SLOT, bars + B_RFULL * 8);
      }
      if (lane == 0) PROF(5, 19);
      mbar_wait(bars + B_PREP * 8, 0);
      mbar_wait(bars + B_SEEN * 8, 0);
      fence_async_global();
      if (elect()) {
        PROF(5, 18);
        const unsigned char* src = g_X + (m * 2 + kh) * HALF_XR;
#pragma unroll
        for (int i = 0; i < 4; i++) {
          mbar_expect(bars + (B_PQFULL + i) * 8, i < 3 ? 14336 : 14336 + 256);
          bulk_g2s(sb + OFF_PQ + i * 14336, src + i * 14336, 14336, bars + (B_PQFULL + i) * 8);
        }
        bulk_g2s(sb + OFF_G, g_gate + m * 128 + kh * 64, 256, bars + (B_PQFULL + 3) * 8);
      }
    }
    __syncwarp();
    asm volatile("barrier.cluster.wait.aligned;" ::: "memory");
  }
}

typedef CUresult (*EncodeFn)(CUtensorMap*, CUtensorMapDataType, cuuint32_t, void*, const cuuint64_t*, const cuuint64_t*, const cuuint32_t*,
                             const cuuint32_t*, CUtensorMapInterleave, CUtensorMapSwizzle, CUtensorMapL2promotion, CUtensorMapFloatOOBfill);

void make_map(EncodeFn enc, CUtensorMap* tm, const void* base, int cols, int rows, int bc, int br, CUtensorMapSwizzle sw) {
  cuuint64_t gd[2] = {(cuuint64_t)cols, (cuuint64_t)rows};
  cuuint64_t gs[1] = {(cuuint64_t)cols * 2};
  cuuint32_t bd[2] = {(cuuint32_t)bc, (cuuint32_t)br};
  cuuint32_t es[2] = {1, 1};
  enc(tm, CU_TENSOR_MAP_DATA_TYPE_BFLOAT16, 2, const_cast<void*>(base), gd, gs, bd, es, CU_TENSOR_MAP_INTERLEAVE_NONE, sw,
      CU_TENSOR_MAP_L2_PROMOTION_L2_128B, CU_TENSOR_MAP_FLOAT_OOB_FILL_NONE);
}

}

extern "C" void kernel_launch(void* const* d_in, const int* in_sizes, int n_in, void* d_out, int out_size) {
  (void)in_sizes; (void)n_in; (void)out_size;
  const __nv_bfloat16* x = (const __nv_bfloat16*)d_in[0];
  const __nv_bfloat16* w_r = (const __nv_bfloat16*)d_in[1];
  const __nv_bfloat16* w_i = (const __nv_bfloat16*)d_in[2];
  const __nv_bfloat16* w_gate = (const __nv_bfloat16*)d_in[4];
  const __nv_bfloat16* w_up = (const __nv_bfloat16*)d_in[5];
  const __nv_bfloat16* w_down = (const __nv_bfloat16*)d_in[6];
  const __nv_bfloat16* gate_w = (const __nv_bfloat16*)d_in[7];
  static EncodeFn enc = nullptr;
  static void* xbuf = nullptr;
  static bool ok = false;
  if (!enc) {
    cudaDriverEntryPointQueryResult qr;
    cudaGetDriverEntryPoint("cuTensorMapEncodeTiled", (void**)&enc, cudaEnableDefault, &qr);
    cudaFuncSetAttribute(fused_kernel, cudaFuncAttributeMaxDynamicSharedMemorySize, SMEM_BYTES);
    cudaGetSymbolAddress(&xbuf, g_X);
    cudaFuncAttributes fa;
    cudaFuncGetAttributes(&fa, fused_kernel);
    ok = (fa.numRegs == 128);
  }
  if (!ok) return;
  CUtensorMap tx, tg, tu, tg32, tu32, td, ts;
  {
    cuuint64_t gd[3] = {64, (cuuint64_t)S_, 7};
    cuuint64_t gs[2] = {(cuuint64_t)D_ * 2, 128};
    cuuint32_t bd[3] = {64, 64, 7};
    cuuint32_t es[3] = {1, 1, 1};
    enc(&tx, CU_TENSOR_MAP_DATA_TYPE_BFLOAT16, 3, const_cast<__nv_bfloat16*>(x), gd, gs, bd, es, CU_TENSOR_MAP_INTERLEAVE_NONE, CU_TENSOR_MAP_SWIZZLE_128B,
        CU_TENSOR_MAP_L2_PROMOTION_L2_128B, CU_TENSOR_MAP_FLOAT_OOB_FILL_NONE);
  }
  make_map(enc, &tg, w_gate, F_, D_, 64, 64, CU_TENSOR_MAP_SWIZZLE_128B);
  make_map(enc, &tu, w_up, F_, D_, 64, 64, CU_TENSOR_MAP_SWIZZLE_128B);
  make_map(enc, &tg32, w_gate, F_, D_, 32, 128, CU_TENSOR_MAP_SWIZZLE_64B);
  make_map(enc, &tu32, w_up, F_, D_, 32, 128, CU_TENSOR_MAP_SWIZZLE_64B);
  make_map(enc, &td, w_down, D_, F_, 64, 32, CU_TENSOR_MAP_SWIZZLE_128B);
  make_map(enc, &ts, (const __nv_bfloat16*)xbuf, XP / 2, 448, 64, 64, CU_TENSOR_MAP_SWIZZLE_NONE);
  fused_kernel<<<128, NTHREADS, SMEM_BYTES>>>(tx, tg, tu, tg32, tu32, td, ts, w_r, w_i, w_gate, w_up, w_down, gate_w, (__nv_bfloat16*)d_out);
}
```

```cpp
#include <cuda_runtime.h>
#include <cuda_bf16.h>
#include <cuda.h>
#include <stdint.h>

namespace {

constexpr int S_ = 2048, D_ = 448, F_ = 1792;
constexpr int NTHREADS = 512;
constexpr int SLOT = 16384, NSLOT = 7;
constexpr int HALF_XR = 57344;
constexpr int OFF_PQ = NSLOT * SLOT;
constexpr int OFF_R = OFF_PQ + HALF_XR;
constexpr int OFF_EXCH = OFF_PQ;
constexpr int OFF_WS = OFF_EXCH + 18432;
constexpr int OFF_TW = OFF_WS + 16384;
constexpr int OFF_MISC = OFF_R + HALF_XR;
constexpr int OFF_G = OFF_MISC;
constexpr int OFF_BAR = OFF_MISC + 512;
constexpr int SMEM_BYTES = OFF_BAR + 512;
constexpr int B_FULL = 0, B_EMPTY = 7, B_XFULL = 14  ;
constexpr int B_XFREE = 16  , B_PUBX = 18, B_RFREE = 19, B_LFREE = 20;
constexpr int B_PUBW = 21;
constexpr int B_PQFULL = 22  , B_RECV = 26, B_WFULL = 27, B_XCFULL = 28, B_PREP = 29, B_RFULL = 30, B_GFULL = 31, B_XDONE = 32, B_WDONE = 33, B_SEEN = 34, B_END = 35, B_PIN = 35;

constexpr int G_IMG = 224 * 56 * 2;

__device__ __align__(1024) unsigned char g_H[32 * 56 * 4096];
constexpr int XP = 28672;
__device__ __align__(1024) unsigned char g_X[448 * XP];
__device__ __align__(1024) unsigned char g_G[8 * G_IMG];
__device__ __align__(1024) float g_gate[S_];
__device__ __align__(128) unsigned int g_ep[128];
__device__ __align__(128) unsigned int g_cnt[8 * 32];

#define POLL ld_relaxed
#define PROF(role, idx) do {} while (0)
#define PROFG(role, idx) do {} while (0)

__device__ __forceinline__ uint32_t s2u(const void* p) { return (uint32_t)__cvta_generic_to_shared(p); }
__device__ __forceinline__ void mbar_init(uint32_t b, int c) { asm volatile("mbarrier.init.shared::cta.b64 [%0], %1;" :: "r"(b), "r"(c) : "memory"); }
__device__ __forceinline__ void mbar_expect(uint32_t b, int bytes) { asm volatile("mbarrier.arrive.expect_tx.shared::cta.b64 _, [%0], %1;" :: "r"(b), "r"(bytes) : "memory"); }
__device__ __forceinline__ void mbar_arrive(uint32_t b) { asm volatile("mbarrier.arrive.shared::cta.b64 _, [%0];" :: "r"(b) : "memory"); }
__device__ __forceinline__ void mbar_wait(uint32_t b, int ph) {
  asm volatile("{\n.reg .pred p;\n.reg .u32 c;\nmov.u32 c, 0;\nL_WAIT:\nmbarrier.try_wait.parity.shared::cta.b64 p, [%0], %1;\n@p bra.uni L_DONE;\n"
               "add.u32 c, c, 1;\nsetp.lt.u32 p, c, 4194304;\n@p bra.uni L_WAIT;\ntrap;\nL_DONE:\n}" :: "r"(b), "r"(ph) : "memory");
}
__device__ __forceinline__ void mbar_wait_cluster(uint32_t b, int ph) {
  asm volatile("{\n.reg .pred p;\n.reg .u32 c;\nmov.u32 c, 0;\nL_WAIT:\nmbarrier.try_wait.parity.acquire.cluster.shared::cta.b64 p, [%0], %1;\n@p bra.uni L_DONE;\n"
               "add.u32 c, c, 1;\nsetp.lt.u32 p, c, 4194304;\n@p bra.uni L_WAIT;\ntrap;\nL_DONE:\n}" :: "r"(b), "r"(ph) : "memory");
}
__device__ __forceinline__ uint32_t ld_acquire(const unsigned int* p) { uint32_t v; asm volatile("ld.acquire.gpu.global.u32 %0, [%1];" : "=r"(v) : "l"(p) : "memory"); return v; }
__device__ __forceinline__ uint32_t ld_relaxed(const unsigned int* p) { uint32_t v; asm volatile("ld.relaxed.gpu.global.u32 %0, [%1];" : "=r"(v) : "l"(p) : "memory"); return v; }
__device__ __forceinline__ void wait_ge(const unsigned int* p, uint32_t target) {
#pragma unroll 1
  for (int i = 0; i < (1 << 22); i++) { if ((int)(POLL(p) - target) >= 0) return; }
  __trap();
}
__device__ __forceinline__ void red_relaxed(unsigned int* p) { asm volatile("red.relaxed.gpu.global.add.u32 [%0], 1;" :: "l"(p) : "memory"); }
__device__ __forceinline__ bool elect() { uint32_t p; asm volatile("{\n.reg .pred p;\nelect.sync _|p, 0xffffffff;\nselp.u32 %0, 1, 0, p;\n}" : "=r"(p)); return p; }
__device__ __forceinline__ void fence_async_smem() { asm volatile("fence.proxy.async.shared::cta;" ::: "memory"); }
__device__ __forceinline__ void fence_async_global() { asm volatile("fence.proxy.async.global;" ::: "memory"); }
template <int ID, int N> __device__ __forceinline__ void bar_sync() { asm volatile("bar.sync %0, %1;" :: "n"(ID), "n"(N) : "memory"); }
template <int ID, int N> __device__ __forceinline__ void bar_arrive() { asm volatile("bar.arrive %0, %1;" :: "n"(ID), "n"(N) : "memory"); }
__device__ __forceinline__ void tma2d(uint32_t dst, const CUtensorMap* tm, int c0, int c1, uint32_t bar) {
  asm volatile("cp.async.bulk.tensor.2d.shared::cluster.global.mbarrier::complete_tx::bytes [%0], [%1, {%3, %4}], [%2];"
               :: "r"(dst), "l"(tm), "r"(bar), "r"(c0), "r"(c1) : "memory");
}
__device__ __forceinline__ void tma3d(uint32_t dst, const CUtensorMap* tm, int c0, int c1, int c2, uint32_t bar) {
  asm volatile("cp.async.bulk.tensor.3d.shared::cluster.global.mbarrier::complete_tx::bytes [%0], [%1, {%3, %4, %5}], [%2];"
               :: "r"(dst), "l"(tm), "r"(bar), "r"(c0), "r"(c1), "r"(c2) : "memory");
}
__device__ __forceinline__ void bulk_g2s(uint32_t dst, const void* src, int bytes, uint32_t bar) {
  asm volatile("cp.async.bulk.shared::cluster.global.mbarrier::complete_tx::bytes [%0], [%1], %2, [%3];"
               :: "r"(dst), "l"(src), "r"(bytes), "r"(bar) : "memory");
}
__device__ __forceinline__ void tma_store(const CUtensorMap* tm, int c0, int c1, uint32_t src) {
  asm volatile("cp.async.bulk.tensor.2d.global.shared::cta.bulk_group [%0, {%1, %2}], [%3];" :: "l"(tm), "r"(c0), "r"(c1), "r"(src) : "memory");
}
__device__ __forceinline__ void bulk_done() { asm volatile("cp.async.bulk.commit_group;\ncp.async.bulk.wait_group 0;\nfence.proxy.async.global;" ::: "memory"); }
__device__ __forceinline__ void sts32(uint32_t a, uint32_t x) { asm volatile("st.shared.b32 [%0], %1;" :: "r"(a), "r"(x) : "memory"); }
__device__ __forceinline__ void prefetch_l2(const void* src, int bytes) {
  asm volatile("cp.async.bulk.prefetch.L2.global [%0], %1;" :: "l"(src), "r"(bytes) : "memory");
}
__device__ __forceinline__ uint64_t mkdesc(uint32_t addr, uint32_t lbo, uint32_t sbo, uint32_t mode) {
  return (uint64_t)((addr & 0x3FFFF) >> 4) | ((uint64_t)(lbo >> 4) << 16) | ((uint64_t)(sbo >> 4) << 32) | ((uint64_t)mode << 62);
}
__device__ __forceinline__ void wg_fence() { asm volatile("wgmma.fence.sync.aligned;" ::: "memory"); }
__device__ __forceinline__ void wg_commit() { asm volatile("wgmma.commit_group.sync.aligned;" ::: "memory"); }
template <int N> __device__ __forceinline__ void wg_wait() { asm volatile("wgmma.wait_group.sync.aligned %0;" :: "n"(N) : "memory"); }
template <int N> __device__ __forceinline__ void keep(float (&d)[N]) {
#pragma unroll
  for (int i = 0; i < N; i++) asm volatile("" : "+f"(d[i]) :: "memory");
}
__device__ __forceinline__ uint32_t pack_bf16(float lo, float hi) { uint32_t r; asm("cvt.rn.bf16x2.f32 %0, %1, %2;" : "=r"(r) : "f"(hi), "f"(lo)); return r; }
__device__ __forceinline__ float bf16_round(float v) { return __bfloat162float(__float2bfloat16_rn(v)); }
__device__ __forceinline__ void sts128(uint32_t a, uint32_t x, uint32_t y, uint32_t z, uint32_t w) { asm volatile("st.shared.v4.b32 [%0], {%1,%2,%3,%4};" :: "r"(a), "r"(x), "r"(y), "r"(z), "r"(w) : "memory"); }
__device__ __forceinline__ float4 lds128f(uint32_t a) { float4 v; asm volatile("ld.shared.v4.f32 {%0,%1,%2,%3}, [%4];" : "=f"(v.x), "=f"(v.y), "=f"(v.z), "=f"(v.w) : "r"(a) : "memory"); return v; }

__device__ __forceinline__ uint2 lds64(uint32_t a) { uint2 v; asm volatile("ld.shared.v2.b32 {%0,%1}, [%2];" : "=r"(v.x), "=r"(v.y) : "r"(a) : "memory"); return v; }
__device__ __forceinline__ float bf_lo(uint32_t w) { return __uint_as_float(w << 16); }
__device__ __forceinline__ float bf_hi(uint32_t w) { return __uint_as_float(w & 0xffff0000u); }
__device__ __forceinline__ uint32_t opaque(uint32_t v) { asm volatile("" : "+r"(v)); return v; }
__device__ __forceinline__ uint4 ldg128(const void* p) { uint4 v; asm volatile("ld.global.nc.v4.b32 {%0,%1,%2,%3}, [%4];" : "=r"(v.x), "=r"(v.y), "=r"(v.z), "=r"(v.w) : "l"(p)); return v; }
__device__ __forceinline__ void stg128(void* p, uint32_t x, uint32_t y, uint32_t z, uint32_t w) { asm volatile("st.global.v4.b32 [%0], {%1,%2,%3,%4};" :: "l"(p), "r"(x), "r"(y), "r"(z), "r"(w) : "memory"); }
__device__ __forceinline__ void stg128_l2(void* p, uint32_t x, uint32_t y, uint32_t z, uint32_t w) { asm volatile("st.relaxed.gpu.global.v4.b32 [%0], {%1,%2,%3,%4};" :: "l"(p), "r"(x), "r"(y), "r"(z), "r"(w) : "memory"); }
__device__ __forceinline__ uint2 ldg64_l2(const void* p) { uint2 v; asm volatile("ld.relaxed.gpu.global.v2.b32 {%0,%1}, [%2];" : "=r"(v.x), "=r"(v.y) : "l"(p) : "memory"); return v; }
__device__ __forceinline__ void ldg128_l2(uint32_t (&v)[4], const void* p) { asm volatile("ld.relaxed.gpu.global.v4.b32 {%0,%1,%2,%3}, [%4];" : "=r"(v[0]), "=r"(v[1]), "=r"(v[2]), "=r"(v[3]) : "l"(p) : "memory"); }
__device__ __forceinline__ uint4 lds128(uint32_t a) { uint4 v; asm volatile("ld.shared.v4.b32 {%0,%1,%2,%3}, [%4];" : "=r"(v.x), "=r"(v.y), "=r"(v.z), "=r"(v.w) : "r"(a) : "memory"); return v; }
__device__ __forceinline__ uint32_t lds16(uint32_t a) { uint32_t v; asm volatile("ld.shared.u16 %0, [%1];" : "=r"(v) : "r"(a) : "memory"); return v; }
__device__ __forceinline__ void sts64(uint32_t a, uint32_t x, uint32_t y) { asm volatile("st.shared.v2.b32 [%0], {%1,%2};" :: "r"(a), "r"(x), "r"(y) : "memory"); }
template <int TB> __device__ __forceinline__ void wgmma_rs_128(float (&d)[64], const uint32_t (&a)[4], uint64_t db, int sc) {
  asm volatile("{\n.reg .pred p;\nsetp.ne.b32 p, %69, 0;\n"
    "wgmma.mma_async.sync.aligned.m64n128k16.f32.bf16.bf16 {%0, %1, %2, %3, %4, %5, %6, %7, %8, %9, %10, %11, %12, %13, %14, %15, %16, %17, %18, %19, %20, %21, %22, %23, %24, %25, %26, %27, %28, %29, %30, %31, %32, %33, %34, %35, %36, %37, %38, %39, %40, %41, %42, %43, %44, %45, %46, %47, %48, %49, %50, %51, %52, %53, %54, %55, %56, %57, %58, %59, %60, %61, %62, %63}, {%64, %65, %66, %67}, %68, p, 1, 1, %70;\n}\n"
    : "+f"(d[0]), "+f"(d[1]), "+f"(d[2]), "+f"(d[3]), "+f"(d[4]), "+f"(d[5]), "+f"(d[6]), "+f"(d[7]), "+f"(d[8]), "+f"(d[9]), "+f"(d[10]), "+f"(d[11]), "+f"(d[12]), "+f"(d[13]), "+f"(d[14]), "+f"(d[15]), "+f"(d[16]), "+f"(d[17]), "+f"(d[18]), "+f"(d[19]), "+f"(d[20]), "+f"(d[21]), "+f"(d[22]), "+f"(d[23]), "+f"(d[24]), "+f"(d[25]), "+f"(d[26]), "+f"(d[27]), "+f"(d[28]), "+f"(d[29]), "+f"(d[30]), "+f"(d[31]), "+f"(d[32]), "+f"(d[33]), "+f"(d[34]), "+f"(d[35]), "+f"(d[36]), "+f"(d[37]), "+f"(d[38]), "+f"(d[39]), "+f"(d[40]), "+f"(d[41]), "+f"(d[42]), "+f"(d[43]), "+f"(d[44]), "+f"(d[45]), "+f"(d[46]), "+f"(d[47]), "+f"(d[48]), "+f"(d[49]), "+f"(d[50]), "+f"(d[51]), "+f"(d[52]), "+f"(d[53]), "+f"(d[54]), "+f"(d[55]), "+f"(d[56]), "+f"(d[57]), "+f"(d[58]), "+f"(d[59]), "+f"(d[60]), "+f"(d[61]), "+f"(d[62]), "+f"(d[63])
    : "r"(a[0]), "r"(a[1]), "r"(a[2]), "r"(a[3]), "l"(db), "r"(sc), "n"(TB));
}
template <int TB> __device__ __forceinline__ void wgmma_rs_64(float (&d)[32], const uint32_t (&a)[4], uint64_t db, int sc) {
  asm volatile("{\n.reg .pred p;\nsetp.ne.b32 p, %37, 0;\n"
    "wgmma.mma_async.sync.aligned.m64n64k16.f32.bf16.bf16 {%0, %1, %2, %3, %4, %5, %6, %7, %8, %9, %10, %11, %12, %13, %14, %15, %16, %17, %18, %19, %20, %21, %22, %23, %24, %25, %26, %27, %28, %29, %30, %31}, {%32, %33, %34, %35}, %36, p, 1, 1, %38;\n}\n"
    : "+f"(d[0]), "+f"(d[1]), "+f"(d[2]), "+f"(d[3]), "+f"(d[4]), "+f"(d[5]), "+f"(d[6]), "+f"(d[7]), "+f"(d[8]), "+f"(d[9]), "+f"(d[10]), "+f"(d[11]), "+f"(d[12]), "+f"(d[13]), "+f"(d[14]), "+f"(d[15]), "+f"(d[16]), "+f"(d[17]), "+f"(d[18]), "+f"(d[19]), "+f"(d[20]), "+f"(d[21]), "+f"(d[22]), "+f"(d[23]), "+f"(d[24]), "+f"(d[25]), "+f"(d[26]), "+f"(d[27]), "+f"(d[28]), "+f"(d[29]), "+f"(d[30]), "+f"(d[31])
    : "r"(a[0]), "r"(a[1]), "r"(a[2]), "r"(a[3]), "l"(db), "r"(sc), "n"(TB));
}
template <int TB> __device__ __forceinline__ void wgmma_rs_56(float (&d)[28], const uint32_t (&a)[4], uint64_t db, int sc) {
  asm volatile("{\n.reg .pred p;\nsetp.ne.b32 p, %33, 0;\n"
    "wgmma.mma_async.sync.aligned.m64n56k16.f32.bf16.bf16 {%0, %1, %2, %3, %4, %5, %6, %7, %8, %9, %10, %11, %12, %13, %14, %15, %16, %17, %18, %19, %20, %21, %22, %23, %24, %25, %26, %27}, {%28, %29, %30, %31}, %32, p, 1, 1, %34;\n}\n"
    : "+f"(d[0]), "+f"(d[1]), "+f"(d[2]), "+f"(d[3]), "+f"(d[4]), "+f"(d[5]), "+f"(d[6]), "+f"(d[7]), "+f"(d[8]), "+f"(d[9]), "+f"(d[10]), "+f"(d[11]), "+f"(d[12]), "+f"(d[13]), "+f"(d[14]), "+f"(d[15]), "+f"(d[16]), "+f"(d[17]), "+f"(d[18]), "+f"(d[19]), "+f"(d[20]), "+f"(d[21]), "+f"(d[22]), "+f"(d[23]), "+f"(d[24]), "+f"(d[25]), "+f"(d[26]), "+f"(d[27])
    : "r"(a[0]), "r"(a[1]), "r"(a[2]), "r"(a[3]), "l"(db), "r"(sc), "n"(TB));
}
template <int TB> __device__ __forceinline__ void wgmma_rs_112(float (&d)[56], const uint32_t (&a)[4], uint64_t db, int sc) {
  asm volatile("{\n.reg .pred p;\nsetp.ne.b32 p, %61, 0;\n"
    "wgmma.mma_async.sync.aligned.m64n112k16.f32.bf16.bf16 {%0, %1, %2, %3, %4, %5, %6, %7, %8, %9, %10, %11, %12, %13, %14, %15, %16, %17, %18, %19, %20, %21, %22, %23, %24, %25, %26, %27, %28, %29, %30, %31, %32, %33, %34, %35, %36, %37, %38, %39, %40, %41, %42, %43, %44, %45, %46, %47, %48, %49, %50, %51, %52, %53, %54, %55}, {%56, %57, %58, %59}, %60, p, 1, 1, %62;\n}\n"
    : "+f"(d[0]), "+f"(d[1]), "+f"(d[2]), "+f"(d[3]), "+f"(d[4]), "+f"(d[5]), "+f"(d[6]), "+f"(d[7]), "+f"(d[8]), "+f"(d[9]), "+f"(d[10]), "+f"(d[11]), "+f"(d[12]), "+f"(d[13]), "+f"(d[14]), "+f"(d[15]), "+f"(d[16]), "+f"(d[17]), "+f"(d[18]), "+f"(d[19]), "+f"(d[20]), "+f"(d[21]), "+f"(d[22]), "+f"(d[23]), "+f"(d[24]), "+f"(d[25]), "+f"(d[26]), "+f"(d[27]), "+f"(d[28]), "+f"(d[29]), "+f"(d[30]), "+f"(d[31]), "+f"(d[32]), "+f"(d[33]), "+f"(d[34]), "+f"(d[35]), "+f"(d[36]), "+f"(d[37]), "+f"(d[38]), "+f"(d[39]), "+f"(d[40]), "+f"(d[41]), "+f"(d[42]), "+f"(d[43]), "+f"(d[44]), "+f"(d[45]), "+f"(d[46]), "+f"(d[47]), "+f"(d[48]), "+f"(d[49]), "+f"(d[50]), "+f"(d[51]), "+f"(d[52]), "+f"(d[53]), "+f"(d[54]), "+f"(d[55])
    : "r"(a[0]), "r"(a[1]), "r"(a[2]), "r"(a[3]), "l"(db), "r"(sc), "n"(TB));
}
template <int TA, int TB> __device__ __forceinline__ void wgmma_ss_56(float (&d)[28], uint64_t da, uint64_t db, int sc) {
  asm volatile("{\n.reg .pred p;\nsetp.ne.b32 p, %30, 0;\n"
    "wgmma.mma_async.sync.aligned.m64n56k16.f32.bf16.bf16 {%0, %1, %2, %3, %4, %5, %6, %7, %8, %9, %10, %11, %12, %13, %14, %15, %16, %17, %18, %19, %20, %21, %22, %23, %24, %25, %26, %27}, %28, %29, p, 1, 1, %31, %32;\n}\n"
    : "+f"(d[0]), "+f"(d[1]), "+f"(d[2]), "+f"(d[3]), "+f"(d[4]), "+f"(d[5]), "+f"(d[6]), "+f"(d[7]), "+f"(d[8]), "+f"(d[9]), "+f"(d[10]), "+f"(d[11]), "+f"(d[12]), "+f"(d[13]), "+f"(d[14]), "+f"(d[15]), "+f"(d[16]), "+f"(d[17]), "+f"(d[18]), "+f"(d[19]), "+f"(d[20]), "+f"(d[21]), "+f"(d[22]), "+f"(d[23]), "+f"(d[24]), "+f"(d[25]), "+f"(d[26]), "+f"(d[27])
    : "l"(da), "l"(db), "r"(sc), "n"(TA), "n"(TB));
}

__device__ __forceinline__ uint32_t cis(float a) { return pack_bf16(__cosf(a), __sinf(a)); }

typedef __nv_bfloat162 b2;
struct c2 { b2 x, y; };
__device__ __forceinline__ b2 as_b2(uint32_t u) { return *reinterpret_cast<b2*>(&u); }
__device__ __forceinline__ uint32_t as_u(b2 v) { return *reinterpret_cast<uint32_t*>(&v); }
__device__ __forceinline__ c2 mk(b2 x, b2 y) { c2 r; r.x = x; r.y = y; return r; }
__device__ __forceinline__ c2 cmul(c2 a, b2 wr, b2 wi) { return mk(__hfma2(a.x, wr, __hneg2(__hmul2(a.y, wi))), __hfma2(a.x, wi, __hmul2(a.y, wr))); }
__device__ __forceinline__ void fft4(c2& a0, c2& a1, c2& a2, c2& a3) {
  c2 t0 = mk(__hadd2(a0.x, a2.x), __hadd2(a0.y, a2.y)), t1 = mk(__hsub2(a0.x, a2.x), __hsub2(a0.y, a2.y));
  c2 t2 = mk(__hadd2(a1.x, a3.x), __hadd2(a1.y, a3.y)), t3 = mk(__hsub2(a1.x, a3.x), __hsub2(a1.y, a3.y));
  a0 = mk(__hadd2(t0.x, t2.x), __hadd2(t0.y, t2.y)); a2 = mk(__hsub2(t0.x, t2.x), __hsub2(t0.y, t2.y));
  a1 = mk(__hadd2(t1.x, t3.y), __hsub2(t1.y, t3.x)); a3 = mk(__hsub2(t1.x, t3.y), __hadd2(t1.y, t3.x));
}
__device__ __forceinline__ void fft4_s2(c2& a0, c2& a1, c2& a2, c2& a3, b2 r) {
  const b2 nr = __hneg2(r);
  c2 t0 = mk(__hfma2(a2.x, r, a0.x), __hfma2(a2.y, r, a0.y)), t1 = mk(__hfma2(a2.x, nr, a0.x), __hfma2(a2.y, nr, a0.y));
  c2 t2 = mk(__hadd2(a1.x, a3.x), __hadd2(a1.y, a3.y)), t3 = mk(__hsub2(a1.x, a3.x), __hsub2(a1.y, a3.y));
  a0 = mk(__hadd2(t0.x, t2.x), __hadd2(t0.y, t2.y)); a2 = mk(__hsub2(t0.x, t2.x), __hsub2(t0.y, t2.y));
  a1 = mk(__hadd2(t1.x, t3.y), __hsub2(t1.y, t3.x)); a3 = mk(__hsub2(t1.x, t3.y), __hadd2(t1.y, t3.x));
}
__device__ __forceinline__ void fft4_s13(c2& a0, c2& a1, c2& a2, c2& a3, b2 r) {
  const b2 nr = __hneg2(r);
  c2 t0 = mk(__hadd2(a0.x, a2.x), __hadd2(a0.y, a2.y)), t1 = mk(__hsub2(a0.x, a2.x), __hsub2(a0.y, a2.y));
  c2 t2 = mk(__hadd2(a1.x, a3.x), __hadd2(a1.y, a3.y)), t3 = mk(__hsub2(a1.x, a3.x), __hsub2(a1.y, a3.y));
  a0 = mk(__hfma2(t2.x, r, t0.x), __hfma2(t2.y, r, t0.y)); a2 = mk(__hfma2(t2.x, nr, t0.x), __hfma2(t2.y, nr, t0.y));
  a1 = mk(__hfma2(t3.y, r, t1.x), __hfma2(t3.x, nr, t1.y)); a3 = mk(__hfma2(t3.y, nr, t1.x), __hfma2(t3.x, r, t1.y));
}
__device__ __forceinline__ c2 rot1(c2 a) { return mk(__hadd2(a.x, a.y), __hsub2(a.y, a.x)); }
__device__ __forceinline__ c2 rot3(c2 a) { return mk(__hsub2(a.y, a.x), __hneg2(__hadd2(a.x, a.y))); }
__device__ __forceinline__ c2 mul_mi(c2 a) { return mk(a.y, __hneg2(a.x)); }
template <int O> __device__ __forceinline__ void fft8(c2 (&v)[16]) {
  const b2 r = as_b2(0x3F353F35u), nr = as_b2(0xBF35BF35u);
  fft4(v[O], v[O + 4], v[O + 8], v[O + 12]);
  fft4(v[O + 2], v[O + 6], v[O + 10], v[O + 14]);
  const c2 o0 = v[O + 2], o1 = rot1(v[O + 6]), o2 = v[O + 10], o3 = rot1(v[O + 14]);
  const c2 e0 = v[O], e1 = v[O + 4], e2 = v[O + 8], e3 = v[O + 12];
  v[O] = mk(__hadd2(e0.x, o0.x), __hadd2(e0.y, o0.y));              v[O + 8] = mk(__hsub2(e0.x, o0.x), __hsub2(e0.y, o0.y));
  v[O + 2] = mk(__hfma2(o1.x, r, e1.x), __hfma2(o1.y, r, e1.y));    v[O + 10] = mk(__hfma2(o1.x, nr, e1.x), __hfma2(o1.y, nr, e1.y));
  v[O + 4] = mk(__hadd2(e2.x, o2.y), __hsub2(e2.y, o2.x));          v[O + 12] = mk(__hsub2(e2.x, o2.y), __hadd2(e2.y, o2.x));
  v[O + 6] = mk(__hfma2(o3.y, r, e3.x), __hfma2(o3.x, nr, e3.y));   v[O + 14] = mk(__hfma2(o3.y, nr, e3.x), __hfma2(o3.x, r, e3.y));
}
__device__ __forceinline__ void fft16(c2 (&v)[16]) {
  const b2 r = as_b2(0x3F353F35u), c1 = as_b2(0x3F6D3F6Du), s1 = as_b2(0x3EC43EC4u), nc1 = as_b2(0xBF6DBF6Du), ns1 = as_b2(0xBEC4BEC4u);
#pragma unroll
  for (int a = 0; a < 4; a++) fft4(v[a], v[a + 4], v[a + 8], v[a + 12]);
  v[5] = cmul(v[5], c1, ns1); v[6] = rot1(v[6]); v[7] = cmul(v[7], s1, nc1);
  v[9] = rot1(v[9]); v[10] = mul_mi(v[10]); v[11] = rot3(v[11]);
  v[13] = cmul(v[13], s1, nc1); v[14] = rot3(v[14]); v[15] = cmul(v[15], nc1, s1);
  fft4(v[0], v[1], v[2], v[3]); fft4_s2(v[4], v[5], v[6], v[7], r); fft4_s13(v[8], v[9], v[10], v[11], r); fft4_s2(v[12], v[13], v[14], v[15], r);
  c2 t;
  t = v[1]; v[1] = v[4]; v[4] = t;  t = v[2]; v[2] = v[8]; v[8] = t;  t = v[3]; v[3] = v[12]; v[12] = t;
  t = v[6]; v[6] = v[9]; v[9] = t;  t = v[7]; v[7] = v[13]; v[13] = t; t = v[11]; v[11] = v[14]; v[14] = t;
}

__device__ __forceinline__ void columns(c2 (&v)[16], uint32_t sb, int t) {
  const int l16 = t & 15;
  const uint32_t row = sb + OFF_EXCH + (t >> 4) * 2304;
  const uint32_t pos = sb + OFF_EXCH + (t >> 3) * 144 + (t & 7) * 16;
#pragma unroll 1
  for (int ps = 0; ps < 6; ps++) {
    if (ps == 0 || ps == 5) { fft8<0>(v); fft8<1>(v); } else fft16(v);
    if (ps == 5) break;
    if (ps == 2) {
      const uint32_t ws = sb + OFF_WS + (l16 >> 1) * 128 + ((((t >> 4) + (l16 >> 1)) & 7) * 2 + (l16 & 1)) * 8;
      mbar_wait(sb + OFF_BAR + B_WFULL * 8, 0);
#pragma unroll
      for (int q = 0; q < 16; q++) {
        const uint2 w = lds64(ws + q * 1024);
        const c2 z = cmul(v[q], as_b2(w.x), as_b2(w.y));
        v[q] = mk(z.y, z.x);
      }
      continue;
    }
    {
      const bool full = ps == 0 || ps == 4;
      const uint32_t tw = sb + OFF_TW + (full ? ps * 2048 + t * 16 : 16384 + l16 * 16);
      const uint32_t st = full ? 2048 : 256;
#pragma unroll
      for (int i = 0; i < 4; i++) {
        const uint4 w4 = lds128(tw + i * st);
        const uint32_t w[4] = {w4.x, w4.y, w4.z, w4.w};
#pragma unroll
        for (int e = 0; e < 4; e++) v[4 * i + e] = cmul(v[4 * i + e], __low2bfloat162(as_b2(w[e])), __high2bfloat162(as_b2(w[e])));
      }
    }
    if (ps == 0) {
      mbar_wait(sb + OFF_BAR + B_XDONE * 8, 0);
#pragma unroll
      for (int q = 0; q < 8; q++) sts128(pos + q * 2304, as_u(v[2 * q].x), as_u(v[2 * q].y), as_u(v[2 * q + 1].x), as_u(v[2 * q + 1].y));
      bar_sync<3, 128>();
#pragma unroll
      for (int q = 0; q < 16; q++) { const uint2 a = lds64(row + q * 144 + l16 * 8); v[q] = mk(as_b2(a.x), as_b2(a.y)); }
    } else {
      __syncwarp();
#pragma unroll
      for (int q = 0; q < 16; q++) sts64(row + q * 144 + l16 * 8, as_u(v[q].x), as_u(v[q].y));
      if (ps == 4) bar_sync<3, 128>(); else __syncwarp();
      const uint32_t src = ps == 4 ? pos : row + l16 * 144, st = ps == 4 ? 2304 : 16;
#pragma unroll
      for (int q = 0; q < 8; q++) { const uint4 a = lds128(src + q * st); v[2 * q] = mk(as_b2(a.x), as_b2(a.y)); v[2 * q + 1] = mk(as_b2(a.z), as_b2(a.w)); }
    }
  }
}

template <int NH> __device__ __forceinline__ void h_epilogue(float (&acc)[NH * 8], unsigned char* gdst, uint32_t tag) {
#pragma unroll
  for (int c = 0; c < NH / 2; c++) {
    uint32_t pk[4];
#pragma unroll
    for (int i = 0; i < 4; i++) {
      float hv[2];
#pragma unroll
      for (int e = 0; e < 2; e++) {
        float hg = 0.5f * acc[c * 8 + i * 2 + e], up = acc[NH * 4 + c * 8 + i * 2 + e];
        float th; asm("tanh.approx.f32 %0, %1;" : "=f"(th) : "f"(hg));
        hv[e] = fmaf(hg, th, hg) * up;
      }
      pk[i] = pack_bf16(hv[0], hv[1]);
    }
    stg128_l2(gdst + c * 4096, (pk[0] & ~1u) | tag, pk[1], pk[2], pk[3]);
  }
}

__device__ __forceinline__ void frag_ready(uint32_t (&a)[4], uint32_t (&b)[4], uint32_t (&c)[4], uint32_t (&d)[4], const unsigned char* p, uint32_t tag) {
  asm volatile("{\n.reg .pred p;\n.reg .u32 c, m, q;\nmov.u32 c, 0;\nL_TRY:\n"
               "lop3.b32 m, %0, %4, %17, 0x7E;\nlop3.b32 q, %8, %12, %17, 0x7E;\nlop3.b32 m, m, q, 1, 0xA8;\nsetp.ne.u32 p, m, 0;\n"
               "vote.sync.any.pred p, p, 0xffffffff;\n@!p bra.uni L_OK;\n"
               "ld.relaxed.gpu.global.v4.b32 {%0,%1,%2,%3}, [%16];\nld.relaxed.gpu.global.v4.b32 {%4,%5,%6,%7}, [%16+4096];\n"
               "ld.relaxed.gpu.global.v4.b32 {%8,%9,%10,%11}, [%16+8192];\nld.relaxed.gpu.global.v4.b32 {%12,%13,%14,%15}, [%16+12288];\n"
               "add.u32 c, c, 1;\nsetp.lt.u32 p, c, 262144;\n@p bra.uni L_TRY;\ntrap;\nL_OK:\n}"
               : "+r"(a[0]), "+r"(a[1]), "+r"(a[2]), "+r"(a[3]), "+r"(b[0]), "+r"(b[1]), "+r"(b[2]), "+r"(b[3]),
                 "+r"(c[0]), "+r"(c[1]), "+r"(c[2]), "+r"(c[3]), "+r"(d[0]), "+r"(d[1]), "+r"(d[2]), "+r"(d[3])
               : "l"(p), "r"(tag) : "memory");
}

#define MAP 0
#define STAG 250
#define DPF 1
#define RP0 6
#define LEAD2 0
#define LEAD1 2

__global__ void __cluster_dims__(2, 1, 1) __launch_bounds__(NTHREADS, 1)
fused_kernel(const __grid_constant__ CUtensorMap tm_x, const __grid_constant__ CUtensorMap tm_g, const __grid_constant__ CUtensorMap tm_u,
             const __grid_constant__ CUtensorMap tm_g32, const __grid_constant__ CUtensorMap tm_u32, const __grid_constant__ CUtensorMap tm_d,
             const __grid_constant__ CUtensorMap tm_s,
             const __nv_bfloat16* __restrict__ w_r, const __nv_bfloat16* __restrict__ w_i,
             const __nv_bfloat16* __restrict__ w_gate, const __nv_bfloat16* __restrict__ w_up,
             const __nv_bfloat16* __restrict__ w_down, const __nv_bfloat16* __restrict__ gate_w, __nv_bfloat16* __restrict__ out) {
  extern __shared__ __align__(1024) unsigned char smem[];
  const uint32_t sb = s2u(smem);
  const uint32_t bars = sb + OFF_BAR;
  const int tid = threadIdx.x, warp = __shfl_sync(0xffffffffu, tid >> 5, 0), lane = tid & 31;
  const int cl = blockIdx.x >> 1, kh = blockIdx.x & 1;
  const int n0 = cl < 4 ? cl : (cl < 36 ? (cl - 4) >> 3 : (cl - 36) / 7);
  const int m0 = cl < 4 ? 15 : (cl < 36 ? (cl - 4) & 7 : cl - 28 - 7 * n0);
  const int n = MAP == 0 ? n0 : (MAP == 1 ? (m0 & 3) : ((n0 & 1) | ((m0 & 1) << 1)));
  const int m = MAP == 0 ? m0 : (MAP == 1 ? ((m0 & 12) | n0) : ((m0 & 14) | (n0 >> 1)));
  const int j = kh * 4 + n, bid = m * 8 + n * 2 + kh;

  const int c64 = 224 * j + (j & 1) * 32;
  if (warp < 8) {
    asm volatile("setmaxnreg.inc.sync.aligned.u32 208;");
    const int wg = warp >> 2, w4 = warp & 3, g = lane >> 2, t = lane & 3;
    const int rh = wg ^ kh ^ 1;
    const int p = j & 1, r = (j >> 1) & 1, hh = j >> 2;
    const uint32_t epoch = ld_relaxed(&g_ep[bid]);
    if ((tid & 127) == 0) PROF(wg, 30);
#pragma unroll 1
    for (int it = tid; it < 392; it += 256) {
      const int kc = it / 28, sg = it - kc * 28;
      const int k = 2 * (28 * hh + sg) + r;
      const float kf = (float)k * (-6.283185307179586f / 448.0f), a0 = (float)(16 * kc + p) * kf;
      uint32_t c[4], s[4];
#pragma unroll
      for (int q = 0; q < 4; q++) {
        const float a1 = fmaf((float)(2 * q), kf, a0), a2 = fmaf((float)(2 * q + 8), kf, a0);
        c[q] = pack_bf16(__cosf(a1), __cosf(a2)); s[q] = pack_bf16(__sinf(a1), __sinf(a2));
        if (k == 0) s[q] = ((q ^ p) & 1) ? 0xBF80BF80u : 0x3F803F80u;
      }
      const uint32_t a = sb + 6 * SLOT + (kc * 56 + 2 * sg) * 16;
      sts128(a, c[0], c[1], c[2], c[3]);
      sts128(a + 16, s[0], s[1], s[2], s[3]);
    }
    if ((tid & 127) == 0) PROF(wg, 31);
    fence_async_smem();
    bar_sync<0, NTHREADS - 64>();
    asm volatile("barrier.cluster.arrive.relaxed.aligned;" ::: "memory");
    if ((tid & 127) == 0) PROF(wg, 1);

    uint32_t xa[28][4];
    {
      const uint32_t xb = sb + OFF_PQ + wg * HALF_XR + (w4 * 16 + (lane & 15)) * 128;
      mbar_wait(bars + (B_XFULL + wg) * 8, 0);
      if ((tid & 127) == 0) PROF(wg, 2);
#pragma unroll
      for (int kb = 0; kb < 7; kb++) {
#pragma unroll
        for (int kk = 0; kk < 4; kk++) {
          uint32_t a = xb + kb * 8192 + (((2 * kk + (lane >> 4)) ^ (lane & 7)) << 4);
          asm volatile("ldmatrix.sync.aligned.m8n8.x4.shared.b16 {%0,%1,%2,%3}, [%4];"
                       : "=r"(xa[kb * 4 + kk][0]), "=r"(xa[kb * 4 + kk][1]), "=r"(xa[kb * 4 + kk][2]), "=r"(xa[kb * 4 + kk][3]) : "r"(a) : "memory");
        }
      }
    }
    {
      uint32_t ad[7][4];
      const uint32_t sel = p ? 0x7632 : 0x5410;
      const uint32_t sgn = r ? 0xBF80BF80u : 0x3F803F80u;
#pragma unroll
      for (int jj = 0; jj < 7; jj++) {
#pragma unroll
        for (int i = 0; i < 4; i++) {
          int ks = 2 * jj + (i >> 1), rr = i & 1;
          uint32_t lo = __byte_perm(xa[ks][rr], xa[ks][rr + 2], sel);
          uint32_t hi = __byte_perm(xa[ks + 14][rr], xa[ks + 14][rr + 2], sel);
          asm("fma.rn.bf16x2 %0, %1, %2, %3;" : "=r"(ad[jj][i]) : "r"(hi), "r"(sgn), "r"(lo));
        }
      }
      __syncwarp();
      if (lane == 0) mbar_arrive(bars + (B_XFREE + wg) * 8);
      float acc[28];
      wg_fence();
      uint64_t db = mkdesc(sb + 6 * SLOT, 896, 128, 0);
#pragma unroll
      for (int jj = 0; jj < 7; jj++) wgmma_rs_56<0>(acc, ad[jj], db + jj * 112, jj != 0);
      wg_commit();
      wg_wait<0>(); keep(acc);
      if (lane == 0) mbar_arrive(bars + (B_EMPTY + 6) * 8);
      const uint32_t xc = sb + OFF_EXCH + wg * 8192 + t * 256 + w4 * 64 + g * 4;
      mbar_wait(bars + B_XFREE * 8, 0);
#pragma unroll
      for (int i = 0; i < 7; i++) {
        sts32(xc + i * 1024, pack_bf16(acc[4 * i], acc[4 * i + 1]));
        sts32(xc + i * 1024 + 32, pack_bf16(acc[4 * i + 2], acc[4 * i + 3]));
      }
      fence_async_smem();
      __syncwarp();
      if (lane == 0) mbar_arrive(bars + B_PUBX * 8);
    }
    if ((tid & 127) == 0) PROF(wg, 3);
    const uint32_t tag = ~epoch & 1;
    unsigned char* const hbase = g_H + (size_t)(m * 2 + kh) * (56 * 4096) + rh * 2048 + (tid & 127) * 16;
#pragma unroll 1
    for (int u = 0; u < 3; u++) {
      float acc[64];
      if (wg == 1) { if (u & 1) bar_sync<6, 256>(); else bar_sync<2, 256>(); }
      const uint32_t sbu = opaque(sb);
#pragma unroll
      for (int kb = 0; kb < 7; kb++) {
        mbar_wait(sbu + OFF_BAR + (B_FULL + kb) * 8, u & 1);
        wg_fence();
        uint64_t db = mkdesc(sbu + kb * SLOT, 8192, 1024, 1);
#pragma unroll
        for (int kk = 0; kk < 4; kk++) wgmma_rs_128<1>(acc, xa[kb * 4 + kk], db + kk * 128, (kb | kk) != 0);
        wg_commit();
        if (kb == LEAD1 && wg == 0) { if (u & 1) bar_arrive<6, 256>(); else bar_arrive<2, 256>(); }
        if (kb > 0) { wg_wait<1>(); if (lane == 0) mbar_arrive(sbu + OFF_BAR + (B_EMPTY + kb - 1) * 8); }
      }
      wg_wait<0>(); keep(acc);
      if (lane == 0) mbar_arrive(sbu + OFF_BAR + (B_EMPTY + 6) * 8);
      if ((tid & 127) == 0) PROF(wg, 4 + 2 * u);
      h_epilogue<8>(acc, hbase + (u * 16 + n * 4) * 4096, tag);
      if ((tid & 127) == 0) PROF(wg, 5 + 2 * u);
    }
    uint32_t ha[14][4][4];
    auto check = [&](int b0, int b1) {
#pragma unroll
      for (int b = b0; b < b1; b++) frag_ready(ha[b][0], ha[b][1], ha[b][2], ha[b][3], hbase + b * 16384, tag);
    };
    auto load = [&](int b0, int b1) {
#pragma unroll
      for (int i = b0; i < b1; i++) ldg128_l2(ha[i >> 2][i & 3], hbase + i * 4096);
    };
    {
      float acc[32];
      load(0, 3);
      if (wg == 1) bar_sync<6, 256>();
      const uint32_t sbu = opaque(sb);
#pragma unroll
      for (int it = 0; it < 4; it++) {
        mbar_wait(sbu + OFF_BAR + (B_FULL + it) * 8, 1);
        wg_fence();
        uint64_t db = mkdesc(sbu + it * SLOT, 8192, 512, 2);
#pragma unroll
        for (int kk = 0; kk < 8; kk++) if (it * 8 + kk < 28) wgmma_rs_64<1>(acc, xa[it * 8 + kk], db + kk * 64, (it | kk) != 0);
        wg_commit();
        if (it == 2 && wg == 0) bar_arrive<6, 256>();
        if (it > 0) {
          wg_wait<1>();
          if (lane == 0) mbar_arrive(sbu + OFF_BAR + (B_EMPTY + it - 1) * 8);
          if (it == 1) load(3, 11);
          if (it == 2) load(11, 16);
        }
      }
      wg_wait<0>(); keep(acc);
      if (lane == 0) mbar_arrive(sbu + OFF_BAR + (B_EMPTY + 3) * 8);
      if ((tid & 127) == 0) PROF(wg, 10);
      h_epilogue<4>(acc, hbase + (48 + n * 2) * 4096, tag);
    }
    asm volatile("barrier.cluster.wait.aligned;" ::: "memory");
    if ((tid & 127) == 0) PROF(wg, 11);

    float acc[56];
    check(0, 4);
    if (wg == 1) bar_sync<2, 256>();
#pragma unroll
    for (int b = 0; b < 14; b++) {
      if ((tid & 127) == 0) PROF(wg, 16 + b);
      if (b >= 3) mbar_wait(bars + (B_FULL + (b + 1) % 7) * 8, b < 6 || b == 13);
      else if (b == 0) mbar_wait(bars + B_RFULL * 8, 0);
      if (b == 4) check(4, 7);
      if (b == 7) check(7, 11);
      if (b == 11) check(11, 14);
      wg_fence();
      const uint64_t db = mkdesc(b < 3 ? sb + OFF_R + b * SLOT : sb + (b + 1) % 7 * SLOT, 8192, 1024, 1);
#pragma unroll
      for (int kk = 0; kk < 4; kk++) wgmma_rs_112<1>(acc, ha[b][kk], db + kk * 128, (b | kk) != 0);
      wg_commit();
      if (b == LEAD2 && wg == 0) bar_arrive<2, 256>();
      if (b == 0) load(16, 24);
      if (b == 1) load(24, 28);
      if (b == 4 || b == 5) load(8 * b - 4, 8 * b + 4);
      if (b == 7) load(44, 52);
      if (b == 8) load(52, 56);
      if (b > 0) wg_wait<1>();
      if (lane == 0) {
        if (b >= 4 && b <= 9) mbar_arrive(bars + (B_EMPTY + b % 7) * 8);
        if (b == 3) {
          mbar_arrive(bars + B_LFREE * 8);
          asm volatile("{\n.reg .b32 ra;\nmapa.shared::cluster.u32 ra, %0, %1;\nmbarrier.arrive.relaxed.cluster.shared::cluster.b64 _, [ra];\n}"
                       :: "r"(bars + B_RFREE * 8), "r"(kh ^ 1) : "memory");
        }
      }
    }
    const int t128 = tid & 127;
    wg_wait<0>(); keep(acc);
    if (wg == 0) {
      if (t128 == 0) PROF(wg, 12);
      mbar_wait_cluster(bars + B_RFREE * 8, 0);
      uint32_t rdst, rbar;
      asm volatile("mapa.shared::cluster.u32 %0, %1, %2;" : "=r"(rdst) : "r"(sb + OFF_R + t128 * 16), "r"(kh ^ 1));
      asm volatile("mapa.shared::cluster.u32 %0, %1, %2;" : "=r"(rbar) : "r"(bars + B_RECV * 8), "r"(kh ^ 1));
#pragma unroll
      for (int i = 0; i < 7; i++)
        asm volatile("st.async.weak.shared::cluster.mbarrier::complete_tx::bytes.v4.b32 [%0], {%1,%2,%3,%4}, [%5];"
                     :: "r"(rdst + i * 2048), "r"(pack_bf16(acc[8 * i], acc[8 * i + 1])), "r"(pack_bf16(acc[8 * i + 2], acc[8 * i + 3])),
                        "r"(pack_bf16(acc[8 * i + 4], acc[8 * i + 5])), "r"(pack_bf16(acc[8 * i + 6], acc[8 * i + 7])), "r"(rbar) : "memory");
    } else {
      float spec[2][28];
      if (t128 == 0) PROF(wg, 12);
#pragma unroll
      for (int i = 0; i < 4; i++) {
        if (i == 0) mbar_wait(bars + B_GFULL * 8, 0);
        if (i >= 2) mbar_wait(bars + (B_FULL + i - 1) * 8, 1);
        mbar_wait(bars + (B_PQFULL + i) * 8, 0);
        if (i == 0 && t128 == 0) { PROF(wg, 13); g_ep[bid] = epoch + 1; }
        wg_fence();
        const uint64_t da = mkdesc(sb + OFF_PQ + i * 14336, 1024, 1024, 1);
        const uint64_t db = mkdesc(i < 2 ? sb + OFF_R + 28672 + i * (G_IMG / 2) : sb + (i - 1) * SLOT, 896, 128, 0);
#pragma unroll
        for (int kk = 0; kk < 7; kk++) wgmma_ss_56<1, 0>(spec[i >> 1], da + kk * 128, db + kk * 112, ((i & 1) | kk) != 0);
        wg_commit();
      }
      const float* gs = reinterpret_cast<const float*>(smem + OFF_G) + w4 * 16 + g;
      const float o0 = bf16_round(1.0f - gs[0]), o1 = bf16_round(1.0f - gs[8]);
      const float g0 = gs[0] * (1.0f / (float)(S_ * D_)), g1 = gs[8] * (1.0f / (float)(S_ * D_));
      mbar_wait_cluster(bars + B_RECV * 8, 0);
      if (t128 == 0) PROF(wg, 0);
#pragma unroll
      for (int i = 0; i < 7; i++) {
        const uint4 o4 = lds128(sb + OFF_R + t128 * 16 + i * 2048);
        const uint32_t o[4] = {o4.x, o4.y, o4.z, o4.w};
#pragma unroll
        for (int e = 0; e < 4; e++) {
          acc[8 * i + 2 * e] = (acc[8 * i + 2 * e] + bf_lo(o[e])) * ((e & 1) ? o1 : o0);
          acc[8 * i + 2 * e + 1] = (acc[8 * i + 2 * e + 1] + bf_hi(o[e])) * ((e & 1) ? o1 : o0);
        }
      }
      keep(acc);
      wg_wait<0>(); keep(spec[0]); keep(spec[1]);
      if (t128 == 0) PROF(wg, 14);
      bar_sync<5, 128>();
      const uint32_t st = sb + OFF_PQ + w4 * 3840;
#pragma unroll
      for (int i = 0; i < 7; i++) {
        uint32_t pk[4];
#pragma unroll
        for (int e = 0; e < 2; e++) {
          const int c = 2 * i + e, si = i * 4 + e;
          pk[2 * e] = pack_bf16(fmaf(g0, spec[0][si], acc[4 * c]), fmaf(g0, spec[1][si], acc[4 * c + 1]));
          pk[2 * e + 1] = pack_bf16(fmaf(g1, spec[0][si + 2], acc[4 * c + 2]), fmaf(g1, spec[1][si + 2], acc[4 * c + 3]));
        }
        asm volatile("stmatrix.sync.aligned.m8n8.x4.shared.b16 [%0], {%1,%2,%3,%4};"
                     :: "r"(st + (lane & 15) * 240 + (lane >> 4) * 16 + i * 32), "r"(pk[0]), "r"(pk[1]), "r"(pk[2]), "r"(pk[3]) : "memory");
      }
      __syncwarp();
      if (lane < 28) {
        const int r2 = lane >= 14, cc = lane - r2 * 14;
        unsigned char* ob = reinterpret_cast<unsigned char*>(out) + (size_t)(m * 128 + kh * 64 + w4 * 16 + r2) * (D_ * 2) + n * 224 + cc * 16;
        float4 v[8];
#pragma unroll
        for (int i = 0; i < 8; i++) v[i] = lds128f(st + r2 * 240 + cc * 16 + i * 480);
#pragma unroll
        for (int i = 0; i < 8; i++) stg128(ob + i * (D_ * 4), __float_as_uint(v[i].x), __float_as_uint(v[i].y), __float_as_uint(v[i].z), __float_as_uint(v[i].w));
      }
    }
    if (t128 == 0) { PROF(wg, 15); if (wg) { PROFG(4, 30); PROF(4, 31); } }
  } else if (warp < 12) {
    asm volatile("setmaxnreg.dec.sync.aligned.u32 72;");
    const int t = tid - 256;
    const int k = bid;
    if (t == 0) PROF(2, 0);
    uint4 gv[7];
#pragma unroll
    for (int i = 0; i < 7; i++) gv[i] = ldg128(reinterpret_cast<const uint4*>(gate_w) + i * 8 + (t & 7));
    if (t < 98) {
      int cid = m * 98 + t, kc = cid / 56, nn = cid - kc * 56;
      int d = 112 * n + 8 * (2 * (nn >> 3) + (nn & 1)) + (nn & 6) + kh;
      int dr = d > 224 ? d - 448 : d;
      const float df = (float)dr * (-6.283185307179586f / 448.0f);
      uint32_t pk[4];
#pragma unroll
      for (int e = 0; e < 4; e++) {
        const float a = (float)(4 * kc + e) * df;
        pk[e] = pack_bf16(2.0f * __cosf(a), 2.0f * __sinf(a));
      }
      if (kc == 0) pk[0] = (((d >> 1) ^ kh) & 1) ? 0xBF803F80u : 0x3F803F80u;
      stg128(g_G + (size_t)(n * 2 + kh) * G_IMG + cid * 16, pk[0], pk[1], pk[2], pk[3]);
    }
    bar_sync<0, NTHREADS - 64>();
    asm volatile("barrier.cluster.arrive.relaxed.aligned;" ::: "memory");
    {
      const int row = n * 16 + (t >> 3), l8 = t & 7;
      mbar_wait(bars + (B_XFULL + 1) * 8, 0);
      float sum = 0.f;
#pragma unroll
      for (int i = 0; i < 7; i++) {
        const uint4 a = lds128(sb + OFF_R + i * 8192 + row * 128 + ((l8 ^ (row & 7)) << 4));
        const uint32_t aa[4] = {a.x, a.y, a.z, a.w}, bb[4] = {gv[i].x, gv[i].y, gv[i].z, gv[i].w};
#pragma unroll
        for (int e = 0; e < 4; e++) {
          const uint32_t pr = as_u(__hmul2(as_b2(aa[e]), as_b2(bb[e])));
          sum += bf_lo(pr) + bf_hi(pr);
        }
      }
      sum += __shfl_xor_sync(0xffffffffu, sum, 1); sum += __shfl_xor_sync(0xffffffffu, sum, 2); sum += __shfl_xor_sync(0xffffffffu, sum, 4);
      if (l8 == 0) g_gate[m * 128 + kh * 64 + row] = bf16_round(__fdividef(1.0f, 1.0f + __expf(-bf16_round(sum))));
    }
    __syncwarp();
    if (lane == 0) mbar_arrive(bars + (B_XFREE + 1) * 8);
    if (t == 0) PROF(2, 11);
    mbar_wait(bars + B_XFREE * 8, 0);
    {
      const float u = -6.283185307179586f / 2048.0f, t2 = (float)(2 * t) * u;
#pragma unroll 1
      for (int i = 0; i < 4; i++) {
        const float q = (float)(2 * i);
        sts128(sb + OFF_TW + i * 2048 + t * 16, cis(t2 * q), cis((t2 + u) * q), cis(t2 * (q + 1.0f)), cis((t2 + u) * (q + 1.0f)));
      }
      const float l = (float)((t >> 1) & 15) * (8.0f * u), jj = (float)((t >> 5) * 4 + (t & 1) * 2);
      sts64(sb + OFF_TW + 16384 + t * 8, cis(l * jj), cis(l * (jj + 1.0f)));
    }
    mbar_wait(bars + B_PIN * 8, 0);
    mbar_wait(bars + (B_XFREE + 1) * 8, 0);
    if (t == 0) PROF(2, 4);
    {
      const uint32_t wa = sb + OFF_WS + (((t & 7) - bid) & 7) * 450 + (t >> 3) * 2, wc = wa + 448 - (t >> 3) * 4;
#pragma unroll 1
      for (int h = 0; h < 2; h++) {
        uint32_t w[4][8];
#pragma unroll
        for (int i = 0; i < 4; i++) {
#pragma unroll
          for (int e = 0; e < 4; e++) { w[i][2 * e] = lds16(wa + h * 128 + i * 32 + e * 3600); w[i][2 * e + 1] = lds16(wc - h * 128 - i * 32 + e * 3600); }
        }
#pragma unroll
        for (int i = 0; i < 4; i++)
          sts128(sb + OFF_R + h * 8192 + i * 2048 + t * 16, __byte_perm(w[i][0], w[i][1], 0x5410), __byte_perm(w[i][4], w[i][5], 0x5410), __byte_perm(w[i][2], w[i][3], 0x5410), __byte_perm(w[i][6], w[i][7], 0x5410));
      }
    }
    fence_async_smem();
    __syncwarp();
    if (lane == 0) mbar_arrive(bars + B_PUBW * 8);
    if (k < 113) {
      if (t == 0) PROF(2, 2);
      mbar_wait(bars + B_XCFULL * 8, 0);
      if (t == 0) PROF(2, 3);
      c2 v[16];
      uint2 xe[8], xo[8];
      const int sl = k == 112 ? 0 : k, hi = sl >= 56;
      const unsigned char* xs = g_X + (192 + (sl & 1) * 64 + hi * 72 + (sl & ~1) + ((t >> 4) & 1)) * XP + (t >> 5) * 256 + (t & 15) * 8;
#pragma unroll
      for (int jj = 0; jj < 8; jj++) { xe[jj] = ldg64_l2(xs + jj * 1024); xo[jj] = ldg64_l2(xs + jj * 1024 + 128); }
      {
        const float rr = (float)(t >> 4) * (-6.283185307179586f / 2048.0f);
#pragma unroll 1
        for (int i = 0; i < 4; i++) {
          const float l = (float)((t & 15) + 64 * i);
          sts128(sb + OFF_TW + 8192 + i * 2048 + t * 16, cis(rr * l), cis(rr * (l + 16.0f)), cis(rr * (l + 32.0f)), cis(rr * (l + 48.0f)));
        }
      }
      if (t == 0) PROF(2, 9);
      const uint32_t se = k == 0 ? 0x4410 : (k == 112 ? 0x4432 : 0x3210), so = k == 0 ? 0x4410 : (k == 112 ? 0x3244 : 0x3210);
#pragma unroll
      for (int jj = 0; jj < 8; jj++) {
        const uint2 e2 = xe[jj], o2 = xo[jj];
#pragma unroll
        for (int h = 0; h < 2; h++) {
          const b2 e = as_b2(__byte_perm(h ? e2.y : e2.x, 0, se)), o = as_b2(__byte_perm(h ? o2.y : o2.x, 0, so));
          const uint32_t s = as_u(__hadd2(e, o)), d = as_u(__hsub2(e, o)) ^ 0x80000000u;
          v[2 * jj + h] = mk(as_b2(__byte_perm(s, d, 0x5410)), as_b2(__byte_perm(s, d, 0x7632)));
        }
      }
      if (t == 0) PROF(2, 12);
      columns(v, sb, t);
      if (t == 0) PROF(2, 14);
      const int pre = (k == 112) ? 1 : 2 * k, pim = (k == 112) ? 1 : 2 * k + 1;
      const uint32_t pr = sb + OFF_EXCH + (t >> 5) * 256 + ((((lane >> 2) ^ pre) & 7) << 4) + (lane & 3) * 4;
      const uint32_t pi = sb + OFF_EXCH + 8192 + (t >> 5) * 256 + ((((lane >> 2) ^ pim) & 7) << 4) + (lane & 3) * 4;
      bar_sync<3, 128>();
#pragma unroll
      for (int jj = 0; jj < 8; jj++) {
        const b2 ar = as_b2(__byte_perm(as_u(v[2 * jj].y), as_u(v[2 * jj + 1].y), 0x5410)), br = as_b2(__byte_perm(as_u(v[2 * jj].y), as_u(v[2 * jj + 1].y), 0x7632));
        const b2 ai = as_b2(__byte_perm(as_u(v[2 * jj].x), as_u(v[2 * jj + 1].x), 0x5410)), bi = as_b2(__byte_perm(as_u(v[2 * jj].x), as_u(v[2 * jj + 1].x), 0x7632));
        sts32(pr + jj * 1024, as_u(__hadd2(ar, br)));
        sts32(pr + jj * 1024 + 128, as_u(k == 112 ? __hadd2(ai, bi) : __hsub2(ar, br)));
        sts32(pi + jj * 1024 + 128, as_u(__hadd2(ai, bi)));
        sts32(pi + jj * 1024, as_u(__hsub2(ai, bi)));
      }
      fence_async_smem();
      bar_sync<3, 128>();
      if (t == 0) {
        PROF(2, 5);
        tma_store(&tm_s, pre * 64, 0, sb + OFF_EXCH);
        if (k != 0 && k != 112) tma_store(&tm_s, pim * 64, 0, sb + OFF_EXCH + 8192);
        bulk_done();
      }
    }
    if (t == 0) { red_relaxed(&g_cnt[5 * 32]); PROF(2, 7); }
    if (t >= 32) {
      if (k >= 113) mbar_wait(bars + B_LFREE * 8, 0);
      __nanosleep((t >> 5) * STAG);
      wait_ge(&g_cnt[5 * 32], (lds64(sb + OFF_G + 256).x + 1) * 128);
      if (lane == 0) mbar_arrive(bars + B_SEEN * 8);
    }
    __syncwarp();
    asm volatile("barrier.cluster.wait.aligned;" ::: "memory");
  } else {
    asm volatile("setmaxnreg.dec.sync.aligned.u32 24;");
    auto wd_tile = [&](int b, uint32_t dst, uint32_t fb) {
#pragma unroll
      for (int hf = 0; hf < 2; hf++) {
        const int js = kh * 4 + (b < 12 ? (b & 3) : (b & 1) * 2 + hf);
        const int row = 224 * js + (b < 12 ? (js & 1) * 32 + (b >> 2) * 64 + hf * 32 : 192 - hf * 192);
        tma2d(dst + hf * 4096, &tm_d, 112 * n, row, fb);
        tma2d(dst + 8192 + hf * 4096, &tm_d, 112 * n + 64, row, fb);
      }
    };
    if (warp == 12) {
      if (elect()) {
        mbar_init(bars + B_XFULL * 8, 1); mbar_init(bars + (B_XFULL + 1) * 8, 1);
        fence_async_smem();
#pragma unroll
        for (int w = 0; w < 2; w++) {
          mbar_expect(bars + (B_XFULL + w) * 8, HALF_XR);
          tma3d(sb + OFF_PQ + w * HALF_XR, &tm_x, 0, m * 128 + (w ^ kh ^ 1) * 64, 0, bars + (B_XFULL + w) * 8);
        }
        PROF(3, 3);
#pragma unroll
        for (int i = 0; i < NSLOT; i++) mbar_init(bars + (B_FULL + i) * 8, 1);
        mbar_init(bars + B_PIN * 8, 1);
        fence_async_smem();
      }
      bar_arrive<0, NTHREADS - 64>();
#pragma unroll 1
      for (int i = 0; i < 6; i++) {
        if (elect()) {
          const uint32_t fb = bars + (B_FULL + i) * 8;
          mbar_expect(fb, SLOT);
          tma2d(sb + i * SLOT, &tm_g, c64, i * 64, fb);
          tma2d(sb + i * SLOT + 8192, &tm_u, c64, i * 64, fb);
          PROF(3, 4 + i);
        }
      }
      if (elect()) {
        prefetch_l2(reinterpret_cast<const unsigned char*>(w_r) + bid * 7200, 7200);
        prefetch_l2(reinterpret_cast<const unsigned char*>(w_i) + bid * 7200, 7200);
        prefetch_l2(reinterpret_cast<const unsigned char*>(w_gate) + bid * 12544, 12544);
        prefetch_l2(reinterpret_cast<const unsigned char*>(w_up) + bid * 12544, 12544);
      }
    } else if (warp == 14) {
      if (elect()) {
#pragma unroll
        for (int i = B_EMPTY; i < B_END; i++)
          if (i < B_XFULL || i >= B_XFREE) mbar_init(bars + i * 8, i >= B_PQFULL ? 1 : (i == B_XFREE ? 4 : (i == B_PUBW ? 5 : 8)));
        asm volatile("fence.mbarrier_init.release.cluster;" ::: "memory");
        fence_async_smem();
        mbar_expect(bars + B_RECV * 8, 64 * 112 * 2);
      }
      bar_arrive<0, NTHREADS - 64>();
    }
    const uint32_t epoch = ld_relaxed(&g_ep[bid]);
    if (warp == 13 && lane == 0) { PROFG(4, 0); PROF(4, 1); }
    bar_sync<1, 128>();
    asm volatile("barrier.cluster.arrive.relaxed.aligned;" ::: "memory");
    if (warp == 12) {
      int slot = 6, ph = 1;
      auto wait_slot = [&]() { mbar_wait(bars + (B_EMPTY + slot) * 8, ph ^ (slot == 6)); };
      auto adv = [&]() { if (++slot == NSLOT) { slot = 0; ph ^= 1; } };
      const int c32 = 224 * j + ((j & 1) ? 0 : 192);
#pragma unroll 1
      for (int i = 6; i < 25; i++) {
        wait_slot();
        if (elect()) {
          const uint32_t dst = sb + slot * SLOT, fb = bars + (B_FULL + slot) * 8;
          const bool last = i >= 21;
          const int cc = last ? c32 : c64 + 64 * (i / 7), rr = last ? slot * 128 : slot * 64;
          mbar_expect(fb, SLOT);
          tma2d(dst, last ? &tm_g32 : &tm_g, cc, rr, fb);
          tma2d(dst + 8192, last ? &tm_u32 : &tm_u, cc, rr, fb);
        }
        adv();
      }
      if (lane == 0) PROF(3, 0);
#pragma unroll 1
      for (int i = 3; i < 16; i++) {
        if (lane == 0) PROF(3, 16 + i);
        if (i == 14) mbar_wait(bars + B_PREP * 8, 0);
        wait_slot();
        if (elect()) {
          const uint32_t fb = bars + (B_FULL + slot) * 8;
          mbar_expect(fb, i < 14 ? SLOT : G_IMG / 2);
          if (i < 14) wd_tile(i, sb + slot * SLOT, fb);
          else bulk_g2s(sb + slot * SLOT, g_G + (size_t)(n * 4 + i - 12) * (G_IMG / 2), G_IMG / 2, fb);
        }
        adv();
      }
      if (lane == 0) PROF(3, 2);
    } else if (warp == 13) {
      mbar_wait(bars + B_PUBX * 8, 0);
      if (elect()) {
        PROF(4, 8);
#pragma unroll
        for (int w = 0; w < 2; w++) tma_store(&tm_s, ((m * 2 + (w ^ kh ^ 1)) * 2 + (j & 1)) * 64, 192 + (j >> 1) * 64, sb + OFF_EXCH + w * 8192);
        bulk_done();
        red_relaxed(&g_cnt[(j >> 1) * 32]);
        mbar_arrive(bars + B_XDONE * 8);
        PROF(4, 12);
      }
      mbar_wait(bars + B_PUBW * 8, 0);
      if (elect()) {
        PROF(4, 9);
        tma_store(&tm_s, bid * 64, 64, sb + OFF_R);
        tma_store(&tm_s, bid * 64, 128, sb + OFF_R + 8192);
        bulk_done();
        red_relaxed(&g_cnt[4 * 32]);
        mbar_arrive(bars + B_WDONE * 8);
        PROF(4, 13);
      }
      mbar_wait(bars + B_PREP * 8, 0);
      mbar_wait(bars + B_LFREE * 8, 0);
      if (elect()) {
        mbar_expect(bars + B_GFULL * 8, G_IMG);
        bulk_g2s(sb + OFF_R + 28672, g_G + (size_t)(n * 2) * G_IMG, G_IMG, bars + B_GFULL * 8);
      }
    } else if (warp == 14) {
      mbar_wait(bars + (B_XFREE + 1) * 8, 0);
      asm volatile("fence.acq_rel.gpu;" ::: "memory");
      if (lane == 0) { mbar_arrive(bars + B_PUBW * 8); PROF(5, 3); }
      mbar_wait(bars + B_WDONE * 8, 0);
      wait_ge(&g_cnt[4 * 32], (epoch + 1) * 128);
      fence_async_global();
      if (elect()) {
        mbar_arrive(bars + B_PREP * 8);
        if (bid < 113) {
          mbar_expect(bars + B_WFULL * 8, 16384);
          bulk_g2s(sb + OFF_WS, g_X + (64 + bid) * XP, 16384, bars + B_WFULL * 8);
        }
        PROF(5, 17);
      }
    } else {
      mbar_wait(bars + B_XFREE * 8, 0);
      if (elect()) {
        sts32(sb + OFF_G + 256, epoch);
        mbar_expect(bars + B_PIN * 8, 14400);
        bulk_g2s(sb + OFF_WS, reinterpret_cast<const unsigned char*>(w_r) + bid * 7200, 7200, bars + B_PIN * 8);
        bulk_g2s(sb + OFF_WS + 7200, reinterpret_cast<const unsigned char*>(w_i) + bid * 7200, 7200, bars + B_PIN * 8);
        PROF(5, 2);
      }
      if (DPF) mbar_wait(bars + B_PIN * 8, 0);
#pragma unroll 1
      for (int i = lane; i < 98; i += 32) asm volatile("prefetch.global.L2 [%0];\nprefetch.global.L2 [%0+64];" :: "l"(reinterpret_cast<const unsigned char*>(w_down) + bid * 12544 + i * 128));
      if (bid < 113) {
        const int sl = (bid == 112) ? 0 : bid;
        wait_ge(&g_cnt[((sl & 1) + 2 * ((sl >> 1) / 28)) * 32], (epoch + 1) * 32);
        if (elect()) { PROF(5, 16); mbar_arrive(bars + B_XCFULL * 8); }
      }
      mbar_wait(bars + B_WDONE * 8, 0);
      if (elect()) mbar_expect(bars + B_RFULL * 8, 3 * SLOT);
#pragma unroll 1
      for (int i = 0; i < 3; i++) {
        mbar_wait(bars + (B_FULL + (i == 0 ? RP0 : 2 * i - 1)) * 8, i == 0);
        if (elect()) wd_tile(i, sb + OFF_R + i * SLOT, bars + B_RFULL * 8);
      }
      if (lane == 0) PROF(5, 19);
      mbar_wait(bars + B_PREP * 8, 0);
      mbar_wait(bars + B_SEEN * 8, 0);
      fence_async_global();
      if (elect()) {
        PROF(5, 18);
        const unsigned char* src = g_X + (m * 2 + kh) * HALF_XR;
#pragma unroll
        for (int i = 0; i < 4; i++) {
          mbar_expect(bars + (B_PQFULL + i) * 8, i < 3 ? 14336 : 14336 + 256);
          bulk_g2s(sb + OFF_PQ + i * 14336, src + i * 14336, 14336, bars + (B_PQFULL + i) * 8);
        }
        bulk_g2s(sb + OFF_G, g_gate + m * 128 + kh * 64, 256, bars + (B_PQFULL + 3) * 8);
      }
    }
    __syncwarp();
    asm volatile("barrier.cluster.wait.aligned;" ::: "memory");
  }
}

typedef CUresult (*EncodeFn)(CUtensorMap*, CUtensorMapDataType, cuuint32_t, void*, const cuuint64_t*, const cuuint64_t*, const cuuint32_t*,
                             const cuuint32_t*, CUtensorMapInterleave, CUtensorMapSwizzle, CUtensorMapL2promotion, CUtensorMapFloatOOBfill);

void make_map(EncodeFn enc, CUtensorMap* tm, const void* base, int cols, int rows, int bc, int br, CUtensorMapSwizzle sw) {
  cuuint64_t gd[2] = {(cuuint64_t)cols, (cuuint64_t)rows};
  cuuint64_t gs[1] = {(cuuint64_t)cols * 2};
  cuuint32_t bd[2] = {(cuuint32_t)bc, (cuuint32_t)br};
  cuuint32_t es[2] = {1, 1};
  enc(tm, CU_TENSOR_MAP_DATA_TYPE_BFLOAT16, 2, const_cast<void*>(base), gd, gs, bd, es, CU_TENSOR_MAP_INTERLEAVE_NONE, sw,
      CU_TENSOR_MAP_L2_PROMOTION_L2_128B, CU_TENSOR_MAP_FLOAT_OOB_FILL_NONE);
}

}

extern "C" void kernel_launch(void* const* d_in, const int* in_sizes, int n_in, void* d_out, int out_size) {
  (void)in_sizes; (void)n_in; (void)out_size;
  const __nv_bfloat16* x = (const __nv_bfloat16*)d_in[0];
  const __nv_bfloat16* w_r = (const __nv_bfloat16*)d_in[1];
  const __nv_bfloat16* w_i = (const __nv_bfloat16*)d_in[2];
  const __nv_bfloat16* w_gate = (const __nv_bfloat16*)d_in[4];
  const __nv_bfloat16* w_up = (const __nv_bfloat16*)d_in[5];
  const __nv_bfloat16* w_down = (const __nv_bfloat16*)d_in[6];
  const __nv_bfloat16* gate_w = (const __nv_bfloat16*)d_in[7];
  static EncodeFn enc = nullptr;
  static void* xbuf = nullptr;
  static bool ok = false;
  if (!enc) {
    cudaDriverEntryPointQueryResult qr;
    cudaGetDriverEntryPoint("cuTensorMapEncodeTiled", (void**)&enc, cudaEnableDefault, &qr);
    cudaFuncSetAttribute(fused_kernel, cudaFuncAttributeMaxDynamicSharedMemorySize, SMEM_BYTES);
    cudaGetSymbolAddress(&xbuf, g_X);
    cudaFuncAttributes fa;
    cudaFuncGetAttributes(&fa, fused_kernel);
    ok = (fa.numRegs == 128);
  }
  if (!ok) return;
  CUtensorMap tx, tg, tu, tg32, tu32, td, ts;
  {
    cuuint64_t gd[3] = {64, (cuuint64_t)S_, 7};
    cuuint64_t gs[2] = {(cuuint64_t)D_ * 2, 128};
    cuuint32_t bd[3] = {64, 64, 7};
    cuuint32_t es[3] = {1, 1, 1};
    enc(&tx, CU_TENSOR_MAP_DATA_TYPE_BFLOAT16, 3, const_cast<__nv_bfloat16*>(x), gd, gs, bd, es, CU_TENSOR_MAP_INTERLEAVE_NONE, CU_TENSOR_MAP_SWIZZLE_128B,
        CU_TENSOR_MAP_L2_PROMOTION_L2_128B, CU_TENSOR_MAP_FLOAT_OOB_FILL_NONE);
  }
  make_map(enc, &tg, w_gate, F_, D_, 64, 64, CU_TENSOR_MAP_SWIZZLE_128B);
  make_map(enc, &tu, w_up, F_, D_, 64, 64, CU_TENSOR_MAP_SWIZZLE_128B);
  make_map(enc, &tg32, w_gate, F_, D_, 32, 128, CU_TENSOR_MAP_SWIZZLE_64B);
  make_map(enc, &tu32, w_up, F_, D_, 32, 128, CU_TENSOR_MAP_SWIZZLE_64B);
  make_map(enc, &td, w_down, D_, F_, 64, 32, CU_TENSOR_MAP_SWIZZLE_128B);
  make_map(enc, &ts, (const __nv_bfloat16*)xbuf, XP / 2, 448, 64, 64, CU_TENSOR_MAP_SWIZZLE_NONE);
  fused_kernel<<<128, NTHREADS, SMEM_BYTES>>>(tx, tg, tu, tg32, tu32, td, ts, w_r, w_i, w_gate, w_up, w_down, gate_w, (__nv_bfloat16*)d_out);
}
```

```cpp
#include <cuda_runtime.h>
#include <cuda_bf16.h>
#include <cuda.h>
#include <stdint.h>

namespace {

constexpr int S_ = 2048, D_ = 448, F_ = 1792;
constexpr int NTHREADS = 512;
constexpr int SLOT = 16384, NSLOT = 7;
constexpr int HALF_XR = 57344;
constexpr int OFF_PQ = NSLOT * SLOT;
constexpr int OFF_R = OFF_PQ + HALF_XR;
constexpr int OFF_EXCH = OFF_PQ;
constexpr int OFF_WS = OFF_EXCH + 18432;
constexpr int OFF_TW = OFF_WS + 16384;
constexpr int OFF_MISC = OFF_R + HALF_XR;
constexpr int OFF_G = OFF_MISC;
constexpr int OFF_BAR = OFF_MISC + 512;
constexpr int SMEM_BYTES = OFF_BAR + 512;
constexpr int B_FULL = 0, B_EMPTY = 7, B_XFULL = 14  ;
constexpr int B_XFREE = 16  , B_PUBX = 18, B_RFREE = 19, B_LFREE = 20;
constexpr int B_PUBW = 21;
constexpr int B_PQFULL = 22  , B_RECV = 26, B_WFULL = 27, B_XCFULL = 28, B_PREP = 29, B_RFULL = 30, B_GFULL = 31, B_XDONE = 32, B_WDONE = 33, B_SEEN = 34, B_END = 35, B_PIN = 35;

constexpr int G_IMG = 224 * 56 * 2;

__device__ __align__(1024) unsigned char g_H[32 * 56 * 4096];
constexpr int XP = 28672;
__device__ __align__(1024) unsigned char g_X[448 * XP];
__device__ __align__(1024) unsigned char g_G[8 * G_IMG];
__device__ __align__(1024) float g_gate[S_];
__device__ __align__(128) unsigned int g_ep[128];
__device__ __align__(128) unsigned int g_cnt[8 * 32];

#define POLL ld_relaxed
#define PROF(role, idx) do {} while (0)
#define PROFG(role, idx) do {} while (0)

__device__ __forceinline__ uint32_t s2u(const void* p) { return (uint32_t)__cvta_generic_to_shared(p); }
__device__ __forceinline__ void mbar_init(uint32_t b, int c) { asm volatile("mbarrier.init.shared::cta.b64 [%0], %1;" :: "r"(b), "r"(c) : "memory"); }
__device__ __forceinline__ void mbar_expect(uint32_t b, int bytes) { asm volatile("mbarrier.arrive.expect_tx.shared::cta.b64 _, [%0], %1;" :: "r"(b), "r"(bytes) : "memory"); }
__device__ __forceinline__ void mbar_arrive(uint32_t b) { asm volatile("mbarrier.arrive.shared::cta.b64 _, [%0];" :: "r"(b) : "memory"); }
__device__ __forceinline__ void mbar_wait(uint32_t b, int ph) {
  asm volatile("{\n.reg .pred p;\n.reg .u32 c;\nmov.u32 c, 0;\nL_WAIT:\nmbarrier.try_wait.parity.shared::cta.b64 p, [%0], %1;\n@p bra.uni L_DONE;\n"
               "add.u32 c, c, 1;\nsetp.lt.u32 p, c, 4194304;\n@p bra.uni L_WAIT;\ntrap;\nL_DONE:\n}" :: "r"(b), "r"(ph) : "memory");
}
__device__ __forceinline__ void mbar_wait_cluster(uint32_t b, int ph) {
  asm volatile("{\n.reg .pred p;\n.reg .u32 c;\nmov.u32 c, 0;\nL_WAIT:\nmbarrier.try_wait.parity.acquire.cluster.shared::cta.b64 p, [%0], %1;\n@p bra.uni L_DONE;\n"
               "add.u32 c, c, 1;\nsetp.lt.u32 p, c, 4194304;\n@p bra.uni L_WAIT;\ntrap;\nL_DONE:\n}" :: "r"(b), "r"(ph) : "memory");
}
__device__ __forceinline__ uint32_t ld_acquire(const unsigned int* p) { uint32_t v; asm volatile("ld.acquire.gpu.global.u32 %0, [%1];" : "=r"(v) : "l"(p) : "memory"); return v; }
__device__ __forceinline__ uint32_t ld_relaxed(const unsigned int* p) { uint32_t v; asm volatile("ld.relaxed.gpu.global.u32 %0, [%1];" : "=r"(v) : "l"(p) : "memory"); return v; }
__device__ __forceinline__ void wait_ge(const unsigned int* p, uint32_t target) {
#pragma unroll 1
  for (int i = 0; i < (1 << 22); i++) { if ((int)(POLL(p) - target) >= 0) return; }
  __trap();
}
__device__ __forceinline__ void red_relaxed(unsigned int* p) { asm volatile("red.relaxed.gpu.global.add.u32 [%0], 1;" :: "l"(p) : "memory"); }
__device__ __forceinline__ bool elect() { uint32_t p; asm volatile("{\n.reg .pred p;\nelect.sync _|p, 0xffffffff;\nselp.u32 %0, 1, 0, p;\n}" : "=r"(p)); return p; }
__device__ __forceinline__ void fence_async_smem() { asm volatile("fence.proxy.async.shared::cta;" ::: "memory"); }
__device__ __forceinline__ void fence_async_global() { asm volatile("fence.proxy.async.global;" ::: "memory"); }
template <int ID, int N> __device__ __forceinline__ void bar_sync() { asm volatile("bar.sync %0, %1;" :: "n"(ID), "n"(N) : "memory"); }
template <int ID, int N> __device__ __forceinline__ void bar_arrive() { asm volatile("bar.arrive %0, %1;" :: "n"(ID), "n"(N) : "memory"); }
__device__ __forceinline__ void tma2d(uint32_t dst, const CUtensorMap* tm, int c0, int c1, uint32_t bar) {
  asm volatile("cp.async.bulk.tensor.2d.shared::cluster.global.mbarrier::complete_tx::bytes [%0], [%1, {%3, %4}], [%2];"
               :: "r"(dst), "l"(tm), "r"(bar), "r"(c0), "r"(c1) : "memory");
}
__device__ __forceinline__ void tma3d(uint32_t dst, const CUtensorMap* tm, int c0, int c1, int c2, uint32_t bar) {
  asm volatile("cp.async.bulk.tensor.3d.shared::cluster.global.mbarrier::complete_tx::bytes [%0], [%1, {%3, %4, %5}], [%2];"
               :: "r"(dst), "l"(tm), "r"(bar), "r"(c0), "r"(c1), "r"(c2) : "memory");
}
__device__ __forceinline__ void bulk_g2s(uint32_t dst, const void* src, int bytes, uint32_t bar) {
  asm volatile("cp.async.bulk.shared::cluster.global.mbarrier::complete_tx::bytes [%0], [%1], %2, [%3];"
               :: "r"(dst), "l"(src), "r"(bytes), "r"(bar) : "memory");
}
__device__ __forceinline__ void tma_store(const CUtensorMap* tm, int c0, int c1, uint32_t src) {
  asm volatile("cp.async.bulk.tensor.2d.global.shared::cta.bulk_group [%0, {%1, %2}], [%3];" :: "l"(tm), "r"(c0), "r"(c1), "r"(src) : "memory");
}
__device__ __forceinline__ void bulk_done() { asm volatile("cp.async.bulk.commit_group;\ncp.async.bulk.wait_group 0;\nfence.proxy.async.global;" ::: "memory"); }
__device__ __forceinline__ void sts32(uint32_t a, uint32_t x) { asm volatile("st.shared.b32 [%0], %1;" :: "r"(a), "r"(x) : "memory"); }
__device__ __forceinline__ void prefetch_l2(const void* src, int bytes) {
  asm volatile("cp.async.bulk.prefetch.L2.global [%0], %1;" :: "l"(src), "r"(bytes) : "memory");
}
__device__ __forceinline__ uint64_t mkdesc(uint32_t addr, uint32_t lbo, uint32_t sbo, uint32_t mode) {
  return (uint64_t)((addr & 0x3FFFF) >> 4) | ((uint64_t)(lbo >> 4) << 16) | ((uint64_t)(sbo >> 4) << 32) | ((uint64_t)mode << 62);
}
__device__ __forceinline__ void wg_fence() { asm volatile("wgmma.fence.sync.aligned;" ::: "memory"); }
__device__ __forceinline__ void wg_commit() { asm volatile("wgmma.commit_group.sync.aligned;" ::: "memory"); }
template <int N> __device__ __forceinline__ void wg_wait() { asm volatile("wgmma.wait_group.sync.aligned %0;" :: "n"(N) : "memory"); }
template <int N> __device__ __forceinline__ void keep(float (&d)[N]) {
#pragma unroll
  for (int i = 0; i < N; i++) asm volatile("" : "+f"(d[i]) :: "memory");
}
__device__ __forceinline__ uint32_t pack_bf16(float lo, float hi) { uint32_t r; asm("cvt.rn.bf16x2.f32 %0, %1, %2;" : "=r"(r) : "f"(hi), "f"(lo)); return r; }
__device__ __forceinline__ float bf16_round(float v) { return __bfloat162float(__float2bfloat16_rn(v)); }
__device__ __forceinline__ void sts128(uint32_t a, uint32_t x, uint32_t y, uint32_t z, uint32_t w) { asm volatile("st.shared.v4.b32 [%0], {%1,%2,%3,%4};" :: "r"(a), "r"(x), "r"(y), "r"(z), "r"(w) : "memory"); }
__device__ __forceinline__ float4 lds128f(uint32_t a) { float4 v; asm volatile("ld.shared.v4.f32 {%0,%1,%2,%3}, [%4];" : "=f"(v.x), "=f"(v.y), "=f"(v.z), "=f"(v.w) : "r"(a) : "memory"); return v; }

__device__ __forceinline__ uint2 lds64(uint32_t a) { uint2 v; asm volatile("ld.shared.v2.b32 {%0,%1}, [%2];" : "=r"(v.x), "=r"(v.y) : "r"(a) : "memory"); return v; }
__device__ __forceinline__ float bf_lo(uint32_t w) { return __uint_as_float(w << 16); }
__device__ __forceinline__ float bf_hi(uint32_t w) { return __uint_as_float(w & 0xffff0000u); }
__device__ __forceinline__ uint32_t opaque(uint32_t v) { asm volatile("" : "+r"(v)); return v; }
__device__ __forceinline__ uint4 ldg128(const void* p) { uint4 v; asm volatile("ld.global.nc.v4.b32 {%0,%1,%2,%3}, [%4];" : "=r"(v.x), "=r"(v.y), "=r"(v.z), "=r"(v.w) : "l"(p)); return v; }
__device__ __forceinline__ void stg128(void* p, uint32_t x, uint32_t y, uint32_t z, uint32_t w) { asm volatile("st.global.v4.b32 [%0], {%1,%2,%3,%4};" :: "l"(p), "r"(x), "r"(y), "r"(z), "r"(w) : "memory"); }
__device__ __forceinline__ void stg128_l2(void* p, uint32_t x, uint32_t y, uint32_t z, uint32_t w) { asm volatile("st.relaxed.gpu.global.v4.b32 [%0], {%1,%2,%3,%4};" :: "l"(p), "r"(x), "r"(y), "r"(z), "r"(w) : "memory"); }
__device__ __forceinline__ uint2 ldg64_l2(const void* p) { uint2 v; asm volatile("ld.relaxed.gpu.global.v2.b32 {%0,%1}, [%2];" : "=r"(v.x), "=r"(v.y) : "l"(p) : "memory"); return v; }
__device__ __forceinline__ void ldg128_l2(uint32_t (&v)[4], const void* p) { asm volatile("ld.relaxed.gpu.global.v4.b32 {%0,%1,%2,%3}, [%4];" : "=r"(v[0]), "=r"(v[1]), "=r"(v[2]), "=r"(v[3]) : "l"(p) : "memory"); }
__device__ __forceinline__ uint4 lds128(uint32_t a) { uint4 v; asm volatile("ld.shared.v4.b32 {%0,%1,%2,%3}, [%4];" : "=r"(v.x), "=r"(v.y), "=r"(v.z), "=r"(v.w) : "r"(a) : "memory"); return v; }
__device__ __forceinline__ uint32_t lds16(uint32_t a) { uint32_t v; asm volatile("ld.shared.u16 %0, [%1];" : "=r"(v) : "r"(a) : "memory"); return v; }
__device__ __forceinline__ void sts64(uint32_t a, uint32_t x, uint32_t y) { asm volatile("st.shared.v2.b32 [%0], {%1,%2};" :: "r"(a), "r"(x), "r"(y) : "memory"); }
template <int TB> __device__ __forceinline__ void wgmma_rs_128(float (&d)[64], const uint32_t (&a)[4], uint64_t db, int sc) {
  asm volatile("{\n.reg .pred p;\nsetp.ne.b32 p, %69, 0;\n"
    "wgmma.mma_async.sync.aligned.m64n128k16.f32.bf16.bf16 {%0, %1, %2, %3, %4, %5, %6, %7, %8, %9, %10, %11, %12, %13, %14, %15, %16, %17, %18, %19, %20, %21, %22, %23, %24, %25, %26, %27, %28, %29, %30, %31, %32, %33, %34, %35, %36, %37, %38, %39, %40, %41, %42, %43, %44, %45, %46, %47, %48, %49, %50, %51, %52, %53, %54, %55, %56, %57, %58, %59, %60, %61, %62, %63}, {%64, %65, %66, %67}, %68, p, 1, 1, %70;\n}\n"
    : "+f"(d[0]), "+f"(d[1]), "+f"(d[2]), "+f"(d[3]), "+f"(d[4]), "+f"(d[5]), "+f"(d[6]), "+f"(d[7]), "+f"(d[8]), "+f"(d[9]), "+f"(d[10]), "+f"(d[11]), "+f"(d[12]), "+f"(d[13]), "+f"(d[14]), "+f"(d[15]), "+f"(d[16]), "+f"(d[17]), "+f"(d[18]), "+f"(d[19]), "+f"(d[20]), "+f"(d[21]), "+f"(d[22]), "+f"(d[23]), "+f"(d[24]), "+f"(d[25]), "+f"(d[26]), "+f"(d[27]), "+f"(d[28]), "+f"(d[29]), "+f"(d[30]), "+f"(d[31]), "+f"(d[32]), "+f"(d[33]), "+f"(d[34]), "+f"(d[35]), "+f"(d[36]), "+f"(d[37]), "+f"(d[38]), "+f"(d[39]), "+f"(d[40]), "+f"(d[41]), "+f"(d[42]), "+f"(d[43]), "+f"(d[44]), "+f"(d[45]), "+f"(d[46]), "+f"(d[47]), "+f"(d[48]), "+f"(d[49]), "+f"(d[50]), "+f"(d[51]), "+f"(d[52]), "+f"(d[53]), "+f"(d[54]), "+f"(d[55]), "+f"(d[56]), "+f"(d[57]), "+f"(d[58]), "+f"(d[59]), "+f"(d[60]), "+f"(d[61]), "+f"(d[62]), "+f"(d[63])
    : "r"(a[0]), "r"(a[1]), "r"(a[2]), "r"(a[3]), "l"(db), "r"(sc), "n"(TB));
}
template <int TB> __device__ __forceinline__ void wgmma_rs_64(float (&d)[32], const uint32_t (&a)[4], uint64_t db, int sc) {
  asm volatile("{\n.reg .pred p;\nsetp.ne.b32 p, %37, 0;\n"
    "wgmma.mma_async.sync.aligned.m64n64k16.f32.bf16.bf16 {%0, %1, %2, %3, %4, %5, %6, %7, %8, %9, %10, %11, %12, %13, %14, %15, %16, %17, %18, %19, %20, %21, %22, %23, %24, %25, %26, %27, %28, %29, %30, %31}, {%32, %33, %34, %35}, %36, p, 1, 1, %38;\n}\n"
    : "+f"(d[0]), "+f"(d[1]), "+f"(d[2]), "+f"(d[3]), "+f"(d[4]), "+f"(d[5]), "+f"(d[6]), "+f"(d[7]), "+f"(d[8]), "+f"(d[9]), "+f"(d[10]), "+f"(d[11]), "+f"(d[12]), "+f"(d[13]), "+f"(d[14]), "+f"(d[15]), "+f"(d[16]), "+f"(d[17]), "+f"(d[18]), "+f"(d[19]), "+f"(d[20]), "+f"(d[21]), "+f"(d[22]), "+f"(d[23]), "+f"(d[24]), "+f"(d[25]), "+f"(d[26]), "+f"(d[27]), "+f"(d[28]), "+f"(d[29]), "+f"(d[30]), "+f"(d[31])
    : "r"(a[0]), "r"(a[1]), "r"(a[2]), "r"(a[3]), "l"(db), "r"(sc), "n"(TB));
}
template <int TB> __device__ __forceinline__ void wgmma_rs_56(float (&d)[28], const uint32_t (&a)[4], uint64_t db, int sc) {
  asm volatile("{\n.reg .pred p;\nsetp.ne.b32 p, %33, 0;\n"
    "wgmma.mma_async.sync.aligned.m64n56k16.f32.bf16.bf16 {%0, %1, %2, %3, %4, %5, %6, %7, %8, %9, %10, %11, %12, %13, %14, %15, %16, %17, %18, %19, %20, %21, %22, %23, %24, %25, %26, %27}, {%28, %29, %30, %31}, %32, p, 1, 1, %34;\n}\n"
    : "+f"(d[0]), "+f"(d[1]), "+f"(d[2]), "+f"(d[3]), "+f"(d[4]), "+f"(d[5]), "+f"(d[6]), "+f"(d[7]), "+f"(d[8]), "+f"(d[9]), "+f"(d[10]), "+f"(d[11]), "+f"(d[12]), "+f"(d[13]), "+f"(d[14]), "+f"(d[15]), "+f"(d[16]), "+f"(d[17]), "+f"(d[18]), "+f"(d[19]), "+f"(d[20]), "+f"(d[21]), "+f"(d[22]), "+f"(d[23]), "+f"(d[24]), "+f"(d[25]), "+f"(d[26]), "+f"(d[27])
    : "r"(a[0]), "r"(a[1]), "r"(a[2]), "r"(a[3]), "l"(db), "r"(sc), "n"(TB));
}
template <int TB> __device__ __forceinline__ void wgmma_rs_112(float (&d)[56], const uint32_t (&a)[4], uint64_t db, int sc) {
  asm volatile("{\n.reg .pred p;\nsetp.ne.b32 p, %61, 0;\n"
    "wgmma.mma_async.sync.aligned.m64n112k16.f32.bf16.bf16 {%0, %1, %2, %3, %4, %5, %6, %7, %8, %9, %10, %11, %12, %13, %14, %15, %16, %17, %18, %19, %20, %21, %22, %23, %24, %25, %26, %27, %28, %29, %30, %31, %32, %33, %34, %35, %36, %37, %38, %39, %40, %41, %42, %43, %44, %45, %46, %47, %48, %49, %50, %51, %52, %53, %54, %55}, {%56, %57, %58, %59}, %60, p, 1, 1, %62;\n}\n"
    : "+f"(d[0]), "+f"(d[1]), "+f"(d[2]), "+f"(d[3]), "+f"(d[4]), "+f"(d[5]), "+f"(d[6]), "+f"(d[7]), "+f"(d[8]), "+f"(d[9]), "+f"(d[10]), "+f"(d[11]), "+f"(d[12]), "+f"(d[13]), "+f"(d[14]), "+f"(d[15]), "+f"(d[16]), "+f"(d[17]), "+f"(d[18]), "+f"(d[19]), "+f"(d[20]), "+f"(d[21]), "+f"(d[22]), "+f"(d[23]), "+f"(d[24]), "+f"(d[25]), "+f"(d[26]), "+f"(d[27]), "+f"(d[28]), "+f"(d[29]), "+f"(d[30]), "+f"(d[31]), "+f"(d[32]), "+f"(d[33]), "+f"(d[34]), "+f"(d[35]), "+f"(d[36]), "+f"(d[37]), "+f"(d[38]), "+f"(d[39]), "+f"(d[40]), "+f"(d[41]), "+f"(d[42]), "+f"(d[43]), "+f"(d[44]), "+f"(d[45]), "+f"(d[46]), "+f"(d[47]), "+f"(d[48]), "+f"(d[49]), "+f"(d[50]), "+f"(d[51]), "+f"(d[52]), "+f"(d[53]), "+f"(d[54]), "+f"(d[55])
    : "r"(a[0]), "r"(a[1]), "r"(a[2]), "r"(a[3]), "l"(db), "r"(sc), "n"(TB));
}
template <int TA, int TB> __device__ __forceinline__ void wgmma_ss_56(float (&d)[28], uint64_t da, uint64_t db, int sc) {
  asm volatile("{\n.reg .pred p;\nsetp.ne.b32 p, %30, 0;\n"
    "wgmma.mma_async.sync.aligned.m64n56k16.f32.bf16.bf16 {%0, %1, %2, %3, %4, %5, %6, %7, %8, %9, %10, %11, %12, %13, %14, %15, %16, %17, %18, %19, %20, %21, %22, %23, %24, %25, %26, %27}, %28, %29, p, 1, 1, %31, %32;\n}\n"
    : "+f"(d[0]), "+f"(d[1]), "+f"(d[2]), "+f"(d[3]), "+f"(d[4]), "+f"(d[5]), "+f"(d[6]), "+f"(d[7]), "+f"(d[8]), "+f"(d[9]), "+f"(d[10]), "+f"(d[11]), "+f"(d[12]), "+f"(d[13]), "+f"(d[14]), "+f"(d[15]), "+f"(d[16]), "+f"(d[17]), "+f"(d[18]), "+f"(d[19]), "+f"(d[20]), "+f"(d[21]), "+f"(d[22]), "+f"(d[23]), "+f"(d[24]), "+f"(d[25]), "+f"(d[26]), "+f"(d[27])
    : "l"(da), "l"(db), "r"(sc), "n"(TA), "n"(TB));
}

__device__ __forceinline__ uint32_t cis(float a) { return pack_bf16(__cosf(a), __sinf(a)); }

typedef __nv_bfloat162 b2;
struct c2 { b2 x, y; };
__device__ __forceinline__ b2 as_b2(uint32_t u) { return *reinterpret_cast<b2*>(&u); }
__device__ __forceinline__ uint32_t as_u(b2 v) { return *reinterpret_cast<uint32_t*>(&v); }
__device__ __forceinline__ c2 mk(b2 x, b2 y) { c2 r; r.x = x; r.y = y; return r; }
__device__ __forceinline__ c2 cmul(c2 a, b2 wr, b2 wi) { return mk(__hfma2(a.x, wr, __hneg2(__hmul2(a.y, wi))), __hfma2(a.x, wi, __hmul2(a.y, wr))); }
__device__ __forceinline__ void fft4(c2& a0, c2& a1, c2& a2, c2& a3) {
  c2 t0 = mk(__hadd2(a0.x, a2.x), __hadd2(a0.y, a2.y)), t1 = mk(__hsub2(a0.x, a2.x), __hsub2(a0.y, a2.y));
  c2 t2 = mk(__hadd2(a1.x, a3.x), __hadd2(a1.y, a3.y)), t3 = mk(__hsub2(a1.x, a3.x), __hsub2(a1.y, a3.y));
  a0 = mk(__hadd2(t0.x, t2.x), __hadd2(t0.y, t2.y)); a2 = mk(__hsub2(t0.x, t2.x), __hsub2(t0.y, t2.y));
  a1 = mk(__hadd2(t1.x, t3.y), __hsub2(t1.y, t3.x)); a3 = mk(__hsub2(t1.x, t3.y), __hadd2(t1.y, t3.x));
}
__device__ __forceinline__ void fft4_s2(c2& a0, c2& a1, c2& a2, c2& a3, b2 r) {
  const b2 nr = __hneg2(r);
  c2 t0 = mk(__hfma2(a2.x, r, a0.x), __hfma2(a2.y, r, a0.y)), t1 = mk(__hfma2(a2.x, nr, a0.x), __hfma2(a2.y, nr, a0.y));
  c2 t2 = mk(__hadd2(a1.x, a3.x), __hadd2(a1.y, a3.y)), t3 = mk(__hsub2(a1.x, a3.x), __hsub2(a1.y, a3.y));
  a0 = mk(__hadd2(t0.x, t2.x), __hadd2(t0.y, t2.y)); a2 = mk(__hsub2(t0.x, t2.x), __hsub2(t0.y, t2.y));
  a1 = mk(__hadd2(t1.x, t3.y), __hsub2(t1.y, t3.x)); a3 = mk(__hsub2(t1.x, t3.y), __hadd2(t1.y, t3.x));
}
__device__ __forceinline__ void fft4_s13(c2& a0, c2& a1, c2& a2, c2& a3, b2 r) {
  const b2 nr = __hneg2(r);
  c2 t0 = mk(__hadd2(a0.x, a2.x), __hadd2(a0.y, a2.y)), t1 = mk(__hsub2(a0.x, a2.x), __hsub2(a0.y, a2.y));
  c2 t2 = mk(__hadd2(a1.x, a3.x), __hadd2(a1.y, a3.y)), t3 = mk(__hsub2(a1.x, a3.x), __hsub2(a1.y, a3.y));
  a0 = mk(__hfma2(t2.x, r, t0.x), __hfma2(t2.y, r, t0.y)); a2 = mk(__hfma2(t2.x, nr, t0.x), __hfma2(t2.y, nr, t0.y));
  a1 = mk(__hfma2(t3.y, r, t1.x), __hfma2(t3.x, nr, t1.y)); a3 = mk(__hfma2(t3.y, nr, t1.x), __hfma2(t3.x, r, t1.y));
}
__device__ __forceinline__ c2 rot1(c2 a) { return mk(__hadd2(a.x, a.y), __hsub2(a.y, a.x)); }
__device__ __forceinline__ c2 rot3(c2 a) { return mk(__hsub2(a.y, a.x), __hneg2(__hadd2(a.x, a.y))); }
__device__ __forceinline__ c2 mul_mi(c2 a) { return mk(a.y, __hneg2(a.x)); }
template <int O> __device__ __forceinline__ void fft8(c2 (&v)[16]) {
  const b2 r = as_b2(0x3F353F35u), nr = as_b2(0xBF35BF35u);
  fft4(v[O], v[O + 4], v[O + 8], v[O + 12]);
  fft4(v[O + 2], v[O + 6], v[O + 10], v[O + 14]);
  const c2 o0 = v[O + 2], o1 = rot1(v[O + 6]), o2 = v[O + 10], o3 = rot1(v[O + 14]);
  const c2 e0 = v[O], e1 = v[O + 4], e2 = v[O + 8], e3 = v[O + 12];
  v[O] = mk(__hadd2(e0.x, o0.x), __hadd2(e0.y, o0.y));              v[O + 8] = mk(__hsub2(e0.x, o0.x), __hsub2(e0.y, o0.y));
  v[O + 2] = mk(__hfma2(o1.x, r, e1.x), __hfma2(o1.y, r, e1.y));    v[O + 10] = mk(__hfma2(o1.x, nr, e1.x), __hfma2(o1.y, nr, e1.y));
  v[O + 4] = mk(__hadd2(e2.x, o2.y), __hsub2(e2.y, o2.x));          v[O + 12] = mk(__hsub2(e2.x, o2.y), __hadd2(e2.y, o2.x));
  v[O + 6] = mk(__hfma2(o3.y, r, e3.x), __hfma2(o3.x, nr, e3.y));   v[O + 14] = mk(__hfma2(o3.y, nr, e3.x), __hfma2(o3.x, r, e3.y));
}
__device__ __forceinline__ void fft16(c2 (&v)[16]) {
  const b2 r = as_b2(0x3F353F35u), c1 = as_b2(0x3F6D3F6Du), s1 = as_b2(0x3EC43EC4u), nc1 = as_b2(0xBF6DBF6Du), ns1 = as_b2(0xBEC4BEC4u);
#pragma unroll
  for (int a = 0; a < 4; a++) fft4(v[a], v[a + 4], v[a + 8], v[a + 12]);
  v[5] = cmul(v[5], c1, ns1); v[6] = rot1(v[6]); v[7] = cmul(v[7], s1, nc1);
  v[9] = rot1(v[9]); v[10] = mul_mi(v[10]); v[11] = rot3(v[11]);
  v[13] = cmul(v[13], s1, nc1); v[14] = rot3(v[14]); v[15] = cmul(v[15], nc1, s1);
  fft4(v[0], v[1], v[2], v[3]); fft4_s2(v[4], v[5], v[6], v[7], r); fft4_s13(v[8], v[9], v[10], v[11], r); fft4_s2(v[12], v[13], v[14], v[15], r);
  c2 t;
  t = v[1]; v[1] = v[4]; v[4] = t;  t = v[2]; v[2] = v[8]; v[8] = t;  t = v[3]; v[3] = v[12]; v[12] = t;
  t = v[6]; v[6] = v[9]; v[9] = t;  t = v[7]; v[7] = v[13]; v[13] = t; t = v[11]; v[11] = v[14]; v[14] = t;
}

__device__ __forceinline__ void columns(c2 (&v)[16], uint32_t sb, int t) {
  const int l16 = t & 15;
  const uint32_t row = sb + OFF_EXCH + (t >> 4) * 2304;
  const uint32_t pos = sb + OFF_EXCH + (t >> 3) * 144 + (t & 7) * 16;
#pragma unroll 1
  for (int ps = 0; ps < 6; ps++) {
    if (ps == 0 || ps == 5) { fft8<0>(v); fft8<1>(v); } else fft16(v);
    if (ps == 5) break;
    if (ps == 2) {
      const uint32_t ws = sb + OFF_WS + (l16 >> 1) * 128 + ((((t >> 4) + (l16 >> 1)) & 7) * 2 + (l16 & 1)) * 8;
      mbar_wait(sb + OFF_BAR + B_WFULL * 8, 0);
#pragma unroll
      for (int q = 0; q < 16; q++) {
        const uint2 w = lds64(ws + q * 1024);
        const c2 z = cmul(v[q], as_b2(w.x), as_b2(w.y));
        v[q] = mk(z.y, z.x);
      }
      continue;
    }
    {
      const bool full = ps == 0 || ps == 4;
      const uint32_t tw = sb + OFF_TW + (full ? ps * 2048 + t * 16 : 16384 + l16 * 16);
      const uint32_t st = full ? 2048 : 256;
#pragma unroll
      for (int i = 0; i < 4; i++) {
        const uint4 w4 = lds128(tw + i * st);
        const uint32_t w[4] = {w4.x, w4.y, w4.z, w4.w};
#pragma unroll
        for (int e = 0; e < 4; e++) v[4 * i + e] = cmul(v[4 * i + e], __low2bfloat162(as_b2(w[e])), __high2bfloat162(as_b2(w[e])));
      }
    }
    if (ps == 0) {
      mbar_wait(sb + OFF_BAR + B_XDONE * 8, 0);
#pragma unroll
      for (int q = 0; q < 8; q++) sts128(pos + q * 2304, as_u(v[2 * q].x), as_u(v[2 * q].y), as_u(v[2 * q + 1].x), as_u(v[2 * q + 1].y));
      bar_sync<3, 128>();
#pragma unroll
      for (int q = 0; q < 16; q++) { const uint2 a = lds64(row + q * 144 + l16 * 8); v[q] = mk(as_b2(a.x), as_b2(a.y)); }
    } else {
      __syncwarp();
#pragma unroll
      for (int q = 0; q < 16; q++) sts64(row + q * 144 + l16 * 8, as_u(v[q].x), as_u(v[q].y));
      if (ps == 4) bar_sync<3, 128>(); else __syncwarp();
      const uint32_t src = ps == 4 ? pos : row + l16 * 144, st = ps == 4 ? 2304 : 16;
#pragma unroll
      for (int q = 0; q < 8; q++) { const uint4 a = lds128(src + q * st); v[2 * q] = mk(as_b2(a.x), as_b2(a.y)); v[2 * q + 1] = mk(as_b2(a.z), as_b2(a.w)); }
    }
  }
}

template <int NH> __device__ __forceinline__ void h_epilogue(float (&acc)[NH * 8], unsigned char* gdst, uint32_t tag) {
#pragma unroll
  for (int c = 0; c < NH / 2; c++) {
    uint32_t pk[4];
#pragma unroll
    for (int i = 0; i < 4; i++) {
      float hv[2];
#pragma unroll
      for (int e = 0; e < 2; e++) {
        float hg = 0.5f * acc[c * 8 + i * 2 + e], up = acc[NH * 4 + c * 8 + i * 2 + e];
        float th; asm("tanh.approx.f32 %0, %1;" : "=f"(th) : "f"(hg));
        hv[e] = fmaf(hg, th, hg) * up;
      }
      pk[i] = pack_bf16(hv[0], hv[1]);
    }
    stg128_l2(gdst + c * 4096, (pk[0] & ~1u) | tag, pk[1], pk[2], pk[3]);
  }
}

__device__ __forceinline__ void frag_ready(uint32_t (&a)[4], uint32_t (&b)[4], uint32_t (&c)[4], uint32_t (&d)[4], const unsigned char* p, uint32_t tag) {
  asm volatile("{\n.reg .pred p;\n.reg .u32 c, m, q;\nmov.u32 c, 0;\nL_TRY:\n"
               "lop3.b32 m, %0, %4, %17, 0x7E;\nlop3.b32 q, %8, %12, %17, 0x7E;\nlop3.b32 m, m, q, 1, 0xA8;\nsetp.ne.u32 p, m, 0;\n"
               "vote.sync.any.pred p, p, 0xffffffff;\n@!p bra.uni L_OK;\n"
               "ld.relaxed.gpu.global.v4.b32 {%0,%1,%2,%3}, [%16];\nld.relaxed.gpu.global.v4.b32 {%4,%5,%6,%7}, [%16+4096];\n"
               "ld.relaxed.gpu.global.v4.b32 {%8,%9,%10,%11}, [%16+8192];\nld.relaxed.gpu.global.v4.b32 {%12,%13,%14,%15}, [%16+12288];\n"
               "add.u32 c, c, 1;\nsetp.lt.u32 p, c, 262144;\n@p bra.uni L_TRY;\ntrap;\nL_OK:\n}"
               : "+r"(a[0]), "+r"(a[1]), "+r"(a[2]), "+r"(a[3]), "+r"(b[0]), "+r"(b[1]), "+r"(b[2]), "+r"(b[3]),
                 "+r"(c[0]), "+r"(c[1]), "+r"(c[2]), "+r"(c[3]), "+r"(d[0]), "+r"(d[1]), "+r"(d[2]), "+r"(d[3])
               : "l"(p), "r"(tag) : "memory");
}

#define MAP 0
#define STAG 250
#define RP0 6
#define LEAD2 0
#define LEAD1 2

__global__ void __cluster_dims__(2, 1, 1) __launch_bounds__(NTHREADS, 1)
fused_kernel(const __grid_constant__ CUtensorMap tm_x, const __grid_constant__ CUtensorMap tm_g, const __grid_constant__ CUtensorMap tm_u,
             const __grid_constant__ CUtensorMap tm_g32, const __grid_constant__ CUtensorMap tm_u32, const __grid_constant__ CUtensorMap tm_d,
             const __grid_constant__ CUtensorMap tm_s,
             const __nv_bfloat16* __restrict__ w_r, const __nv_bfloat16* __restrict__ w_i,
             const __nv_bfloat16* __restrict__ w_gate, const __nv_bfloat16* __restrict__ w_up,
             const __nv_bfloat16* __restrict__ w_down, const __nv_bfloat16* __restrict__ gate_w, __nv_bfloat16* __restrict__ out) {
  extern __shared__ __align__(1024) unsigned char smem[];
  const uint32_t sb = s2u(smem);
  const uint32_t bars = sb + OFF_BAR;
  const int tid = threadIdx.x, warp = __shfl_sync(0xffffffffu, tid >> 5, 0), lane = tid & 31;
  const int cl = blockIdx.x >> 1, kh = blockIdx.x & 1;
  const int n0 = cl < 4 ? cl : (cl < 36 ? (cl - 4) >> 3 : (cl - 36) / 7);
  const int m0 = cl < 4 ? 15 : (cl < 36 ? (cl - 4) & 7 : cl - 28 - 7 * n0);
  const int n = MAP == 0 ? n0 : (MAP == 1 ? (m0 & 3) : ((n0 & 1) | ((m0 & 1) << 1)));
  const int m = MAP == 0 ? m0 : (MAP == 1 ? ((m0 & 12) | n0) : ((m0 & 14) | (n0 >> 1)));
  const int j = kh * 4 + n, bid = m * 8 + n * 2 + kh;

  const int c64 = 224 * j + (j & 1) * 32;
  if (warp < 8) {
    asm volatile("setmaxnreg.inc.sync.aligned.u32 208;");
    const int wg = warp >> 2, w4 = warp & 3, g = lane >> 2, t = lane & 3;
    const int rh = wg ^ kh ^ 1;
    const int p = j & 1, r = (j >> 1) & 1, hh = j >> 2;
    const uint32_t epoch = ld_relaxed(&g_ep[bid]);
    if ((tid & 127) == 0) PROF(wg, 30);
#pragma unroll 1
    for (int it = tid; it < 392; it += 256) {
      const int kc = it / 28, sg = it - kc * 28;
      const int k = 2 * (28 * hh + sg) + r;
      const float kf = (float)k * (-6.283185307179586f / 448.0f), a0 = (float)(16 * kc + p) * kf;
      uint32_t c[4], s[4];
#pragma unroll
      for (int q = 0; q < 4; q++) {
        const float a1 = fmaf((float)(2 * q), kf, a0), a2 = fmaf((float)(2 * q + 8), kf, a0);
        c[q] = pack_bf16(__cosf(a1), __cosf(a2)); s[q] = pack_bf16(__sinf(a1), __sinf(a2));
        if (k == 0) s[q] = ((q ^ p) & 1) ? 0xBF80BF80u : 0x3F803F80u;
      }
      const uint32_t a = sb + 6 * SLOT + (kc * 56 + 2 * sg) * 16;
      sts128(a, c[0], c[1], c[2], c[3]);
      sts128(a + 16, s[0], s[1], s[2], s[3]);
    }
    if ((tid & 127) == 0) PROF(wg, 31);
    fence_async_smem();
    bar_sync<0, NTHREADS - 64>();
    asm volatile("barrier.cluster.arrive.relaxed.aligned;" ::: "memory");
    if ((tid & 127) == 0) PROF(wg, 1);

    uint32_t xa[28][4];
    {
      const uint32_t xb = sb + OFF_PQ + wg * HALF_XR + (w4 * 16 + (lane & 15)) * 128;
      mbar_wait(bars + (B_XFULL + wg) * 8, 0);
      if ((tid & 127) == 0) PROF(wg, 2);
#pragma unroll
      for (int kb = 0; kb < 7; kb++) {
#pragma unroll
        for (int kk = 0; kk < 4; kk++) {
          uint32_t a = xb + kb * 8192 + (((2 * kk + (lane >> 4)) ^ (lane & 7)) << 4);
          asm volatile("ldmatrix.sync.aligned.m8n8.x4.shared.b16 {%0,%1,%2,%3}, [%4];"
                       : "=r"(xa[kb * 4 + kk][0]), "=r"(xa[kb * 4 + kk][1]), "=r"(xa[kb * 4 + kk][2]), "=r"(xa[kb * 4 + kk][3]) : "r"(a) : "memory");
        }
      }
    }
    {
      uint32_t ad[7][4];
      const uint32_t sel = p ? 0x7632 : 0x5410;
      const uint32_t sgn = r ? 0xBF80BF80u : 0x3F803F80u;
#pragma unroll
      for (int jj = 0; jj < 7; jj++) {
#pragma unroll
        for (int i = 0; i < 4; i++) {
          int ks = 2 * jj + (i >> 1), rr = i & 1;
          uint32_t lo = __byte_perm(xa[ks][rr], xa[ks][rr + 2], sel);
          uint32_t hi = __byte_perm(xa[ks + 14][rr], xa[ks + 14][rr + 2], sel);
          asm("fma.rn.bf16x2 %0, %1, %2, %3;" : "=r"(ad[jj][i]) : "r"(hi), "r"(sgn), "r"(lo));
        }
      }
      __syncwarp();
      if (lane == 0) mbar_arrive(bars + (B_XFREE + wg) * 8);
      float acc[28];
      wg_fence();
      uint64_t db = mkdesc(sb + 6 * SLOT, 896, 128, 0);
#pragma unroll
      for (int jj = 0; jj < 7; jj++) wgmma_rs_56<0>(acc, ad[jj], db + jj * 112, jj != 0);
      wg_commit();
      wg_wait<0>(); keep(acc);
      if (lane == 0) mbar_arrive(bars + (B_EMPTY + 6) * 8);
      const uint32_t xc = sb + OFF_EXCH + wg * 8192 + t * 256 + w4 * 64 + g * 4;
      mbar_wait(bars + B_XFREE * 8, 0);
#pragma unroll
      for (int i = 0; i < 7; i++) {
        sts32(xc + i * 1024, pack_bf16(acc[4 * i], acc[4 * i + 1]));
        sts32(xc + i * 1024 + 32, pack_bf16(acc[4 * i + 2], acc[4 * i + 3]));
      }
      fence_async_smem();
      __syncwarp();
      if (lane == 0) mbar_arrive(bars + B_PUBX * 8);
    }
    if ((tid & 127) == 0) PROF(wg, 3);
    const uint32_t tag = ~epoch & 1;
    unsigned char* const hbase = g_H + (size_t)(m * 2 + kh) * (56 * 4096) + rh * 2048 + (tid & 127) * 16;
#pragma unroll 1
    for (int u = 0; u < 3; u++) {
      float acc[64];
      if (wg == 1) { if (u & 1) bar_sync<6, 256>(); else bar_sync<2, 256>(); }
      const uint32_t sbu = opaque(sb);
#pragma unroll
      for (int kb = 0; kb < 7; kb++) {
        mbar_wait(sbu + OFF_BAR + (B_FULL + kb) * 8, u & 1);
        wg_fence();
        uint64_t db = mkdesc(sbu + kb * SLOT, 8192, 1024, 1);
#pragma unroll
        for (int kk = 0; kk < 4; kk++) wgmma_rs_128<1>(acc, xa[kb * 4 + kk], db + kk * 128, (kb | kk) != 0);
        wg_commit();
        if (kb == LEAD1 && wg == 0) { if (u & 1) bar_arrive<6, 256>(); else bar_arrive<2, 256>(); }
        if (kb > 0) { wg_wait<1>(); if (lane == 0) mbar_arrive(sbu + OFF_BAR + (B_EMPTY + kb - 1) * 8); }
      }
      wg_wait<0>(); keep(acc);
      if (lane == 0) mbar_arrive(sbu + OFF_BAR + (B_EMPTY + 6) * 8);
      if ((tid & 127) == 0) PROF(wg, 4 + 2 * u);
      h_epilogue<8>(acc, hbase + (u * 16 + n * 4) * 4096, tag);
      if ((tid & 127) == 0) PROF(wg, 5 + 2 * u);
    }
    uint32_t ha[14][4][4];
    auto check = [&](int b0, int b1) {
#pragma unroll
      for (int b = b0; b < b1; b++) frag_ready(ha[b][0], ha[b][1], ha[b][2], ha[b][3], hbase + b * 16384, tag);
    };
    auto load = [&](int b0, int b1) {
#pragma unroll
      for (int i = b0; i < b1; i++) ldg128_l2(ha[i >> 2][i & 3], hbase + i * 4096);
    };
    {
      float acc[32];
      load(0, 3);
      if (wg == 1) bar_sync<6, 256>();
      const uint32_t sbu = opaque(sb);
#pragma unroll
      for (int it = 0; it < 4; it++) {
        mbar_wait(sbu + OFF_BAR + (B_FULL + it) * 8, 1);
        wg_fence();
        uint64_t db = mkdesc(sbu + it * SLOT, 8192, 512, 2);
#pragma unroll
        for (int kk = 0; kk < 8; kk++) if (it * 8 + kk < 28) wgmma_rs_64<1>(acc, xa[it * 8 + kk], db + kk * 64, (it | kk) != 0);
        wg_commit();
        if (it == 2 && wg == 0) bar_arrive<6, 256>();
        if (it > 0) {
          wg_wait<1>();
          if (lane == 0) mbar_arrive(sbu + OFF_BAR + (B_EMPTY + it - 1) * 8);
          if (it == 1) load(3, 11);
          if (it == 2) load(11, 16);
        }
      }
      wg_wait<0>(); keep(acc);
      if (lane == 0) mbar_arrive(sbu + OFF_BAR + (B_EMPTY + 3) * 8);
      if ((tid & 127) == 0) PROF(wg, 10);
      h_epilogue<4>(acc, hbase + (48 + n * 2) * 4096, tag);
    }
    asm volatile("barrier.cluster.wait.aligned;" ::: "memory");
    if ((tid & 127) == 0) PROF(wg, 11);

    float acc[56];
    check(0, 4);
    if (wg == 1) bar_sync<2, 256>();
#pragma unroll
    for (int b = 0; b < 14; b++) {
      if ((tid & 127) == 0) PROF(wg, 16 + b);
      if (b >= 3) mbar_wait(bars + (B_FULL + (b + 1) % 7) * 8, b < 6 || b == 13);
      else if (b == 0) mbar_wait(bars + B_RFULL * 8, 0);
      if (b == 4) check(4, 7);
      if (b == 7) check(7, 11);
      if (b == 11) check(11, 14);
      wg_fence();
      const uint64_t db = mkdesc(b < 3 ? sb + OFF_R + b * SLOT : sb + (b + 1) % 7 * SLOT, 8192, 1024, 1);
#pragma unroll
      for (int kk = 0; kk < 4; kk++) wgmma_rs_112<1>(acc, ha[b][kk], db + kk * 128, (b | kk) != 0);
      wg_commit();
      if (b == LEAD2 && wg == 0) bar_arrive<2, 256>();
      if (b == 0) load(16, 24);
      if (b == 1) load(24, 28);
      if (b == 4 || b == 5) load(8 * b - 4, 8 * b + 4);
      if (b == 7) load(44, 52);
      if (b == 8) load(52, 56);
      if (b > 0) wg_wait<1>();
      if (lane == 0) {
        if (b >= 4 && b <= 9) mbar_arrive(bars + (B_EMPTY + b % 7) * 8);
        if (b == 3) {
          mbar_arrive(bars + B_LFREE * 8);
          asm volatile("{\n.reg .b32 ra;\nmapa.shared::cluster.u32 ra, %0, %1;\nmbarrier.arrive.relaxed.cluster.shared::cluster.b64 _, [ra];\n}"
                       :: "r"(bars + B_RFREE * 8), "r"(kh ^ 1) : "memory");
        }
      }
    }
    const int t128 = tid & 127;
    wg_wait<0>(); keep(acc);
    if (wg == 0) {
      if (t128 == 0) PROF(wg, 12);
      mbar_wait_cluster(bars + B_RFREE * 8, 0);
      uint32_t rdst, rbar;
      asm volatile("mapa.shared::cluster.u32 %0, %1, %2;" : "=r"(rdst) : "r"(sb + OFF_R + t128 * 16), "r"(kh ^ 1));
      asm volatile("mapa.shared::cluster.u32 %0, %1, %2;" : "=r"(rbar) : "r"(bars + B_RECV * 8), "r"(kh ^ 1));
#pragma unroll
      for (int i = 0; i < 7; i++)
        asm volatile("st.async.weak.shared::cluster.mbarrier::complete_tx::bytes.v4.b32 [%0], {%1,%2,%3,%4}, [%5];"
                     :: "r"(rdst + i * 2048), "r"(pack_bf16(acc[8 * i], acc[8 * i + 1])), "r"(pack_bf16(acc[8 * i + 2], acc[8 * i + 3])),
                        "r"(pack_bf16(acc[8 * i + 4], acc[8 * i + 5])), "r"(pack_bf16(acc[8 * i + 6], acc[8 * i + 7])), "r"(rbar) : "memory");
    } else {
      float spec[2][28];
      if (t128 == 0) PROF(wg, 12);
#pragma unroll
      for (int i = 0; i < 4; i++) {
        if (i == 0) mbar_wait(bars + B_GFULL * 8, 0);
        if (i >= 2) mbar_wait(bars + (B_FULL + i - 1) * 8, 1);
        mbar_wait(bars + (B_PQFULL + i) * 8, 0);
        if (i == 0 && t128 == 0) { PROF(wg, 13); g_ep[bid] = epoch + 1; }
        wg_fence();
        const uint64_t da = mkdesc(sb + OFF_PQ + i * 14336, 1024, 1024, 1);
        const uint64_t db = mkdesc(i < 2 ? sb + OFF_R + 28672 + i * (G_IMG / 2) : sb + (i - 1) * SLOT, 896, 128, 0);
#pragma unroll
        for (int kk = 0; kk < 7; kk++) wgmma_ss_56<1, 0>(spec[i >> 1], da + kk * 128, db + kk * 112, ((i & 1) | kk) != 0);
        wg_commit();
      }
      const float* gs = reinterpret_cast<const float*>(smem + OFF_G) + w4 * 16 + g;
      const float o0 = bf16_round(1.0f - gs[0]), o1 = bf16_round(1.0f - gs[8]);
      const float g0 = gs[0] * (1.0f / (float)(S_ * D_)), g1 = gs[8] * (1.0f / (float)(S_ * D_));
      mbar_wait_cluster(bars + B_RECV * 8, 0);
      if (t128 == 0) PROF(wg, 0);
#pragma unroll
      for (int i = 0; i < 7; i++) {
        const uint4 o4 = lds128(sb + OFF_R + t128 * 16 + i * 2048);
        const uint32_t o[4] = {o4.x, o4.y, o4.z, o4.w};
#pragma unroll
        for (int e = 0; e < 4; e++) {
          acc[8 * i + 2 * e] = (acc[8 * i + 2 * e] + bf_lo(o[e])) * ((e & 1) ? o1 : o0);
          acc[8 * i + 2 * e + 1] = (acc[8 * i + 2 * e + 1] + bf_hi(o[e])) * ((e & 1) ? o1 : o0);
        }
      }
      keep(acc);
      wg_wait<0>(); keep(spec[0]); keep(spec[1]);
      if (t128 == 0) PROF(wg, 14);
      bar_sync<5, 128>();
      const uint32_t st = sb + OFF_PQ + w4 * 3840;
#pragma unroll
      for (int i = 0; i < 7; i++) {
        uint32_t pk[4];
#pragma unroll
        for (int e = 0; e < 2; e++) {
          const int c = 2 * i + e, si = i * 4 + e;
          pk[2 * e] = pack_bf16(fmaf(g0, spec[0][si], acc[4 * c]), fmaf(g0, spec[1][si], acc[4 * c + 1]));
          pk[2 * e + 1] = pack_bf16(fmaf(g1, spec[0][si + 2], acc[4 * c + 2]), fmaf(g1, spec[1][si + 2], acc[4 * c + 3]));
        }
        asm volatile("stmatrix.sync.aligned.m8n8.x4.shared.b16 [%0], {%1,%2,%3,%4};"
                     :: "r"(st + (lane & 15) * 240 + (lane >> 4) * 16 + i * 32), "r"(pk[0]), "r"(pk[1]), "r"(pk[2]), "r"(pk[3]) : "memory");
      }
      __syncwarp();
      if (lane < 28) {
        const int r2 = lane >= 14, cc = lane - r2 * 14;
        unsigned char* ob = reinterpret_cast<unsigned char*>(out) + (size_t)(m * 128 + kh * 64 + w4 * 16 + r2) * (D_ * 2) + n * 224 + cc * 16;
        float4 v[8];
#pragma unroll
        for (int i = 0; i < 8; i++) v[i] = lds128f(st + r2 * 240 + cc * 16 + i * 480);
#pragma unroll
        for (int i = 0; i < 8; i++) stg128(ob + i * (D_ * 4), __float_as_uint(v[i].x), __float_as_uint(v[i].y), __float_as_uint(v[i].z), __float_as_uint(v[i].w));
      }
    }
    if (t128 == 0) { PROF(wg, 15); if (wg) { PROFG(4, 30); PROF(4, 31); } }
  } else if (warp < 12) {
    asm volatile("setmaxnreg.dec.sync.aligned.u32 72;");
    const int t = tid - 256;
    const int k = bid;
    if (t == 0) PROF(2, 0);
    uint4 gv[7];
#pragma unroll
    for (int i = 0; i < 7; i++) gv[i] = ldg128(reinterpret_cast<const uint4*>(gate_w) + i * 8 + (t & 7));
    if (t < 98) {
      int cid = m * 98 + t, kc = cid / 56, nn = cid - kc * 56;
      int d = 112 * n + 8 * (2 * (nn >> 3) + (nn & 1)) + (nn & 6) + kh;
      int dr = d > 224 ? d - 448 : d;
      const float df = (float)dr * (-6.283185307179586f / 448.0f);
      uint32_t pk[4];
#pragma unroll
      for (int e = 0; e < 4; e++) {
        const float a = (float)(4 * kc + e) * df;
        pk[e] = pack_bf16(2.0f * __cosf(a), 2.0f * __sinf(a));
      }
      if (kc == 0) pk[0] = (((d >> 1) ^ kh) & 1) ? 0xBF803F80u : 0x3F803F80u;
      stg128(g_G + (size_t)(n * 2 + kh) * G_IMG + cid * 16, pk[0], pk[1], pk[2], pk[3]);
    }
    bar_sync<0, NTHREADS - 64>();
    asm volatile("barrier.cluster.arrive.relaxed.aligned;" ::: "memory");
    {
      const int row = n * 16 + (t >> 3), l8 = t & 7;
      mbar_wait(bars + (B_XFULL + 1) * 8, 0);
      float sum = 0.f;
#pragma unroll
      for (int i = 0; i < 7; i++) {
        const uint4 a = lds128(sb + OFF_R + i * 8192 + row * 128 + ((l8 ^ (row & 7)) << 4));
        const uint32_t aa[4] = {a.x, a.y, a.z, a.w}, bb[4] = {gv[i].x, gv[i].y, gv[i].z, gv[i].w};
#pragma unroll
        for (int e = 0; e < 4; e++) {
          const uint32_t pr = as_u(__hmul2(as_b2(aa[e]), as_b2(bb[e])));
          sum += bf_lo(pr) + bf_hi(pr);
        }
      }
      sum += __shfl_xor_sync(0xffffffffu, sum, 1); sum += __shfl_xor_sync(0xffffffffu, sum, 2); sum += __shfl_xor_sync(0xffffffffu, sum, 4);
      if (l8 == 0) g_gate[m * 128 + kh * 64 + row] = bf16_round(__fdividef(1.0f, 1.0f + __expf(-bf16_round(sum))));
    }
    __syncwarp();
    if (lane == 0) mbar_arrive(bars + (B_XFREE + 1) * 8);
    if (t == 0) PROF(2, 11);
    mbar_wait(bars + B_XFREE * 8, 0);
    {
      const float u = -6.283185307179586f / 2048.0f, t2 = (float)(2 * t) * u;
#pragma unroll 1
      for (int i = 0; i < 4; i++) {
        const float q = (float)(2 * i);
        sts128(sb + OFF_TW + i * 2048 + t * 16, cis(t2 * q), cis((t2 + u) * q), cis(t2 * (q + 1.0f)), cis((t2 + u) * (q + 1.0f)));
      }
      const float l = (float)((t >> 1) & 15) * (8.0f * u), jj = (float)((t >> 5) * 4 + (t & 1) * 2);
      sts64(sb + OFF_TW + 16384 + t * 8, cis(l * jj), cis(l * (jj + 1.0f)));
    }
    mbar_wait(bars + B_PIN * 8, 0);
    mbar_wait(bars + (B_XFREE + 1) * 8, 0);
    if (t == 0) PROF(2, 4);
    {
      const uint32_t wa = sb + OFF_WS + (((t & 7) - bid) & 7) * 450 + (t >> 3) * 2, wc = wa + 448 - (t >> 3) * 4;
#pragma unroll 1
      for (int h = 0; h < 2; h++) {
        uint32_t w[4][8];
#pragma unroll
        for (int i = 0; i < 4; i++) {
#pragma unroll
          for (int e = 0; e < 4; e++) { w[i][2 * e] = lds16(wa + h * 128 + i * 32 + e * 3600); w[i][2 * e + 1] = lds16(wc - h * 128 - i * 32 + e * 3600); }
        }
#pragma unroll
        for (int i = 0; i < 4; i++)
          sts128(sb + OFF_R + h * 8192 + i * 2048 + t * 16, __byte_perm(w[i][0], w[i][1], 0x5410), __byte_perm(w[i][4], w[i][5], 0x5410), __byte_perm(w[i][2], w[i][3], 0x5410), __byte_perm(w[i][6], w[i][7], 0x5410));
      }
    }
    fence_async_smem();
    __syncwarp();
    if (lane == 0) mbar_arrive(bars + B_PUBW * 8);
    if (k < 113) {
      if (t == 0) PROF(2, 2);
      mbar_wait(bars + B_XCFULL * 8, 0);
      if (t == 0) PROF(2, 3);
      c2 v[16];
      uint2 xe[8], xo[8];
      const int sl = k == 112 ? 0 : k, hi = sl >= 56;
      const unsigned char* xs = g_X + (192 + (sl & 1) * 64 + hi * 72 + (sl & ~1) + ((t >> 4) & 1)) * XP + (t >> 5) * 256 + (t & 15) * 8;
#pragma unroll
      for (int jj = 0; jj < 8; jj++) { xe[jj] = ldg64_l2(xs + jj * 1024); xo[jj] = ldg64_l2(xs + jj * 1024 + 128); }
      {
        const float rr = (float)(t >> 4) * (-6.283185307179586f / 2048.0f);
#pragma unroll 1
        for (int i = 0; i < 4; i++) {
          const float l = (float)((t & 15) + 64 * i);
          sts128(sb + OFF_TW + 8192 + i * 2048 + t * 16, cis(rr * l), cis(rr * (l + 16.0f)), cis(rr * (l + 32.0f)), cis(rr * (l + 48.0f)));
        }
      }
      if (t == 0) PROF(2, 9);
      const uint32_t se = k == 0 ? 0x4410 : (k == 112 ? 0x4432 : 0x3210), so = k == 0 ? 0x4410 : (k == 112 ? 0x3244 : 0x3210);
#pragma unroll
      for (int jj = 0; jj < 8; jj++) {
        const uint2 e2 = xe[jj], o2 = xo[jj];
#pragma unroll
        for (int h = 0; h < 2; h++) {
          const b2 e = as_b2(__byte_perm(h ? e2.y : e2.x, 0, se)), o = as_b2(__byte_perm(h ? o2.y : o2.x, 0, so));
          const uint32_t s = as_u(__hadd2(e, o)), d = as_u(__hsub2(e, o)) ^ 0x80000000u;
          v[2 * jj + h] = mk(as_b2(__byte_perm(s, d, 0x5410)), as_b2(__byte_perm(s, d, 0x7632)));
        }
      }
      if (t == 0) PROF(2, 12);
      columns(v, sb, t);
      if (t == 0) PROF(2, 14);
      const int pre = (k == 112) ? 1 : 2 * k, pim = (k == 112) ? 1 : 2 * k + 1;
      const uint32_t pr = sb + OFF_WS + (t >> 5) * 256 + ((((lane >> 2) ^ pre) & 7) << 4) + (lane & 3) * 4;
      const uint32_t pi = sb + OFF_WS + 8192 + (t >> 5) * 256 + ((((lane >> 2) ^ pim) & 7) << 4) + (lane & 3) * 4;
#pragma unroll
      for (int jj = 0; jj < 8; jj++) {
        const b2 ar = as_b2(__byte_perm(as_u(v[2 * jj].y), as_u(v[2 * jj + 1].y), 0x5410)), br = as_b2(__byte_perm(as_u(v[2 * jj].y), as_u(v[2 * jj + 1].y), 0x7632));
        const b2 ai = as_b2(__byte_perm(as_u(v[2 * jj].x), as_u(v[2 * jj + 1].x), 0x5410)), bi = as_b2(__byte_perm(as_u(v[2 * jj].x), as_u(v[2 * jj + 1].x), 0x7632));
        sts32(pr + jj * 1024, as_u(__hadd2(ar, br)));
        sts32(pr + jj * 1024 + 128, as_u(k == 112 ? __hadd2(ai, bi) : __hsub2(ar, br)));
        sts32(pi + jj * 1024 + 128, as_u(__hadd2(ai, bi)));
        sts32(pi + jj * 1024, as_u(__hsub2(ai, bi)));
      }
      fence_async_smem();
      bar_sync<3, 128>();
      if (t == 0) {
        PROF(2, 5);
        tma_store(&tm_s, pre * 64, 0, sb + OFF_WS);
        if (k != 0 && k != 112) tma_store(&tm_s, pim * 64, 0, sb + OFF_WS + 8192);
        bulk_done();
      }
    }
    if (t == 0) { red_relaxed(&g_cnt[5 * 32]); PROF(2, 7); }
    if (t >= 32) {
      if (k >= 113) mbar_wait(bars + B_LFREE * 8, 0);
      __nanosleep((t >> 5) * STAG);
      wait_ge(&g_cnt[5 * 32], (lds64(sb + OFF_G + 256).x + 1) * 128);
      if (lane == 0) mbar_arrive(bars + B_SEEN * 8);
    }
    __syncwarp();
    asm volatile("barrier.cluster.wait.aligned;" ::: "memory");
  } else {
    asm volatile("setmaxnreg.dec.sync.aligned.u32 24;");
    auto wd_tile = [&](int b, uint32_t dst, uint32_t fb) {
#pragma unroll
      for (int hf = 0; hf < 2; hf++) {
        const int js = kh * 4 + (b < 12 ? (b & 3) : (b & 1) * 2 + hf);
        const int row = 224 * js + (b < 12 ? (js & 1) * 32 + (b >> 2) * 64 + hf * 32 : 192 - hf * 192);
        tma2d(dst + hf * 4096, &tm_d, 112 * n, row, fb);
        tma2d(dst + 8192 + hf * 4096, &tm_d, 112 * n + 64, row, fb);
      }
    };
    if (warp == 12) {
      if (elect()) {
        mbar_init(bars + B_XFULL * 8, 1); mbar_init(bars + (B_XFULL + 1) * 8, 1);
        fence_async_smem();
#pragma unroll
        for (int w = 0; w < 2; w++) {
          mbar_expect(bars + (B_XFULL + w) * 8, HALF_XR);
          tma3d(sb + OFF_PQ + w * HALF_XR, &tm_x, 0, m * 128 + (w ^ kh ^ 1) * 64, 0, bars + (B_XFULL + w) * 8);
        }
        PROF(3, 3);
#pragma unroll
        for (int i = 0; i < NSLOT; i++) mbar_init(bars + (B_FULL + i) * 8, 1);
        mbar_init(bars + B_PIN * 8, 1);
        fence_async_smem();
      }
      bar_arrive<0, NTHREADS - 64>();
#pragma unroll 1
      for (int i = 0; i < 6; i++) {
        if (elect()) {
          const uint32_t fb = bars + (B_FULL + i) * 8;
          mbar_expect(fb, SLOT);
          tma2d(sb + i * SLOT, &tm_g, c64, i * 64, fb);
          tma2d(sb + i * SLOT + 8192, &tm_u, c64, i * 64, fb);
          PROF(3, 4 + i);
        }
      }
      if (elect()) {
        prefetch_l2(reinterpret_cast<const unsigned char*>(w_r) + bid * 7200, 7200);
        prefetch_l2(reinterpret_cast<const unsigned char*>(w_i) + bid * 7200, 7200);
        prefetch_l2(reinterpret_cast<const unsigned char*>(w_gate) + bid * 12544, 12544);
        prefetch_l2(reinterpret_cast<const unsigned char*>(w_up) + bid * 12544, 12544);
      }
    } else if (warp == 14) {
      if (elect()) {
#pragma unroll
        for (int i = B_EMPTY; i < B_END; i++)
          if (i < B_XFULL || i >= B_XFREE) mbar_init(bars + i * 8, i >= B_PQFULL ? 1 : (i == B_XFREE ? 4 : (i == B_PUBW ? 5 : 8)));
        asm volatile("fence.mbarrier_init.release.cluster;" ::: "memory");
        fence_async_smem();
        mbar_expect(bars + B_RECV * 8, 64 * 112 * 2);
      }
      bar_arrive<0, NTHREADS - 64>();
    }
    const uint32_t epoch = ld_relaxed(&g_ep[bid]);
    if (warp == 13 && lane == 0) { PROFG(4, 0); PROF(4, 1); }
    bar_sync<1, 128>();
    asm volatile("barrier.cluster.arrive.relaxed.aligned;" ::: "memory");
    if (warp == 12) {
      int slot = 6, ph = 1;
      auto wait_slot = [&]() { mbar_wait(bars + (B_EMPTY + slot) * 8, ph ^ (slot == 6)); };
      auto adv = [&]() { if (++slot == NSLOT) { slot = 0; ph ^= 1; } };
      const int c32 = 224 * j + ((j & 1) ? 0 : 192);
#pragma unroll 1
      for (int i = 6; i < 25; i++) {
        wait_slot();
        if (elect()) {
          const uint32_t dst = sb + slot * SLOT, fb = bars + (B_FULL + slot) * 8;
          const bool last = i >= 21;
          const int cc = last ? c32 : c64 + 64 * (i / 7), rr = last ? slot * 128 : slot * 64;
          mbar_expect(fb, SLOT);
          tma2d(dst, last ? &tm_g32 : &tm_g, cc, rr, fb);
          tma2d(dst + 8192, last ? &tm_u32 : &tm_u, cc, rr, fb);
        }
        adv();
      }
      if (lane == 0) PROF(3, 0);
#pragma unroll 1
      for (int i = 3; i < 16; i++) {
        if (lane == 0) PROF(3, 16 + i);
        if (i == 14) mbar_wait(bars + B_PREP * 8, 0);
        wait_slot();
        if (elect()) {
          const uint32_t fb = bars + (B_FULL + slot) * 8;
          mbar_expect(fb, i < 14 ? SLOT : G_IMG / 2);
          if (i < 14) wd_tile(i, sb + slot * SLOT, fb);
          else bulk_g2s(sb + slot * SLOT, g_G + (size_t)(n * 4 + i - 12) * (G_IMG / 2), G_IMG / 2, fb);
        }
        adv();
      }
      if (lane == 0) PROF(3, 2);
    } else if (warp == 13) {
      mbar_wait(bars + B_PUBX * 8, 0);
      if (elect()) {
        PROF(4, 8);
#pragma unroll
        for (int w = 0; w < 2; w++) tma_store(&tm_s, ((m * 2 + (w ^ kh ^ 1)) * 2 + (j & 1)) * 64, 192 + (j >> 1) * 64, sb + OFF_EXCH + w * 8192);
        bulk_done();
        red_relaxed(&g_cnt[(j >> 1) * 32]);
        mbar_arrive(bars + B_XDONE * 8);
        PROF(4, 12);
      }
      mbar_wait(bars + B_PUBW * 8, 0);
      if (elect()) {
        PROF(4, 9);
        tma_store(&tm_s, bid * 64, 64, sb + OFF_R);
        tma_store(&tm_s, bid * 64, 128, sb + OFF_R + 8192);
        bulk_done();
        red_relaxed(&g_cnt[4 * 32]);
        mbar_arrive(bars + B_WDONE * 8);
        PROF(4, 13);
      }
      mbar_wait(bars + B_PREP * 8, 0);
      mbar_wait(bars + B_LFREE * 8, 0);
      if (elect()) {
        mbar_expect(bars + B_GFULL * 8, G_IMG);
        bulk_g2s(sb + OFF_R + 28672, g_G + (size_t)(n * 2) * G_IMG, G_IMG, bars + B_GFULL * 8);
      }
    } else if (warp == 14) {
      mbar_wait(bars + (B_XFREE + 1) * 8, 0);
      asm volatile("fence.acq_rel.gpu;" ::: "memory");
      if (lane == 0) { mbar_arrive(bars + B_PUBW * 8); PROF(5, 3); }
      mbar_wait(bars + B_WDONE * 8, 0);
      wait_ge(&g_cnt[4 * 32], (epoch + 1) * 128);
      fence_async_global();
      if (elect()) {
        mbar_arrive(bars + B_PREP * 8);
        if (bid < 113) {
          mbar_expect(bars + B_WFULL * 8, 16384);
          bulk_g2s(sb + OFF_WS, g_X + (64 + bid) * XP, 16384, bars + B_WFULL * 8);
        }
        PROF(5, 17);
      }
    } else {
      mbar_wait(bars + B_XFREE * 8, 0);
      if (elect()) {
        sts32(sb + OFF_G + 256, epoch);
        mbar_expect(bars + B_PIN * 8, 14400);
        bulk_g2s(sb + OFF_WS, reinterpret_cast<const unsigned char*>(w_r) + bid * 7200, 7200, bars + B_PIN * 8);
        bulk_g2s(sb + OFF_WS + 7200, reinterpret_cast<const unsigned char*>(w_i) + bid * 7200, 7200, bars + B_PIN * 8);
        PROF(5, 2);
      }
#pragma unroll 1
      for (int i = lane; i < 98; i += 32) asm volatile("prefetch.global.L2 [%0];\nprefetch.global.L2 [%0+64];" :: "l"(reinterpret_cast<const unsigned char*>(w_down) + bid * 12544 + i * 128));
      if (bid < 113) {
        const int sl = (bid == 112) ? 0 : bid;
        wait_ge(&g_cnt[((sl & 1) + 2 * ((sl >> 1) / 28)) * 32], (epoch + 1) * 32);
        if (elect()) { PROF(5, 16); mbar_arrive(bars + B_XCFULL * 8); }
      }
      mbar_wait(bars + B_WDONE * 8, 0);
      if (elect()) mbar_expect(bars + B_RFULL * 8, 3 * SLOT);
#pragma unroll 1
      for (int i = 0; i < 3; i++) {
        mbar_wait(bars + (B_FULL + (i == 0 ? RP0 : 2 * i - 1)) * 8, i == 0);
        if (elect()) wd_tile(i, sb + OFF_R + i * SLOT, bars + B_RFULL * 8);
      }
      if (lane == 0) PROF(5, 19);
      mbar_wait(bars + B_PREP * 8, 0);
      mbar_wait(bars + B_SEEN * 8, 0);
      fence_async_global();
      if (elect()) {
        PROF(5, 18);
        const unsigned char* src = g_X + (m * 2 + kh) * HALF_XR;
#pragma unroll
        for (int i = 0; i < 4; i++) {
          mbar_expect(bars + (B_PQFULL + i) * 8, i < 3 ? 14336 : 14336 + 256);
          bulk_g2s(sb + OFF_PQ + i * 14336, src + i * 14336, 14336, bars + (B_PQFULL + i) * 8);
        }
        bulk_g2s(sb + OFF_G, g_gate + m * 128 + kh * 64, 256, bars + (B_PQFULL + 3) * 8);
      }
    }
    __syncwarp();
    asm volatile("barrier.cluster.wait.aligned;" ::: "memory");
  }
}

typedef CUresult (*EncodeFn)(CUtensorMap*, CUtensorMapDataType, cuuint32_t, void*, const cuuint64_t*, const cuuint64_t*, const cuuint32_t*,
                             const cuuint32_t*, CUtensorMapInterleave, CUtensorMapSwizzle, CUtensorMapL2promotion, CUtensorMapFloatOOBfill);

void make_map(EncodeFn enc, CUtensorMap* tm, const void* base, int cols, int rows, int bc, int br, CUtensorMapSwizzle sw) {
  cuuint64_t gd[2] = {(cuuint64_t)cols, (cuuint64_t)rows};
  cuuint64_t gs[1] = {(cuuint64_t)cols * 2};
  cuuint32_t bd[2] = {(cuuint32_t)bc, (cuuint32_t)br};
  cuuint32_t es[2] = {1, 1};
  enc(tm, CU_TENSOR_MAP_DATA_TYPE_BFLOAT16, 2, const_cast<void*>(base), gd, gs, bd, es, CU_TENSOR_MAP_INTERLEAVE_NONE, sw,
      CU_TENSOR_MAP_L2_PROMOTION_L2_128B, CU_TENSOR_MAP_FLOAT_OOB_FILL_NONE);
}

}

extern "C" void kernel_launch(void* const* d_in, const int* in_sizes, int n_in, void* d_out, int out_size) {
  (void)in_sizes; (void)n_in; (void)out_size;
  const __nv_bfloat16* x = (const __nv_bfloat16*)d_in[0];
  const __nv_bfloat16* w_r = (const __nv_bfloat16*)d_in[1];
  const __nv_bfloat16* w_i = (const __nv_bfloat16*)d_in[2];
  const __nv_bfloat16* w_gate = (const __nv_bfloat16*)d_in[4];
  const __nv_bfloat16* w_up = (const __nv_bfloat16*)d_in[5];
  const __nv_bfloat16* w_down = (const __nv_bfloat16*)d_in[6];
  const __nv_bfloat16* gate_w = (const __nv_bfloat16*)d_in[7];
  static EncodeFn enc = nullptr;
  static void* xbuf = nullptr;
  static bool ok = false;
  if (!enc) {
    cudaDriverEntryPointQueryResult qr;
    cudaGetDriverEntryPoint("cuTensorMapEncodeTiled", (void**)&enc, cudaEnableDefault, &qr);
    cudaFuncSetAttribute(fused_kernel, cudaFuncAttributeMaxDynamicSharedMemorySize, SMEM_BYTES);
    cudaGetSymbolAddress(&xbuf, g_X);
    cudaFuncAttributes fa;
    cudaFuncGetAttributes(&fa, fused_kernel);
    ok = (fa.numRegs == 128);
  }
  if (!ok) return;
  CUtensorMap tx, tg, tu, tg32, tu32, td, ts;
  {
    cuuint64_t gd[3] = {64, (cuuint64_t)S_, 7};
    cuuint64_t gs[2] = {(cuuint64_t)D_ * 2, 128};
    cuuint32_t bd[3] = {64, 64, 7};
    cuuint32_t es[3] = {1, 1, 1};
    enc(&tx, CU_TENSOR_MAP_DATA_TYPE_BFLOAT16, 3, const_cast<__nv_bfloat16*>(x), gd, gs, bd, es, CU_TENSOR_MAP_INTERLEAVE_NONE, CU_TENSOR_MAP_SWIZZLE_128B,
        CU_TENSOR_MAP_L2_PROMOTION_L2_128B, CU_TENSOR_MAP_FLOAT_OOB_FILL_NONE);
  }
  make_map(enc, &tg, w_gate, F_, D_, 64, 64, CU_TENSOR_MAP_SWIZZLE_128B);
  make_map(enc, &tu, w_up, F_, D_, 64, 64, CU_TENSOR_MAP_SWIZZLE_128B);
  make_map(enc, &tg32, w_gate, F_, D_, 32, 128, CU_TENSOR_MAP_SWIZZLE_64B);
  make_map(enc, &tu32, w_up, F_, D_, 32, 128, CU_TENSOR_MAP_SWIZZLE_64B);
  make_map(enc, &td, w_down, D_, F_, 64, 32, CU_TENSOR_MAP_SWIZZLE_128B);
  make_map(enc, &ts, (const __nv_bfloat16*)xbuf, XP / 2, 448, 64, 64, CU_TENSOR_MAP_SWIZZLE_NONE);
  fused_kernel<<<128, NTHREADS, SMEM_BYTES>>>(tx, tg, tu, tg32, tu32, td, ts, w_r, w_i, w_gate, w_up, w_down, gate_w, (__nv_bfloat16*)d_out);
}
```

```cpp
#include <cuda_runtime.h>
#include <cuda_bf16.h>
#include <cuda.h>
#include <stdint.h>

namespace {

constexpr int S_ = 2048, D_ = 448, F_ = 1792;
constexpr int NTHREADS = 512;
constexpr int SLOT = 16384, NSLOT = 7;
constexpr int HALF_XR = 57344;
constexpr int OFF_PQ = NSLOT * SLOT;
constexpr int OFF_R = OFF_PQ + HALF_XR;
constexpr int OFF_EXCH = OFF_PQ;
constexpr int OFF_WS = OFF_EXCH + 18432;
constexpr int OFF_TW = OFF_WS + 16384;
constexpr int OFF_MISC = OFF_R + HALF_XR;
constexpr int OFF_G = OFF_MISC;
constexpr int OFF_BAR = OFF_MISC + 512;
constexpr int SMEM_BYTES = OFF_BAR + 512;
constexpr int B_FULL = 0, B_EMPTY = 7, B_XFULL = 14  ;
constexpr int B_XFREE = 16  , B_PUBX = 18, B_RFREE = 19, B_LFREE = 20;
constexpr int B_PUBW = 21;
constexpr int B_PQFULL = 22  , B_RECV = 26, B_WFULL = 27, B_XCFULL = 28, B_PREP = 29, B_RFULL = 30, B_GFULL = 31, B_XDONE = 32, B_WDONE = 33, B_SEEN = 34, B_END = 35, B_PIN = 35;

constexpr int G_IMG = 224 * 56 * 2;

__device__ __align__(1024) unsigned char g_H[32 * 56 * 4096];
constexpr int XP = 28672;
__device__ __align__(1024) unsigned char g_X[448 * XP];
__device__ __align__(1024) unsigned char g_G[8 * G_IMG];
__device__ __align__(1024) float g_gate[S_];
__device__ __align__(128) unsigned int g_ep[128];
__device__ __align__(128) unsigned int g_cnt[8 * 32];

#define PROF(role, idx) do {} while (0)
#define PROFG(role, idx) do {} while (0)

__device__ __forceinline__ uint32_t s2u(const void* p) { return (uint32_t)__cvta_generic_to_shared(p); }
__device__ __forceinline__ void mbar_init(uint32_t b, int c) { asm volatile("mbarrier.init.shared::cta.b64 [%0], %1;" :: "r"(b), "r"(c) : "memory"); }
__device__ __forceinline__ void mbar_expect(uint32_t b, int bytes) { asm volatile("mbarrier.arrive.expect_tx.shared::cta.b64 _, [%0], %1;" :: "r"(b), "r"(bytes) : "memory"); }
__device__ __forceinline__ void mbar_arrive(uint32_t b) { asm volatile("mbarrier.arrive.shared::cta.b64 _, [%0];" :: "r"(b) : "memory"); }
__device__ __forceinline__ void mbar_wait(uint32_t b, int ph) {
  asm volatile("{\n.reg .pred p;\n.reg .u32 c;\nmov.u32 c, 0;\nL_WAIT:\nmbarrier.try_wait.parity.shared::cta.b64 p, [%0], %1;\n@p bra.uni L_DONE;\n"
               "add.u32 c, c, 1;\nsetp.lt.u32 p, c, 4194304;\n@p bra.uni L_WAIT;\ntrap;\nL_DONE:\n}" :: "r"(b), "r"(ph) : "memory");
}
__device__ __forceinline__ void mbar_wait_cluster(uint32_t b, int ph) {
  asm volatile("{\n.reg .pred p;\n.reg .u32 c;\nmov.u32 c, 0;\nL_WAIT:\nmbarrier.try_wait.parity.acquire.cluster.shared::cta.b64 p, [%0], %1;\n@p bra.uni L_DONE;\n"
               "add.u32 c, c, 1;\nsetp.lt.u32 p, c, 4194304;\n@p bra.uni L_WAIT;\ntrap;\nL_DONE:\n}" :: "r"(b), "r"(ph) : "memory");
}
__device__ __forceinline__ uint32_t ld_relaxed(const unsigned int* p) { uint32_t v; asm volatile("ld.relaxed.gpu.global.u32 %0, [%1];" : "=r"(v) : "l"(p) : "memory"); return v; }
__device__ __forceinline__ void wait_ge(const unsigned int* p, uint32_t target) {
#pragma unroll 1
  for (int i = 0; i < (1 << 22); i++) { if ((int)(ld_relaxed(p) - target) >= 0) return; }
  __trap();
}
__device__ __forceinline__ void red_relaxed(unsigned int* p) { asm volatile("red.relaxed.gpu.global.add.u32 [%0], 1;" :: "l"(p) : "memory"); }
__device__ __forceinline__ bool elect() { uint32_t p; asm volatile("{\n.reg .pred p;\nelect.sync _|p, 0xffffffff;\nselp.u32 %0, 1, 0, p;\n}" : "=r"(p)); return p; }
__device__ __forceinline__ void fence_async_smem() { asm volatile("fence.proxy.async.shared::cta;" ::: "memory"); }
__device__ __forceinline__ void fence_async_global() { asm volatile("fence.proxy.async.global;" ::: "memory"); }
template <int ID, int N> __device__ __forceinline__ void bar_sync() { asm volatile("bar.sync %0, %1;" :: "n"(ID), "n"(N) : "memory"); }
template <int ID, int N> __device__ __forceinline__ void bar_arrive() { asm volatile("bar.arrive %0, %1;" :: "n"(ID), "n"(N) : "memory"); }
__device__ __forceinline__ void tma2d(uint32_t dst, const CUtensorMap* tm, int c0, int c1, uint32_t bar) {
  asm volatile("cp.async.bulk.tensor.2d.shared::cluster.global.mbarrier::complete_tx::bytes [%0], [%1, {%3, %4}], [%2];"
               :: "r"(dst), "l"(tm), "r"(bar), "r"(c0), "r"(c1) : "memory");
}
__device__ __forceinline__ void tma3d(uint32_t dst, const CUtensorMap* tm, int c0, int c1, int c2, uint32_t bar) {
  asm volatile("cp.async.bulk.tensor.3d.shared::cluster.global.mbarrier::complete_tx::bytes [%0], [%1, {%3, %4, %5}], [%2];"
               :: "r"(dst), "l"(tm), "r"(bar), "r"(c0), "r"(c1), "r"(c2) : "memory");
}
__device__ __forceinline__ void bulk_g2s(uint32_t dst, const void* src, int bytes, uint32_t bar) {
  asm volatile("cp.async.bulk.shared::cluster.global.mbarrier::complete_tx::bytes [%0], [%1], %2, [%3];"
               :: "r"(dst), "l"(src), "r"(bytes), "r"(bar) : "memory");
}
__device__ __forceinline__ void tma_store(const CUtensorMap* tm, int c0, int c1, uint32_t src) {
  asm volatile("cp.async.bulk.tensor.2d.global.shared::cta.bulk_group [%0, {%1, %2}], [%3];" :: "l"(tm), "r"(c0), "r"(c1), "r"(src) : "memory");
}
__device__ __forceinline__ void bulk_done() { asm volatile("cp.async.bulk.commit_group;\ncp.async.bulk.wait_group 0;\nfence.proxy.async.global;" ::: "memory"); }
__device__ __forceinline__ void sts32(uint32_t a, uint32_t x) { asm volatile("st.shared.b32 [%0], %1;" :: "r"(a), "r"(x) : "memory"); }
__device__ __forceinline__ void prefetch_l2(const void* src, int bytes) {
  asm volatile("cp.async.bulk.prefetch.L2.global [%0], %1;" :: "l"(src), "r"(bytes) : "memory");
}
__device__ __forceinline__ uint64_t mkdesc(uint32_t addr, uint32_t lbo, uint32_t sbo, uint32_t mode) {
  return (uint64_t)((addr & 0x3FFFF) >> 4) | ((uint64_t)(lbo >> 4) << 16) | ((uint64_t)(sbo >> 4) << 32) | ((uint64_t)mode << 62);
}
__device__ __forceinline__ void wg_fence() { asm volatile("wgmma.fence.sync.aligned;" ::: "memory"); }
__device__ __forceinline__ void wg_commit() { asm volatile("wgmma.commit_group.sync.aligned;" ::: "memory"); }
template <int N> __device__ __forceinline__ void wg_wait() { asm volatile("wgmma.wait_group.sync.aligned %0;" :: "n"(N) : "memory"); }
template <int N> __device__ __forceinline__ void keep(float (&d)[N]) {
#pragma unroll
  for (int i = 0; i < N; i++) asm volatile("" : "+f"(d[i]) :: "memory");
}
__device__ __forceinline__ uint32_t pack_bf16(float lo, float hi) { uint32_t r; asm("cvt.rn.bf16x2.f32 %0, %1, %2;" : "=r"(r) : "f"(hi), "f"(lo)); return r; }
__device__ __forceinline__ float bf16_round(float v) { return __bfloat162float(__float2bfloat16_rn(v)); }
__device__ __forceinline__ void sts128(uint32_t a, uint32_t x, uint32_t y, uint32_t z, uint32_t w) { asm volatile("st.shared.v4.b32 [%0], {%1,%2,%3,%4};" :: "r"(a), "r"(x), "r"(y), "r"(z), "r"(w) : "memory"); }
__device__ __forceinline__ float4 lds128f(uint32_t a) { float4 v; asm volatile("ld.shared.v4.f32 {%0,%1,%2,%3}, [%4];" : "=f"(v.x), "=f"(v.y), "=f"(v.z), "=f"(v.w) : "r"(a) : "memory"); return v; }

__device__ __forceinline__ uint2 lds64(uint32_t a) { uint2 v; asm volatile("ld.shared.v2.b32 {%0,%1}, [%2];" : "=r"(v.x), "=r"(v.y) : "r"(a) : "memory"); return v; }
__device__ __forceinline__ float bf_lo(uint32_t w) { return __uint_as_float(w << 16); }
__device__ __forceinline__ float bf_hi(uint32_t w) { return __uint_as_float(w & 0xffff0000u); }
__device__ __forceinline__ uint32_t opaque(uint32_t v) { asm volatile("" : "+r"(v)); return v; }
__device__ __forceinline__ uint4 ldg128(const void* p) { uint4 v; asm volatile("ld.global.nc.v4.b32 {%0,%1,%2,%3}, [%4];" : "=r"(v.x), "=r"(v.y), "=r"(v.z), "=r"(v.w) : "l"(p)); return v; }
__device__ __forceinline__ void stg128(void* p, uint32_t x, uint32_t y, uint32_t z, uint32_t w) { asm volatile("st.global.v4.b32 [%0], {%1,%2,%3,%4};" :: "l"(p), "r"(x), "r"(y), "r"(z), "r"(w) : "memory"); }
__device__ __forceinline__ void stg128_l2(void* p, uint32_t x, uint32_t y, uint32_t z, uint32_t w) { asm volatile("st.relaxed.gpu.global.v4.b32 [%0], {%1,%2,%3,%4};" :: "l"(p), "r"(x), "r"(y), "r"(z), "r"(w) : "memory"); }
__device__ __forceinline__ uint2 ldg64_l2(const void* p) { uint2 v; asm volatile("ld.relaxed.gpu.global.v2.b32 {%0,%1}, [%2];" : "=r"(v.x), "=r"(v.y) : "l"(p) : "memory"); return v; }
__device__ __forceinline__ void ldg128_l2(uint32_t (&v)[4], const void* p) { asm volatile("ld.relaxed.gpu.global.v4.b32 {%0,%1,%2,%3}, [%4];" : "=r"(v[0]), "=r"(v[1]), "=r"(v[2]), "=r"(v[3]) : "l"(p) : "memory"); }
__device__ __forceinline__ uint4 lds128(uint32_t a) { uint4 v; asm volatile("ld.shared.v4.b32 {%0,%1,%2,%3}, [%4];" : "=r"(v.x), "=r"(v.y), "=r"(v.z), "=r"(v.w) : "r"(a) : "memory"); return v; }
__device__ __forceinline__ uint32_t lds16(uint32_t a) { uint32_t v; asm volatile("ld.shared.u16 %0, [%1];" : "=r"(v) : "r"(a) : "memory"); return v; }
__device__ __forceinline__ void sts64(uint32_t a, uint32_t x, uint32_t y) { asm volatile("st.shared.v2.b32 [%0], {%1,%2};" :: "r"(a), "r"(x), "r"(y) : "memory"); }
template <int TB> __device__ __forceinline__ void wgmma_rs_128(float (&d)[64], const uint32_t (&a)[4], uint64_t db, int sc) {
  asm volatile("{\n.reg .pred p;\nsetp.ne.b32 p, %69, 0;\n"
    "wgmma.mma_async.sync.aligned.m64n128k16.f32.bf16.bf16 {%0, %1, %2, %3, %4, %5, %6, %7, %8, %9, %10, %11, %12, %13, %14, %15, %16, %17, %18, %19, %20, %21, %22, %23, %24, %25, %26, %27, %28, %29, %30, %31, %32, %33, %34, %35, %36, %37, %38, %39, %40, %41, %42, %43, %44, %45, %46, %47, %48, %49, %50, %51, %52, %53, %54, %55, %56, %57, %58, %59, %60, %61, %62, %63}, {%64, %65, %66, %67}, %68, p, 1, 1, %70;\n}\n"
    : "+f"(d[0]), "+f"(d[1]), "+f"(d[2]), "+f"(d[3]), "+f"(d[4]), "+f"(d[5]), "+f"(d[6]), "+f"(d[7]), "+f"(d[8]), "+f"(d[9]), "+f"(d[10]), "+f"(d[11]), "+f"(d[12]), "+f"(d[13]), "+f"(d[14]), "+f"(d[15]), "+f"(d[16]), "+f"(d[17]), "+f"(d[18]), "+f"(d[19]), "+f"(d[20]), "+f"(d[21]), "+f"(d[22]), "+f"(d[23]), "+f"(d[24]), "+f"(d[25]), "+f"(d[26]), "+f"(d[27]), "+f"(d[28]), "+f"(d[29]), "+f"(d[30]), "+f"(d[31]), "+f"(d[32]), "+f"(d[33]), "+f"(d[34]), "+f"(d[35]), "+f"(d[36]), "+f"(d[37]), "+f"(d[38]), "+f"(d[39]), "+f"(d[40]), "+f"(d[41]), "+f"(d[42]), "+f"(d[43]), "+f"(d[44]), "+f"(d[45]), "+f"(d[46]), "+f"(d[47]), "+f"(d[48]), "+f"(d[49]), "+f"(d[50]), "+f"(d[51]), "+f"(d[52]), "+f"(d[53]), "+f"(d[54]), "+f"(d[55]), "+f"(d[56]), "+f"(d[57]), "+f"(d[58]), "+f"(d[59]), "+f"(d[60]), "+f"(d[61]), "+f"(d[62]), "+f"(d[63])
    : "r"(a[0]), "r"(a[1]), "r"(a[2]), "r"(a[3]), "l"(db), "r"(sc), "n"(TB));
}
template <int TB> __device__ __forceinline__ void wgmma_rs_64(float (&d)[32], const uint32_t (&a)[4], uint64_t db, int sc) {
  asm volatile("{\n.reg .pred p;\nsetp.ne.b32 p, %37, 0;\n"
    "wgmma.mma_async.sync.aligned.m64n64k16.f32.bf16.bf16 {%0, %1, %2, %3, %4, %5, %6, %7, %8, %9, %10, %11, %12, %13, %14, %15, %16, %17, %18, %19, %20, %21, %22, %23, %24, %25, %26, %27, %28, %29, %30, %31}, {%32, %33, %34, %35}, %36, p, 1, 1, %38;\n}\n"
    : "+f"(d[0]), "+f"(d[1]), "+f"(d[2]), "+f"(d[3]), "+f"(d[4]), "+f"(d[5]), "+f"(d[6]), "+f"(d[7]), "+f"(d[8]), "+f"(d[9]), "+f"(d[10]), "+f"(d[11]), "+f"(d[12]), "+f"(d[13]), "+f"(d[14]), "+f"(d[15]), "+f"(d[16]), "+f"(d[17]), "+f"(d[18]), "+f"(d[19]), "+f"(d[20]), "+f"(d[21]), "+f"(d[22]), "+f"(d[23]), "+f"(d[24]), "+f"(d[25]), "+f"(d[26]), "+f"(d[27]), "+f"(d[28]), "+f"(d[29]), "+f"(d[30]), "+f"(d[31])
    : "r"(a[0]), "r"(a[1]), "r"(a[2]), "r"(a[3]), "l"(db), "r"(sc), "n"(TB));
}
template <int TB> __device__ __forceinline__ void wgmma_rs_56(float (&d)[28], const uint32_t (&a)[4], uint64_t db, int sc) {
  asm volatile("{\n.reg .pred p;\nsetp.ne.b32 p, %33, 0;\n"
    "wgmma.mma_async.sync.aligned.m64n56k16.f32.bf16.bf16 {%0, %1, %2, %3, %4, %5, %6, %7, %8, %9, %10, %11, %12, %13, %14, %15, %16, %17, %18, %19, %20, %21, %22, %23, %24, %25, %26, %27}, {%28, %29, %30, %31}, %32, p, 1, 1, %34;\n}\n"
    : "+f"(d[0]), "+f"(d[1]), "+f"(d[2]), "+f"(d[3]), "+f"(d[4]), "+f"(d[5]), "+f"(d[6]), "+f"(d[7]), "+f"(d[8]), "+f"(d[9]), "+f"(d[10]), "+f"(d[11]), "+f"(d[12]), "+f"(d[13]), "+f"(d[14]), "+f"(d[15]), "+f"(d[16]), "+f"(d[17]), "+f"(d[18]), "+f"(d[19]), "+f"(d[20]), "+f"(d[21]), "+f"(d[22]), "+f"(d[23]), "+f"(d[24]), "+f"(d[25]), "+f"(d[26]), "+f"(d[27])
    : "r"(a[0]), "r"(a[1]), "r"(a[2]), "r"(a[3]), "l"(db), "r"(sc), "n"(TB));
}
template <int TB> __device__ __forceinline__ void wgmma_rs_112(float (&d)[56], const uint32_t (&a)[4], uint64_t db, int sc) {
  asm volatile("{\n.reg .pred p;\nsetp.ne.b32 p, %61, 0;\n"
    "wgmma.mma_async.sync.aligned.m64n112k16.f32.bf16.bf16 {%0, %1, %2, %3, %4, %5, %6, %7, %8, %9, %10, %11, %12, %13, %14, %15, %16, %17, %18, %19, %20, %21, %22, %23, %24, %25, %26, %27, %28, %29, %30, %31, %32, %33, %34, %35, %36, %37, %38, %39, %40, %41, %42, %43, %44, %45, %46, %47, %48, %49, %50, %51, %52, %53, %54, %55}, {%56, %57, %58, %59}, %60, p, 1, 1, %62;\n}\n"
    : "+f"(d[0]), "+f"(d[1]), "+f"(d[2]), "+f"(d[3]), "+f"(d[4]), "+f"(d[5]), "+f"(d[6]), "+f"(d[7]), "+f"(d[8]), "+f"(d[9]), "+f"(d[10]), "+f"(d[11]), "+f"(d[12]), "+f"(d[13]), "+f"(d[14]), "+f"(d[15]), "+f"(d[16]), "+f"(d[17]), "+f"(d[18]), "+f"(d[19]), "+f"(d[20]), "+f"(d[21]), "+f"(d[22]), "+f"(d[23]), "+f"(d[24]), "+f"(d[25]), "+f"(d[26]), "+f"(d[27]), "+f"(d[28]), "+f"(d[29]), "+f"(d[30]), "+f"(d[31]), "+f"(d[32]), "+f"(d[33]), "+f"(d[34]), "+f"(d[35]), "+f"(d[36]), "+f"(d[37]), "+f"(d[38]), "+f"(d[39]), "+f"(d[40]), "+f"(d[41]), "+f"(d[42]), "+f"(d[43]), "+f"(d[44]), "+f"(d[45]), "+f"(d[46]), "+f"(d[47]), "+f"(d[48]), "+f"(d[49]), "+f"(d[50]), "+f"(d[51]), "+f"(d[52]), "+f"(d[53]), "+f"(d[54]), "+f"(d[55])
    : "r"(a[0]), "r"(a[1]), "r"(a[2]), "r"(a[3]), "l"(db), "r"(sc), "n"(TB));
}
template <int TA, int TB> __device__ __forceinline__ void wgmma_ss_56(float (&d)[28], uint64_t da, uint64_t db, int sc) {
  asm volatile("{\n.reg .pred p;\nsetp.ne.b32 p, %30, 0;\n"
    "wgmma.mma_async.sync.aligned.m64n56k16.f32.bf16.bf16 {%0, %1, %2, %3, %4, %5, %6, %7, %8, %9, %10, %11, %12, %13, %14, %15, %16, %17, %18, %19, %20, %21, %22, %23, %24, %25, %26, %27}, %28, %29, p, 1, 1, %31, %32;\n}\n"
    : "+f"(d[0]), "+f"(d[1]), "+f"(d[2]), "+f"(d[3]), "+f"(d[4]), "+f"(d[5]), "+f"(d[6]), "+f"(d[7]), "+f"(d[8]), "+f"(d[9]), "+f"(d[10]), "+f"(d[11]), "+f"(d[12]), "+f"(d[13]), "+f"(d[14]), "+f"(d[15]), "+f"(d[16]), "+f"(d[17]), "+f"(d[18]), "+f"(d[19]), "+f"(d[20]), "+f"(d[21]), "+f"(d[22]), "+f"(d[23]), "+f"(d[24]), "+f"(d[25]), "+f"(d[26]), "+f"(d[27])
    : "l"(da), "l"(db), "r"(sc), "n"(TA), "n"(TB));
}

__device__ __forceinline__ uint32_t cis(float a) { return pack_bf16(__cosf(a), __sinf(a)); }

typedef __nv_bfloat162 b2;
struct c2 { b2 x, y; };
__device__ __forceinline__ b2 as_b2(uint32_t u) { return *reinterpret_cast<b2*>(&u); }
__device__ __forceinline__ uint32_t as_u(b2 v) { return *reinterpret_cast<uint32_t*>(&v); }
__device__ __forceinline__ c2 mk(b2 x, b2 y) { c2 r; r.x = x; r.y = y; return r; }
__device__ __forceinline__ c2 cmul(c2 a, b2 wr, b2 wi) { return mk(__hfma2(a.x, wr, __hneg2(__hmul2(a.y, wi))), __hfma2(a.x, wi, __hmul2(a.y, wr))); }
__device__ __forceinline__ void fft4(c2& a0, c2& a1, c2& a2, c2& a3) {
  c2 t0 = mk(__hadd2(a0.x, a2.x), __hadd2(a0.y, a2.y)), t1 = mk(__hsub2(a0.x, a2.x), __hsub2(a0.y, a2.y));
  c2 t2 = mk(__hadd2(a1.x, a3.x), __hadd2(a1.y, a3.y)), t3 = mk(__hsub2(a1.x, a3.x), __hsub2(a1.y, a3.y));
  a0 = mk(__hadd2(t0.x, t2.x), __hadd2(t0.y, t2.y)); a2 = mk(__hsub2(t0.x, t2.x), __hsub2(t0.y, t2.y));
  a1 = mk(__hadd2(t1.x, t3.y), __hsub2(t1.y, t3.x)); a3 = mk(__hsub2(t1.x, t3.y), __hadd2(t1.y, t3.x));
}
__device__ __forceinline__ void fft4_s2(c2& a0, c2& a1, c2& a2, c2& a3, b2 r) {
  const b2 nr = __hneg2(r);
  c2 t0 = mk(__hfma2(a2.x, r, a0.x), __hfma2(a2.y, r, a0.y)), t1 = mk(__hfma2(a2.x, nr, a0.x), __hfma2(a2.y, nr, a0.y));
  c2 t2 = mk(__hadd2(a1.x, a3.x), __hadd2(a1.y, a3.y)), t3 = mk(__hsub2(a1.x, a3.x), __hsub2(a1.y, a3.y));
  a0 = mk(__hadd2(t0.x, t2.x), __hadd2(t0.y, t2.y)); a2 = mk(__hsub2(t0.x, t2.x), __hsub2(t0.y, t2.y));
  a1 = mk(__hadd2(t1.x, t3.y), __hsub2(t1.y, t3.x)); a3 = mk(__hsub2(t1.x, t3.y), __hadd2(t1.y, t3.x));
}
__device__ __forceinline__ void fft4_s13(c2& a0, c2& a1, c2& a2, c2& a3, b2 r) {
  const b2 nr = __hneg2(r);
  c2 t0 = mk(__hadd2(a0.x, a2.x), __hadd2(a0.y, a2.y)), t1 = mk(__hsub2(a0.x, a2.x), __hsub2(a0.y, a2.y));
  c2 t2 = mk(__hadd2(a1.x, a3.x), __hadd2(a1.y, a3.y)), t3 = mk(__hsub2(a1.x, a3.x), __hsub2(a1.y, a3.y));
  a0 = mk(__hfma2(t2.x, r, t0.x), __hfma2(t2.y, r, t0.y)); a2 = mk(__hfma2(t2.x, nr, t0.x), __hfma2(t2.y, nr, t0.y));
  a1 = mk(__hfma2(t3.y, r, t1.x), __hfma2(t3.x, nr, t1.y)); a3 = mk(__hfma2(t3.y, nr, t1.x), __hfma2(t3.x, r, t1.y));
}
__device__ __forceinline__ c2 rot1(c2 a) { return mk(__hadd2(a.x, a.y), __hsub2(a.y, a.x)); }
__device__ __forceinline__ c2 rot3(c2 a) { return mk(__hsub2(a.y, a.x), __hneg2(__hadd2(a.x, a.y))); }
__device__ __forceinline__ c2 mul_mi(c2 a) { return mk(a.y, __hneg2(a.x)); }
template <int O> __device__ __forceinline__ void fft8(c2 (&v)[16]) {
  const b2 r = as_b2(0x3F353F35u), nr = as_b2(0xBF35BF35u);
  fft4(v[O], v[O + 4], v[O + 8], v[O + 12]);
  fft4(v[O + 2], v[O + 6], v[O + 10], v[O + 14]);
  const c2 o0 = v[O + 2], o1 = rot1(v[O + 6]), o2 = v[O + 10], o3 = rot1(v[O + 14]);
  const c2 e0 = v[O], e1 = v[O + 4], e2 = v[O + 8], e3 = v[O + 12];
  v[O] = mk(__hadd2(e0.x, o0.x), __hadd2(e0.y, o0.y));              v[O + 8] = mk(__hsub2(e0.x, o0.x), __hsub2(e0.y, o0.y));
  v[O + 2] = mk(__hfma2(o1.x, r, e1.x), __hfma2(o1.y, r, e1.y));    v[O + 10] = mk(__hfma2(o1.x, nr, e1.x), __hfma2(o1.y, nr, e1.y));
  v[O + 4] = mk(__hadd2(e2.x, o2.y), __hsub2(e2.y, o2.x));          v[O + 12] = mk(__hsub2(e2.x, o2.y), __hadd2(e2.y, o2.x));
  v[O + 6] = mk(__hfma2(o3.y, r, e3.x), __hfma2(o3.x, nr, e3.y));   v[O + 14] = mk(__hfma2(o3.y, nr, e3.x), __hfma2(o3.x, r, e3.y));
}
__device__ __forceinline__ void fft16(c2 (&v)[16]) {
  const b2 r = as_b2(0x3F353F35u), c1 = as_b2(0x3F6D3F6Du), s1 = as_b2(0x3EC43EC4u), nc1 = as_b2(0xBF6DBF6Du), ns1 = as_b2(0xBEC4BEC4u);
#pragma unroll
  for (int a = 0; a < 4; a++) fft4(v[a], v[a + 4], v[a + 8], v[a + 12]);
  v[5] = cmul(v[5], c1, ns1); v[6] = rot1(v[6]); v[7] = cmul(v[7], s1, nc1);
  v[9] = rot1(v[9]); v[10] = mul_mi(v[10]); v[11] = rot3(v[11]);
  v[13] = cmul(v[13], s1, nc1); v[14] = rot3(v[14]); v[15] = cmul(v[15], nc1, s1);
  fft4(v[0], v[1], v[2], v[3]); fft4_s2(v[4], v[5], v[6], v[7], r); fft4_s13(v[8], v[9], v[10], v[11], r); fft4_s2(v[12], v[13], v[14], v[15], r);
  c2 t;
  t = v[1]; v[1] = v[4]; v[4] = t;  t = v[2]; v[2] = v[8]; v[8] = t;  t = v[3]; v[3] = v[12]; v[12] = t;
  t = v[6]; v[6] = v[9]; v[9] = t;  t = v[7]; v[7] = v[13]; v[13] = t; t = v[11]; v[11] = v[14]; v[14] = t;
}

__device__ __forceinline__ void columns(c2 (&v)[16], uint32_t sb, int t) {
  const int l16 = t & 15;
  const uint32_t row = sb + OFF_EXCH + (t >> 4) * 2304;
  const uint32_t pos = sb + OFF_EXCH + (t >> 3) * 144 + (t & 7) * 16;
#pragma unroll 1
  for (int ps = 0; ps < 6; ps++) {
    if (ps == 0 || ps == 5) { fft8<0>(v); fft8<1>(v); } else fft16(v);
    if (ps == 5) break;
    if (ps == 2) {
      const uint32_t ws = sb + OFF_WS + (l16 >> 1) * 128 + ((((t >> 4) + (l16 >> 1)) & 7) * 2 + (l16 & 1)) * 8;
      mbar_wait(sb + OFF_BAR + B_WFULL * 8, 0);
#pragma unroll
      for (int q = 0; q < 16; q++) {
        const uint2 w = lds64(ws + q * 1024);
        const c2 z = cmul(v[q], as_b2(w.x), as_b2(w.y));
        v[q] = mk(z.y, z.x);
      }
      continue;
    }
    {
      const bool full = ps == 0 || ps == 4;
      const uint32_t tw = sb + OFF_TW + (full ? ps * 2048 + t * 16 : 16384 + l16 * 16);
      const uint32_t st = full ? 2048 : 256;
#pragma unroll
      for (int i = 0; i < 4; i++) {
        const uint4 w4 = lds128(tw + i * st);
        const uint32_t w[4] = {w4.x, w4.y, w4.z, w4.w};
#pragma unroll
        for (int e = 0; e < 4; e++) v[4 * i + e] = cmul(v[4 * i + e], __low2bfloat162(as_b2(w[e])), __high2bfloat162(as_b2(w[e])));
      }
    }
    if (ps == 0) {
      mbar_wait(sb + OFF_BAR + B_XDONE * 8, 0);
#pragma unroll
      for (int q = 0; q < 8; q++) sts128(pos + q * 2304, as_u(v[2 * q].x), as_u(v[2 * q].y), as_u(v[2 * q + 1].x), as_u(v[2 * q + 1].y));
      bar_sync<3, 128>();
#pragma unroll
      for (int q = 0; q < 16; q++) { const uint2 a = lds64(row + q * 144 + l16 * 8); v[q] = mk(as_b2(a.x), as_b2(a.y)); }
    } else {
      __syncwarp();
#pragma unroll
      for (int q = 0; q < 16; q++) sts64(row + q * 144 + l16 * 8, as_u(v[q].x), as_u(v[q].y));
      if (ps == 4) bar_sync<3, 128>(); else __syncwarp();
      const uint32_t src = ps == 4 ? pos : row + l16 * 144, st = ps == 4 ? 2304 : 16;
#pragma unroll
      for (int q = 0; q < 8; q++) { const uint4 a = lds128(src + q * st); v[2 * q] = mk(as_b2(a.x), as_b2(a.y)); v[2 * q + 1] = mk(as_b2(a.z), as_b2(a.w)); }
    }
  }
}

template <int NH> __device__ __forceinline__ void h_epilogue(float (&acc)[NH * 8], unsigned char* gdst, uint32_t tag) {
#pragma unroll
  for (int c = 0; c < NH / 2; c++) {
    uint32_t pk[4];
#pragma unroll
    for (int i = 0; i < 4; i++) {
      float hv[2];
#pragma unroll
      for (int e = 0; e < 2; e++) {
        float hg = 0.5f * acc[c * 8 + i * 2 + e], up = acc[NH * 4 + c * 8 + i * 2 + e];
        float th; asm("tanh.approx.f32 %0, %1;" : "=f"(th) : "f"(hg));
        hv[e] = fmaf(hg, th, hg) * up;
      }
      pk[i] = pack_bf16(hv[0], hv[1]);
    }
    stg128_l2(gdst + c * 4096, (pk[0] & ~1u) | tag, pk[1], pk[2], pk[3]);
  }
}

__device__ __forceinline__ void frag_ready(uint32_t (&a)[4], uint32_t (&b)[4], uint32_t (&c)[4], uint32_t (&d)[4], const unsigned char* p, uint32_t tag) {
  asm volatile("{\n.reg .pred p;\n.reg .u32 c, m, q;\nmov.u32 c, 0;\nL_TRY:\n"
               "lop3.b32 m, %0, %4, %17, 0x7E;\nlop3.b32 q, %8, %12, %17, 0x7E;\nlop3.b32 m, m, q, 1, 0xA8;\nsetp.ne.u32 p, m, 0;\n"
               "vote.sync.any.pred p, p, 0xffffffff;\n@!p bra.uni L_OK;\n"
               "ld.relaxed.gpu.global.v4.b32 {%0,%1,%2,%3}, [%16];\nld.relaxed.gpu.global.v4.b32 {%4,%5,%6,%7}, [%16+4096];\n"
               "ld.relaxed.gpu.global.v4.b32 {%8,%9,%10,%11}, [%16+8192];\nld.relaxed.gpu.global.v4.b32 {%12,%13,%14,%15}, [%16+12288];\n"
               "add.u32 c, c, 1;\nsetp.lt.u32 p, c, 262144;\n@p bra.uni L_TRY;\ntrap;\nL_OK:\n}"
               : "+r"(a[0]), "+r"(a[1]), "+r"(a[2]), "+r"(a[3]), "+r"(b[0]), "+r"(b[1]), "+r"(b[2]), "+r"(b[3]),
                 "+r"(c[0]), "+r"(c[1]), "+r"(c[2]), "+r"(c[3]), "+r"(d[0]), "+r"(d[1]), "+r"(d[2]), "+r"(d[3])
               : "l"(p), "r"(tag) : "memory");
}

#define STAG 120
#define RP0 6
#define LEAD2 0
#define LEAD1 2

__global__ void __cluster_dims__(2, 1, 1) __launch_bounds__(NTHREADS, 1)
fused_kernel(const __grid_constant__ CUtensorMap tm_x, const __grid_constant__ CUtensorMap tm_g, const __grid_constant__ CUtensorMap tm_u,
             const __grid_constant__ CUtensorMap tm_g32, const __grid_constant__ CUtensorMap tm_u32, const __grid_constant__ CUtensorMap tm_d,
             const __grid_constant__ CUtensorMap tm_s,
             const __nv_bfloat16* __restrict__ w_r, const __nv_bfloat16* __restrict__ w_i,
             const __nv_bfloat16* __restrict__ w_gate, const __nv_bfloat16* __restrict__ w_up,
             const __nv_bfloat16* __restrict__ w_down, const __nv_bfloat16* __restrict__ gate_w, __nv_bfloat16* __restrict__ out) {
  extern __shared__ __align__(1024) unsigned char smem[];
  const uint32_t sb = s2u(smem);
  const uint32_t bars = sb + OFF_BAR;
  const int tid = threadIdx.x, warp = __shfl_sync(0xffffffffu, tid >> 5, 0), lane = tid & 31;
  const int cl = blockIdx.x >> 1, kh = blockIdx.x & 1;
  const int n0 = cl < 4 ? cl : (cl < 36 ? (cl - 4) >> 3 : (cl - 36) / 7);
  const int m0 = cl < 4 ? 15 : (cl < 36 ? (cl - 4) & 7 : cl - 28 - 7 * n0);
  const int n = n0, m = m0;
  const int j = kh * 4 + n, bid = m * 8 + n * 2 + kh;

  const int c64 = 224 * j + (j & 1) * 32;
  if (warp < 8) {
    asm volatile("setmaxnreg.inc.sync.aligned.u32 208;");
    const int wg = warp >> 2, w4 = warp & 3, g = lane >> 2, t = lane & 3;
    const int rh = wg ^ kh ^ 1;
    const int p = j & 1, r = (j >> 1) & 1, hh = j >> 2;
    const uint32_t epoch = ld_relaxed(&g_ep[bid]);
    if ((tid & 127) == 0) PROF(wg, 30);
#pragma unroll 1
    for (int it = tid; it < 392; it += 256) {
      const int kc = it / 28, sg = it - kc * 28;
      const int k = 2 * (28 * hh + sg) + r;
      const float kf = (float)k * (-6.283185307179586f / 448.0f), a0 = (float)(16 * kc + p) * kf;
      uint32_t c[4], s[4];
#pragma unroll
      for (int q = 0; q < 4; q++) {
        const float a1 = fmaf((float)(2 * q), kf, a0), a2 = fmaf((float)(2 * q + 8), kf, a0);
        c[q] = pack_bf16(__cosf(a1), __cosf(a2)); s[q] = pack_bf16(__sinf(a1), __sinf(a2));
        if (k == 0) s[q] = ((q ^ p) & 1) ? 0xBF80BF80u : 0x3F803F80u;
      }
      const uint32_t a = sb + 6 * SLOT + (kc * 56 + 2 * sg) * 16;
      sts128(a, c[0], c[1], c[2], c[3]);
      sts128(a + 16, s[0], s[1], s[2], s[3]);
    }
    if ((tid & 127) == 0) PROF(wg, 31);
    fence_async_smem();
    bar_sync<0, NTHREADS - 64>();
    asm volatile("barrier.cluster.arrive.relaxed.aligned;" ::: "memory");
    if ((tid & 127) == 0) PROF(wg, 1);

    uint32_t xa[28][4];
    {
      const uint32_t xb = sb + OFF_PQ + wg * HALF_XR + (w4 * 16 + (lane & 15)) * 128;
      mbar_wait(bars + (B_XFULL + wg) * 8, 0);
      if ((tid & 127) == 0) PROF(wg, 2);
#pragma unroll
      for (int kb = 0; kb < 7; kb++) {
#pragma unroll
        for (int kk = 0; kk < 4; kk++) {
          uint32_t a = xb + kb * 8192 + (((2 * kk + (lane >> 4)) ^ (lane & 7)) << 4);
          asm volatile("ldmatrix.sync.aligned.m8n8.x4.shared.b16 {%0,%1,%2,%3}, [%4];"
                       : "=r"(xa[kb * 4 + kk][0]), "=r"(xa[kb * 4 + kk][1]), "=r"(xa[kb * 4 + kk][2]), "=r"(xa[kb * 4 + kk][3]) : "r"(a) : "memory");
        }
      }
    }
    {
      uint32_t ad[7][4];
      const uint32_t sel = p ? 0x7632 : 0x5410;
      const uint32_t sgn = r ? 0xBF80BF80u : 0x3F803F80u;
#pragma unroll
      for (int jj = 0; jj < 7; jj++) {
#pragma unroll
        for (int i = 0; i < 4; i++) {
          int ks = 2 * jj + (i >> 1), rr = i & 1;
          uint32_t lo = __byte_perm(xa[ks][rr], xa[ks][rr + 2], sel);
          uint32_t hi = __byte_perm(xa[ks + 14][rr], xa[ks + 14][rr + 2], sel);
          asm("fma.rn.bf16x2 %0, %1, %2, %3;" : "=r"(ad[jj][i]) : "r"(hi), "r"(sgn), "r"(lo));
        }
      }
      __syncwarp();
      if (lane == 0) mbar_arrive(bars + (B_XFREE + wg) * 8);
      float acc[28];
      wg_fence();
      uint64_t db = mkdesc(sb + 6 * SLOT, 896, 128, 0);
#pragma unroll
      for (int jj = 0; jj < 7; jj++) wgmma_rs_56<0>(acc, ad[jj], db + jj * 112, jj != 0);
      wg_commit();
      wg_wait<0>(); keep(acc);
      if (lane == 0) mbar_arrive(bars + (B_EMPTY + 6) * 8);
      const uint32_t xc = sb + OFF_EXCH + wg * 8192 + t * 256 + w4 * 64 + g * 4;
      mbar_wait(bars + B_XFREE * 8, 0);
#pragma unroll
      for (int i = 0; i < 7; i++) {
        sts32(xc + i * 1024, pack_bf16(acc[4 * i], acc[4 * i + 1]));
        sts32(xc + i * 1024 + 32, pack_bf16(acc[4 * i + 2], acc[4 * i + 3]));
      }
      fence_async_smem();
      __syncwarp();
      if (lane == 0) mbar_arrive(bars + B_PUBX * 8);
    }
    if ((tid & 127) == 0) PROF(wg, 3);
    const uint32_t tag = ~epoch & 1;
    unsigned char* const hbase = g_H + (size_t)(m * 2 + kh) * (56 * 4096) + rh * 2048 + (tid & 127) * 16;
#pragma unroll 1
    for (int u = 0; u < 3; u++) {
      float acc[64];
      if (wg == 1) { if (u & 1) bar_sync<6, 256>(); else bar_sync<2, 256>(); }
      const uint32_t sbu = opaque(sb);
#pragma unroll
      for (int kb = 0; kb < 7; kb++) {
        mbar_wait(sbu + OFF_BAR + (B_FULL + kb) * 8, u & 1);
        wg_fence();
        uint64_t db = mkdesc(sbu + kb * SLOT, 8192, 1024, 1);
#pragma unroll
        for (int kk = 0; kk < 4; kk++) wgmma_rs_128<1>(acc, xa[kb * 4 + kk], db + kk * 128, (kb | kk) != 0);
        wg_commit();
        if (kb == LEAD1 && wg == 0) { if (u & 1) bar_arrive<6, 256>(); else bar_arrive<2, 256>(); }
        if (kb > 0) { wg_wait<1>(); if (lane == 0) mbar_arrive(sbu + OFF_BAR + (B_EMPTY + kb - 1) * 8); }
      }
      wg_wait<0>(); keep(acc);
      if (lane == 0) mbar_arrive(sbu + OFF_BAR + (B_EMPTY + 6) * 8);
      if ((tid & 127) == 0) PROF(wg, 4 + 2 * u);
      h_epilogue<8>(acc, hbase + (u * 16 + n * 4) * 4096, tag);
      if ((tid & 127) == 0) PROF(wg, 5 + 2 * u);
    }
    uint32_t ha[14][4][4];
    auto check = [&](int b0, int b1) {
#pragma unroll
      for (int b = b0; b < b1; b++) frag_ready(ha[b][0], ha[b][1], ha[b][2], ha[b][3], hbase + b * 16384, tag);
    };
    auto load = [&](int b0, int b1) {
#pragma unroll
      for (int i = b0; i < b1; i++) ldg128_l2(ha[i >> 2][i & 3], hbase + i * 4096);
    };
    {
      float acc[32];
      load(0, 3);
      if (wg == 1) bar_sync<6, 256>();
      const uint32_t sbu = opaque(sb);
#pragma unroll
      for (int it = 0; it < 4; it++) {
        mbar_wait(sbu + OFF_BAR + (B_FULL + it) * 8, 1);
        wg_fence();
        uint64_t db = mkdesc(sbu + it * SLOT, 8192, 512, 2);
#pragma unroll
        for (int kk = 0; kk < 8; kk++) if (it * 8 + kk < 28) wgmma_rs_64<1>(acc, xa[it * 8 + kk], db + kk * 64, (it | kk) != 0);
        wg_commit();
        if (it == 2 && wg == 0) bar_arrive<6, 256>();
        if (it > 0) {
          wg_wait<1>();
          if (lane == 0) mbar_arrive(sbu + OFF_BAR + (B_EMPTY + it - 1) * 8);
          if (it == 1) load(3, 11);
          if (it == 2) load(11, 16);
        }
      }
      wg_wait<0>(); keep(acc);
      if (lane == 0) mbar_arrive(sbu + OFF_BAR + (B_EMPTY + 3) * 8);
      if ((tid & 127) == 0) PROF(wg, 10);
      h_epilogue<4>(acc, hbase + (48 + n * 2) * 4096, tag);
    }
    asm volatile("barrier.cluster.wait.aligned;" ::: "memory");
    if ((tid & 127) == 0) PROF(wg, 11);

    float acc[56];
    check(0, 4);
    if (wg == 1) bar_sync<2, 256>();
#pragma unroll
    for (int b = 0; b < 14; b++) {
      if ((tid & 127) == 0) PROF(wg, 16 + b);
      if (b >= 3) mbar_wait(bars + (B_FULL + (b + 1) % 7) * 8, b < 6 || b == 13);
      else if (b == 0) mbar_wait(bars + B_RFULL * 8, 0);
      if (b == 4) check(4, 7);
      if (b == 7) check(7, 11);
      if (b == 11) check(11, 14);
      wg_fence();
      const uint64_t db = mkdesc(b < 3 ? sb + OFF_R + b * SLOT : sb + (b + 1) % 7 * SLOT, 8192, 1024, 1);
#pragma unroll
      for (int kk = 0; kk < 4; kk++) wgmma_rs_112<1>(acc, ha[b][kk], db + kk * 128, (b | kk) != 0);
      wg_commit();
      if (b == LEAD2 && wg == 0) bar_arrive<2, 256>();
      if (b == 0) load(16, 24);
      if (b == 1) load(24, 28);
      if (b == 4 || b == 5) load(8 * b - 4, 8 * b + 4);
      if (b == 7) load(44, 52);
      if (b == 8) load(52, 56);
      if (b > 0) wg_wait<1>();
      if (lane == 0) {
        if (b >= 4 && b <= 9) mbar_arrive(bars + (B_EMPTY + b % 7) * 8);
        if (b == 3) {
          mbar_arrive(bars + B_LFREE * 8);
          asm volatile("{\n.reg .b32 ra;\nmapa.shared::cluster.u32 ra, %0, %1;\nmbarrier.arrive.relaxed.cluster.shared::cluster.b64 _, [ra];\n}"
                       :: "r"(bars + B_RFREE * 8), "r"(kh ^ 1) : "memory");
        }
      }
    }
    const int t128 = tid & 127;
    wg_wait<0>(); keep(acc);
    if (wg == 0) {
      if (t128 == 0) PROF(wg, 12);
      mbar_wait_cluster(bars + B_RFREE * 8, 0);
      uint32_t rdst, rbar;
      asm volatile("mapa.shared::cluster.u32 %0, %1, %2;" : "=r"(rdst) : "r"(sb + OFF_R + t128 * 16), "r"(kh ^ 1));
      asm volatile("mapa.shared::cluster.u32 %0, %1, %2;" : "=r"(rbar) : "r"(bars + B_RECV * 8), "r"(kh ^ 1));
#pragma unroll
      for (int i = 0; i < 7; i++)
        asm volatile("st.async.weak.shared::cluster.mbarrier::complete_tx::bytes.v4.b32 [%0], {%1,%2,%3,%4}, [%5];"
                     :: "r"(rdst + i * 2048), "r"(pack_bf16(acc[8 * i], acc[8 * i + 1])), "r"(pack_bf16(acc[8 * i + 2], acc[8 * i + 3])),
                        "r"(pack_bf16(acc[8 * i + 4], acc[8 * i + 5])), "r"(pack_bf16(acc[8 * i + 6], acc[8 * i + 7])), "r"(rbar) : "memory");
    } else {
      float spec[2][28];
      if (t128 == 0) PROF(wg, 12);
#pragma unroll
      for (int i = 0; i < 4; i++) {
        if (i == 0) mbar_wait(bars + B_GFULL * 8, 0);
        if (i >= 2) mbar_wait(bars + (B_FULL + i - 1) * 8, 1);
        mbar_wait(bars + (B_PQFULL + i) * 8, 0);
        if (i == 0 && t128 == 0) { PROF(wg, 13); g_ep[bid] = epoch + 1; }
        wg_fence();
        const uint64_t da = mkdesc(sb + OFF_PQ + i * 14336, 1024, 1024, 1);
        const uint64_t db = mkdesc(i < 2 ? sb + OFF_R + 28672 + i * (G_IMG / 2) : sb + (i - 1) * SLOT, 896, 128, 0);
#pragma unroll
        for (int kk = 0; kk < 7; kk++) wgmma_ss_56<1, 0>(spec[i >> 1], da + kk * 128, db + kk * 112, ((i & 1) | kk) != 0);
        wg_commit();
      }
      const float* gs = reinterpret_cast<const float*>(smem + OFF_G) + w4 * 16 + g;
      const float o0 = bf16_round(1.0f - gs[0]), o1 = bf16_round(1.0f - gs[8]);
      const float g0 = gs[0] * (1.0f / (float)(S_ * D_)), g1 = gs[8] * (1.0f / (float)(S_ * D_));
      mbar_wait_cluster(bars + B_RECV * 8, 0);
      if (t128 == 0) PROF(wg, 0);
#pragma unroll
      for (int i = 0; i < 7; i++) {
        const uint4 o4 = lds128(sb + OFF_R + t128 * 16 + i * 2048);
        const uint32_t o[4] = {o4.x, o4.y, o4.z, o4.w};
#pragma unroll
        for (int e = 0; e < 4; e++) {
          acc[8 * i + 2 * e] = (acc[8 * i + 2 * e] + bf_lo(o[e])) * ((e & 1) ? o1 : o0);
          acc[8 * i + 2 * e + 1] = (acc[8 * i + 2 * e + 1] + bf_hi(o[e])) * ((e & 1) ? o1 : o0);
        }
      }
      keep(acc);
      wg_wait<0>(); keep(spec[0]); keep(spec[1]);
      if (t128 == 0) PROF(wg, 14);
      bar_sync<5, 128>();
      const uint32_t st = sb + OFF_PQ + w4 * 3840;
#pragma unroll
      for (int i = 0; i < 7; i++) {
        uint32_t pk[4];
#pragma unroll
        for (int e = 0; e < 2; e++) {
          const int c = 2 * i + e, si = i * 4 + e;
          pk[2 * e] = pack_bf16(fmaf(g0, spec[0][si], acc[4 * c]), fmaf(g0, spec[1][si], acc[4 * c + 1]));
          pk[2 * e + 1] = pack_bf16(fmaf(g1, spec[0][si + 2], acc[4 * c + 2]), fmaf(g1, spec[1][si + 2], acc[4 * c + 3]));
        }
        asm volatile("stmatrix.sync.aligned.m8n8.x4.shared.b16 [%0], {%1,%2,%3,%4};"
                     :: "r"(st + (lane & 15) * 240 + (lane >> 4) * 16 + i * 32), "r"(pk[0]), "r"(pk[1]), "r"(pk[2]), "r"(pk[3]) : "memory");
      }
      __syncwarp();
      if (lane < 28) {
        const int r2 = lane >= 14, cc = lane - r2 * 14;
        unsigned char* ob = reinterpret_cast<unsigned char*>(out) + (size_t)(m * 128 + kh * 64 + w4 * 16 + r2) * (D_ * 2) + n * 224 + cc * 16;
        float4 v[8];
#pragma unroll
        for (int i = 0; i < 8; i++) v[i] = lds128f(st + r2 * 240 + cc * 16 + i * 480);
#pragma unroll
        for (int i = 0; i < 8; i++) stg128(ob + i * (D_ * 4), __float_as_uint(v[i].x), __float_as_uint(v[i].y), __float_as_uint(v[i].z), __float_as_uint(v[i].w));
      }
    }
    if (t128 == 0) { PROF(wg, 15); if (wg) { PROFG(4, 30); PROF(4, 31); } }
  } else if (warp < 12) {
    asm volatile("setmaxnreg.dec.sync.aligned.u32 72;");
    const int t = tid - 256;
    const int k = bid;
    if (t == 0) PROF(2, 0);
    uint4 gv[7];
#pragma unroll
    for (int i = 0; i < 7; i++) gv[i] = ldg128(reinterpret_cast<const uint4*>(gate_w) + i * 8 + (t & 7));
    if (t < 98) {
      int cid = m * 98 + t, kc = cid / 56, nn = cid - kc * 56;
      int d = 112 * n + 8 * (2 * (nn >> 3) + (nn & 1)) + (nn & 6) + kh;
      int dr = d > 224 ? d - 448 : d;
      const float df = (float)dr * (-6.283185307179586f / 448.0f);
      uint32_t pk[4];
#pragma unroll
      for (int e = 0; e < 4; e++) {
        const float a = (float)(4 * kc + e) * df;
        pk[e] = pack_bf16(2.0f * __cosf(a), 2.0f * __sinf(a));
      }
      if (kc == 0) pk[0] = (((d >> 1) ^ kh) & 1) ? 0xBF803F80u : 0x3F803F80u;
      stg128(g_G + (size_t)(n * 2 + kh) * G_IMG + cid * 16, pk[0], pk[1], pk[2], pk[3]);
    }
    bar_sync<0, NTHREADS - 64>();
    asm volatile("barrier.cluster.arrive.relaxed.aligned;" ::: "memory");
    {
      const int row = n * 16 + (t >> 3), l8 = t & 7;
      mbar_wait(bars + (B_XFULL + 1) * 8, 0);
      float sum = 0.f;
#pragma unroll
      for (int i = 0; i < 7; i++) {
        const uint4 a = lds128(sb + OFF_R + i * 8192 + row * 128 + ((l8 ^ (row & 7)) << 4));
        const uint32_t aa[4] = {a.x, a.y, a.z, a.w}, bb[4] = {gv[i].x, gv[i].y, gv[i].z, gv[i].w};
#pragma unroll
        for (int e = 0; e < 4; e++) {
          const uint32_t pr = as_u(__hmul2(as_b2(aa[e]), as_b2(bb[e])));
          sum += bf_lo(pr) + bf_hi(pr);
        }
      }
      sum += __shfl_xor_sync(0xffffffffu, sum, 1); sum += __shfl_xor_sync(0xffffffffu, sum, 2); sum += __shfl_xor_sync(0xffffffffu, sum, 4);
      if (l8 == 0) g_gate[m * 128 + kh * 64 + row] = bf16_round(__fdividef(1.0f, 1.0f + __expf(-bf16_round(sum))));
    }
    __syncwarp();
    if (lane == 0) mbar_arrive(bars + (B_XFREE + 1) * 8);
    if (t == 0) PROF(2, 11);
    mbar_wait(bars + B_XFREE * 8, 0);
    {
      const float u = -6.283185307179586f / 2048.0f, t2 = (float)(2 * t) * u;
#pragma unroll 1
      for (int i = 0; i < 4; i++) {
        const float q = (float)(2 * i);
        sts128(sb + OFF_TW + i * 2048 + t * 16, cis(t2 * q), cis((t2 + u) * q), cis(t2 * (q + 1.0f)), cis((t2 + u) * (q + 1.0f)));
      }
      const float l = (float)((t >> 1) & 15) * (8.0f * u), jj = (float)((t >> 5) * 4 + (t & 1) * 2);
      sts64(sb + OFF_TW + 16384 + t * 8, cis(l * jj), cis(l * (jj + 1.0f)));
    }
    mbar_wait(bars + B_PIN * 8, 0);
    mbar_wait(bars + (B_XFREE + 1) * 8, 0);
    if (t == 0) PROF(2, 4);
    {
      const uint32_t wa = sb + OFF_WS + (((t & 7) - bid) & 7) * 450 + (t >> 3) * 2, wc = wa + 448 - (t >> 3) * 4;
#pragma unroll 1
      for (int h = 0; h < 2; h++) {
        uint32_t w[4][8];
#pragma unroll
        for (int i = 0; i < 4; i++) {
#pragma unroll
          for (int e = 0; e < 4; e++) { w[i][2 * e] = lds16(wa + h * 128 + i * 32 + e * 3600); w[i][2 * e + 1] = lds16(wc - h * 128 - i * 32 + e * 3600); }
        }
#pragma unroll
        for (int i = 0; i < 4; i++)
          sts128(sb + OFF_R + h * 8192 + i * 2048 + t * 16, __byte_perm(w[i][0], w[i][1], 0x5410), __byte_perm(w[i][4], w[i][5], 0x5410), __byte_perm(w[i][2], w[i][3], 0x5410), __byte_perm(w[i][6], w[i][7], 0x5410));
      }
    }
    fence_async_smem();
    __syncwarp();
    if (lane == 0) mbar_arrive(bars + B_PUBW * 8);
    if (k < 113) {
      if (t == 0) PROF(2, 2);
      mbar_wait(bars + B_XCFULL * 8, 0);
      if (t == 0) PROF(2, 3);
      c2 v[16];
      uint2 xe[8], xo[8];
      const int sl = k == 112 ? 0 : k, hi = sl >= 56;
      const unsigned char* xs = g_X + (192 + (sl & 1) * 64 + hi * 72 + (sl & ~1) + ((t >> 4) & 1)) * XP + (t >> 5) * 256 + (t & 15) * 8;
#pragma unroll
      for (int jj = 0; jj < 8; jj++) { xe[jj] = ldg64_l2(xs + jj * 1024); xo[jj] = ldg64_l2(xs + jj * 1024 + 128); }
      {
        const float rr = (float)(t >> 4) * (-6.283185307179586f / 2048.0f);
#pragma unroll 1
        for (int i = 0; i < 4; i++) {
          const float l = (float)((t & 15) + 64 * i);
          sts128(sb + OFF_TW + 8192 + i * 2048 + t * 16, cis(rr * l), cis(rr * (l + 16.0f)), cis(rr * (l + 32.0f)), cis(rr * (l + 48.0f)));
        }
      }
      if (t == 0) PROF(2, 9);
      const uint32_t se = k == 0 ? 0x4410 : (k == 112 ? 0x4432 : 0x3210), so = k == 0 ? 0x4410 : (k == 112 ? 0x3244 : 0x3210);
#pragma unroll
      for (int jj = 0; jj < 8; jj++) {
        const uint2 e2 = xe[jj], o2 = xo[jj];
#pragma unroll
        for (int h = 0; h < 2; h++) {
          const b2 e = as_b2(__byte_perm(h ? e2.y : e2.x, 0, se)), o = as_b2(__byte_perm(h ? o2.y : o2.x, 0, so));
          const uint32_t s = as_u(__hadd2(e, o)), d = as_u(__hsub2(e, o)) ^ 0x80000000u;
          v[2 * jj + h] = mk(as_b2(__byte_perm(s, d, 0x5410)), as_b2(__byte_perm(s, d, 0x7632)));
        }
      }
      if (t == 0) PROF(2, 12);
      columns(v, sb, t);
      if (t == 0) PROF(2, 14);
      const int pre = (k == 112) ? 1 : 2 * k, pim = (k == 112) ? 1 : 2 * k + 1;
      const uint32_t pr = sb + OFF_WS + (t >> 5) * 256 + ((((lane >> 2) ^ pre) & 7) << 4) + (lane & 3) * 4;
      const uint32_t pi = sb + OFF_WS + 8192 + (t >> 5) * 256 + ((((lane >> 2) ^ pim) & 7) << 4) + (lane & 3) * 4;
#pragma unroll
      for (int jj = 0; jj < 8; jj++) {
        const b2 ar = as_b2(__byte_perm(as_u(v[2 * jj].y), as_u(v[2 * jj + 1].y), 0x5410)), br = as_b2(__byte_perm(as_u(v[2 * jj].y), as_u(v[2 * jj + 1].y), 0x7632));
        const b2 ai = as_b2(__byte_perm(as_u(v[2 * jj].x), as_u(v[2 * jj + 1].x), 0x5410)), bi = as_b2(__byte_perm(as_u(v[2 * jj].x), as_u(v[2 * jj + 1].x), 0x7632));
        sts32(pr + jj * 1024, as_u(__hadd2(ar, br)));
        sts32(pr + jj * 1024 + 128, as_u(k == 112 ? __hadd2(ai, bi) : __hsub2(ar, br)));
        sts32(pi + jj * 1024 + 128, as_u(__hadd2(ai, bi)));
        sts32(pi + jj * 1024, as_u(__hsub2(ai, bi)));
      }
      fence_async_smem();
      bar_sync<3, 128>();
      if (t == 0) {
        PROF(2, 5);
        tma_store(&tm_s, pre * 64, 0, sb + OFF_WS);
        if (k != 0 && k != 112) tma_store(&tm_s, pim * 64, 0, sb + OFF_WS + 8192);
        bulk_done();
      }
    }
    if (t == 0) { red_relaxed(&g_cnt[5 * 32]); PROF(2, 7); }
    if (t >= 32) {
      if (k >= 113) mbar_wait(bars + B_LFREE * 8, 0);
      __nanosleep((t >> 5) * STAG);
      wait_ge(&g_cnt[5 * 32], (lds64(sb + OFF_G + 256).x + 1) * 128);
      if (lane == 0) mbar_arrive(bars + B_SEEN * 8);
    }
    __syncwarp();
    asm volatile("barrier.cluster.wait.aligned;" ::: "memory");
  } else {
    asm volatile("setmaxnreg.dec.sync.aligned.u32 24;");
    auto wd_tile = [&](int b, uint32_t dst, uint32_t fb) {
#pragma unroll
      for (int hf = 0; hf < 2; hf++) {
        const int js = kh * 4 + (b < 12 ? (b & 3) : (b & 1) * 2 + hf);
        const int row = 224 * js + (b < 12 ? (js & 1) * 32 + (b >> 2) * 64 + hf * 32 : 192 - hf * 192);
        tma2d(dst + hf * 4096, &tm_d, 112 * n, row, fb);
        tma2d(dst + 8192 + hf * 4096, &tm_d, 112 * n + 64, row, fb);
      }
    };
    if (warp == 12) {
      if (elect()) {
        mbar_init(bars + B_XFULL * 8, 1); mbar_init(bars + (B_XFULL + 1) * 8, 1);
        fence_async_smem();
#pragma unroll
        for (int w = 0; w < 2; w++) {
          mbar_expect(bars + (B_XFULL + w) * 8, HALF_XR);
          tma3d(sb + OFF_PQ + w * HALF_XR, &tm_x, 0, m * 128 + (w ^ kh ^ 1) * 64, 0, bars + (B_XFULL + w) * 8);
        }
        PROF(3, 3);
#pragma unroll
        for (int i = 0; i < NSLOT; i++) mbar_init(bars + (B_FULL + i) * 8, 1);
        mbar_init(bars + B_PIN * 8, 1);
        fence_async_smem();
      }
      bar_arrive<0, NTHREADS - 64>();
#pragma unroll 1
      for (int i = 0; i < 6; i++) {
        if (elect()) {
          const uint32_t fb = bars + (B_FULL + i) * 8;
          mbar_expect(fb, SLOT);
          tma2d(sb + i * SLOT, &tm_g, c64, i * 64, fb);
          tma2d(sb + i * SLOT + 8192, &tm_u, c64, i * 64, fb);
          PROF(3, 4 + i);
        }
      }
      if (elect()) {
        prefetch_l2(reinterpret_cast<const unsigned char*>(w_r) + bid * 7200, 7200);
        prefetch_l2(reinterpret_cast<const unsigned char*>(w_i) + bid * 7200, 7200);
        prefetch_l2(reinterpret_cast<const unsigned char*>(w_gate) + bid * 12544, 12544);
        prefetch_l2(reinterpret_cast<const unsigned char*>(w_up) + bid * 12544, 12544);
      }
    } else if (warp == 14) {
      if (elect()) {
#pragma unroll
        for (int i = B_EMPTY; i < B_END; i++)
          if (i < B_XFULL || i >= B_XFREE) mbar_init(bars + i * 8, i >= B_PQFULL ? 1 : (i == B_XFREE ? 4 : (i == B_PUBW ? 5 : 8)));
        asm volatile("fence.mbarrier_init.release.cluster;" ::: "memory");
        fence_async_smem();
        mbar_expect(bars + B_RECV * 8, 64 * 112 * 2);
      }
      bar_arrive<0, NTHREADS - 64>();
    }
    const uint32_t epoch = ld_relaxed(&g_ep[bid]);
    if (warp == 13 && lane == 0) { PROFG(4, 0); PROF(4, 1); }
    bar_sync<1, 128>();
    asm volatile("barrier.cluster.arrive.relaxed.aligned;" ::: "memory");
    if (warp == 12) {
      int slot = 6, ph = 1;
      auto wait_slot = [&]() { mbar_wait(bars + (B_EMPTY + slot) * 8, ph ^ (slot == 6)); };
      auto adv = [&]() { if (++slot == NSLOT) { slot = 0; ph ^= 1; } };
      const int c32 = 224 * j + ((j & 1) ? 0 : 192);
#pragma unroll 1
      for (int i = 6; i < 25; i++) {
        wait_slot();
        if (elect()) {
          const uint32_t dst = sb + slot * SLOT, fb = bars + (B_FULL + slot) * 8;
          const bool last = i >= 21;
          const int cc = last ? c32 : c64 + 64 * (i / 7), rr = last ? slot * 128 : slot * 64;
          mbar_expect(fb, SLOT);
          tma2d(dst, last ? &tm_g32 : &tm_g, cc, rr, fb);
          tma2d(dst + 8192, last ? &tm_u32 : &tm_u, cc, rr, fb);
        }
        adv();
      }
      if (lane == 0) PROF(3, 0);
#pragma unroll 1
      for (int i = 3; i < 16; i++) {
        if (lane == 0) PROF(3, 16 + i);
        if (i == 14) mbar_wait(bars + B_PREP * 8, 0);
        wait_slot();
        if (elect()) {
          const uint32_t fb = bars + (B_FULL + slot) * 8;
          mbar_expect(fb, i < 14 ? SLOT : G_IMG / 2);
          if (i < 14) wd_tile(i, sb + slot * SLOT, fb);
          else bulk_g2s(sb + slot * SLOT, g_G + (size_t)(n * 4 + i - 12) * (G_IMG / 2), G_IMG / 2, fb);
        }
        adv();
      }
      if (lane == 0) PROF(3, 2);
    } else if (warp == 13) {
      mbar_wait(bars + B_PUBX * 8, 0);
      if (elect()) {
        PROF(4, 8);
#pragma unroll
        for (int w = 0; w < 2; w++) tma_store(&tm_s, ((m * 2 + (w ^ kh ^ 1)) * 2 + (j & 1)) * 64, 192 + (j >> 1) * 64, sb + OFF_EXCH + w * 8192);
        bulk_done();
        red_relaxed(&g_cnt[(j >> 1) * 32]);
        mbar_arrive(bars + B_XDONE * 8);
        PROF(4, 12);
      }
      mbar_wait(bars + B_PUBW * 8, 0);
      if (elect()) {
        PROF(4, 9);
        tma_store(&tm_s, bid * 64, 64, sb + OFF_R);
        tma_store(&tm_s, bid * 64, 128, sb + OFF_R + 8192);
        bulk_done();
        red_relaxed(&g_cnt[4 * 32]);
        mbar_arrive(bars + B_WDONE * 8);
        PROF(4, 13);
      }
      mbar_wait(bars + B_PREP * 8, 0);
      mbar_wait(bars + B_LFREE * 8, 0);
      if (elect()) {
        mbar_expect(bars + B_GFULL * 8, G_IMG);
        bulk_g2s(sb + OFF_R + 28672, g_G + (size_t)(n * 2) * G_IMG, G_IMG, bars + B_GFULL * 8);
      }
    } else if (warp == 14) {
      mbar_wait(bars + (B_XFREE + 1) * 8, 0);
      asm volatile("fence.acq_rel.gpu;" ::: "memory");
      if (lane == 0) { mbar_arrive(bars + B_PUBW * 8); PROF(5, 3); }
      mbar_wait(bars + B_WDONE * 8, 0);
      wait_ge(&g_cnt[4 * 32], (epoch + 1) * 128);
      fence_async_global();
      if (elect()) {
        mbar_arrive(bars + B_PREP * 8);
        if (bid < 113) {
          mbar_expect(bars + B_WFULL * 8, 16384);
          bulk_g2s(sb + OFF_WS, g_X + (64 + bid) * XP, 16384, bars + B_WFULL * 8);
        }
        PROF(5, 17);
      }
    } else {
      mbar_wait(bars + B_XFREE * 8, 0);
      if (elect()) {
        sts32(sb + OFF_G + 256, epoch);
        mbar_expect(bars + B_PIN * 8, 14400);
        bulk_g2s(sb + OFF_WS, reinterpret_cast<const unsigned char*>(w_r) + bid * 7200, 7200, bars + B_PIN * 8);
        bulk_g2s(sb + OFF_WS + 7200, reinterpret_cast<const unsigned char*>(w_i) + bid * 7200, 7200, bars + B_PIN * 8);
        PROF(5, 2);
      }
#pragma unroll 1
      for (int i = lane; i < 98; i += 32) asm volatile("prefetch.global.L2 [%0];\nprefetch.global.L2 [%0+64];" :: "l"(reinterpret_cast<const unsigned char*>(w_down) + bid * 12544 + i * 128));
      if (bid < 113) {
        const int sl = (bid == 112) ? 0 : bid;
        wait_ge(&g_cnt[((sl & 1) + 2 * ((sl >> 1) / 28)) * 32], (epoch + 1) * 32);
        if (elect()) { PROF(5, 16); mbar_arrive(bars + B_XCFULL * 8); }
      }
      mbar_wait(bars + B_WDONE * 8, 0);
      if (elect()) mbar_expect(bars + B_RFULL * 8, 3 * SLOT);
#pragma unroll 1
      for (int i = 0; i < 3; i++) {
        mbar_wait(bars + (B_FULL + (i == 0 ? RP0 : 2 * i - 1)) * 8, i == 0);
        if (elect()) wd_tile(i, sb + OFF_R + i * SLOT, bars + B_RFULL * 8);
      }
      if (lane == 0) PROF(5, 19);
      mbar_wait(bars + B_PREP * 8, 0);
      mbar_wait(bars + B_SEEN * 8, 0);
      fence_async_global();
      if (elect()) {
        PROF(5, 18);
        const unsigned char* src = g_X + (m * 2 + kh) * HALF_XR;
#pragma unroll
        for (int i = 0; i < 4; i++) {
          mbar_expect(bars + (B_PQFULL + i) * 8, i < 3 ? 14336 : 14336 + 256);
          bulk_g2s(sb + OFF_PQ + i * 14336, src + i * 14336, 14336, bars + (B_PQFULL + i) * 8);
        }
        bulk_g2s(sb + OFF_G, g_gate + m * 128 + kh * 64, 256, bars + (B_PQFULL + 3) * 8);
      }
    }
    __syncwarp();
    asm volatile("barrier.cluster.wait.aligned;" ::: "memory");
  }
}

typedef CUresult (*EncodeFn)(CUtensorMap*, CUtensorMapDataType, cuuint32_t, void*, const cuuint64_t*, const cuuint64_t*, const cuuint32_t*,
                             const cuuint32_t*, CUtensorMapInterleave, CUtensorMapSwizzle, CUtensorMapL2promotion, CUtensorMapFloatOOBfill);

void make_map(EncodeFn enc, CUtensorMap* tm, const void* base, int cols, int rows, int bc, int br, CUtensorMapSwizzle sw) {
  cuuint64_t gd[2] = {(cuuint64_t)cols, (cuuint64_t)rows};
  cuuint64_t gs[1] = {(cuuint64_t)cols * 2};
  cuuint32_t bd[2] = {(cuuint32_t)bc, (cuuint32_t)br};
  cuuint32_t es[2] = {1, 1};
  enc(tm, CU_TENSOR_MAP_DATA_TYPE_BFLOAT16, 2, const_cast<void*>(base), gd, gs, bd, es, CU_TENSOR_MAP_INTERLEAVE_NONE, sw,
      CU_TENSOR_MAP_L2_PROMOTION_L2_128B, CU_TENSOR_MAP_FLOAT_OOB_FILL_NONE);
}

}

extern "C" void kernel_launch(void* const* d_in, const int* in_sizes, int n_in, void* d_out, int out_size) {
  (void)in_sizes; (void)n_in; (void)out_size;
  const __nv_bfloat16* x = (const __nv_bfloat16*)d_in[0];
  const __nv_bfloat16* w_r = (const __nv_bfloat16*)d_in[1];
  const __nv_bfloat16* w_i = (const __nv_bfloat16*)d_in[2];
  const __nv_bfloat16* w_gate = (const __nv_bfloat16*)d_in[4];
  const __nv_bfloat16* w_up = (const __nv_bfloat16*)d_in[5];
  const __nv_bfloat16* w_down = (const __nv_bfloat16*)d_in[6];
  const __nv_bfloat16* gate_w = (const __nv_bfloat16*)d_in[7];
  static EncodeFn enc = nullptr;
  static void* xbuf = nullptr;
  static bool ok = false;
  if (!enc) {
    cudaDriverEntryPointQueryResult qr;
    cudaGetDriverEntryPoint("cuTensorMapEncodeTiled", (void**)&enc, cudaEnableDefault, &qr);
    cudaFuncSetAttribute(fused_kernel, cudaFuncAttributeMaxDynamicSharedMemorySize, SMEM_BYTES);
    cudaGetSymbolAddress(&xbuf, g_X);
    cudaFuncAttributes fa;
    cudaFuncGetAttributes(&fa, fused_kernel);
    ok = (fa.numRegs == 128);
  }
  if (!ok) return;
  CUtensorMap tx, tg, tu, tg32, tu32, td, ts;
  {
    cuuint64_t gd[3] = {64, (cuuint64_t)S_, 7};
    cuuint64_t gs[2] = {(cuuint64_t)D_ * 2, 128};
    cuuint32_t bd[3] = {64, 64, 7};
    cuuint32_t es[3] = {1, 1, 1};
    enc(&tx, CU_TENSOR_MAP_DATA_TYPE_BFLOAT16, 3, const_cast<__nv_bfloat16*>(x), gd, gs, bd, es, CU_TENSOR_MAP_INTERLEAVE_NONE, CU_TENSOR_MAP_SWIZZLE_128B,
        CU_TENSOR_MAP_L2_PROMOTION_L2_128B, CU_TENSOR_MAP_FLOAT_OOB_FILL_NONE);
  }
  make_map(enc, &tg, w_gate, F_, D_, 64, 64, CU_TENSOR_MAP_SWIZZLE_128B);
  make_map(enc, &tu, w_up, F_, D_, 64, 64, CU_TENSOR_MAP_SWIZZLE_128B);
  make_map(enc, &tg32, w_gate, F_, D_, 32, 128, CU_TENSOR_MAP_SWIZZLE_64B);
  make_map(enc, &tu32, w_up, F_, D_, 32, 128, CU_TENSOR_MAP_SWIZZLE_64B);
  make_map(enc, &td, w_down, D_, F_, 64, 32, CU_TENSOR_MAP_SWIZZLE_128B);
  make_map(enc, &ts, (const __nv_bfloat16*)xbuf, XP / 2, 448, 64, 64, CU_TENSOR_MAP_SWIZZLE_NONE);
  fused_kernel<<<128, NTHREADS, SMEM_BYTES>>>(tx, tg, tu, tg32, tu32, td, ts, w_r, w_i, w_gate, w_up, w_down, gate_w, (__nv_bfloat16*)d_out);
}
```
